```python
import torch

def _softmax(x, axis=-1):
    return torch.softmax(x, dim=axis)

def _gelu(x):
    return torch.nn.functional.gelu(x, approximate='tanh')

def _silu(x):
    return torch.nn.functional.silu(x)

def _sigmoid(x):
    return torch.sigmoid(x)

def _layernorm(x, axis=-1, eps=1e-05):
    m = x.mean(dim=axis, keepdim=True)
    v = x.var(dim=axis, keepdim=True, unbiased=False)
    return (x - m) / torch.sqrt(v + eps)

def _scatter_add(tgt, idx, src, axis=0):
    return tgt.clone().index_add_(axis, idx, src)

def _segment_sum(src, seg, n):
    out = torch.zeros((n,) + src.shape[1:], dtype=src.dtype)
    return out.index_add_(0, seg, src)

def _pad(x, pw):
    flat = tuple((v for pair in reversed(pw) for v in pair))
    return torch.nn.functional.pad(x, flat)
kernel_name = 'standalone__conformer_family_branchformer__speech'

def setup_inputs():

    _w = lambda a: (lambda t: t.to(torch.bfloat16) if t.is_floating_point() else t)(torch.as_tensor(a))
    B, T, D, K = (2, 4000, 512, 3)
    s = float(D) ** (-0.5)
    return {'x': _w((lambda *s: torch.randn(*s, dtype=torch.bfloat16) * 0.05)(B, T, D)), 'w_q': _w((lambda *s: torch.randn(*s, dtype=torch.bfloat16) * 1.6)(D, D) * s), 'w_k': _w((lambda *s: torch.randn(*s, dtype=torch.bfloat16) * 1.6)(D, D) * s), 'w_v': _w((lambda *s: torch.randn(*s, dtype=torch.bfloat16) * 0.4)(D, D) * s), 'w_ao': _w((lambda *s: torch.randn(*s, dtype=torch.bfloat16) * 0.4)(D, D) * s), 'w_up': _w((lambda *s: torch.randn(*s, dtype=torch.bfloat16) * 0.8)(D, 2 * D) * s), 'dw': _w((lambda *s: torch.randn(*s, dtype=torch.bfloat16) * 0.8)(K, D) * (1.0 / K)), 'w_dn': _w((lambda *s: torch.randn(*s, dtype=torch.bfloat16) * 0.4)(D, D) * s), 'w_merge': _w((lambda *s: torch.randn(*s, dtype=torch.bfloat16) * 0.4)(2 * D, D) * s)}

def reference(x, w_q, w_k, w_v, w_ao, w_up, dw, w_dn, w_merge):
    B, T, D = x.shape
    K = dw.shape[0]
    xa = _layernorm(x, axis=-1)
    q = torch.einsum('btd,de->bte', xa, w_q)
    k = torch.einsum('btd,de->bte', xa, w_k)
    v = torch.einsum('btd,de->bte', xa, w_v)
    logits = torch.einsum('btd,bsd->bts', q, k) * float(D) ** (-0.5)
    attn = _softmax(logits, axis=-1)
    ya = torch.einsum('bts,bsd->btd', attn, v)
    ya = torch.einsum('btd,de->bte', ya, w_ao)
    xc = _layernorm(x, axis=-1)
    h = _gelu(torch.einsum('btd,de->bte', xc, w_up))
    u = h[..., :D].clone()
    g = _layernorm(h[..., D:], axis=-1)
    pad = K // 2
    gp = _pad(g, ((0, 0), (pad, pad), (0, 0)))
    conv = torch.zeros_like(g)
    for i in range(K):
        conv = conv + gp[:, i:i + T, :] * dw[i][None, None, :]
    yc = torch.einsum('btd,de->bte', u * conv, w_dn)
    merged = torch.concatenate([ya, yc], axis=-1)
    out = torch.einsum('btf,fd->btd', merged, w_merge)
    return x + out
```

```cpp
#include <cuda_runtime.h>
#include <cuda_bf16.h>
#include <cuda.h>
#include <mma.h>
#include <stdint.h>

typedef __nv_bfloat16 bf16;

constexpr int T_ = 4000, D_ = 512, NB_ = 2;
constexpr int TPB = 65;
constexpr int NCTA = TPB * NB_;
constexpr int NKV = 63;

__device__ __align__(1024) bf16 g_xa[NB_ * T_ * D_];
__device__ __align__(1024) bf16 g_mqk[D_ * D_];
__device__ __align__(1024) bf16 g_t1[D_ * D_];
__device__ __align__(1024) bf16 g_wepi[2 * D_ * D_];
__device__ __align__(1024) bf16 g_uc[NCTA * 64 * D_];

constexpr uint32_t R0 = 0, R1 = 65536, R2 = 131072, R3 = 196608, QS = 221184, MISC = 229376;
constexpr uint32_t SMEM_BYTES = 232448;
constexpr uint32_t B_A = MISC, B_R1 = MISC + 8, B_H1 = MISC + 88, B_H2 = MISC + 96, B_H3 = MISC + 104,
                   B_KV = MISC + 112, B_P = MISC + 136, B_GO = MISC + 160, B_R2 = MISC + 184, B_UC = MISC + 280,
                   B_X = MISC + 288, CNT = MISC + 296  , SCL = MISC + 512  ,
                   LINV = MISC + 1280  , STAT = MISC + 1536  ;

__device__ __forceinline__ uint32_t smem_u32(const void* p) { return (uint32_t)__cvta_generic_to_shared(p); }
__device__ __forceinline__ void wg_fence() { asm volatile("wgmma.fence.sync.aligned;" ::: "memory"); }
__device__ __forceinline__ void wg_commit() { asm volatile("wgmma.commit_group.sync.aligned;" ::: "memory"); }
template <int N> __device__ __forceinline__ void wg_wait() { asm volatile("wgmma.wait_group.sync.aligned %0;" ::"n"(N) : "memory"); }
__device__ __forceinline__ uint64_t mkdesc(uint32_t addr, uint32_t lbo) {
    uint32_t lo = ((addr & 0x3FFFF) >> 4) | ((lbo >> 4) << 16);
    uint32_t hi = (1024u >> 4) | (1u << 30);
    return ((uint64_t)hi << 32) | lo;
}
__device__ __forceinline__ void mbar_init(uint32_t bar, int cnt) { asm volatile("mbarrier.init.shared::cta.b64 [%0], %1;" ::"r"(bar), "r"(cnt) : "memory"); }
__device__ __forceinline__ void mbar_expect_tx(uint32_t bar, uint32_t bytes) { asm volatile("mbarrier.arrive.expect_tx.shared::cta.b64 _, [%0], %1;" ::"r"(bar), "r"(bytes) : "memory"); }
__device__ __forceinline__ void mbar_arrive(uint32_t bar) { asm volatile("mbarrier.arrive.shared::cta.b64 _, [%0];" ::"r"(bar) : "memory"); }
__device__ __forceinline__ void mbar_wait(uint32_t bar, uint32_t parity) {
    uint32_t ok;
#pragma unroll 1
    for (uint32_t it = 0;; ++it) {
        asm volatile("{\n.reg .pred p;\nmbarrier.try_wait.parity.shared::cta.b64 p, [%1], %2;\nselp.u32 %0, 1, 0, p;\n}\n" : "=r"(ok) : "r"(bar), "r"(parity) : "memory");
        if (ok) break;
        if (it > (1u << 20)) __trap();
    }
}
__device__ __forceinline__ void fence_async() { asm volatile("fence.proxy.async.shared::cta;" ::: "memory"); }
__device__ __forceinline__ void fence_async_g() { asm volatile("fence.proxy.async.global;" ::: "memory"); }
__device__ __forceinline__ void bar_sync(int id, int n) { asm volatile("bar.sync %0, %1;" ::"r"(id), "r"(n) : "memory"); }
__device__ __forceinline__ void tma3(uint32_t dst, const CUtensorMap* tm, int c0, int c1, int c2, uint32_t bar) {
    asm volatile("cp.async.bulk.tensor.3d.shared::cluster.global.mbarrier::complete_tx::bytes [%0], [%1, {%3, %4, %5}], [%2];"
                 ::"r"(dst), "l"(tm), "r"(bar), "r"(c0), "r"(c1), "r"(c2) : "memory");
}
__device__ __forceinline__ void tma4(uint32_t dst, const CUtensorMap* tm, int c0, int c1, int c2, int c3, uint32_t bar) {
    asm volatile("cp.async.bulk.tensor.4d.shared::cluster.global.mbarrier::complete_tx::bytes [%0], [%1, {%3, %4, %5, %6}], [%2];"
                 ::"r"(dst), "l"(tm), "r"(bar), "r"(c0), "r"(c1), "r"(c2), "r"(c3) : "memory");
}
__device__ __forceinline__ void tma4_store(const CUtensorMap* tm, uint32_t src, int c0, int c1, int c2, int c3) {
    asm volatile("cp.async.bulk.tensor.4d.global.shared::cta.bulk_group [%0, {%2, %3, %4, %5}], [%1];"
                 ::"l"(tm), "r"(src), "r"(c0), "r"(c1), "r"(c2), "r"(c3) : "memory");
}
__device__ __forceinline__ void stsm4(uint32_t addr, uint32_t a, uint32_t b, uint32_t c, uint32_t d) {
    asm volatile("stmatrix.sync.aligned.m8n8.x4.shared.b16 [%0], {%1, %2, %3, %4};" ::"r"(addr), "r"(a), "r"(b), "r"(c), "r"(d) : "memory");
}
__device__ __forceinline__ void ldsm4(uint32_t addr, uint32_t (&r)[4]) {
    asm volatile("ldmatrix.sync.aligned.m8n8.x4.shared.b16 {%0, %1, %2, %3}, [%4];" : "=r"(r[0]), "=r"(r[1]), "=r"(r[2]), "=r"(r[3]) : "r"(addr) : "memory");
}
__device__ __forceinline__ uint32_t pack2(float lo, float hi) {
    uint32_t r;
    asm("cvt.rn.bf16x2.f32 %0, %1, %2;" : "=r"(r) : "f"(hi), "f"(lo));
    return r;
}
__device__ __forceinline__ uint32_t pack2v(float lo, float hi) {
    uint32_t r;
    asm volatile("cvt.rn.bf16x2.f32 %0, %1, %2;" : "=r"(r) : "f"(hi), "f"(lo));
    return r;
}
__device__ __forceinline__ uint32_t bmul2(uint32_t a, uint32_t b) { uint32_t r; asm("mul.rn.bf16x2 %0, %1, %2;" : "=r"(r) : "r"(a), "r"(b)); return r; }
__device__ __forceinline__ uint32_t bfma2(uint32_t a, uint32_t b, uint32_t c) { uint32_t r; asm("fma.rn.bf16x2 %0, %1, %2, %3;" : "=r"(r) : "r"(a), "r"(b), "r"(c)); return r; }
__device__ __forceinline__ float ex2(float x) { float r; asm("ex2.approx.ftz.f32 %0, %1;" : "=f"(r) : "f"(x)); return r; }
__device__ __forceinline__ float gelu(float x) {
    float t = fmaf(x * x, 0.044715f * 0.7978845608028654f, 0.7978845608028654f), th;
    asm("tanh.approx.f32 %0, %1;" : "=f"(th) : "f"(x * t));
    float hx = 0.5f * x;
    return fmaf(hx, th, hx);
}
__device__ __forceinline__ uint32_t ldg_v(const uint32_t* p) { uint32_t v; asm volatile("ld.global.nc.u32 %0, [%1];" : "=r"(v) : "l"(p)); return v; }
__device__ __forceinline__ float lds_f32(uint32_t a) { float v; asm volatile("ld.shared.f32 %0, [%1];" : "=f"(v) : "r"(a) : "memory"); return v; }
__device__ __forceinline__ void sts_f32(uint32_t a, float v) { asm volatile("st.shared.f32 [%0], %1;" ::"r"(a), "f"(v) : "memory"); }
__device__ __forceinline__ uint32_t atom_inc_s(uint32_t a) { uint32_t v; asm volatile("atom.acq_rel.cta.shared.add.u32 %0, [%1], 1;" : "=r"(v) : "r"(a) : "memory"); return v; }
template <int N> __device__ __forceinline__ void pin(float (&a)[N]) {
#pragma unroll
    for (int i = 0; i < N; i++) asm volatile("" : "+f"(a[i])::"memory");
}

template <int N> __device__ __forceinline__ void fresh(float (&a)[N]) {
#pragma unroll
    for (int i = 0; i < N; i++) a[i] = 0.f;
    pin(a);
}

__device__ __forceinline__ void wgmma_rs_n64_tb0(float (&d)[32], uint32_t a0, uint32_t a1, uint32_t a2, uint32_t a3, uint64_t db, int scale_d) {
    asm volatile("{\n.reg .pred p;\nsetp.ne.b32 p, %37, 0;\n"
        "wgmma.mma_async.sync.aligned.m64n64k16.f32.bf16.bf16 {%0, %1, %2, %3, %4, %5, %6, %7, %8, %9, %10, %11, %12, %13, %14, %15, %16, %17, %18, %19, %20, %21, %22, %23, %24, %25, %26, %27, %28, %29, %30, %31}, {%32, %33, %34, %35}, %36, p, 1, 1, 0;\n}\n"
        : "+f"(d[0]), "+f"(d[1]), "+f"(d[2]), "+f"(d[3]), "+f"(d[4]), "+f"(d[5]), "+f"(d[6]), "+f"(d[7]), "+f"(d[8]), "+f"(d[9]), "+f"(d[10]), "+f"(d[11]), "+f"(d[12]), "+f"(d[13]), "+f"(d[14]), "+f"(d[15]), "+f"(d[16]), "+f"(d[17]), "+f"(d[18]), "+f"(d[19]), "+f"(d[20]), "+f"(d[21]), "+f"(d[22]), "+f"(d[23]), "+f"(d[24]), "+f"(d[25]), "+f"(d[26]), "+f"(d[27]), "+f"(d[28]), "+f"(d[29]), "+f"(d[30]), "+f"(d[31])
        : "r"(a0), "r"(a1), "r"(a2), "r"(a3), "l"(db), "r"(scale_d));
}

__device__ __forceinline__ void wgmma_ss_n128_tb1(float (&d)[64], uint64_t da, uint64_t db, int scale_d) {
    asm volatile("{\n.reg .pred p;\nsetp.ne.b32 p, %66, 0;\n"
        "wgmma.mma_async.sync.aligned.m64n128k16.f32.bf16.bf16 {%0, %1, %2, %3, %4, %5, %6, %7, %8, %9, %10, %11, %12, %13, %14, %15, %16, %17, %18, %19, %20, %21, %22, %23, %24, %25, %26, %27, %28, %29, %30, %31, %32, %33, %34, %35, %36, %37, %38, %39, %40, %41, %42, %43, %44, %45, %46, %47, %48, %49, %50, %51, %52, %53, %54, %55, %56, %57, %58, %59, %60, %61, %62, %63}, %64, %65, p, 1, 1, 0, 1;\n}\n"
        : "+f"(d[0]), "+f"(d[1]), "+f"(d[2]), "+f"(d[3]), "+f"(d[4]), "+f"(d[5]), "+f"(d[6]), "+f"(d[7]), "+f"(d[8]), "+f"(d[9]), "+f"(d[10]), "+f"(d[11]), "+f"(d[12]), "+f"(d[13]), "+f"(d[14]), "+f"(d[15]), "+f"(d[16]), "+f"(d[17]), "+f"(d[18]), "+f"(d[19]), "+f"(d[20]), "+f"(d[21]), "+f"(d[22]), "+f"(d[23]), "+f"(d[24]), "+f"(d[25]), "+f"(d[26]), "+f"(d[27]), "+f"(d[28]), "+f"(d[29]), "+f"(d[30]), "+f"(d[31]), "+f"(d[32]), "+f"(d[33]), "+f"(d[34]), "+f"(d[35]), "+f"(d[36]), "+f"(d[37]), "+f"(d[38]), "+f"(d[39]), "+f"(d[40]), "+f"(d[41]), "+f"(d[42]), "+f"(d[43]), "+f"(d[44]), "+f"(d[45]), "+f"(d[46]), "+f"(d[47]), "+f"(d[48]), "+f"(d[49]), "+f"(d[50]), "+f"(d[51]), "+f"(d[52]), "+f"(d[53]), "+f"(d[54]), "+f"(d[55]), "+f"(d[56]), "+f"(d[57]), "+f"(d[58]), "+f"(d[59]), "+f"(d[60]), "+f"(d[61]), "+f"(d[62]), "+f"(d[63])
        : "l"(da), "l"(db), "r"(scale_d));
}

__device__ __forceinline__ void wgmma_ss_n256_tb1(float (&d)[128], uint64_t da, uint64_t db, int scale_d) {
    asm volatile("{\n.reg .pred p;\nsetp.ne.b32 p, %130, 0;\n"
        "wgmma.mma_async.sync.aligned.m64n256k16.f32.bf16.bf16 {%0, %1, %2, %3, %4, %5, %6, %7, %8, %9, %10, %11, %12, %13, %14, %15, %16, %17, %18, %19, %20, %21, %22, %23, %24, %25, %26, %27, %28, %29, %30, %31, %32, %33, %34, %35, %36, %37, %38, %39, %40, %41, %42, %43, %44, %45, %46, %47, %48, %49, %50, %51, %52, %53, %54, %55, %56, %57, %58, %59, %60, %61, %62, %63, %64, %65, %66, %67, %68, %69, %70, %71, %72, %73, %74, %75, %76, %77, %78, %79, %80, %81, %82, %83, %84, %85, %86, %87, %88, %89, %90, %91, %92, %93, %94, %95, %96, %97, %98, %99, %100, %101, %102, %103, %104, %105, %106, %107, %108, %109, %110, %111, %112, %113, %114, %115, %116, %117, %118, %119, %120, %121, %122, %123, %124, %125, %126, %127}, %128, %129, p, 1, 1, 0, 1;\n}\n"
        : "+f"(d[0]), "+f"(d[1]), "+f"(d[2]), "+f"(d[3]), "+f"(d[4]), "+f"(d[5]), "+f"(d[6]), "+f"(d[7]), "+f"(d[8]), "+f"(d[9]), "+f"(d[10]), "+f"(d[11]), "+f"(d[12]), "+f"(d[13]), "+f"(d[14]), "+f"(d[15]), "+f"(d[16]), "+f"(d[17]), "+f"(d[18]), "+f"(d[19]), "+f"(d[20]), "+f"(d[21]), "+f"(d[22]), "+f"(d[23]), "+f"(d[24]), "+f"(d[25]), "+f"(d[26]), "+f"(d[27]), "+f"(d[28]), "+f"(d[29]), "+f"(d[30]), "+f"(d[31]), "+f"(d[32]), "+f"(d[33]), "+f"(d[34]), "+f"(d[35]), "+f"(d[36]), "+f"(d[37]), "+f"(d[38]), "+f"(d[39]), "+f"(d[40]), "+f"(d[41]), "+f"(d[42]), "+f"(d[43]), "+f"(d[44]), "+f"(d[45]), "+f"(d[46]), "+f"(d[47]), "+f"(d[48]), "+f"(d[49]), "+f"(d[50]), "+f"(d[51]), "+f"(d[52]), "+f"(d[53]), "+f"(d[54]), "+f"(d[55]), "+f"(d[56]), "+f"(d[57]), "+f"(d[58]), "+f"(d[59]), "+f"(d[60]), "+f"(d[61]), "+f"(d[62]), "+f"(d[63]), "+f"(d[64]), "+f"(d[65]), "+f"(d[66]), "+f"(d[67]), "+f"(d[68]), "+f"(d[69]), "+f"(d[70]), "+f"(d[71]), "+f"(d[72]), "+f"(d[73]), "+f"(d[74]), "+f"(d[75]), "+f"(d[76]), "+f"(d[77]), "+f"(d[78]), "+f"(d[79]), "+f"(d[80]), "+f"(d[81]), "+f"(d[82]), "+f"(d[83]), "+f"(d[84]), "+f"(d[85]), "+f"(d[86]), "+f"(d[87]), "+f"(d[88]), "+f"(d[89]), "+f"(d[90]), "+f"(d[91]), "+f"(d[92]), "+f"(d[93]), "+f"(d[94]), "+f"(d[95]), "+f"(d[96]), "+f"(d[97]), "+f"(d[98]), "+f"(d[99]), "+f"(d[100]), "+f"(d[101]), "+f"(d[102]), "+f"(d[103]), "+f"(d[104]), "+f"(d[105]), "+f"(d[106]), "+f"(d[107]), "+f"(d[108]), "+f"(d[109]), "+f"(d[110]), "+f"(d[111]), "+f"(d[112]), "+f"(d[113]), "+f"(d[114]), "+f"(d[115]), "+f"(d[116]), "+f"(d[117]), "+f"(d[118]), "+f"(d[119]), "+f"(d[120]), "+f"(d[121]), "+f"(d[122]), "+f"(d[123]), "+f"(d[124]), "+f"(d[125]), "+f"(d[126]), "+f"(d[127])
        : "l"(da), "l"(db), "r"(scale_d));
}

__device__ __forceinline__ void wgmma_ss_n64_tb0(float (&d)[32], uint64_t da, uint64_t db, int scale_d) {
    asm volatile("{\n.reg .pred p;\nsetp.ne.b32 p, %34, 0;\n"
        "wgmma.mma_async.sync.aligned.m64n64k16.f32.bf16.bf16 {%0, %1, %2, %3, %4, %5, %6, %7, %8, %9, %10, %11, %12, %13, %14, %15, %16, %17, %18, %19, %20, %21, %22, %23, %24, %25, %26, %27, %28, %29, %30, %31}, %32, %33, p, 1, 1, 0, 0;\n}\n"
        : "+f"(d[0]), "+f"(d[1]), "+f"(d[2]), "+f"(d[3]), "+f"(d[4]), "+f"(d[5]), "+f"(d[6]), "+f"(d[7]), "+f"(d[8]), "+f"(d[9]), "+f"(d[10]), "+f"(d[11]), "+f"(d[12]), "+f"(d[13]), "+f"(d[14]), "+f"(d[15]), "+f"(d[16]), "+f"(d[17]), "+f"(d[18]), "+f"(d[19]), "+f"(d[20]), "+f"(d[21]), "+f"(d[22]), "+f"(d[23]), "+f"(d[24]), "+f"(d[25]), "+f"(d[26]), "+f"(d[27]), "+f"(d[28]), "+f"(d[29]), "+f"(d[30]), "+f"(d[31])
        : "l"(da), "l"(db), "r"(scale_d));
}


struct Maps {
    CUtensorMap xa, xa1, wup, mqk4, mqk2, wepi, uc, x, out;
};

__device__ __forceinline__ uint32_t r1_slot_addr(uint32_t sb, int slot) { return sb + (slot < 8 ? R1 + slot * 8192 : R3 + (slot - 7) * 8192); }

__device__ __forceinline__ void r1_issue(const Maps& mp, uint32_t sb, int n, int b) {
    int slot = (n + 8) % 10;
    uint32_t dst = r1_slot_addr(sb, slot), bar = sb + B_R1 + slot * 8;
    if (n < 192) {
        mbar_expect_tx(bar, 8192);
        if (n < 64) tma3(dst, &mp.wup, 0, 16 * (n >> 1), 8 + 4 * (n & 1), bar);
        else if (n < 96) tma3(dst, &mp.mqk4, 0, 16 * (n - 64), 4, bar);
        else if (n < 160) tma3(dst, &mp.wup, 0, 16 * ((n - 96) >> 1), 4 * (n & 1), bar);
        else tma3(dst, &mp.mqk2, 0, 32 * ((n - 160) & 15), 2 * ((n - 160) >> 4), bar);
    } else if (n < 200) {
        if (n == 192) mbar_expect_tx(sb + B_KV + 8, 65536);
        tma4(dst, &mp.xa1, 0, 0, n - 192, b, sb + B_KV + 8);
    }
}
__device__ __forceinline__ uint32_t r2_slot_addr(uint32_t sb, int slot) {
    return sb + (slot < 8 ? R1 + slot * 8192 : (slot == 10 ? R3 : (slot == 11 ? QS : R3 + (slot - 7) * 8192)));
}
__device__ __forceinline__ void r2_issue(const Maps& mp, uint32_t sb, int n) {
    if (n < 128) {
        int slot = n % 12;
        uint32_t bar = sb + B_R2 + slot * 8;
        mbar_expect_tx(bar, 8192);
        tma3(r2_slot_addr(sb, slot), &mp.wepi, 0, 16 * (n >> 1), 4 * (n & 1), bar);
    }
}

__global__ void __launch_bounds__(384, 1) main_kernel(const __grid_constant__ Maps mp, const bf16* __restrict__ dw) {
    extern __shared__ __align__(1024) uint8_t smem[];
    const uint32_t sb = smem_u32(smem);
    const int tid = threadIdx.x;
    const int b = blockIdx.x / TPB, ti = blockIdx.x % TPB;
    if (tid == 0) {
        mbar_init(sb + B_A, 1);
        for (int i = 0; i < 10; i++) mbar_init(sb + B_R1 + 8 * i, 1);
        mbar_init(sb + B_H1, 2); mbar_init(sb + B_H2, 1); mbar_init(sb + B_H3, 2);
        for (int i = 0; i < 3; i++) { mbar_init(sb + B_KV + 8 * i, 1); mbar_init(sb + B_P + 8 * i, 4); mbar_init(sb + B_GO + 8 * i, 1); }
        for (int i = 0; i < 12; i++) mbar_init(sb + B_R2 + 8 * i, 1);
        mbar_init(sb + B_UC, 1); mbar_init(sb + B_X, 1);
        for (int i = 0; i < 4; i++) asm volatile("st.shared.u32 [%0], 0;" ::"r"(sb + CNT + 4 * i) : "memory");
        asm volatile("fence.mbarrier_init.release.cluster;" ::: "memory");
        fence_async();
        mbar_expect_tx(sb + B_A, 65536 + 3072);
        asm volatile("cp.async.bulk.shared::cluster.global.mbarrier::complete_tx::bytes [%0], [%1], 3072, [%2];" ::"r"(sb + R3), "l"(dw), "r"(sb + B_A) : "memory");
        tma4(sb + R2, &mp.xa, 0, 62 * ti - 1, 0, b, sb + B_A);
        for (int n = 0; n < 10; n++) r1_issue(mp, sb, n, b);
    }
    __syncthreads();
    const int wg = __shfl_sync(0xffffffffu, tid >> 7, 0);
    const int lane = tid & 31, w = (tid >> 5) & 3;
    const bool el = (tid & 127) == 0;
    const uint32_t lrow = 16 * w + (lane & 7) + ((lane >> 3) & 1) * 8;
    const uint32_t loff = lrow * 128 + ((((lane >> 4) ^ lrow) & 7) << 4);
    const int r0 = 16 * w + (lane >> 2);

    if (wg == 0) {
        asm volatile("setmaxnreg.inc.sync.aligned.u32 184;");
        uint32_t q[112];
        mbar_wait(sb + B_A, 0);
        mbar_wait(sb + B_H1, 0);
        {
            float acc[128];
            fresh(acc);
#pragma unroll 1
            for (int kk = 0; kk < 32; kk++) {
                int n = 64 + kk, slot = (n + 8) % 10;
                mbar_wait(sb + B_R1 + slot * 8, (n / 10) & 1);
                if (kk == 31 && el) mbar_arrive(sb + B_H2);
                wg_fence();
                wgmma_ss_n256_tb1(acc, mkdesc(sb + R2 + (kk >> 2) * 8192 + (kk & 3) * 32, 16), mkdesc(r1_slot_addr(sb, slot), 2048), 1);
                wg_commit();
                wg_wait<1>();
                if (kk > 0 && el) r1_issue(mp, sb, n + 9, b);
            }
            wg_wait<0>();
            pin(acc);
            if (el) r1_issue(mp, sb, 105, b);
#pragma unroll
            for (int kk = 0; kk < 4; kk++)
                stsm4((sb + QS + loff) ^ (kk << 5), pack2(acc[96 + 8 * kk], acc[97 + 8 * kk]), pack2(acc[98 + 8 * kk], acc[99 + 8 * kk]),
                      pack2(acc[100 + 8 * kk], acc[101 + 8 * kk]), pack2(acc[102 + 8 * kk], acc[103 + 8 * kk]));
            fence_async();
#pragma unroll
            for (int i = 47; i >= 0; i--) q[64 + i] = pack2v(acc[2 * i], acc[2 * i + 1]);
        }
        mbar_wait(sb + B_H3, 0);
#pragma unroll
        for (int half = 0; half < 2; half++) {
            float acc[64];
            fresh(acc);
#pragma unroll 1
            for (int m = 0; m < 16; m++) {
                int n = 160 + 16 * half + m, slot = (n + 8) % 10;
                mbar_wait(sb + B_R1 + slot * 8, (n / 10) & 1);
                uint32_t sa = r1_slot_addr(sb, slot), aa = sb + R2 + (m >> 1) * 8192 + (m & 1) * 64;
                wg_fence();
                wgmma_ss_n128_tb1(acc, mkdesc(aa, 16), mkdesc(sa, 4096), 1);
                wgmma_ss_n128_tb1(acc, mkdesc(aa + 32, 16), mkdesc(sa + 2048, 4096), 1);
                wg_commit();
                wg_wait<1>();
                if (m > 0 && el) r1_issue(mp, sb, n + 9, b);
            }
            wg_wait<0>();
            pin(acc);
            if (el) r1_issue(mp, sb, 160 + 16 * half + 15 + 10, b);
            if (half == 1 && el) {
                mbar_expect_tx(sb + B_KV + 16, 65536);
                tma4(sb + R2, &mp.xa, 0, 64, 0, b, sb + B_KV + 16);
            }
#pragma unroll
            for (int i = 31; i >= 0; i--) q[32 * half + i] = pack2v(acc[2 * i], acc[2 * i + 1]);
        }
        bar_sync(1, 128);

        const float CS = 0.04419417382415922f * 1.4426950408889634f;
        float m0 = -INFINITY, m1 = -INFINITY, l0 = 0.f, l1 = 0.f;
        int s = 1, ph = 0;
#pragma unroll 1
        for (int j = 0; j < NKV; j++) {
            float S[32];
            mbar_wait(sb + B_KV + s * 8, ph);
            const uint32_t kb = sb + s * 65536;
            wg_fence();
#pragma unroll
            for (int kk = 0; kk < 28; kk++)
                wgmma_rs_n64_tb0(S, q[4 * kk], q[4 * kk + 1], q[4 * kk + 2], q[4 * kk + 3], mkdesc(kb + (kk >> 2) * 8192 + (kk & 3) * 32, 16), kk > 0);
            wg_commit();
#pragma unroll
            for (int kk = 0; kk < 4; kk++)
                wgmma_ss_n64_tb0(S, mkdesc(sb + QS + kk * 32, 16), mkdesc(kb + 7 * 8192 + kk * 32, 16), 1);
            wg_commit();
            wg_wait<1>();
            const int sp = s == 0 ? 2 : s - 1;
            if (j > 0 && el) mbar_arrive(sb + B_GO + sp * 8);
            wg_wait<0>();
            pin(S);
            if (j == NKV - 1) {
#pragma unroll
                for (int i = (T_ - 64 * (NKV - 1)) / 2; i < 32; i++) S[i] = -INFINITY;
            }
            float x0 = fmaxf(S[0], S[1]), x1 = fmaxf(S[2], S[3]);
#pragma unroll
            for (int n = 1; n < 8; n++) {
                x0 = fmaxf(x0, fmaxf(S[4 * n], S[4 * n + 1]));
                x1 = fmaxf(x1, fmaxf(S[4 * n + 2], S[4 * n + 3]));
            }
            x0 = fmaxf(x0, __shfl_xor_sync(0xffffffffu, x0, 1));
            x1 = fmaxf(x1, __shfl_xor_sync(0xffffffffu, x1, 1));
            x0 = fmaxf(x0, __shfl_xor_sync(0xffffffffu, x0, 2));
            x1 = fmaxf(x1, __shfl_xor_sync(0xffffffffu, x1, 2));
            x0 = fmaxf(x0, m0); x1 = fmaxf(x1, m1);
            const float sc0 = ex2((m0 - x0) * CS), sc1 = ex2((m1 - x1) * CS);
            m0 = x0; m1 = x1;
            const float n0 = -x0 * CS, n1 = -x1 * CS;
            float a0 = 0.f, a1 = 0.f;
            const uint32_t pb = sb + R3 + s * 8192;
#pragma unroll
            for (int kk = 0; kk < 4; kk++) {
                float p[8];
#pragma unroll
                for (int e = 0; e < 8; e++) p[e] = ex2(fmaf(S[8 * kk + e], CS, (e & 2) ? n1 : n0));
                a0 += (p[0] + p[1]) + (p[4] + p[5]);
                a1 += (p[2] + p[3]) + (p[6] + p[7]);
                stsm4((pb + loff) ^ (kk << 5), pack2(p[0], p[1]), pack2(p[2], p[3]), pack2(p[4], p[5]), pack2(p[6], p[7]));
            }
            l0 = fmaf(l0, sc0, a0); l1 = fmaf(l1, sc1, a1);
            if ((lane & 3) == 0) { sts_f32(sb + SCL + s * 256 + r0 * 4, sc0); sts_f32(sb + SCL + s * 256 + r0 * 4 + 32, sc1); }
            if (j == NKV - 1) {
                l0 += __shfl_xor_sync(0xffffffffu, l0, 1); l1 += __shfl_xor_sync(0xffffffffu, l1, 1);
                l0 += __shfl_xor_sync(0xffffffffu, l0, 2); l1 += __shfl_xor_sync(0xffffffffu, l1, 2);
                if ((lane & 3) == 0) { sts_f32(sb + LINV + r0 * 4, 1.f / l0); sts_f32(sb + LINV + r0 * 4 + 32, 1.f / l1); }
            }
            fence_async();
            __syncwarp();
            if (lane == 0) mbar_arrive(sb + B_P + s * 8);
            if (j == NKV - 1 && el) mbar_arrive(sb + B_GO + s * 8);
            if (++s == 3) s = 0;
            if (s == 1) ph ^= 1;
        }
    } else {
        asm volatile("setmaxnreg.dec.sync.aligned.u32 160;");
        const int h = wg - 1;
        float acc[128];
        mbar_wait(sb + B_A, 0);
#pragma unroll 1
        for (int pass = 0; pass < 2; pass++) {
            if (pass == 1) mbar_wait(sb + B_H2, 0);
            fresh(acc);
            const int nb = pass * 96 + h;
#pragma unroll 1
            for (int kk = 0; kk < 32; kk++) {
                int n = nb + 2 * kk, slot = (n + 8) % 10;
                mbar_wait(sb + B_R1 + slot * 8, (n / 10) & 1);
                if (kk == 31 && el) mbar_arrive(sb + (pass ? B_H3 : B_H1));
                wg_fence();
                wgmma_ss_n256_tb1(acc, mkdesc(sb + R2 + (kk >> 2) * 8192 + (kk & 3) * 32, 16), mkdesc(r1_slot_addr(sb, slot), 2048), 1);
                wg_commit();
                wg_wait<1>();
                if (kk > 0 && el) r1_issue(mp, sb, n + 8, b);
            }
            wg_wait<0>();
            pin(acc);
            if (el) r1_issue(mp, sb, nb + 62 + 10, b);
            if (pass == 0) {
#pragma unroll
                for (int i = 0; i < 128; i++) acc[i] = gelu(acc[i]);
                float s0 = 0.f, s1 = 0.f;
#pragma unroll
                for (int n = 0; n < 32; n++) { s0 += acc[4 * n] + acc[4 * n + 1]; s1 += acc[4 * n + 2] + acc[4 * n + 3]; }
                s0 += __shfl_xor_sync(0xffffffffu, s0, 1); s1 += __shfl_xor_sync(0xffffffffu, s1, 1);
                s0 += __shfl_xor_sync(0xffffffffu, s0, 2); s1 += __shfl_xor_sync(0xffffffffu, s1, 2);
                s0 *= (1.f / 256.f); s1 *= (1.f / 256.f);
                float v0 = 0.f, v1 = 0.f;
#pragma unroll
                for (int n = 0; n < 32; n++) {
                    float d0 = acc[4 * n] - s0, d1 = acc[4 * n + 1] - s0, d2 = acc[4 * n + 2] - s1, d3 = acc[4 * n + 3] - s1;
                    v0 = fmaf(d0, d0, v0); v0 = fmaf(d1, d1, v0); v1 = fmaf(d2, d2, v1); v1 = fmaf(d3, d3, v1);
                }
                v0 += __shfl_xor_sync(0xffffffffu, v0, 1); v1 += __shfl_xor_sync(0xffffffffu, v1, 1);
                v0 += __shfl_xor_sync(0xffffffffu, v0, 2); v1 += __shfl_xor_sync(0xffffffffu, v1, 2);
                if ((lane & 3) == 0) {
                    uint32_t a = sb + STAT + h * 512 + r0 * 8;
                    sts_f32(a, s0); sts_f32(a + 4, v0); sts_f32(a + 64, s1); sts_f32(a + 68, v1);
                }
                bar_sync(2, 256);
                {
                    uint32_t a = sb + STAT + (h ^ 1) * 512 + r0 * 8;
                    float t0 = lds_f32(a), u0 = lds_f32(a + 4), t1 = lds_f32(a + 64), u1 = lds_f32(a + 68);
                    v0 = (v0 + u0 + (s0 - t0) * (s0 - t0) * 128.f) * (1.f / 512.f);
                    v1 = (v1 + u1 + (s1 - t1) * (s1 - t1) * 128.f) * (1.f / 512.f);
                    s0 = 0.5f * (s0 + t0); s1 = 0.5f * (s1 + t1);
                }
                v0 = rsqrtf(v0 + 1e-5f); v1 = rsqrtf(v1 + 1e-5f);
                s0 = -s0 * v0; s1 = -s1 * v1;
#pragma unroll
                for (int p = 0; p < 16; p++)
                    stsm4(((sb + R0 + h * 32768 + loff) ^ ((p & 3) << 5)) + (p >> 2) * 8192,
                          pack2(fmaf(acc[8 * p], v0, s0), fmaf(acc[8 * p + 1], v0, s0)), pack2(fmaf(acc[8 * p + 2], v1, s1), fmaf(acc[8 * p + 3], v1, s1)),
                          pack2(fmaf(acc[8 * p + 4], v0, s0), fmaf(acc[8 * p + 5], v0, s0)), pack2(fmaf(acc[8 * p + 6], v1, s1), fmaf(acc[8 * p + 7], v1, s1)));
            } else {
                uint32_t u2[64];
#pragma unroll
                for (int i = 0; i < 64; i++) u2[i] = pack2(gelu(acc[2 * i]), gelu(acc[2 * i + 1]));
                bar_sync(3 + h, 128);
                const uint32_t rm = lrow == 0 ? 0 : lrow - 1, rp = lrow == 63 ? 63 : lrow + 1;
                const uint32_t offm = rm * 128 + ((((lane >> 4) ^ rm) & 7) << 4), offp = rp * 128 + ((((lane >> 4) ^ rp) & 7) << 4);
                const uint32_t dwa = sb + R3 + 512 * h + (lane >> 3) * 16;
                uint4* ucp = reinterpret_cast<uint4*>(g_uc + ((size_t)blockIdx.x * 64 + r0) * D_ + 256 * h + 8 * (lane & 3));
#pragma unroll
                for (int m = 0; m < 8; m++) {
                    uint32_t o[8], d0[4], d1[4], d2[4];
                    ldsm4(dwa + 64 * m, d0);
                    ldsm4(dwa + 64 * m + 1024, d1);
                    ldsm4(dwa + 64 * m + 2048, d2);
#pragma unroll
                    for (int pp = 0; pp < 2; pp++) {
                        const int p = 2 * m + pp;
                        const uint32_t cb = sb + R0 + (4 * h + (p >> 2)) * 8192;
                        uint32_t gm[4], gc[4], gp[4];
                        ldsm4(cb + (offm ^ ((p & 3) << 5)), gm);
                        ldsm4(cb + (loff ^ ((p & 3) << 5)), gc);
                        ldsm4(cb + (offp ^ ((p & 3) << 5)), gp);
#pragma unroll
                        for (int c = 0; c < 2; c++) {
#pragma unroll
                            for (int rr = 0; rr < 2; rr++) {
                                const int e = 2 * c + rr;
                                uint32_t cv = bfma2(gp[e], d2[2 * pp + c], bfma2(gc[e], d1[2 * pp + c], bmul2(gm[e], d0[2 * pp + c])));
                                o[4 * rr + 2 * pp + c] = bmul2(u2[4 * p + e], cv);
                            }
                        }
                    }
                    ucp[4 * m] = make_uint4(o[0], o[1], o[2], o[3]);
                    ucp[4 * m + 8 * (D_ / 8)] = make_uint4(o[4], o[5], o[6], o[7]);
                }
                fence_async_g();
                bar_sync(2, 256);
                if (tid == 128) {
                    mbar_expect_tx(sb + B_KV, 65536);
                    tma4(sb + R0, &mp.xa, 0, 128, 0, b, sb + B_KV);
                }
            }
        }
        int s = 1, ph = 0;
        fresh(acc);
#pragma unroll 1
        for (int j = 0; j < NKV; j++) {
            mbar_wait(sb + B_P + s * 8, ph);
            if (j > 0) {
                const float sc0 = lds_f32(sb + SCL + s * 256 + r0 * 4), sc1 = lds_f32(sb + SCL + s * 256 + r0 * 4 + 32);
                if (__any_sync(0xffffffffu, sc0 != 1.f || sc1 != 1.f)) {
#pragma unroll
                    for (int n = 0; n < 32; n++) { acc[4 * n] *= sc0; acc[4 * n + 1] *= sc0; acc[4 * n + 2] *= sc1; acc[4 * n + 3] *= sc1; }
                }
            }
            mbar_wait(sb + B_KV + s * 8, ph);
            mbar_wait(sb + B_GO + s * 8, ph);
            const uint32_t vb = sb + s * 65536 + h * 32768, pb = sb + R3 + s * 8192;
            pin(acc);
            wg_fence();
#pragma unroll
            for (int kk = 0; kk < 4; kk++) wgmma_ss_n256_tb1(acc, mkdesc(pb + kk * 32, 16), mkdesc(vb + kk * 2048, 8192), 1);
            wg_commit();
            wg_wait<0>();
            pin(acc);
            if (el) {
                if (atom_inc_s(sb + CNT + 4 * s) & 1) {
                    if (j + 3 < NKV) {
                        mbar_expect_tx(sb + B_KV + s * 8, 65536);
                        tma4(sb + s * 65536, &mp.xa, 0, 64 * (j + 3), 0, b, sb + B_KV + s * 8);
                    } else if (j == NKV - 3) {
                        for (int n = 0; n < 9; n++) r2_issue(mp, sb, n);
                    } else if (j == NKV - 2) {
                        mbar_expect_tx(sb + B_UC, 65536);
                        tma3(sb + R2, &mp.uc, 0, 64 * blockIdx.x, 0, sb + B_UC);
                        r2_issue(mp, sb, 9);
                    } else {
                        r2_issue(mp, sb, 10);
                        r2_issue(mp, sb, 11);
                    }
                }
            }
            if (++s == 3) s = 0;
            if (s == 1) ph ^= 1;
        }
        {
            const float i0 = lds_f32(sb + LINV + r0 * 4), i1 = lds_f32(sb + LINV + r0 * 4 + 32);
#pragma unroll
            for (int p = 0; p < 16; p++)
                stsm4(((sb + R0 + h * 32768 + loff) ^ ((p & 3) << 5)) + (p >> 2) * 8192,
                      pack2(acc[8 * p] * i0, acc[8 * p + 1] * i0), pack2(acc[8 * p + 2] * i1, acc[8 * p + 3] * i1),
                      pack2(acc[8 * p + 4] * i0, acc[8 * p + 5] * i0), pack2(acc[8 * p + 6] * i1, acc[8 * p + 7] * i1));
        }
        fence_async();
        bar_sync(2, 256);
        fresh(acc);
#pragma unroll 1
        for (int kk = 0; kk < 64; kk++) {
            const int n = 2 * kk + h, slot = n % 12;
            if (kk == 32) mbar_wait(sb + B_UC, 0);
            mbar_wait(sb + B_R2 + slot * 8, (n / 12) & 1);
            wg_fence();
            wgmma_ss_n256_tb1(acc, mkdesc(sb + (kk < 32 ? R0 : R2) + ((kk >> 2) & 7) * 8192 + (kk & 3) * 32, 16), mkdesc(r2_slot_addr(sb, slot), 2048), 1);
            wg_commit();
            wg_wait<1>();
            if (el) {
                if (kk > 0) r2_issue(mp, sb, n + 10);
                if (kk == 32 && (atom_inc_s(sb + CNT + 12) & 1)) {
                    mbar_expect_tx(sb + B_X, 65536);
                    tma4(sb + R0, &mp.x, 0, 62 * ti, 0, b, sb + B_X);
                }
            }
        }
        wg_wait<0>();
        pin(acc);
        mbar_wait(sb + B_X, 0);
        {
            const uint32_t sr = (lrow + 63) & 63;
            const uint32_t xoff = sr * 128 + ((((lane >> 4) ^ sr) & 7) << 4);
#pragma unroll
            for (int p = 0; p < 16; p++) {
                const uint32_t a = ((sb + R0 + h * 32768 + xoff) ^ ((p & 3) << 5)) + (p >> 2) * 8192;
                uint32_t xv[4];
                ldsm4(a, xv);
#pragma unroll
                for (int e = 0; e < 4; e++)
                    xv[e] = pack2(acc[8 * p + 2 * e] + __uint_as_float(xv[e] << 16), acc[8 * p + 2 * e + 1] + __uint_as_float(xv[e] & 0xffff0000u));
                stsm4(a, xv[0], xv[1], xv[2], xv[3]);
            }
        }
        fence_async();
        bar_sync(3 + h, 128);
        if (el) {
            for (int c = 0; c < 4; c++) tma4_store(&mp.out, sb + R0 + (4 * h + c) * 8192, 0, 62 * ti, 4 * h + c, b);
            asm volatile("cp.async.bulk.commit_group;" ::: "memory");
            asm volatile("cp.async.bulk.wait_group.read 0;" ::: "memory");
        }
    }
}

__device__ __forceinline__ float bfr(float x) { return __bfloat162float(__float2bfloat16_rn(x)); }

__global__ void __launch_bounds__(256) ln_kernel(const bf16* __restrict__ x) {
    const int row = blockIdx.x * 8 + (threadIdx.x >> 5), lane = threadIdx.x & 31;
    const uint4* src = reinterpret_cast<const uint4*>(x + (size_t)row * D_);
    uint4 v[2] = {src[lane], src[lane + 32]};
    float f[16];
    const uint32_t* u = reinterpret_cast<const uint32_t*>(v);
#pragma unroll
    for (int i = 0; i < 8; i++) { f[2 * i] = __uint_as_float(u[i] << 16); f[2 * i + 1] = __uint_as_float(u[i] & 0xffff0000u); }
    float s = 0.f;
#pragma unroll
    for (int i = 0; i < 16; i++) s += f[i];
#pragma unroll
    for (int o = 16; o; o >>= 1) s += __shfl_xor_sync(0xffffffffu, s, o);
    s *= (1.f / D_);
    float q = 0.f;
#pragma unroll
    for (int i = 0; i < 16; i++) { float d = f[i] - s; q = fmaf(d, d, q); }
#pragma unroll
    for (int o = 16; o; o >>= 1) q += __shfl_xor_sync(0xffffffffu, q, o);
    const float m = bfr(s), var = bfr(q * (1.f / D_));
    const float rinv = 1.f / bfr(sqrtf(bfr(var + 1e-5f)));
    uint32_t o[8];
#pragma unroll
    for (int i = 0; i < 8; i++) o[i] = pack2(bfr(f[2 * i] - m) * rinv, bfr(f[2 * i + 1] - m) * rinv);
    uint4* dst = reinterpret_cast<uint4*>(g_xa + (size_t)row * D_);
    dst[lane] = make_uint4(o[0], o[1], o[2], o[3]);
    dst[lane + 32] = make_uint4(o[4], o[5], o[6], o[7]);
}

__global__ void __launch_bounds__(128) fold_kernel(const bf16* wq, const bf16* wk, const bf16* wv, const bf16* wao,
                                                   const bf16* wdn, const bf16* wm, int stage) {
    using namespace nvcuda;
    __shared__ float cs[4][16][20];
    const int z = stage == 0 ? blockIdx.z : 3;
    const bf16* A = z == 0 ? wq : z == 1 ? wv : z == 2 ? wdn : g_t1;
    const bf16* B = z == 0 ? wk : z == 1 ? wao : z == 2 ? wm + 512 * D_ : wm;
    bf16* C = z == 0 ? g_mqk : z == 1 ? g_t1 : z == 2 ? g_wepi + 512 * D_ : g_wepi;
    const int w = threadIdx.x >> 5, lane = threadIdx.x & 31;
    const int rb = blockIdx.y * 32 + (w >> 1) * 16, cb = blockIdx.x * 32 + (w & 1) * 16;
    wmma::fragment<wmma::accumulator, 16, 16, 16, float> c;
    wmma::fill_fragment(c, 0.f);
    for (int k = 0; k < D_; k += 16) {
        wmma::fragment<wmma::matrix_a, 16, 16, 16, bf16, wmma::row_major> a;
        wmma::load_matrix_sync(a, A + rb * D_ + k, D_);
        if (z == 0) {
            wmma::fragment<wmma::matrix_b, 16, 16, 16, bf16, wmma::col_major> bb;
            wmma::load_matrix_sync(bb, B + cb * D_ + k, D_);
            wmma::mma_sync(c, a, bb, c);
        } else {
            wmma::fragment<wmma::matrix_b, 16, 16, 16, bf16, wmma::row_major> bb;
            wmma::load_matrix_sync(bb, B + k * D_ + cb, D_);
            wmma::mma_sync(c, a, bb, c);
        }
    }
    wmma::store_matrix_sync(&cs[w][0][0], c, 20, wmma::mem_row_major);
    __syncwarp();
    for (int i = lane; i < 256; i += 32) {
        int r = rb + (i >> 4), cc = cb + (i & 15);
        if (z == 2) r = (r & ~31) | (((r >> 1) & 3) << 3) | (((r >> 3) & 3) << 1) | (r & 1);
        C[r * D_ + cc] = __float2bfloat16_rn(cs[w][i >> 4][i & 15]);
    }
}

typedef CUresult (*PFN_enc)(CUtensorMap*, CUtensorMapDataType, cuuint32_t, void*, const cuuint64_t*, const cuuint64_t*,
                            const cuuint32_t*, const cuuint32_t*, CUtensorMapInterleave, CUtensorMapSwizzle,
                            CUtensorMapL2promotion, CUtensorMapFloatOOBfill);

static void enc(PFN_enc f, CUtensorMap* m, void* base, int rank, const cuuint64_t* dims, const cuuint64_t* strides, const cuuint32_t* box) {
    cuuint32_t es[5] = {1, 1, 1, 1, 1};
    f(m, CU_TENSOR_MAP_DATA_TYPE_BFLOAT16, rank, base, dims, strides, box, es, CU_TENSOR_MAP_INTERLEAVE_NONE,
      CU_TENSOR_MAP_SWIZZLE_128B, CU_TENSOR_MAP_L2_PROMOTION_L2_256B, CU_TENSOR_MAP_FLOAT_OOB_FILL_NONE);
}
static void enc_act(PFN_enc f, CUtensorMap* m, void* base, int rows, int chunks) {
    cuuint64_t dims[4] = {64, (cuuint64_t)T_, 8, (cuuint64_t)NB_};
    cuuint64_t st[3] = {1024, 128, (cuuint64_t)T_ * 1024};
    cuuint32_t box[4] = {64, (cuuint32_t)rows, (cuuint32_t)chunks, 1};
    enc(f, m, base, 4, dims, st, box);
}
static void enc_w(PFN_enc f, CUtensorMap* m, void* base, int krows, int ncols, int bk, int bc) {
    cuuint64_t dims[3] = {64, (cuuint64_t)krows, (cuuint64_t)(ncols / 64)};
    cuuint64_t st[2] = {(cuuint64_t)ncols * 2, 128};
    cuuint32_t box[3] = {64, (cuuint32_t)bk, (cuuint32_t)bc};
    enc(f, m, base, 3, dims, st, box);
}

extern "C" void kernel_launch(void* const* d_in, const int* in_sizes, int n_in, void* d_out, int out_size) {
    const bf16* x = (const bf16*)d_in[0];
    static PFN_enc fenc = nullptr;
    static void *p_xa, *p_mqk, *p_wepi, *p_uc;
    if (!fenc) {
        void* fn = nullptr;
        cudaDriverEntryPointQueryResult qr;
        cudaGetDriverEntryPoint("cuTensorMapEncodeTiled", &fn, cudaEnableDefault, &qr);
        fenc = (PFN_enc)fn;
        cudaGetSymbolAddress(&p_xa, g_xa);
        cudaGetSymbolAddress(&p_mqk, g_mqk);
        cudaGetSymbolAddress(&p_wepi, g_wepi);
        cudaGetSymbolAddress(&p_uc, g_uc);
        cudaFuncSetAttribute(main_kernel, cudaFuncAttributeMaxDynamicSharedMemorySize, SMEM_BYTES);
    }
    Maps mp;
    enc_act(fenc, &mp.xa, p_xa, 64, 8);
    enc_act(fenc, &mp.xa1, p_xa, 64, 1);
    enc_act(fenc, &mp.x, (void*)x, 64, 8);
    enc_act(fenc, &mp.out, d_out, 62, 1);
    enc_w(fenc, &mp.wup, d_in[5], 512, 1024, 16, 4);
    enc_w(fenc, &mp.mqk4, p_mqk, 512, 512, 16, 4);
    enc_w(fenc, &mp.mqk2, p_mqk, 512, 512, 32, 2);
    enc_w(fenc, &mp.wepi, p_wepi, 1024, 512, 16, 4);
    enc_w(fenc, &mp.uc, p_uc, NCTA * 64, 512, 64, 8);
    cudaStream_t st = cudaStreamPerThread;
    ln_kernel<<<NB_ * T_ / 8, 256, 0, st>>>(x);
    fold_kernel<<<dim3(16, 16, 3), 128, 0, st>>>((const bf16*)d_in[1], (const bf16*)d_in[2], (const bf16*)d_in[3], (const bf16*)d_in[4],
                                                 (const bf16*)d_in[7], (const bf16*)d_in[8], 0);
    fold_kernel<<<dim3(16, 16, 1), 128, 0, st>>>((const bf16*)d_in[1], (const bf16*)d_in[2], (const bf16*)d_in[3], (const bf16*)d_in[4],
                                                 (const bf16*)d_in[7], (const bf16*)d_in[8], 1);
    main_kernel<<<NCTA, 384, SMEM_BYTES, st>>>(mp, (const bf16*)d_in[6]);
}
```

```cpp
#include <cuda_runtime.h>
#include <cuda_bf16.h>
#include <cuda.h>
#include <mma.h>
#include <stdint.h>

typedef __nv_bfloat16 bf16;

constexpr int T_ = 4000, D_ = 512, NB_ = 2;
constexpr int TPB = 65;
constexpr int NCTA = TPB * NB_;
constexpr int NKV = 63;

__device__ __align__(1024) bf16 g_xa[NB_ * T_ * D_];
__device__ __align__(1024) bf16 g_mqk[D_ * D_];
__device__ __align__(1024) bf16 g_t1[D_ * D_];
__device__ __align__(1024) bf16 g_wepi[2 * D_ * D_];
__device__ __align__(1024) bf16 g_uc[NCTA * 64 * D_];

#define PT(i)
#define PL(j, q)
#define PDUMP()

constexpr uint32_t R0 = 0, R1 = 65536, R2 = 131072, R3 = 196608, QS = 221184, MISC = 229376;
constexpr uint32_t AT = 147456, DWS = R3 + 16384, UCT = 163840;
constexpr uint32_t SMEM_BYTES = 232448;
constexpr uint32_t B_A = MISC, B_R1 = MISC + 8, B_H1 = MISC + 88, B_H2 = MISC + 96, B_H3 = MISC + 104,
                   B_KV = MISC + 112, B_P = MISC + 136, B_GO = MISC + 160, B_R2 = MISC + 184, B_UC = MISC + 280,
                   B_X = MISC + 288, CNT = MISC + 296  , SCL = MISC + 512  ,
                   LINV = MISC + 1280  , STAT = MISC + 1536  ;

__device__ __forceinline__ uint32_t smem_u32(const void* p) { return (uint32_t)__cvta_generic_to_shared(p); }
__device__ __forceinline__ void wg_fence() { asm volatile("wgmma.fence.sync.aligned;" ::: "memory"); }
__device__ __forceinline__ void wg_commit() { asm volatile("wgmma.commit_group.sync.aligned;" ::: "memory"); }
template <int N> __device__ __forceinline__ void wg_wait() { asm volatile("wgmma.wait_group.sync.aligned %0;" ::"n"(N) : "memory"); }
__device__ __forceinline__ uint64_t dsc(uint32_t sd, uint32_t off, uint32_t lbo) {
    uint32_t lo = sd + (off >> 4) + ((lbo >> 4) << 16);
    uint64_t d;
    asm("mov.b64 %0, {%1, %2};" : "=l"(d) : "r"(lo), "r"((1024u >> 4) | (1u << 30)));
    return d;
}
__device__ __forceinline__ bool elect1() {
    uint32_t p;
    asm volatile("{\n.reg .pred p;\nelect.sync _|p, 0xffffffff;\nselp.u32 %0, 1, 0, p;\n}\n" : "=r"(p));
    return p != 0;
}
__device__ __forceinline__ void mbar_init(uint32_t bar, int cnt) { asm volatile("mbarrier.init.shared::cta.b64 [%0], %1;" ::"r"(bar), "r"(cnt) : "memory"); }
__device__ __forceinline__ void mbar_expect_tx(uint32_t bar, uint32_t bytes) { asm volatile("mbarrier.arrive.expect_tx.shared::cta.b64 _, [%0], %1;" ::"r"(bar), "r"(bytes) : "memory"); }
__device__ __forceinline__ void mbar_arrive(uint32_t bar) { asm volatile("mbarrier.arrive.shared::cta.b64 _, [%0];" ::"r"(bar) : "memory"); }
__device__ __forceinline__ void mbar_wait(uint32_t bar, uint32_t parity) {
    uint32_t ok;
#pragma unroll 1
    for (uint32_t it = 0;; ++it) {
        asm volatile("{\n.reg .pred p;\nmbarrier.try_wait.parity.shared::cta.b64 p, [%1], %2;\nselp.u32 %0, 1, 0, p;\n}\n" : "=r"(ok) : "r"(bar), "r"(parity) : "memory");
        if (ok) break;
        if (it > (1u << 20)) __trap();
    }
}
__device__ __forceinline__ void fence_async() { asm volatile("fence.proxy.async.shared::cta;" ::: "memory"); }
__device__ __forceinline__ void fence_async_g() { asm volatile("fence.proxy.async.global;" ::: "memory"); }
__device__ __forceinline__ void bar_sync(int id, int n) { asm volatile("bar.sync %0, %1;" ::"r"(id), "r"(n) : "memory"); }
__device__ __forceinline__ void tma3(uint32_t dst, const CUtensorMap* tm, int c0, int c1, int c2, uint32_t bar) {
    asm volatile("cp.async.bulk.tensor.3d.shared::cluster.global.mbarrier::complete_tx::bytes [%0], [%1, {%3, %4, %5}], [%2];"
                 ::"r"(dst), "l"(tm), "r"(bar), "r"(c0), "r"(c1), "r"(c2) : "memory");
}
__device__ __forceinline__ void tma4(uint32_t dst, const CUtensorMap* tm, int c0, int c1, int c2, int c3, uint32_t bar) {
    asm volatile("cp.async.bulk.tensor.4d.shared::cluster.global.mbarrier::complete_tx::bytes [%0], [%1, {%3, %4, %5, %6}], [%2];"
                 ::"r"(dst), "l"(tm), "r"(bar), "r"(c0), "r"(c1), "r"(c2), "r"(c3) : "memory");
}
__device__ __forceinline__ void tma4_store(const CUtensorMap* tm, uint32_t src, int c0, int c1, int c2, int c3) {
    asm volatile("cp.async.bulk.tensor.4d.global.shared::cta.bulk_group [%0, {%2, %3, %4, %5}], [%1];"
                 ::"l"(tm), "r"(src), "r"(c0), "r"(c1), "r"(c2), "r"(c3) : "memory");
}
__device__ __forceinline__ void stsm4(uint32_t addr, uint32_t a, uint32_t b, uint32_t c, uint32_t d) {
    asm volatile("stmatrix.sync.aligned.m8n8.x4.shared.b16 [%0], {%1, %2, %3, %4};" ::"r"(addr), "r"(a), "r"(b), "r"(c), "r"(d) : "memory");
}
__device__ __forceinline__ void ldsm4(uint32_t addr, uint32_t (&r)[4]) {
    asm volatile("ldmatrix.sync.aligned.m8n8.x4.shared.b16 {%0, %1, %2, %3}, [%4];" : "=r"(r[0]), "=r"(r[1]), "=r"(r[2]), "=r"(r[3]) : "r"(addr) : "memory");
}
__device__ __forceinline__ void ldsm2(uint32_t addr, uint32_t (&r)[2]) {
    asm volatile("ldmatrix.sync.aligned.m8n8.x2.shared.b16 {%0, %1}, [%2];" : "=r"(r[0]), "=r"(r[1]) : "r"(addr) : "memory");
}
__device__ __forceinline__ void stg4(void* p, uint32_t a, uint32_t b, uint32_t c, uint32_t d) {
    asm volatile("st.global.v4.u32 [%0], {%1, %2, %3, %4};" ::"l"(p), "r"(a), "r"(b), "r"(c), "r"(d) : "memory");
}
__device__ __forceinline__ uint32_t pack2(float lo, float hi) {
    uint32_t r;
    asm("cvt.rn.bf16x2.f32 %0, %1, %2;" : "=r"(r) : "f"(hi), "f"(lo));
    return r;
}
__device__ __forceinline__ uint32_t pack2v(float lo, float hi) {
    uint32_t r;
    asm volatile("cvt.rn.bf16x2.f32 %0, %1, %2;" : "=r"(r) : "f"(hi), "f"(lo));
    return r;
}
__device__ __forceinline__ uint32_t bmul2(uint32_t a, uint32_t b) { uint32_t r; asm("mul.rn.bf16x2 %0, %1, %2;" : "=r"(r) : "r"(a), "r"(b)); return r; }
__device__ __forceinline__ uint32_t bfma2(uint32_t a, uint32_t b, uint32_t c) { uint32_t r; asm("fma.rn.bf16x2 %0, %1, %2, %3;" : "=r"(r) : "r"(a), "r"(b), "r"(c)); return r; }
__device__ __forceinline__ float ex2(float x) { float r; asm("ex2.approx.ftz.f32 %0, %1;" : "=f"(r) : "f"(x)); return r; }
__device__ __forceinline__ float gelu(float x) {
    float t = fmaf(x * x, 0.044715f * 0.7978845608028654f, 0.7978845608028654f), th;
    asm("tanh.approx.f32 %0, %1;" : "=f"(th) : "f"(x * t));
    float hx = 0.5f * x;
    return fmaf(hx, th, hx);
}
__device__ __forceinline__ uint32_t ldg_v(const uint32_t* p) { uint32_t v; asm volatile("ld.global.nc.u32 %0, [%1];" : "=r"(v) : "l"(p)); return v; }
__device__ __forceinline__ float lds_f32(uint32_t a) { float v; asm volatile("ld.shared.f32 %0, [%1];" : "=f"(v) : "r"(a) : "memory"); return v; }
__device__ __forceinline__ void sts_f32(uint32_t a, float v) { asm volatile("st.shared.f32 [%0], %1;" ::"r"(a), "f"(v) : "memory"); }
__device__ __forceinline__ uint32_t atom_inc_s(uint32_t a) { uint32_t v; asm volatile("atom.relaxed.cta.shared.add.u32 %0, [%1], 1;" : "=r"(v) : "r"(a) : "memory"); return v; }
template <int N> __device__ __forceinline__ void pin(float (&a)[N]) {
#pragma unroll
    for (int i = 0; i < N; i++) asm volatile("" : "+f"(a[i])::"memory");
}

template <int N> __device__ __forceinline__ void fresh(float (&a)[N]) {
#pragma unroll
    for (int i = 0; i < N; i++) a[i] = 0.f;
    pin(a);
}

__device__ __forceinline__ void wgmma_rs_n64_tb0(float (&d)[32], uint32_t a0, uint32_t a1, uint32_t a2, uint32_t a3, uint64_t db, int scale_d) {
    asm volatile("{\n.reg .pred p;\nsetp.ne.b32 p, %37, 0;\n"
        "wgmma.mma_async.sync.aligned.m64n64k16.f32.bf16.bf16 {%0, %1, %2, %3, %4, %5, %6, %7, %8, %9, %10, %11, %12, %13, %14, %15, %16, %17, %18, %19, %20, %21, %22, %23, %24, %25, %26, %27, %28, %29, %30, %31}, {%32, %33, %34, %35}, %36, p, 1, 1, 0;\n}\n"
        : "+f"(d[0]), "+f"(d[1]), "+f"(d[2]), "+f"(d[3]), "+f"(d[4]), "+f"(d[5]), "+f"(d[6]), "+f"(d[7]), "+f"(d[8]), "+f"(d[9]), "+f"(d[10]), "+f"(d[11]), "+f"(d[12]), "+f"(d[13]), "+f"(d[14]), "+f"(d[15]), "+f"(d[16]), "+f"(d[17]), "+f"(d[18]), "+f"(d[19]), "+f"(d[20]), "+f"(d[21]), "+f"(d[22]), "+f"(d[23]), "+f"(d[24]), "+f"(d[25]), "+f"(d[26]), "+f"(d[27]), "+f"(d[28]), "+f"(d[29]), "+f"(d[30]), "+f"(d[31])
        : "r"(a0), "r"(a1), "r"(a2), "r"(a3), "l"(db), "r"(scale_d));
}

__device__ __forceinline__ void wgmma_ss_n128_tb1(float (&d)[64], uint64_t da, uint64_t db, int scale_d) {
    asm volatile("{\n.reg .pred p;\nsetp.ne.b32 p, %66, 0;\n"
        "wgmma.mma_async.sync.aligned.m64n128k16.f32.bf16.bf16 {%0, %1, %2, %3, %4, %5, %6, %7, %8, %9, %10, %11, %12, %13, %14, %15, %16, %17, %18, %19, %20, %21, %22, %23, %24, %25, %26, %27, %28, %29, %30, %31, %32, %33, %34, %35, %36, %37, %38, %39, %40, %41, %42, %43, %44, %45, %46, %47, %48, %49, %50, %51, %52, %53, %54, %55, %56, %57, %58, %59, %60, %61, %62, %63}, %64, %65, p, 1, 1, 0, 1;\n}\n"
        : "+f"(d[0]), "+f"(d[1]), "+f"(d[2]), "+f"(d[3]), "+f"(d[4]), "+f"(d[5]), "+f"(d[6]), "+f"(d[7]), "+f"(d[8]), "+f"(d[9]), "+f"(d[10]), "+f"(d[11]), "+f"(d[12]), "+f"(d[13]), "+f"(d[14]), "+f"(d[15]), "+f"(d[16]), "+f"(d[17]), "+f"(d[18]), "+f"(d[19]), "+f"(d[20]), "+f"(d[21]), "+f"(d[22]), "+f"(d[23]), "+f"(d[24]), "+f"(d[25]), "+f"(d[26]), "+f"(d[27]), "+f"(d[28]), "+f"(d[29]), "+f"(d[30]), "+f"(d[31]), "+f"(d[32]), "+f"(d[33]), "+f"(d[34]), "+f"(d[35]), "+f"(d[36]), "+f"(d[37]), "+f"(d[38]), "+f"(d[39]), "+f"(d[40]), "+f"(d[41]), "+f"(d[42]), "+f"(d[43]), "+f"(d[44]), "+f"(d[45]), "+f"(d[46]), "+f"(d[47]), "+f"(d[48]), "+f"(d[49]), "+f"(d[50]), "+f"(d[51]), "+f"(d[52]), "+f"(d[53]), "+f"(d[54]), "+f"(d[55]), "+f"(d[56]), "+f"(d[57]), "+f"(d[58]), "+f"(d[59]), "+f"(d[60]), "+f"(d[61]), "+f"(d[62]), "+f"(d[63])
        : "l"(da), "l"(db), "r"(scale_d));
}

__device__ __forceinline__ void wgmma_ss_n256_tb1(float (&d)[128], uint64_t da, uint64_t db, int scale_d) {
    asm volatile("{\n.reg .pred p;\nsetp.ne.b32 p, %130, 0;\n"
        "wgmma.mma_async.sync.aligned.m64n256k16.f32.bf16.bf16 {%0, %1, %2, %3, %4, %5, %6, %7, %8, %9, %10, %11, %12, %13, %14, %15, %16, %17, %18, %19, %20, %21, %22, %23, %24, %25, %26, %27, %28, %29, %30, %31, %32, %33, %34, %35, %36, %37, %38, %39, %40, %41, %42, %43, %44, %45, %46, %47, %48, %49, %50, %51, %52, %53, %54, %55, %56, %57, %58, %59, %60, %61, %62, %63, %64, %65, %66, %67, %68, %69, %70, %71, %72, %73, %74, %75, %76, %77, %78, %79, %80, %81, %82, %83, %84, %85, %86, %87, %88, %89, %90, %91, %92, %93, %94, %95, %96, %97, %98, %99, %100, %101, %102, %103, %104, %105, %106, %107, %108, %109, %110, %111, %112, %113, %114, %115, %116, %117, %118, %119, %120, %121, %122, %123, %124, %125, %126, %127}, %128, %129, p, 1, 1, 0, 1;\n}\n"
        : "+f"(d[0]), "+f"(d[1]), "+f"(d[2]), "+f"(d[3]), "+f"(d[4]), "+f"(d[5]), "+f"(d[6]), "+f"(d[7]), "+f"(d[8]), "+f"(d[9]), "+f"(d[10]), "+f"(d[11]), "+f"(d[12]), "+f"(d[13]), "+f"(d[14]), "+f"(d[15]), "+f"(d[16]), "+f"(d[17]), "+f"(d[18]), "+f"(d[19]), "+f"(d[20]), "+f"(d[21]), "+f"(d[22]), "+f"(d[23]), "+f"(d[24]), "+f"(d[25]), "+f"(d[26]), "+f"(d[27]), "+f"(d[28]), "+f"(d[29]), "+f"(d[30]), "+f"(d[31]), "+f"(d[32]), "+f"(d[33]), "+f"(d[34]), "+f"(d[35]), "+f"(d[36]), "+f"(d[37]), "+f"(d[38]), "+f"(d[39]), "+f"(d[40]), "+f"(d[41]), "+f"(d[42]), "+f"(d[43]), "+f"(d[44]), "+f"(d[45]), "+f"(d[46]), "+f"(d[47]), "+f"(d[48]), "+f"(d[49]), "+f"(d[50]), "+f"(d[51]), "+f"(d[52]), "+f"(d[53]), "+f"(d[54]), "+f"(d[55]), "+f"(d[56]), "+f"(d[57]), "+f"(d[58]), "+f"(d[59]), "+f"(d[60]), "+f"(d[61]), "+f"(d[62]), "+f"(d[63]), "+f"(d[64]), "+f"(d[65]), "+f"(d[66]), "+f"(d[67]), "+f"(d[68]), "+f"(d[69]), "+f"(d[70]), "+f"(d[71]), "+f"(d[72]), "+f"(d[73]), "+f"(d[74]), "+f"(d[75]), "+f"(d[76]), "+f"(d[77]), "+f"(d[78]), "+f"(d[79]), "+f"(d[80]), "+f"(d[81]), "+f"(d[82]), "+f"(d[83]), "+f"(d[84]), "+f"(d[85]), "+f"(d[86]), "+f"(d[87]), "+f"(d[88]), "+f"(d[89]), "+f"(d[90]), "+f"(d[91]), "+f"(d[92]), "+f"(d[93]), "+f"(d[94]), "+f"(d[95]), "+f"(d[96]), "+f"(d[97]), "+f"(d[98]), "+f"(d[99]), "+f"(d[100]), "+f"(d[101]), "+f"(d[102]), "+f"(d[103]), "+f"(d[104]), "+f"(d[105]), "+f"(d[106]), "+f"(d[107]), "+f"(d[108]), "+f"(d[109]), "+f"(d[110]), "+f"(d[111]), "+f"(d[112]), "+f"(d[113]), "+f"(d[114]), "+f"(d[115]), "+f"(d[116]), "+f"(d[117]), "+f"(d[118]), "+f"(d[119]), "+f"(d[120]), "+f"(d[121]), "+f"(d[122]), "+f"(d[123]), "+f"(d[124]), "+f"(d[125]), "+f"(d[126]), "+f"(d[127])
        : "l"(da), "l"(db), "r"(scale_d));
}

__device__ __forceinline__ void wgmma_ss_n64_tb0(float (&d)[32], uint64_t da, uint64_t db, int scale_d) {
    asm volatile("{\n.reg .pred p;\nsetp.ne.b32 p, %34, 0;\n"
        "wgmma.mma_async.sync.aligned.m64n64k16.f32.bf16.bf16 {%0, %1, %2, %3, %4, %5, %6, %7, %8, %9, %10, %11, %12, %13, %14, %15, %16, %17, %18, %19, %20, %21, %22, %23, %24, %25, %26, %27, %28, %29, %30, %31}, %32, %33, p, 1, 1, 0, 0;\n}\n"
        : "+f"(d[0]), "+f"(d[1]), "+f"(d[2]), "+f"(d[3]), "+f"(d[4]), "+f"(d[5]), "+f"(d[6]), "+f"(d[7]), "+f"(d[8]), "+f"(d[9]), "+f"(d[10]), "+f"(d[11]), "+f"(d[12]), "+f"(d[13]), "+f"(d[14]), "+f"(d[15]), "+f"(d[16]), "+f"(d[17]), "+f"(d[18]), "+f"(d[19]), "+f"(d[20]), "+f"(d[21]), "+f"(d[22]), "+f"(d[23]), "+f"(d[24]), "+f"(d[25]), "+f"(d[26]), "+f"(d[27]), "+f"(d[28]), "+f"(d[29]), "+f"(d[30]), "+f"(d[31])
        : "l"(da), "l"(db), "r"(scale_d));
}

struct Maps {
    CUtensorMap xa, xa1, wup, mqk4, mqk2, wepi, uc, x, out;
};

__device__ __forceinline__ uint64_t mkd(uint32_t lo) {
    uint64_t d;
    asm("mov.b64 %0, {%1, %2};" : "=l"(d) : "r"(lo), "r"((1024u >> 4) | (1u << 30)));
    return d;
}
__device__ __forceinline__ void ring_ld(uint32_t sb, uint32_t barbase, uint32_t slot8, const CUtensorMap* tm, int c1, int c2) {
    mbar_expect_tx(sb + barbase + slot8, 8192);
    tma3(sb + R1 + slot8 * 1024, tm, 0, c1, c2, sb + barbase + slot8);
}

__global__ void __launch_bounds__(384, 1) main_kernel(const __grid_constant__ Maps mp, const bf16* __restrict__ dw) {
    extern __shared__ __align__(1024) uint8_t smem[];
    const uint32_t sb = smem_u32(smem);
    const int tid = threadIdx.x;
    const int b = blockIdx.x / TPB, ti = blockIdx.x % TPB;
    if (tid == 0) {
        mbar_init(sb + B_A, 1);
        for (int i = 0; i < 10; i++) mbar_init(sb + B_R1 + 8 * i, 1);
        mbar_init(sb + B_H1, 2); mbar_init(sb + B_H2, 1); mbar_init(sb + B_H3, 2);
        for (int i = 0; i < 3; i++) { mbar_init(sb + B_KV + 8 * i, 1); mbar_init(sb + B_P + 8 * i, 4); mbar_init(sb + B_GO + 8 * i, 1); }
        for (int i = 0; i < 12; i++) mbar_init(sb + B_R2 + 8 * i, 1);
        mbar_init(sb + B_UC, 1); mbar_init(sb + B_X, 1);
        for (int i = 0; i < 4; i++) asm volatile("st.shared.u32 [%0], 0;" ::"r"(sb + CNT + 4 * i) : "memory");
        asm volatile("fence.mbarrier_init.release.cluster;" ::: "memory");
        for (int i = 0; i < 8; i++) mbar_arrive(sb + B_R1 + 8 * i);
        fence_async();
        mbar_expect_tx(sb + B_A, 65536 + 3072);
        asm volatile("cp.async.bulk.shared::cluster.global.mbarrier::complete_tx::bytes [%0], [%1], 3072, [%2];" ::"r"(sb + DWS), "l"(dw), "r"(sb + B_A) : "memory");
        tma4(sb + AT, &mp.xa, 0, 62 * ti - 1, 0, b, sb + B_A);
        #pragma unroll 1
        for (int n = 0; n < 10; n++) ring_ld(sb, B_R1, ((n + 8) % 10) * 8, &mp.wup, 16 * (n >> 1), 8 + 4 * (n & 1));
    }
    __syncthreads();
    const int wg = __shfl_sync(0xffffffffu, tid >> 7, 0);
    const int lane = tid & 31, w = (tid >> 5) & 3;
    const bool w0 = __shfl_sync(0xffffffffu, w, 0) == 0;
    const uint32_t sd = (sb & 0x3FFFF) >> 4;
    const uint32_t adA = sd + (AT >> 4) + (1u << 16);
    const uint32_t bd2k = sd + (R1 >> 4) + ((2048u >> 4) << 16);
    const bool el = (tid & 127) == 0;
    const uint32_t lrow = 16 * w + (lane & 7) + ((lane >> 3) & 1) * 8;
    const uint32_t loff = lrow * 128 + ((((lane >> 4) ^ lrow) & 7) << 4);
    const int r0 = 16 * w + (lane >> 2);

    if (wg == 0) {
        asm volatile("setmaxnreg.inc.sync.aligned.u32 184;");
        uint32_t q[112];
        PT(0);
        mbar_wait(sb + B_A, 0);
        PT(1);
        mbar_wait(sb + B_H1, 0);
        PT(2);
        {
            float acc[128];
            fresh(acc);
            uint32_t slot8 = 16, par = 1, prev8 = 0;
#pragma unroll 1
            for (int kk = 0; kk < 32; kk++) {
                mbar_wait(sb + B_R1 + slot8, par);
                if (kk == 31 && w0 && elect1()) mbar_arrive(sb + B_H2);
                wg_fence();
                wgmma_ss_n256_tb1(acc, mkd(adA + (kk >> 2) * 512 + (kk & 3) * 2), mkd(bd2k + slot8 * 64), 1);
                wg_commit();
                wg_wait<1>();
                if (kk > 0 && w0 && elect1()) {
                    const int i = kk + 9;
                    ring_ld(sb, B_R1, prev8, i < 32 ? &mp.mqk4 : &mp.wup, i < 32 ? 16 * i : 8 * ((i - 32) & ~1), i < 32 ? 4 : 4 * (i & 1));
                }
                prev8 = slot8;
                slot8 += 8;
                if (slot8 >= 80) { slot8 = 0; par ^= 1; }
            }
            wg_wait<0>();
            pin(acc);
            if (w0 && elect1()) ring_ld(sb, B_R1, prev8, &mp.wup, 64, 4);
            PT(3);
#pragma unroll
            for (int kk = 0; kk < 4; kk++)
                stsm4((sb + QS + loff) ^ (kk << 5), pack2(acc[96 + 8 * kk], acc[97 + 8 * kk]), pack2(acc[98 + 8 * kk], acc[99 + 8 * kk]),
                      pack2(acc[100 + 8 * kk], acc[101 + 8 * kk]), pack2(acc[102 + 8 * kk], acc[103 + 8 * kk]));
            fence_async();
#pragma unroll
            for (int i = 47; i >= 0; i--) q[64 + i] = pack2v(acc[2 * i], acc[2 * i + 1]);
        }
        mbar_wait(sb + B_H3, 0);
        PT(4);
        uint32_t slot8 = 64, par = 0, prev8 = 0;
#pragma unroll
        for (int half = 0; half < 2; half++) {
            float acc[64];
            fresh(acc);
            auto refill = [&](int i) {
                if (i < 32) ring_ld(sb, B_R1, prev8, &mp.mqk2, 32 * (i & 15), 2 * (i >> 4));
                else if (i < 40) {
                    if (i == 32) mbar_expect_tx(sb + B_KV + 8, 65536);
                    tma4(sb + R1 + (i - 32) * 8192, &mp.xa1, 0, 0, i - 32, b, sb + B_KV + 8);
                } else if (i == 41) {
                    mbar_expect_tx(sb + B_KV + 16, 65536);
                    tma4(sb + R2, &mp.xa, 0, 64, 0, b, sb + B_KV + 16);
                }
            };
#pragma unroll 1
            for (int m = 0; m < 16; m++) {
                mbar_wait(sb + B_R1 + slot8, par);
                const uint32_t aa = adA + (m >> 1) * 512 + (m & 1) * 4, bb = bd2k + (1u << 23) + slot8 * 64;
                wg_fence();
                wgmma_ss_n128_tb1(acc, mkd(aa), mkd(bb), 1);
                wgmma_ss_n128_tb1(acc, mkd(aa + 2), mkd(bb + 128), 1);
                wg_commit();
                wg_wait<1>();
                if (m > 0 && w0 && elect1()) refill(16 * half + m + 9);
                prev8 = slot8;
                slot8 += 8;
                if (slot8 >= 80) { slot8 = 0; par ^= 1; }
            }
            wg_wait<0>();
            pin(acc);
            if (w0 && elect1()) refill(16 * half + 25);
#pragma unroll
            for (int i = 31; i >= 0; i--) q[32 * half + i] = pack2v(acc[2 * i], acc[2 * i + 1]);
        }
        bar_sync(1, 128);
        PT(5);

        const float CS = 0.04419417382415922f * 1.4426950408889634f;
        float m0 = -INFINITY, m1 = -INFINITY, l0 = 0.f, l1 = 0.f;
        int s = 1, ph = 0;
#pragma unroll 1
        for (int j = 0; j < NKV; j++) {
            float S[32];
            mbar_wait(sb + B_KV + s * 8, ph);
            PL(j, 0);
            const uint32_t kd = sd + s * 4096;
            wg_fence();
#pragma unroll
            for (int kk = 0; kk < 28; kk++)
                wgmma_rs_n64_tb0(S, q[4 * kk], q[4 * kk + 1], q[4 * kk + 2], q[4 * kk + 3], dsc(kd, (kk >> 2) * 8192 + (kk & 3) * 32, 16), kk > 0);
            wg_commit();
#pragma unroll
            for (int kk = 0; kk < 4; kk++)
                wgmma_ss_n64_tb0(S, dsc(sd, QS + kk * 32, 16), dsc(kd, 7 * 8192 + kk * 32, 16), 1);
            wg_commit();
            wg_wait<1>();
            const int sp = s == 0 ? 2 : s - 1;
            if (j > 0 && el) mbar_arrive(sb + B_GO + sp * 8);
            wg_wait<0>();
            pin(S);
            PL(j, 1);
            if (j == NKV - 1) {
#pragma unroll
                for (int i = (T_ - 64 * (NKV - 1)) / 2; i < 32; i++) S[i] = -INFINITY;
            }
            float x0 = fmaxf(S[0], S[1]), x1 = fmaxf(S[2], S[3]);
#pragma unroll
            for (int n = 1; n < 8; n++) {
                x0 = fmaxf(x0, fmaxf(S[4 * n], S[4 * n + 1]));
                x1 = fmaxf(x1, fmaxf(S[4 * n + 2], S[4 * n + 3]));
            }
            x0 = fmaxf(x0, __shfl_xor_sync(0xffffffffu, x0, 1));
            x1 = fmaxf(x1, __shfl_xor_sync(0xffffffffu, x1, 1));
            x0 = fmaxf(x0, __shfl_xor_sync(0xffffffffu, x0, 2));
            x1 = fmaxf(x1, __shfl_xor_sync(0xffffffffu, x1, 2));
            x0 = fmaxf(x0, m0); x1 = fmaxf(x1, m1);
            const float sc0 = ex2((m0 - x0) * CS), sc1 = ex2((m1 - x1) * CS);
            m0 = x0; m1 = x1;
            const float n0 = -x0 * CS, n1 = -x1 * CS;
            float a0 = 0.f, a1 = 0.f;
            const uint32_t pb = sb + R3 + sp * 8192;
#pragma unroll
            for (int kk = 0; kk < 4; kk++) {
                float p[8];
#pragma unroll
                for (int e = 0; e < 8; e++) p[e] = ex2(fmaf(S[8 * kk + e], CS, (e & 2) ? n1 : n0));
                a0 += (p[0] + p[1]) + (p[4] + p[5]);
                a1 += (p[2] + p[3]) + (p[6] + p[7]);
                stsm4((pb + loff) ^ (kk << 5), pack2(p[0], p[1]), pack2(p[2], p[3]), pack2(p[4], p[5]), pack2(p[6], p[7]));
            }
            l0 = fmaf(l0, sc0, a0); l1 = fmaf(l1, sc1, a1);
            if ((lane & 3) == 0) { sts_f32(sb + SCL + s * 256 + r0 * 4, sc0); sts_f32(sb + SCL + s * 256 + r0 * 4 + 32, sc1); }
            if (j == NKV - 1) {
                l0 += __shfl_xor_sync(0xffffffffu, l0, 1); l1 += __shfl_xor_sync(0xffffffffu, l1, 1);
                l0 += __shfl_xor_sync(0xffffffffu, l0, 2); l1 += __shfl_xor_sync(0xffffffffu, l1, 2);
                if ((lane & 3) == 0) { sts_f32(sb + LINV + r0 * 4, 1.f / l0); sts_f32(sb + LINV + r0 * 4 + 32, 1.f / l1); }
            }
            fence_async();
            __syncwarp();
            if (lane == 0) mbar_arrive(sb + B_P + s * 8);
            if (j == NKV - 1 && el) mbar_arrive(sb + B_GO + s * 8);
            PL(j, 2);
            if (++s == 3) s = 0;
            if (s == 1) ph ^= 1;
        }
        PDUMP();
    } else {
        asm volatile("setmaxnreg.dec.sync.aligned.u32 160;");
        const int h = wg - 1;
        float acc[128];
        mbar_wait(sb + B_A, 0);
#pragma unroll
        for (int pass = 0; pass < 2; pass++) {
            if (pass == 1) mbar_wait(sb + B_H2, 0);
            PT(1 + 3 * pass);
            fresh(acc);
            uint32_t slot8 = (pass ? 32 : 64) + 8 * h, par = 0, prev8 = 0;
#pragma unroll 1
            for (int kk = 0; kk < 32; kk++) {
                mbar_wait(sb + B_R1 + slot8, par);
                if (kk == 31 && w0 && elect1()) mbar_arrive(sb + (pass ? B_H3 : B_H1));
                wg_fence();
                wgmma_ss_n256_tb1(acc, mkd(adA + (kk >> 2) * 512 + (kk & 3) * 2), mkd(bd2k + slot8 * 64), 1);
                wg_commit();
                wg_wait<1>();
                if (kk > 0 && w0 && elect1()) {
                    const int i = kk + 4;
                    ring_ld(sb, B_R1, prev8, i < 32 ? &mp.wup : (pass ? &mp.mqk2 : &mp.mqk4),
                            i < 32 ? 16 * i : (pass ? 32 : 16) * (2 * (i - 32) + h), i < 32 ? (pass ? 0 : 8) + 4 * h : (pass ? 0 : 4));
                }
                prev8 = slot8;
                slot8 += 16;
                if (slot8 >= 80) { slot8 -= 80; par ^= 1; }
            }
            wg_wait<0>();
            pin(acc);
            if (w0 && elect1()) ring_ld(sb, B_R1, prev8, pass ? &mp.mqk2 : &mp.mqk4, (pass ? 32 : 16) * (8 + h), pass ? 0 : 4);
            PT(2 + 3 * pass);
            if (pass == 0) {
#pragma unroll
                for (int i = 0; i < 128; i++) acc[i] = gelu(acc[i]);
                float s0 = 0.f, s1 = 0.f;
#pragma unroll
                for (int n = 0; n < 32; n++) { s0 += acc[4 * n] + acc[4 * n + 1]; s1 += acc[4 * n + 2] + acc[4 * n + 3]; }
                s0 += __shfl_xor_sync(0xffffffffu, s0, 1); s1 += __shfl_xor_sync(0xffffffffu, s1, 1);
                s0 += __shfl_xor_sync(0xffffffffu, s0, 2); s1 += __shfl_xor_sync(0xffffffffu, s1, 2);
                s0 *= (1.f / 256.f); s1 *= (1.f / 256.f);
                float v0 = 0.f, v1 = 0.f;
#pragma unroll
                for (int n = 0; n < 32; n++) {
                    float d0 = acc[4 * n] - s0, d1 = acc[4 * n + 1] - s0, d2 = acc[4 * n + 2] - s1, d3 = acc[4 * n + 3] - s1;
                    v0 = fmaf(d0, d0, v0); v0 = fmaf(d1, d1, v0); v1 = fmaf(d2, d2, v1); v1 = fmaf(d3, d3, v1);
                }
                v0 += __shfl_xor_sync(0xffffffffu, v0, 1); v1 += __shfl_xor_sync(0xffffffffu, v1, 1);
                v0 += __shfl_xor_sync(0xffffffffu, v0, 2); v1 += __shfl_xor_sync(0xffffffffu, v1, 2);
                if ((lane & 3) == 0) {
                    uint32_t a = sb + STAT + h * 512 + r0 * 8;
                    sts_f32(a, s0); sts_f32(a + 4, v0); sts_f32(a + 64, s1); sts_f32(a + 68, v1);
                }
                bar_sync(2, 256);
                {
                    uint32_t a = sb + STAT + (h ^ 1) * 512 + r0 * 8;
                    float t0 = lds_f32(a), u0 = lds_f32(a + 4), t1 = lds_f32(a + 64), u1 = lds_f32(a + 68);
                    v0 = (v0 + u0 + (s0 - t0) * (s0 - t0) * 128.f) * (1.f / 512.f);
                    v1 = (v1 + u1 + (s1 - t1) * (s1 - t1) * 128.f) * (1.f / 512.f);
                    s0 = 0.5f * (s0 + t0); s1 = 0.5f * (s1 + t1);
                }
                v0 = rsqrtf(v0 + 1e-5f); v1 = rsqrtf(v1 + 1e-5f);
                s0 = -s0 * v0; s1 = -s1 * v1;
#pragma unroll
                for (int p = 0; p < 16; p++)
                    stsm4(((sb + R0 + h * 32768 + loff) ^ ((p & 3) << 5)) + (p >> 2) * 8192,
                          pack2(fmaf(acc[8 * p], v0, s0), fmaf(acc[8 * p + 1], v0, s0)), pack2(fmaf(acc[8 * p + 2], v1, s1), fmaf(acc[8 * p + 3], v1, s1)),
                          pack2(fmaf(acc[8 * p + 4], v0, s0), fmaf(acc[8 * p + 5], v0, s0)), pack2(fmaf(acc[8 * p + 6], v1, s1), fmaf(acc[8 * p + 7], v1, s1)));
            } else {
                bar_sync(3 + h, 128);
                const uint32_t rm = lrow == 0 ? 0 : lrow - 1, rp = lrow == 63 ? 63 : lrow + 1;
                const uint32_t gb = sb + R0 + h * 32768;
                const uint32_t am = gb + rm * 128 + ((((lane >> 4) ^ rm) & 7) << 4), ap = gb + rp * 128 + ((((lane >> 4) ^ rp) & 7) << 4), ac = gb + loff;
                const uint32_t dwa = sb + DWS + 512 * h + ((lane >> 3) & 1) * 16 + (lane >> 4) * 1024;
                bf16* ucp = g_uc + ((size_t)blockIdx.x * 64 + r0) * D_ + 256 * h + 8 * (lane & 3);
#pragma unroll
                for (int m = 7; m >= 0; m--) {
                    uint32_t o[8];
#pragma unroll
                    for (int pp = 1; pp >= 0; pp--) {
                        const int p = 2 * m + pp;
                        const uint32_t co = (p >> 2) * 8192, cx = (p & 3) << 5;
                        uint32_t u[4], g[4], cv[4], d[4], d2[2];
#pragma unroll
                        for (int e = 3; e >= 0; e--) u[e] = pack2v(gelu(acc[8 * p + 2 * e]), gelu(acc[8 * p + 2 * e + 1]));
                        ldsm4(dwa + 32 * p, d);
                        ldsm2(dwa + 32 * p + 2048, d2);
                        ldsm4((am ^ cx) + co, g);
#pragma unroll
                        for (int e = 0; e < 4; e++) cv[e] = bmul2(g[e], d[e >> 1]);
                        ldsm4((ac ^ cx) + co, g);
#pragma unroll
                        for (int e = 0; e < 4; e++) cv[e] = bfma2(g[e], d[2 + (e >> 1)], cv[e]);
                        ldsm4((ap ^ cx) + co, g);
#pragma unroll
                        for (int e = 0; e < 4; e++) o[4 * (e & 1) + 2 * pp + (e >> 1)] = bmul2(u[e], bfma2(g[e], d2[e >> 1], cv[e]));
                    }
                    stg4(ucp + 32 * m, o[0], o[1], o[2], o[3]);
                    stg4(ucp + 32 * m + 8 * D_, o[4], o[5], o[6], o[7]);
                }
                fence_async_g();
                bar_sync(2, 256);
                if (tid == 128) {
                    mbar_expect_tx(sb + B_KV, 65536);
                    tma4(sb + R0, &mp.xa, 0, 128, 0, b, sb + B_KV);
                }
            }
            PT(3 + 3 * pass);
        }
        int s = 1, ph = 0;
        fresh(acc);
#pragma unroll 1
        for (int j = 0; j < NKV; j++) {
            mbar_wait(sb + B_P + s * 8, ph);
            PL(j, 0);
            if (j > 0) {
                const float sc0 = lds_f32(sb + SCL + s * 256 + r0 * 4), sc1 = lds_f32(sb + SCL + s * 256 + r0 * 4 + 32);
                if (__any_sync(0xffffffffu, sc0 != 1.f || sc1 != 1.f)) {
#pragma unroll
                    for (int n = 0; n < 32; n++) { acc[4 * n] *= sc0; acc[4 * n + 1] *= sc0; acc[4 * n + 2] *= sc1; acc[4 * n + 3] *= sc1; }
                }
            }
            mbar_wait(sb + B_KV + s * 8, ph);
            mbar_wait(sb + B_GO + s * 8, ph);
            PL(j, 1);
            const uint32_t vd = sd + s * 4096 + h * 2048, pd = sd + (s == 0 ? 2 : s - 1) * 512;
            pin(acc);
            wg_fence();
#pragma unroll
            for (int kk = 0; kk < 4; kk++) wgmma_ss_n256_tb1(acc, dsc(pd, R3 + kk * 32, 16), dsc(vd, kk * 2048, 8192), 1);
            wg_commit();
            wg_wait<0>();
            pin(acc);
            PL(j, 2);
            if (w0 && elect1()) {
                if (atom_inc_s(sb + CNT + 4 * s) & 1) {
                    if (j + 3 < NKV) {
                        mbar_expect_tx(sb + B_KV + s * 8, 65536);
                        tma4(sb + s * 65536, &mp.xa, 0, 64 * (j + 3), 0, b, sb + B_KV + s * 8);
                    } else if (j == NKV - 1) {
                        mbar_expect_tx(sb + B_UC, 65536);
                        tma3(sb + UCT, &mp.uc, 0, 64 * blockIdx.x, 0, sb + B_UC);
                    } else {
                        const int n0 = j == NKV - 3 ? 0 : 8, n1 = j == NKV - 3 ? 8 : 12;
#pragma unroll 1
                        for (int n = n0; n < n1; n++) ring_ld(sb, B_R2, n * 8, &mp.wepi, 16 * (n >> 1), 4 * (n & 1));
                    }
                }
            }
            if (++s == 3) s = 0;
            if (s == 1) ph ^= 1;
        }
        {
            const float i0 = lds_f32(sb + LINV + r0 * 4), i1 = lds_f32(sb + LINV + r0 * 4 + 32);
#pragma unroll
            for (int p = 0; p < 16; p++)
                stsm4(((sb + R0 + h * 32768 + loff) ^ ((p & 3) << 5)) + (p >> 2) * 8192,
                      pack2(acc[8 * p] * i0, acc[8 * p + 1] * i0), pack2(acc[8 * p + 2] * i1, acc[8 * p + 3] * i1),
                      pack2(acc[8 * p + 4] * i0, acc[8 * p + 5] * i0), pack2(acc[8 * p + 6] * i1, acc[8 * p + 7] * i1));
        }
        fence_async();
        bar_sync(2, 256);
        PT(7);
        fresh(acc);
        {
            uint32_t slot8 = 8 * h, par = 0, prev8 = 0;
#pragma unroll 1
            for (int kk = 0; kk < 64; kk++) {
                if (kk == 32) mbar_wait(sb + B_UC, 0);
                mbar_wait(sb + B_R2 + slot8, par);
                wg_fence();
                wgmma_ss_n256_tb1(acc, mkd(sd + (1u << 16) + (kk < 32 ? (R0 >> 4) : (UCT >> 4) - 4096) + (kk >> 2) * 512 + (kk & 3) * 2), mkd(bd2k + slot8 * 64), 1);
                wg_commit();
                wg_wait<1>();
                if (kk > 0 && w0 && elect1()) {
                    if (kk < 59) ring_ld(sb, B_R2, prev8, &mp.wepi, 16 * (kk + 5), 4 * h);
                    if (kk == 32 && (atom_inc_s(sb + CNT + 12) & 1)) {
                        mbar_expect_tx(sb + B_X, 65536);
                        tma4(sb + R0, &mp.x, 0, 62 * ti, 0, b, sb + B_X);
                    }
                }
                prev8 = slot8;
                slot8 += 16;
                if (slot8 >= 96) { slot8 -= 96; par ^= 1; }
            }
        }
        wg_wait<0>();
        pin(acc);
        PT(8);
        mbar_wait(sb + B_X, 0);
        PT(9);
        {
            const uint32_t sr = (lrow + 63) & 63;
            const uint32_t xoff = sr * 128 + ((((lane >> 4) ^ sr) & 7) << 4);
#pragma unroll
            for (int p = 0; p < 16; p++) {
                const uint32_t a = ((sb + R0 + h * 32768 + xoff) ^ ((p & 3) << 5)) + (p >> 2) * 8192;
                uint32_t xv[4];
                ldsm4(a, xv);
#pragma unroll
                for (int e = 0; e < 4; e++)
                    xv[e] = pack2(acc[8 * p + 2 * e] + __uint_as_float(xv[e] << 16), acc[8 * p + 2 * e + 1] + __uint_as_float(xv[e] & 0xffff0000u));
                stsm4(a, xv[0], xv[1], xv[2], xv[3]);
            }
        }
        fence_async();
        bar_sync(3 + h, 128);
        if (el) {
            for (int c = 0; c < 4; c++) tma4_store(&mp.out, sb + R0 + (4 * h + c) * 8192, 0, 62 * ti, 4 * h + c, b);
            asm volatile("cp.async.bulk.commit_group;" ::: "memory");
            PT(10);
            asm volatile("cp.async.bulk.wait_group.read 0;" ::: "memory");
        }
        PT(11);
        PDUMP();
    }
}

__device__ __forceinline__ float bfr(float x) { return __bfloat162float(__float2bfloat16_rn(x)); }

__global__ void __launch_bounds__(256) ln_kernel(const bf16* __restrict__ x) {
    const int row = blockIdx.x * 8 + (threadIdx.x >> 5), lane = threadIdx.x & 31;
    const uint4* src = reinterpret_cast<const uint4*>(x + (size_t)row * D_);
    uint4 v[2] = {src[lane], src[lane + 32]};
    float f[16];
    const uint32_t* u = reinterpret_cast<const uint32_t*>(v);
#pragma unroll
    for (int i = 0; i < 8; i++) { f[2 * i] = __uint_as_float(u[i] << 16); f[2 * i + 1] = __uint_as_float(u[i] & 0xffff0000u); }
    float s = 0.f;
#pragma unroll
    for (int i = 0; i < 16; i++) s += f[i];
#pragma unroll
    for (int o = 16; o; o >>= 1) s += __shfl_xor_sync(0xffffffffu, s, o);
    s *= (1.f / D_);
    float q = 0.f;
#pragma unroll
    for (int i = 0; i < 16; i++) { float d = f[i] - s; q = fmaf(d, d, q); }
#pragma unroll
    for (int o = 16; o; o >>= 1) q += __shfl_xor_sync(0xffffffffu, q, o);
    const float m = bfr(s), var = bfr(q * (1.f / D_));
    const float rinv = 1.f / bfr(sqrtf(bfr(var + 1e-5f)));
    uint32_t o[8];
#pragma unroll
    for (int i = 0; i < 8; i++) o[i] = pack2(bfr(f[2 * i] - m) * rinv, bfr(f[2 * i + 1] - m) * rinv);
    uint4* dst = reinterpret_cast<uint4*>(g_xa + (size_t)row * D_);
    dst[lane] = make_uint4(o[0], o[1], o[2], o[3]);
    dst[lane + 32] = make_uint4(o[4], o[5], o[6], o[7]);
}

__global__ void __launch_bounds__(128) fold_kernel(const bf16* wq, const bf16* wk, const bf16* wv, const bf16* wao,
                                                   const bf16* wdn, const bf16* wm, int stage) {
    using namespace nvcuda;
    __shared__ float cs[4][16][20];
    const int z = stage == 0 ? blockIdx.z : 3;
    const bf16* A = z == 0 ? wq : z == 1 ? wv : z == 2 ? wdn : g_t1;
    const bf16* B = z == 0 ? wk : z == 1 ? wao : z == 2 ? wm + 512 * D_ : wm;
    bf16* C = z == 0 ? g_mqk : z == 1 ? g_t1 : z == 2 ? g_wepi + 512 * D_ : g_wepi;
    const int w = threadIdx.x >> 5, lane = threadIdx.x & 31;
    const int rb = blockIdx.y * 32 + (w >> 1) * 16, cb = blockIdx.x * 32 + (w & 1) * 16;
    wmma::fragment<wmma::accumulator, 16, 16, 16, float> c;
    wmma::fill_fragment(c, 0.f);
    for (int k = 0; k < D_; k += 16) {
        wmma::fragment<wmma::matrix_a, 16, 16, 16, bf16, wmma::row_major> a;
        wmma::load_matrix_sync(a, A + rb * D_ + k, D_);
        if (z == 0) {
            wmma::fragment<wmma::matrix_b, 16, 16, 16, bf16, wmma::col_major> bb;
            wmma::load_matrix_sync(bb, B + cb * D_ + k, D_);
            wmma::mma_sync(c, a, bb, c);
        } else {
            wmma::fragment<wmma::matrix_b, 16, 16, 16, bf16, wmma::row_major> bb;
            wmma::load_matrix_sync(bb, B + k * D_ + cb, D_);
            wmma::mma_sync(c, a, bb, c);
        }
    }
    wmma::store_matrix_sync(&cs[w][0][0], c, 20, wmma::mem_row_major);
    __syncwarp();
    for (int i = lane; i < 256; i += 32) {
        int r = rb + (i >> 4), cc = cb + (i & 15);
        if (z == 2) r = (r & ~31) | (((r >> 1) & 3) << 3) | (((r >> 3) & 3) << 1) | (r & 1);
        C[r * D_ + cc] = __float2bfloat16_rn(cs[w][i >> 4][i & 15]);
    }
}

typedef CUresult (*PFN_enc)(CUtensorMap*, CUtensorMapDataType, cuuint32_t, void*, const cuuint64_t*, const cuuint64_t*,
                            const cuuint32_t*, const cuuint32_t*, CUtensorMapInterleave, CUtensorMapSwizzle,
                            CUtensorMapL2promotion, CUtensorMapFloatOOBfill);

static void enc(PFN_enc f, CUtensorMap* m, void* base, int rank, const cuuint64_t* dims, const cuuint64_t* strides, const cuuint32_t* box) {
    cuuint32_t es[5] = {1, 1, 1, 1, 1};
    f(m, CU_TENSOR_MAP_DATA_TYPE_BFLOAT16, rank, base, dims, strides, box, es, CU_TENSOR_MAP_INTERLEAVE_NONE,
      CU_TENSOR_MAP_SWIZZLE_128B, CU_TENSOR_MAP_L2_PROMOTION_L2_256B, CU_TENSOR_MAP_FLOAT_OOB_FILL_NONE);
}
static void enc_act(PFN_enc f, CUtensorMap* m, void* base, int rows, int chunks) {
    cuuint64_t dims[4] = {64, (cuuint64_t)T_, 8, (cuuint64_t)NB_};
    cuuint64_t st[3] = {1024, 128, (cuuint64_t)T_ * 1024};
    cuuint32_t box[4] = {64, (cuuint32_t)rows, (cuuint32_t)chunks, 1};
    enc(f, m, base, 4, dims, st, box);
}
static void enc_w(PFN_enc f, CUtensorMap* m, void* base, int krows, int ncols, int bk, int bc) {
    cuuint64_t dims[3] = {64, (cuuint64_t)krows, (cuuint64_t)(ncols / 64)};
    cuuint64_t st[2] = {(cuuint64_t)ncols * 2, 128};
    cuuint32_t box[3] = {64, (cuuint32_t)bk, (cuuint32_t)bc};
    enc(f, m, base, 3, dims, st, box);
}

extern "C" void kernel_launch(void* const* d_in, const int* in_sizes, int n_in, void* d_out, int out_size) {
    const bf16* x = (const bf16*)d_in[0];
    static PFN_enc fenc = nullptr;
    static void *p_xa, *p_mqk, *p_wepi, *p_uc;
    if (!fenc) {
        void* fn = nullptr;
        cudaDriverEntryPointQueryResult qr;
        cudaGetDriverEntryPoint("cuTensorMapEncodeTiled", &fn, cudaEnableDefault, &qr);
        fenc = (PFN_enc)fn;
        cudaGetSymbolAddress(&p_xa, g_xa);
        cudaGetSymbolAddress(&p_mqk, g_mqk);
        cudaGetSymbolAddress(&p_wepi, g_wepi);
        cudaGetSymbolAddress(&p_uc, g_uc);
        cudaFuncSetAttribute(main_kernel, cudaFuncAttributeMaxDynamicSharedMemorySize, SMEM_BYTES);
    }
    Maps mp;
    enc_act(fenc, &mp.xa, p_xa, 64, 8);
    enc_act(fenc, &mp.xa1, p_xa, 64, 1);
    enc_act(fenc, &mp.x, (void*)x, 64, 8);
    enc_act(fenc, &mp.out, d_out, 62, 1);
    enc_w(fenc, &mp.wup, d_in[5], 512, 1024, 16, 4);
    enc_w(fenc, &mp.mqk4, p_mqk, 512, 512, 16, 4);
    enc_w(fenc, &mp.mqk2, p_mqk, 512, 512, 32, 2);
    enc_w(fenc, &mp.wepi, p_wepi, 1024, 512, 16, 4);
    enc_w(fenc, &mp.uc, p_uc, NCTA * 64, 512, 64, 8);
    cudaStream_t st = cudaStreamPerThread;
    ln_kernel<<<NB_ * T_ / 8, 256, 0, st>>>(x);
    fold_kernel<<<dim3(16, 16, 3), 128, 0, st>>>((const bf16*)d_in[1], (const bf16*)d_in[2], (const bf16*)d_in[3], (const bf16*)d_in[4],
                                                 (const bf16*)d_in[7], (const bf16*)d_in[8], 0);
    fold_kernel<<<dim3(16, 16, 1), 128, 0, st>>>((const bf16*)d_in[1], (const bf16*)d_in[2], (const bf16*)d_in[3], (const bf16*)d_in[4],
                                                 (const bf16*)d_in[7], (const bf16*)d_in[8], 1);
    main_kernel<<<NCTA, 384, SMEM_BYTES, st>>>(mp, (const bf16*)d_in[6]);
}
```

```cpp
#include <cuda_runtime.h>
#include <cuda_bf16.h>
#include <cuda.h>
#include <stdint.h>

typedef __nv_bfloat16 bf16;

constexpr int T_ = 4000, D_ = 512, NB_ = 2;
constexpr int TPB = 65;
constexpr int NCTA = TPB * NB_;
constexpr int NKV = 63;

__device__ __align__(1024) bf16 g_xa[NB_ * (T_ + 8) * D_];
__device__ __align__(1024) bf16 g_mqk[D_ * D_];
__device__ __align__(1024) bf16 g_t1[D_ * D_];
__device__ __align__(1024) bf16 g_wepi[2 * D_ * D_];
__device__ __align__(1024) bf16 g_uc[NCTA * 64 * D_];
__device__ unsigned g_sync[8];

#define PT(i)
#define PL(j, q)
#define PDUMP()

constexpr uint32_t R0 = 0, R1 = 65536, R2 = 131072, R3 = 196608, QS = 221184, MISC = 229376;
constexpr uint32_t AT = 147456, DWS = R3 + 16384, UCT = 163840;
constexpr uint32_t SMEM_BYTES = 232448;
constexpr uint32_t B_A = MISC, B_R1 = MISC + 8  , B_MK = MISC + 48, B_LN = MISC + 56, B_MQ = MISC + 64, B_XA = MISC + 72,
                   B_H1 = MISC + 88, B_H2 = MISC + 96, B_H3 = MISC + 104,
                   B_KV = MISC + 112, B_P = MISC + 136, B_GO = MISC + 160, B_R2 = MISC + 184, B_UC = MISC + 280,
                   B_X = MISC + 288, CNT = MISC + 296  , SCL = MISC + 512  ,
                   LINV = MISC + 1280  , STAT = MISC + 1536  ;

__device__ __forceinline__ uint32_t smem_u32(const void* p) { return (uint32_t)__cvta_generic_to_shared(p); }
__device__ __forceinline__ void wg_fence() { asm volatile("wgmma.fence.sync.aligned;" ::: "memory"); }
__device__ __forceinline__ void wg_commit() { asm volatile("wgmma.commit_group.sync.aligned;" ::: "memory"); }
template <int N> __device__ __forceinline__ void wg_wait() { asm volatile("wgmma.wait_group.sync.aligned %0;" ::"n"(N) : "memory"); }
__device__ __forceinline__ uint64_t dsc(uint32_t sd, uint32_t off, uint32_t lbo) {
    uint32_t lo = sd + (off >> 4) + ((lbo >> 4) << 16);
    uint64_t d;
    asm("mov.b64 %0, {%1, %2};" : "=l"(d) : "r"(lo), "r"((1024u >> 4) | (1u << 30)));
    return d;
}
__device__ __forceinline__ bool elect1() {
    uint32_t p;
    asm volatile("{\n.reg .pred p;\nelect.sync _|p, 0xffffffff;\nselp.u32 %0, 1, 0, p;\n}\n" : "=r"(p));
    return p != 0;
}
__device__ __forceinline__ void mbar_init(uint32_t bar, int cnt) { asm volatile("mbarrier.init.shared::cta.b64 [%0], %1;" ::"r"(bar), "r"(cnt) : "memory"); }
__device__ __forceinline__ void mbar_expect_tx(uint32_t bar, uint32_t bytes) { asm volatile("mbarrier.arrive.expect_tx.shared::cta.b64 _, [%0], %1;" ::"r"(bar), "r"(bytes) : "memory"); }
__device__ __forceinline__ void mbar_arrive(uint32_t bar) { asm volatile("mbarrier.arrive.shared::cta.b64 _, [%0];" ::"r"(bar) : "memory"); }
__device__ __forceinline__ void mbar_wait(uint32_t bar, uint32_t parity) {
    uint32_t ok;
#pragma unroll 1
    for (uint32_t it = 0;; ++it) {
        asm volatile("{\n.reg .pred p;\nmbarrier.try_wait.parity.shared::cta.b64 p, [%1], %2;\nselp.u32 %0, 1, 0, p;\n}\n" : "=r"(ok) : "r"(bar), "r"(parity) : "memory");
        if (ok) break;
        if (it > (1u << 20)) __trap();
    }
}
__device__ __forceinline__ void fence_async() { asm volatile("fence.proxy.async.shared::cta;" ::: "memory"); }
__device__ __forceinline__ void fence_async_g() { asm volatile("fence.proxy.async.global;" ::: "memory"); }
__device__ __forceinline__ void bar_sync(int id, int n) { asm volatile("bar.sync %0, %1;" ::"r"(id), "r"(n) : "memory"); }
__device__ __forceinline__ void tma3(uint32_t dst, const CUtensorMap* tm, int c0, int c1, int c2, uint32_t bar) {
    asm volatile("cp.async.bulk.tensor.3d.shared::cluster.global.mbarrier::complete_tx::bytes [%0], [%1, {%3, %4, %5}], [%2];"
                 ::"r"(dst), "l"(tm), "r"(bar), "r"(c0), "r"(c1), "r"(c2) : "memory");
}
__device__ __forceinline__ void tma4(uint32_t dst, const CUtensorMap* tm, int c0, int c1, int c2, int c3, uint32_t bar) {
    asm volatile("cp.async.bulk.tensor.4d.shared::cluster.global.mbarrier::complete_tx::bytes [%0], [%1, {%3, %4, %5, %6}], [%2];"
                 ::"r"(dst), "l"(tm), "r"(bar), "r"(c0), "r"(c1), "r"(c2), "r"(c3) : "memory");
}
__device__ __forceinline__ void tma4_store(const CUtensorMap* tm, uint32_t src, int c0, int c1, int c2, int c3) {
    asm volatile("cp.async.bulk.tensor.4d.global.shared::cta.bulk_group [%0, {%2, %3, %4, %5}], [%1];"
                 ::"l"(tm), "r"(src), "r"(c0), "r"(c1), "r"(c2), "r"(c3) : "memory");
}
__device__ __forceinline__ void stsm4(uint32_t addr, uint32_t a, uint32_t b, uint32_t c, uint32_t d) {
    asm volatile("stmatrix.sync.aligned.m8n8.x4.shared.b16 [%0], {%1, %2, %3, %4};" ::"r"(addr), "r"(a), "r"(b), "r"(c), "r"(d) : "memory");
}
__device__ __forceinline__ void ldsm4(uint32_t addr, uint32_t (&r)[4]) {
    asm volatile("ldmatrix.sync.aligned.m8n8.x4.shared.b16 {%0, %1, %2, %3}, [%4];" : "=r"(r[0]), "=r"(r[1]), "=r"(r[2]), "=r"(r[3]) : "r"(addr) : "memory");
}
__device__ __forceinline__ void ldsm2(uint32_t addr, uint32_t (&r)[2]) {
    asm volatile("ldmatrix.sync.aligned.m8n8.x2.shared.b16 {%0, %1}, [%2];" : "=r"(r[0]), "=r"(r[1]) : "r"(addr) : "memory");
}
__device__ __forceinline__ void stg4(void* p, uint32_t a, uint32_t b, uint32_t c, uint32_t d) {
    asm volatile("st.global.v4.u32 [%0], {%1, %2, %3, %4};" ::"l"(p), "r"(a), "r"(b), "r"(c), "r"(d) : "memory");
}
__device__ __forceinline__ uint32_t pack2(float lo, float hi) {
    uint32_t r;
    asm("cvt.rn.bf16x2.f32 %0, %1, %2;" : "=r"(r) : "f"(hi), "f"(lo));
    return r;
}
__device__ __forceinline__ uint32_t pack2v(float lo, float hi) {
    uint32_t r;
    asm volatile("cvt.rn.bf16x2.f32 %0, %1, %2;" : "=r"(r) : "f"(hi), "f"(lo));
    return r;
}
__device__ __forceinline__ uint32_t bmul2(uint32_t a, uint32_t b) { uint32_t r; asm("mul.rn.bf16x2 %0, %1, %2;" : "=r"(r) : "r"(a), "r"(b)); return r; }
__device__ __forceinline__ uint32_t bfma2(uint32_t a, uint32_t b, uint32_t c) { uint32_t r; asm("fma.rn.bf16x2 %0, %1, %2, %3;" : "=r"(r) : "r"(a), "r"(b), "r"(c)); return r; }
__device__ __forceinline__ float ex2(float x) { float r; asm("ex2.approx.ftz.f32 %0, %1;" : "=f"(r) : "f"(x)); return r; }
__device__ __forceinline__ float gelu(float x) {
    float t = fmaf(x * x, 0.044715f * 0.7978845608028654f, 0.7978845608028654f), th;
    asm("tanh.approx.f32 %0, %1;" : "=f"(th) : "f"(x * t));
    float hx = 0.5f * x;
    return fmaf(hx, th, hx);
}
__device__ __forceinline__ uint32_t ldg_v(const uint32_t* p) { uint32_t v; asm volatile("ld.global.nc.u32 %0, [%1];" : "=r"(v) : "l"(p)); return v; }
__device__ __forceinline__ float lds_f32(uint32_t a) { float v; asm volatile("ld.shared.f32 %0, [%1];" : "=f"(v) : "r"(a) : "memory"); return v; }
__device__ __forceinline__ void sts_f32(uint32_t a, float v) { asm volatile("st.shared.f32 [%0], %1;" ::"r"(a), "f"(v) : "memory"); }
__device__ __forceinline__ uint32_t atom_inc_s(uint32_t a) { uint32_t v; asm volatile("atom.relaxed.cta.shared.add.u32 %0, [%1], 1;" : "=r"(v) : "r"(a) : "memory"); return v; }
__device__ __forceinline__ void lds4(uint32_t a, uint32_t* r) {
    asm volatile("ld.shared.v4.u32 {%0, %1, %2, %3}, [%4];" : "=r"(r[0]), "=r"(r[1]), "=r"(r[2]), "=r"(r[3]) : "r"(a) : "memory");
}
__device__ __forceinline__ void sts4(uint32_t a, uint32_t x, uint32_t y, uint32_t z, uint32_t t) {
    asm volatile("st.shared.v4.u32 [%0], {%1, %2, %3, %4};" ::"r"(a), "r"(x), "r"(y), "r"(z), "r"(t) : "memory");
}
__device__ __forceinline__ uint32_t bsub2(uint32_t a, uint32_t b) { uint32_t r; asm("sub.rn.bf16x2 %0, %1, %2;" : "=r"(r) : "r"(a), "r"(b)); return r; }
__device__ __forceinline__ float blo(uint32_t v) { return __uint_as_float(v << 16); }
__device__ __forceinline__ float bhi(uint32_t v) { return __uint_as_float(v & 0xffff0000u); }
__device__ __forceinline__ float bfr(float x) { return __bfloat162float(__float2bfloat16_rn(x)); }
__device__ __forceinline__ void flag_add(unsigned* p) { asm volatile("red.release.gpu.global.add.u32 [%0], 1;" ::"l"(p) : "memory"); }
__device__ __forceinline__ void flag_wait(const unsigned* p, unsigned target) {
#pragma unroll 1
    for (uint32_t it = 0;; ++it) {
        unsigned v;
        asm volatile("ld.acquire.gpu.global.u32 %0, [%1];" : "=r"(v) : "l"(p) : "memory");
        if (v >= target) break;
        if (it > (1u << 20)) __trap();
    }
    fence_async_g();
}
template <int N> __device__ __forceinline__ void pin(float (&a)[N]) {
#pragma unroll
    for (int i = 0; i < N; i++) asm volatile("" : "+f"(a[i])::"memory");
}

template <int N> __device__ __forceinline__ void fresh(float (&a)[N]) {
#pragma unroll
    for (int i = 0; i < N; i++) a[i] = 0.f;
    pin(a);
}

__device__ __forceinline__ void wgmma_rs_n64_tb0(float (&d)[32], uint32_t a0, uint32_t a1, uint32_t a2, uint32_t a3, uint64_t db, int scale_d) {
    asm volatile("{\n.reg .pred p;\nsetp.ne.b32 p, %37, 0;\n"
        "wgmma.mma_async.sync.aligned.m64n64k16.f32.bf16.bf16 {%0, %1, %2, %3, %4, %5, %6, %7, %8, %9, %10, %11, %12, %13, %14, %15, %16, %17, %18, %19, %20, %21, %22, %23, %24, %25, %26, %27, %28, %29, %30, %31}, {%32, %33, %34, %35}, %36, p, 1, 1, 0;\n}\n"
        : "+f"(d[0]), "+f"(d[1]), "+f"(d[2]), "+f"(d[3]), "+f"(d[4]), "+f"(d[5]), "+f"(d[6]), "+f"(d[7]), "+f"(d[8]), "+f"(d[9]), "+f"(d[10]), "+f"(d[11]), "+f"(d[12]), "+f"(d[13]), "+f"(d[14]), "+f"(d[15]), "+f"(d[16]), "+f"(d[17]), "+f"(d[18]), "+f"(d[19]), "+f"(d[20]), "+f"(d[21]), "+f"(d[22]), "+f"(d[23]), "+f"(d[24]), "+f"(d[25]), "+f"(d[26]), "+f"(d[27]), "+f"(d[28]), "+f"(d[29]), "+f"(d[30]), "+f"(d[31])
        : "r"(a0), "r"(a1), "r"(a2), "r"(a3), "l"(db), "r"(scale_d));
}

__device__ __forceinline__ void wgmma_ss_n128_tb1(float (&d)[64], uint64_t da, uint64_t db, int scale_d) {
    asm volatile("{\n.reg .pred p;\nsetp.ne.b32 p, %66, 0;\n"
        "wgmma.mma_async.sync.aligned.m64n128k16.f32.bf16.bf16 {%0, %1, %2, %3, %4, %5, %6, %7, %8, %9, %10, %11, %12, %13, %14, %15, %16, %17, %18, %19, %20, %21, %22, %23, %24, %25, %26, %27, %28, %29, %30, %31, %32, %33, %34, %35, %36, %37, %38, %39, %40, %41, %42, %43, %44, %45, %46, %47, %48, %49, %50, %51, %52, %53, %54, %55, %56, %57, %58, %59, %60, %61, %62, %63}, %64, %65, p, 1, 1, 0, 1;\n}\n"
        : "+f"(d[0]), "+f"(d[1]), "+f"(d[2]), "+f"(d[3]), "+f"(d[4]), "+f"(d[5]), "+f"(d[6]), "+f"(d[7]), "+f"(d[8]), "+f"(d[9]), "+f"(d[10]), "+f"(d[11]), "+f"(d[12]), "+f"(d[13]), "+f"(d[14]), "+f"(d[15]), "+f"(d[16]), "+f"(d[17]), "+f"(d[18]), "+f"(d[19]), "+f"(d[20]), "+f"(d[21]), "+f"(d[22]), "+f"(d[23]), "+f"(d[24]), "+f"(d[25]), "+f"(d[26]), "+f"(d[27]), "+f"(d[28]), "+f"(d[29]), "+f"(d[30]), "+f"(d[31]), "+f"(d[32]), "+f"(d[33]), "+f"(d[34]), "+f"(d[35]), "+f"(d[36]), "+f"(d[37]), "+f"(d[38]), "+f"(d[39]), "+f"(d[40]), "+f"(d[41]), "+f"(d[42]), "+f"(d[43]), "+f"(d[44]), "+f"(d[45]), "+f"(d[46]), "+f"(d[47]), "+f"(d[48]), "+f"(d[49]), "+f"(d[50]), "+f"(d[51]), "+f"(d[52]), "+f"(d[53]), "+f"(d[54]), "+f"(d[55]), "+f"(d[56]), "+f"(d[57]), "+f"(d[58]), "+f"(d[59]), "+f"(d[60]), "+f"(d[61]), "+f"(d[62]), "+f"(d[63])
        : "l"(da), "l"(db), "r"(scale_d));
}

__device__ __forceinline__ void wgmma_ss_n256_tb1(float (&d)[128], uint64_t da, uint64_t db, int scale_d) {
    asm volatile("{\n.reg .pred p;\nsetp.ne.b32 p, %130, 0;\n"
        "wgmma.mma_async.sync.aligned.m64n256k16.f32.bf16.bf16 {%0, %1, %2, %3, %4, %5, %6, %7, %8, %9, %10, %11, %12, %13, %14, %15, %16, %17, %18, %19, %20, %21, %22, %23, %24, %25, %26, %27, %28, %29, %30, %31, %32, %33, %34, %35, %36, %37, %38, %39, %40, %41, %42, %43, %44, %45, %46, %47, %48, %49, %50, %51, %52, %53, %54, %55, %56, %57, %58, %59, %60, %61, %62, %63, %64, %65, %66, %67, %68, %69, %70, %71, %72, %73, %74, %75, %76, %77, %78, %79, %80, %81, %82, %83, %84, %85, %86, %87, %88, %89, %90, %91, %92, %93, %94, %95, %96, %97, %98, %99, %100, %101, %102, %103, %104, %105, %106, %107, %108, %109, %110, %111, %112, %113, %114, %115, %116, %117, %118, %119, %120, %121, %122, %123, %124, %125, %126, %127}, %128, %129, p, 1, 1, 0, 1;\n}\n"
        : "+f"(d[0]), "+f"(d[1]), "+f"(d[2]), "+f"(d[3]), "+f"(d[4]), "+f"(d[5]), "+f"(d[6]), "+f"(d[7]), "+f"(d[8]), "+f"(d[9]), "+f"(d[10]), "+f"(d[11]), "+f"(d[12]), "+f"(d[13]), "+f"(d[14]), "+f"(d[15]), "+f"(d[16]), "+f"(d[17]), "+f"(d[18]), "+f"(d[19]), "+f"(d[20]), "+f"(d[21]), "+f"(d[22]), "+f"(d[23]), "+f"(d[24]), "+f"(d[25]), "+f"(d[26]), "+f"(d[27]), "+f"(d[28]), "+f"(d[29]), "+f"(d[30]), "+f"(d[31]), "+f"(d[32]), "+f"(d[33]), "+f"(d[34]), "+f"(d[35]), "+f"(d[36]), "+f"(d[37]), "+f"(d[38]), "+f"(d[39]), "+f"(d[40]), "+f"(d[41]), "+f"(d[42]), "+f"(d[43]), "+f"(d[44]), "+f"(d[45]), "+f"(d[46]), "+f"(d[47]), "+f"(d[48]), "+f"(d[49]), "+f"(d[50]), "+f"(d[51]), "+f"(d[52]), "+f"(d[53]), "+f"(d[54]), "+f"(d[55]), "+f"(d[56]), "+f"(d[57]), "+f"(d[58]), "+f"(d[59]), "+f"(d[60]), "+f"(d[61]), "+f"(d[62]), "+f"(d[63]), "+f"(d[64]), "+f"(d[65]), "+f"(d[66]), "+f"(d[67]), "+f"(d[68]), "+f"(d[69]), "+f"(d[70]), "+f"(d[71]), "+f"(d[72]), "+f"(d[73]), "+f"(d[74]), "+f"(d[75]), "+f"(d[76]), "+f"(d[77]), "+f"(d[78]), "+f"(d[79]), "+f"(d[80]), "+f"(d[81]), "+f"(d[82]), "+f"(d[83]), "+f"(d[84]), "+f"(d[85]), "+f"(d[86]), "+f"(d[87]), "+f"(d[88]), "+f"(d[89]), "+f"(d[90]), "+f"(d[91]), "+f"(d[92]), "+f"(d[93]), "+f"(d[94]), "+f"(d[95]), "+f"(d[96]), "+f"(d[97]), "+f"(d[98]), "+f"(d[99]), "+f"(d[100]), "+f"(d[101]), "+f"(d[102]), "+f"(d[103]), "+f"(d[104]), "+f"(d[105]), "+f"(d[106]), "+f"(d[107]), "+f"(d[108]), "+f"(d[109]), "+f"(d[110]), "+f"(d[111]), "+f"(d[112]), "+f"(d[113]), "+f"(d[114]), "+f"(d[115]), "+f"(d[116]), "+f"(d[117]), "+f"(d[118]), "+f"(d[119]), "+f"(d[120]), "+f"(d[121]), "+f"(d[122]), "+f"(d[123]), "+f"(d[124]), "+f"(d[125]), "+f"(d[126]), "+f"(d[127])
        : "l"(da), "l"(db), "r"(scale_d));
}

__device__ __forceinline__ void wgmma_ss_n32_tb0(float (&d)[16], uint64_t da, uint64_t db, int scale_d) {
    asm volatile("{\n.reg .pred p;\nsetp.ne.b32 p, %18, 0;\n"
        "wgmma.mma_async.sync.aligned.m64n32k16.f32.bf16.bf16 {%0, %1, %2, %3, %4, %5, %6, %7, %8, %9, %10, %11, %12, %13, %14, %15}, %16, %17, p, 1, 1, 0, 0;\n}\n"
        : "+f"(d[0]), "+f"(d[1]), "+f"(d[2]), "+f"(d[3]), "+f"(d[4]), "+f"(d[5]), "+f"(d[6]), "+f"(d[7]), "+f"(d[8]), "+f"(d[9]), "+f"(d[10]), "+f"(d[11]), "+f"(d[12]), "+f"(d[13]), "+f"(d[14]), "+f"(d[15])
        : "l"(da), "l"(db), "r"(scale_d));
}

__device__ __forceinline__ void wgmma_ss_n64_tb0(float (&d)[32], uint64_t da, uint64_t db, int scale_d) {
    asm volatile("{\n.reg .pred p;\nsetp.ne.b32 p, %34, 0;\n"
        "wgmma.mma_async.sync.aligned.m64n64k16.f32.bf16.bf16 {%0, %1, %2, %3, %4, %5, %6, %7, %8, %9, %10, %11, %12, %13, %14, %15, %16, %17, %18, %19, %20, %21, %22, %23, %24, %25, %26, %27, %28, %29, %30, %31}, %32, %33, p, 1, 1, 0, 0;\n}\n"
        : "+f"(d[0]), "+f"(d[1]), "+f"(d[2]), "+f"(d[3]), "+f"(d[4]), "+f"(d[5]), "+f"(d[6]), "+f"(d[7]), "+f"(d[8]), "+f"(d[9]), "+f"(d[10]), "+f"(d[11]), "+f"(d[12]), "+f"(d[13]), "+f"(d[14]), "+f"(d[15]), "+f"(d[16]), "+f"(d[17]), "+f"(d[18]), "+f"(d[19]), "+f"(d[20]), "+f"(d[21]), "+f"(d[22]), "+f"(d[23]), "+f"(d[24]), "+f"(d[25]), "+f"(d[26]), "+f"(d[27]), "+f"(d[28]), "+f"(d[29]), "+f"(d[30]), "+f"(d[31])
        : "l"(da), "l"(db), "r"(scale_d));
}

struct Maps {
    CUtensorMap xa, xa2, xas, wup4, wup8, mqa2, mqa4, mqb1, mqb2, wepi, uc, x, out, wq, wk, fa[3], fb[2];
};

__device__ __forceinline__ uint64_t mkd(uint32_t lo) {
    uint64_t d;
    asm("mov.b64 %0, {%1, %2};" : "=l"(d) : "r"(lo), "r"((1024u >> 4) | (1u << 30)));
    return d;
}
__device__ __forceinline__ void ring_ld(uint32_t sb, uint32_t barbase, uint32_t slot8, const CUtensorMap* tm, int c1, int c2) {
    mbar_expect_tx(sb + barbase + slot8, 8192);
    tma3(sb + R1 + slot8 * 1024, tm, 0, c1, c2, sb + barbase + slot8);
}

__device__ __forceinline__ void ring_half(uint32_t sb, uint32_t slot8, uint32_t hoff, const CUtensorMap* tm, int c1, int c2) {
    mbar_expect_tx(sb + B_R1 + slot8, 8192);
    tma3(sb + R1 + slot8 * 2048 + hoff, tm, 0, c1, c2, sb + B_R1 + slot8);
}
__device__ __forceinline__ void ring_full(uint32_t sb, uint32_t slot8, const CUtensorMap* tm, int c1, int c2) {
    mbar_expect_tx(sb + B_R1 + slot8, 16384);
    mbar_arrive(sb + B_R1 + slot8);
    tma3(sb + R1 + slot8 * 2048, tm, 0, c1, c2, sb + B_R1 + slot8);
}
__device__ __forceinline__ void cta_done(int mode) {
    if (mode == 0 && atomicAdd(&g_sync[4], 1) == NCTA + 1) {
#pragma unroll
        for (int i = 0; i < 5; i++) g_sync[i] = 0;
    }
}

__device__ __forceinline__ void fold_cta(const Maps& mp, uint32_t sb, int mode) {
    constexpr uint32_t F_FULL = MISC, F_EMPTY = MISC + 32, F_T1 = MISC + 64, STG = 49152;
    const int tid = threadIdx.x, f = blockIdx.x - NCTA;
    if (mode == 2) return;
    if (tid == 0) {
        for (int i = 0; i < 4; i++) { mbar_init(sb + F_FULL + 8 * i, 1); mbar_init(sb + F_EMPTY + 8 * i, 2); }
        mbar_init(sb + F_T1, 256);
        asm volatile("fence.mbarrier_init.release.cluster;" ::: "memory");
        fence_async();
    }
    __syncthreads();
    const int wg = __shfl_sync(0xffffffffu, tid >> 7, 0);
    if (wg == 0) {
        if (tid == 0) {
#pragma unroll 1
            for (int it = 0; it < 96; it++) {
                const int p = it >> 3, kc = it & 7, job = p >> 2, st = it & 3;
                if (it == 64) mbar_wait(sb + F_T1, 0);
                if (it >= 4) mbar_wait(sb + F_EMPTY + 8 * st, ((it >> 2) - 1) & 1);
                mbar_expect_tx(sb + F_FULL + 8 * st, STG);
                tma3(sb + st * STG, &mp.fa[job], 0, 256 * f + 128 * ((p >> 1) & 1), kc, sb + F_FULL + 8 * st);
                tma3(sb + st * STG + 16384, &mp.fb[job != 0], 0, 64 * kc + (job == 1 ? 512 : 0), 4 * (p & 1), sb + F_FULL + 8 * st);
            }
        }
        return;
    }
    const int h = wg - 1, lane = tid & 31, w = (tid >> 5) & 3;
    const uint32_t sd = (sb & 0x3FFFF) >> 4;
#pragma unroll 1
    for (int p = 0; p < 12; p++) {
        float acc[128];
        fresh(acc);
#pragma unroll 1
        for (int kc = 0; kc < 8; kc++) {
            const int st = kc & 3;
            mbar_wait(sb + F_FULL + 8 * st, (kc >> 2) & 1);
            wg_fence();
#pragma unroll
            for (int kk = 0; kk < 4; kk++)
                wgmma_ss_n256_tb1(acc, dsc(sd, st * STG + h * 8192 + kk * 32, 16), dsc(sd, st * STG + 16384 + kk * 2048, 8192), 1);
            wg_commit();
            wg_wait<0>();
            if ((tid & 127) == 0) mbar_arrive(sb + F_EMPTY + 8 * st);
        }
        pin(acc);
        const int job = p >> 2;
#pragma unroll
        for (int e = 0; e < 2; e++) {
            int r = 256 * f + 128 * ((p >> 1) & 1) + 64 * h + 16 * w + (lane >> 2) + 8 * e;
            if (job == 1) r = 512 + ((r & ~31) | (((r >> 1) & 3) << 3) | (((r >> 3) & 3) << 1) | (r & 1));
            uint32_t* c = reinterpret_cast<uint32_t*>((job == 0 ? g_t1 : g_wepi) + r * D_ + 256 * (p & 1) + 2 * (lane & 3));
#pragma unroll
            for (int n = 0; n < 32; n++) c[4 * n] = pack2(acc[4 * n + 2 * e], acc[4 * n + 2 * e + 1]);
        }
        if (p == 3) { fence_async_g(); mbar_arrive(sb + F_T1); }
    }
    fence_async_g();
    bar_sync(2, 256);
    if (tid == 128) {
        if (mode == 0) flag_add(&g_sync[3]);
        cta_done(mode);
    }
}

__global__ void __launch_bounds__(384, 1) main_kernel(const __grid_constant__ Maps mp, const bf16* __restrict__ dw, const int mode) {
    extern __shared__ __align__(1024) uint8_t smem[];
    const uint32_t sb = smem_u32(smem);
    const int tid = threadIdx.x;
    if (blockIdx.x >= NCTA) { fold_cta(mp, sb, mode); return; }
    const int b = blockIdx.x / TPB, ti = blockIdx.x % TPB;
    const int piece = blockIdx.x & 127;
    if (tid == 0) {
        mbar_init(sb + B_A, 1); mbar_init(sb + B_MK, 1);
        for (int i = 0; i < 5; i++) mbar_init(sb + B_R1 + 8 * i, 2);
        asm volatile("fence.mbarrier_init.release.cluster;" ::: "memory");
        fence_async();
        mbar_expect_tx(sb + B_A, 65536 + 3072);
        tma4(sb + AT, &mp.x, 0, 62 * ti - 1, 0, b, sb + B_A);
        mbar_expect_tx(sb + B_MK, 65536 + 32768);
        tma3(sb + R0, &mp.wq, 0, 64 * (piece >> 4), 0, sb + B_MK);
        tma3(sb + R1 + 32768, &mp.wk, 0, 32 * (piece & 15), 0, sb + B_MK);
        asm volatile("cp.async.bulk.shared::cluster.global.mbarrier::complete_tx::bytes [%0], [%1], 3072, [%2];" ::"r"(sb + DWS), "l"(dw), "r"(sb + B_A) : "memory");
        for (int i = 0; i < 8; i++) mbar_arrive(sb + B_R1 + 8 * (i >> 1));
        if (mode != 1) {
            ring_full(sb, 32, &mp.wup8, 0, 8);
            ring_full(sb, 0, &mp.wup8, 16, 8);
            ring_full(sb, 8, &mp.wup8, 32, 8);
        }
    } else if (tid == 32) {
        mbar_init(sb + B_LN, 1); mbar_init(sb + B_MQ, 1); mbar_init(sb + B_XA, 1);
        mbar_init(sb + B_H1, 2); mbar_init(sb + B_H2, 1); mbar_init(sb + B_H3, 2);
        for (int i = 0; i < 3; i++) { mbar_init(sb + B_KV + 8 * i, 1); mbar_init(sb + B_P + 8 * i, 4); mbar_init(sb + B_GO + 8 * i, 1); }
        for (int i = 0; i < 12; i++) mbar_init(sb + B_R2 + 8 * i, 1);
        mbar_init(sb + B_UC, 1); mbar_init(sb + B_X, 1);
        for (int i = 0; i < 4; i++) asm volatile("st.shared.u32 [%0], 0;" ::"r"(sb + CNT + 4 * i) : "memory");
        asm volatile("fence.mbarrier_init.release.cluster;" ::: "memory");
        fence_async();
    }
    __syncthreads();
    const int wg = __shfl_sync(0xffffffffu, tid >> 7, 0);
    const int lane = tid & 31, w = (tid >> 5) & 3;
    const bool w0 = __shfl_sync(0xffffffffu, w, 0) == 0;
    const uint32_t sd = (sb & 0x3FFFF) >> 4;
    const uint32_t adA = sd + (AT >> 4) + (1u << 16);
    const uint32_t bd0 = sd + (R1 >> 4);
    const uint32_t bd2k = bd0 + ((2048u >> 4) << 16);
    const bool el = (tid & 127) == 0;
    const uint32_t lrow = 16 * w + (lane & 7) + ((lane >> 3) & 1) * 8;
    const uint32_t loff = lrow * 128 + ((((lane >> 4) ^ lrow) & 7) << 4);
    const int r0 = 16 * w + (lane >> 2);

    if (wg == 0) {
        asm volatile("setmaxnreg.inc.sync.aligned.u32 184;");
        uint32_t q[112];
        PT(0);
        {
            float mq[16];
            fresh(mq);
            mbar_wait(sb + B_MK, 0);
            PT(1);
            wg_fence();
#pragma unroll 1
            for (int c = 0; c < 8; c++)
#pragma unroll
                for (int kk = 0; kk < 4; kk++)
                    wgmma_ss_n32_tb0(mq, dsc(sd, R0 + c * 8192 + kk * 32, 16), dsc(sd, R1 + 32768 + c * 4096 + kk * 32, 16), 1);
            wg_commit();
            wg_wait<0>();
            if (mode != 1 && w0 && elect1()) { ring_full(sb, 16, &mp.wup8, 48, 8); ring_full(sb, 24, &mp.wup8, 64, 8); }
            pin(mq);
            uint32_t* c = reinterpret_cast<uint32_t*>(g_mqk + (64 * (piece >> 4) + r0) * D_ + 32 * (piece & 15) + 2 * (lane & 3));
#pragma unroll
            for (int n = 0; n < 4; n++) { c[4 * n] = pack2(mq[4 * n], mq[4 * n + 1]); c[4 * n + 4 * D_] = pack2(mq[4 * n + 2], mq[4 * n + 3]); }
            fence_async_g();
            bar_sync(1, 128);
            if (el) {
                if (mode == 0) flag_add(&g_sync[2]);
                mbar_wait(sb + B_LN, 0);
                tma4_store(&mp.xas, sb + AT, 0, 62 * ti, 0, b);
                asm volatile("cp.async.bulk.commit_group;" ::: "memory");
                asm volatile("cp.async.bulk.wait_group 0;" ::: "memory");
                if (mode == 0) {
                    fence_async_g();
                    flag_add(&g_sync[b]);
                    PT(12);
                    flag_wait(&g_sync[2], NCTA);
                }
                mbar_arrive(sb + B_MQ);
            }
            PT(13);
            if (mode == 1) return;
        }
        mbar_wait(sb + B_H1, 0);
        PT(2);
        uint32_t slot8 = 8, par = 1, prev8 = 0;
        auto adv = [&]() { prev8 = slot8; slot8 += 8; if (slot8 == 40) { slot8 = 0; par ^= 1; } };
        {
            float acc[128];
            fresh(acc);
            auto step = [&](int i) {
                const uint32_t aa = adA + (i >> 1) * 512 + (i & 1) * 4, bb = bd0 + ((4096u >> 4) << 16) + slot8 * 128;
                wg_fence();
                wgmma_ss_n256_tb1(acc, mkd(aa), mkd(bb), 1);
                wgmma_ss_n256_tb1(acc, mkd(aa + 2), mkd(bb + 128), 1);
                wg_commit();
                wg_wait<1>();
            };
#pragma unroll 1
            for (int i = 0; i < 12; i++) {
                mbar_wait(sb + B_R1 + slot8, par);
                step(i);
                if (i > 0 && w0 && elect1()) ring_full(sb, prev8, &mp.mqa4, 32 * i + 128, 4);
                adv();
            }
#pragma unroll 1
            for (int i = 12; i < 16; i++) {
                mbar_wait(sb + B_R1 + slot8, par);
                if (i == 15 && el) mbar_arrive(sb + B_H2);
                step(i);
                if (w0 && elect1()) ring_full(sb, prev8, &mp.wup8, 16 * i - 192, 0);
                adv();
            }
            wg_wait<0>();
            if (w0 && elect1()) ring_full(sb, prev8, &mp.wup8, 64, 0);
            pin(acc);
            PT(3);
#pragma unroll
            for (int kk = 0; kk < 4; kk++)
                stsm4((sb + QS + loff) ^ (kk << 5), pack2(acc[96 + 8 * kk], acc[97 + 8 * kk]), pack2(acc[98 + 8 * kk], acc[99 + 8 * kk]),
                      pack2(acc[100 + 8 * kk], acc[101 + 8 * kk]), pack2(acc[102 + 8 * kk], acc[103 + 8 * kk]));
            fence_async();
#pragma unroll
            for (int i = 47; i >= 0; i--) q[64 + i] = pack2v(acc[2 * i], acc[2 * i + 1]);
        }
        if (el) {
            if (mode == 0) flag_wait(&g_sync[b], TPB);
            mbar_arrive(sb + B_XA);
        }
        __syncwarp();
        mbar_wait(sb + B_H3, 0);
        PT(4);
        slot8 = 32; par = 0;
#pragma unroll
        for (int half = 0; half < 2; half++) {
            float acc[64];
            fresh(acc);
            auto step = [&](int m) {
                const uint32_t aa = adA + m * 512, bb = bd0 + ((8192u >> 4) << 16) + slot8 * 128;
                mbar_wait(sb + B_R1 + slot8, par);
                wg_fence();
#pragma unroll
                for (int kk = 0; kk < 4; kk++) wgmma_ss_n128_tb1(acc, mkd(aa + 2 * kk), mkd(bb + 128 * kk), 1);
                wg_commit();
                wg_wait<1>();
            };
            if (half == 0) {
#pragma unroll 1
                for (int m = 0; m < 8; m++) {
                    step(m);
                    if (m > 0 && w0 && elect1()) ring_full(sb, prev8, &mp.mqb2, (64 * m + 256) & 511, (m + 4) >> 3 << 1);
                    adv();
                }
            } else {
#pragma unroll 1
                for (int m = 0; m < 4; m++) {
                    step(m);
                    if (m > 0 && w0 && elect1()) ring_full(sb, prev8, &mp.mqb2, 64 * m + 256, 2);
                    adv();
                }
#pragma unroll 1
                for (int m = 4; m < 8; m++) {
                    step(m);
                    if (w0 && elect1()) {
                        if (m == 4) mbar_expect_tx(sb + B_KV + 8, 65536);
                        tma4(sb + R1 + prev8 * 2048, &mp.xa2, 0, 0, 2 * m - 8, b, sb + B_KV + 8);
                    }
                    adv();
                }
            }
            wg_wait<0>();
            if (w0 && elect1()) {
                if (half == 0) ring_full(sb, prev8, &mp.mqb2, 256, 2);
                else {
                    mbar_expect_tx(sb + B_KV + 16, 65536);
                    tma4(sb + R2, &mp.xa, 0, 64, 0, b, sb + B_KV + 16);
                }
            }
            pin(acc);
#pragma unroll
            for (int i = 31; i >= 0; i--) q[32 * half + i] = pack2v(acc[2 * i], acc[2 * i + 1]);
        }
        bar_sync(1, 128);
        PT(5);

        const float CS = 0.04419417382415922f * 1.4426950408889634f;
        float m0 = -INFINITY, m1 = -INFINITY, l0 = 0.f, l1 = 0.f;
        int s = 1, ph = 0;
#pragma unroll 1
        for (int j = 0; j < NKV; j++) {
            float S[32];
            mbar_wait(sb + B_KV + s * 8, ph);
            PL(j, 0);
            const uint32_t kd = sd + s * 4096;
            wg_fence();
#pragma unroll
            for (int kk = 0; kk < 28; kk++)
                wgmma_rs_n64_tb0(S, q[4 * kk], q[4 * kk + 1], q[4 * kk + 2], q[4 * kk + 3], dsc(kd, (kk >> 2) * 8192 + (kk & 3) * 32, 16), kk > 0);
            wg_commit();
#pragma unroll
            for (int kk = 0; kk < 4; kk++)
                wgmma_ss_n64_tb0(S, dsc(sd, QS + kk * 32, 16), dsc(kd, 7 * 8192 + kk * 32, 16), 1);
            wg_commit();
            wg_wait<1>();
            const int sp = s == 0 ? 2 : s - 1;
            if (j > 0 && el) mbar_arrive(sb + B_GO + sp * 8);
            wg_wait<0>();
            pin(S);
            PL(j, 1);
            if (j == NKV - 1) {
#pragma unroll
                for (int i = (T_ - 64 * (NKV - 1)) / 2; i < 32; i++) S[i] = -INFINITY;
            }
            float x0 = fmaxf(S[0], S[1]), x1 = fmaxf(S[2], S[3]);
#pragma unroll
            for (int n = 1; n < 8; n++) {
                x0 = fmaxf(x0, fmaxf(S[4 * n], S[4 * n + 1]));
                x1 = fmaxf(x1, fmaxf(S[4 * n + 2], S[4 * n + 3]));
            }
            x0 = fmaxf(x0, __shfl_xor_sync(0xffffffffu, x0, 1));
            x1 = fmaxf(x1, __shfl_xor_sync(0xffffffffu, x1, 1));
            x0 = fmaxf(x0, __shfl_xor_sync(0xffffffffu, x0, 2));
            x1 = fmaxf(x1, __shfl_xor_sync(0xffffffffu, x1, 2));
            x0 = fmaxf(x0, m0); x1 = fmaxf(x1, m1);
            const float sc0 = ex2((m0 - x0) * CS), sc1 = ex2((m1 - x1) * CS);
            m0 = x0; m1 = x1;
            const float n0 = -x0 * CS, n1 = -x1 * CS;
            float a0 = 0.f, a1 = 0.f;
            const uint32_t pb = sb + R3 + sp * 8192;
#pragma unroll
            for (int kk = 0; kk < 4; kk++) {
                float p[8];
#pragma unroll
                for (int e = 0; e < 8; e++) p[e] = ex2(fmaf(S[8 * kk + e], CS, (e & 2) ? n1 : n0));
                a0 += (p[0] + p[1]) + (p[4] + p[5]);
                a1 += (p[2] + p[3]) + (p[6] + p[7]);
                stsm4((pb + loff) ^ (kk << 5), pack2(p[0], p[1]), pack2(p[2], p[3]), pack2(p[4], p[5]), pack2(p[6], p[7]));
            }
            l0 = fmaf(l0, sc0, a0); l1 = fmaf(l1, sc1, a1);
            if ((lane & 3) == 0) { sts_f32(sb + SCL + s * 256 + r0 * 4, sc0); sts_f32(sb + SCL + s * 256 + r0 * 4 + 32, sc1); }
            if (j == NKV - 1) {
                l0 += __shfl_xor_sync(0xffffffffu, l0, 1); l1 += __shfl_xor_sync(0xffffffffu, l1, 1);
                l0 += __shfl_xor_sync(0xffffffffu, l0, 2); l1 += __shfl_xor_sync(0xffffffffu, l1, 2);
                if ((lane & 3) == 0) { sts_f32(sb + LINV + r0 * 4, 1.f / l0); sts_f32(sb + LINV + r0 * 4 + 32, 1.f / l1); }
            }
            fence_async();
            __syncwarp();
            if (lane == 0) mbar_arrive(sb + B_P + s * 8);
            if (j == NKV - 1 && el) mbar_arrive(sb + B_GO + s * 8);
            PL(j, 2);
            if (++s == 3) s = 0;
            if (s == 1) ph ^= 1;
        }
        PDUMP();
    } else {
        asm volatile("setmaxnreg.dec.sync.aligned.u32 160;");
        const int h = wg - 1;
        mbar_wait(sb + B_A, 0);
        PT(0);
#pragma unroll 1
        for (int bt = 0; bt < 2; bt++) {
            uint32_t v[4][8];
            float mu[4], vr[4];
            const uint32_t la = sb + AT + (lane >> 3) * 8192 + (32 * h + 8 * w + 4 * bt) * 128 + (((lane & 7) ^ (4 * bt)) << 4);
#pragma unroll
            for (int r = 0; r < 4; r++) { lds4((la ^ (r << 4)) + r * 128, v[r]); lds4((la ^ (r << 4)) + r * 128 + 32768, v[r] + 4); }
#pragma unroll
            for (int r = 0; r < 4; r++) {
                float s0 = 0.f, s1 = 0.f;
#pragma unroll
                for (int i = 0; i < 8; i++) { s0 += blo(v[r][i]); s1 += bhi(v[r][i]); }
                mu[r] = s0 + s1;
            }
#pragma unroll
            for (int o = 16; o; o >>= 1)
#pragma unroll
                for (int r = 0; r < 4; r++) mu[r] += __shfl_xor_sync(0xffffffffu, mu[r], o);
#pragma unroll
            for (int r = 0; r < 4; r++) {
                mu[r] *= (1.f / D_);
                float s0 = 0.f, s1 = 0.f;
#pragma unroll
                for (int i = 0; i < 8; i++) { const float d0 = blo(v[r][i]) - mu[r], d1 = bhi(v[r][i]) - mu[r]; s0 = fmaf(d0, d0, s0); s1 = fmaf(d1, d1, s1); }
                vr[r] = s0 + s1;
            }
#pragma unroll
            for (int o = 16; o; o >>= 1)
#pragma unroll
                for (int r = 0; r < 4; r++) vr[r] += __shfl_xor_sync(0xffffffffu, vr[r], o);
#pragma unroll
            for (int r = 0; r < 4; r++) {
                const uint32_t m2 = pack2(mu[r], mu[r]);
                const float rinv = 1.f / bfr(sqrtf(bfr(bfr(vr[r] * (1.f / D_)) + 1e-5f)));
#pragma unroll
                for (int i = 0; i < 8; i++) { const uint32_t d = bsub2(v[r][i], m2); v[r][i] = pack2(blo(d) * rinv, bhi(d) * rinv); }
                sts4((la ^ (r << 4)) + r * 128, v[r][0], v[r][1], v[r][2], v[r][3]);
                sts4((la ^ (r << 4)) + r * 128 + 32768, v[r][4], v[r][5], v[r][6], v[r][7]);
            }
        }
        fence_async();
        bar_sync(2, 256);
        if (tid == 128) mbar_arrive(sb + B_LN);
        if (mode == 1) return;
        float acc[128];
#pragma unroll
        for (int pass = 0; pass < 2; pass++) {
            if (pass == 1) mbar_wait(sb + B_H2, 0);
            PT(1 + 3 * pass);
            fresh(acc);
            uint32_t slot8 = pass ? 16 : 32, par = 0, prev8 = 0;
            auto adv = [&]() { prev8 = slot8; slot8 += 8; if (slot8 == 40) { slot8 = 0; par ^= 1; } };
            auto step = [&](int kk) {
                wg_fence();
                wgmma_ss_n256_tb1(acc, mkd(adA + (kk >> 2) * 512 + (kk & 3) * 2), mkd(bd2k + h * 512 + slot8 * 128), 1);
                wg_commit();
                wg_wait<1>();
            };
#pragma unroll 1
            for (int kk = 0; kk < 28; kk++) {
                mbar_wait(sb + B_R1 + slot8, par);
                step(kk);
                if (kk > 0 && w0 && elect1()) ring_half(sb, prev8, h * 8192, &mp.wup4, 16 * kk + 64, (pass ? 0 : 8) + 4 * h);
                adv();
            }
            if (pass == 0 && w0) mbar_wait(sb + B_MQ, 0);
#pragma unroll 1
            for (int kk = 28; kk < 32; kk++) {
                mbar_wait(sb + B_R1 + slot8, par);
                if (kk == 31 && el) mbar_arrive(sb + (pass ? B_H3 : B_H1));
                step(kk);
                if (w0 && elect1()) ring_half(sb, prev8, h * 8192, pass ? &mp.mqb1 : &mp.mqa2, (pass ? 64 : 32) * (kk - 28), pass ? h : 4 + 2 * h);
                adv();
            }
            wg_wait<0>();
            if (w0 && elect1()) ring_half(sb, prev8, h * 8192, pass ? &mp.mqb1 : &mp.mqa2, pass ? 256 : 128, pass ? h : 4 + 2 * h);
            pin(acc);
            PT(2 + 3 * pass);
            if (pass == 0) {
#pragma unroll
                for (int i = 0; i < 128; i++) acc[i] = gelu(acc[i]);
                float s0 = 0.f, s1 = 0.f;
#pragma unroll
                for (int n = 0; n < 32; n++) { s0 += acc[4 * n] + acc[4 * n + 1]; s1 += acc[4 * n + 2] + acc[4 * n + 3]; }
                s0 += __shfl_xor_sync(0xffffffffu, s0, 1); s1 += __shfl_xor_sync(0xffffffffu, s1, 1);
                s0 += __shfl_xor_sync(0xffffffffu, s0, 2); s1 += __shfl_xor_sync(0xffffffffu, s1, 2);
                s0 *= (1.f / 256.f); s1 *= (1.f / 256.f);
                float v0 = 0.f, v1 = 0.f;
#pragma unroll
                for (int n = 0; n < 32; n++) {
                    float d0 = acc[4 * n] - s0, d1 = acc[4 * n + 1] - s0, d2 = acc[4 * n + 2] - s1, d3 = acc[4 * n + 3] - s1;
                    v0 = fmaf(d0, d0, v0); v0 = fmaf(d1, d1, v0); v1 = fmaf(d2, d2, v1); v1 = fmaf(d3, d3, v1);
                }
                v0 += __shfl_xor_sync(0xffffffffu, v0, 1); v1 += __shfl_xor_sync(0xffffffffu, v1, 1);
                v0 += __shfl_xor_sync(0xffffffffu, v0, 2); v1 += __shfl_xor_sync(0xffffffffu, v1, 2);
                if ((lane & 3) == 0) {
                    uint32_t a = sb + STAT + h * 512 + r0 * 8;
                    sts_f32(a, s0); sts_f32(a + 4, v0); sts_f32(a + 64, s1); sts_f32(a + 68, v1);
                }
                bar_sync(2, 256);
                {
                    uint32_t a = sb + STAT + (h ^ 1) * 512 + r0 * 8;
                    float t0 = lds_f32(a), u0 = lds_f32(a + 4), t1 = lds_f32(a + 64), u1 = lds_f32(a + 68);
                    v0 = (v0 + u0 + (s0 - t0) * (s0 - t0) * 128.f) * (1.f / 512.f);
                    v1 = (v1 + u1 + (s1 - t1) * (s1 - t1) * 128.f) * (1.f / 512.f);
                    s0 = 0.5f * (s0 + t0); s1 = 0.5f * (s1 + t1);
                }
                v0 = rsqrtf(v0 + 1e-5f); v1 = rsqrtf(v1 + 1e-5f);
                s0 = -s0 * v0; s1 = -s1 * v1;
#pragma unroll
                for (int p = 0; p < 16; p++)
                    stsm4(((sb + R0 + h * 32768 + loff) ^ ((p & 3) << 5)) + (p >> 2) * 8192,
                          pack2(fmaf(acc[8 * p], v0, s0), fmaf(acc[8 * p + 1], v0, s0)), pack2(fmaf(acc[8 * p + 2], v1, s1), fmaf(acc[8 * p + 3], v1, s1)),
                          pack2(fmaf(acc[8 * p + 4], v0, s0), fmaf(acc[8 * p + 5], v0, s0)), pack2(fmaf(acc[8 * p + 6], v1, s1), fmaf(acc[8 * p + 7], v1, s1)));
            } else {
                bar_sync(3 + h, 128);
                const uint32_t rm = lrow == 0 ? 0 : lrow - 1, rp = lrow == 63 ? 63 : lrow + 1;
                const uint32_t gb = sb + R0 + h * 32768;
                const uint32_t am = gb + rm * 128 + ((((lane >> 4) ^ rm) & 7) << 4), ap = gb + rp * 128 + ((((lane >> 4) ^ rp) & 7) << 4), ac = gb + loff;
                const uint32_t dwa = sb + DWS + 512 * h + ((lane >> 3) & 1) * 16 + (lane >> 4) * 1024;
                bf16* ucp = g_uc + ((size_t)blockIdx.x * 64 + r0) * D_ + 256 * h + 8 * (lane & 3);
#pragma unroll
                for (int m = 7; m >= 0; m--) {
                    uint32_t o[8];
#pragma unroll
                    for (int pp = 1; pp >= 0; pp--) {
                        const int p = 2 * m + pp;
                        const uint32_t co = (p >> 2) * 8192, cx = (p & 3) << 5;
                        uint32_t u[4], g[4], cv[4], d[4], d2[2];
#pragma unroll
                        for (int e = 3; e >= 0; e--) u[e] = pack2v(gelu(acc[8 * p + 2 * e]), gelu(acc[8 * p + 2 * e + 1]));
                        ldsm4(dwa + 32 * p, d);
                        ldsm2(dwa + 32 * p + 2048, d2);
                        ldsm4((am ^ cx) + co, g);
#pragma unroll
                        for (int e = 0; e < 4; e++) cv[e] = bmul2(g[e], d[e >> 1]);
                        ldsm4((ac ^ cx) + co, g);
#pragma unroll
                        for (int e = 0; e < 4; e++) cv[e] = bfma2(g[e], d[2 + (e >> 1)], cv[e]);
                        ldsm4((ap ^ cx) + co, g);
#pragma unroll
                        for (int e = 0; e < 4; e++) o[4 * (e & 1) + 2 * pp + (e >> 1)] = bmul2(u[e], bfma2(g[e], d2[e >> 1], cv[e]));
                    }
                    stg4(ucp + 32 * m, o[0], o[1], o[2], o[3]);
                    stg4(ucp + 32 * m + 8 * D_, o[4], o[5], o[6], o[7]);
                }
                bar_sync(2, 256);
                if (tid == 128) {
                    mbar_wait(sb + B_XA, 0);
                    mbar_expect_tx(sb + B_KV, 65536);
                    tma4(sb + R0, &mp.xa, 0, 128, 0, b, sb + B_KV);
                }
            }
            PT(3 + 3 * pass);
        }
        int s = 1, ph = 0;
        fresh(acc);
#pragma unroll 1
        for (int j = 0; j < NKV; j++) {
            mbar_wait(sb + B_P + s * 8, ph);
            PL(j, 0);
            if (j > 0) {
                const float sc0 = lds_f32(sb + SCL + s * 256 + r0 * 4), sc1 = lds_f32(sb + SCL + s * 256 + r0 * 4 + 32);
                if (__any_sync(0xffffffffu, sc0 != 1.f || sc1 != 1.f)) {
#pragma unroll
                    for (int n = 0; n < 32; n++) { acc[4 * n] *= sc0; acc[4 * n + 1] *= sc0; acc[4 * n + 2] *= sc1; acc[4 * n + 3] *= sc1; }
                }
            }
            mbar_wait(sb + B_KV + s * 8, ph);
            mbar_wait(sb + B_GO + s * 8, ph);
            PL(j, 1);
            const uint32_t vd = sd + s * 4096 + h * 2048, pd = sd + (s == 0 ? 2 : s - 1) * 512;
            pin(acc);
            wg_fence();
#pragma unroll
            for (int kk = 0; kk < 4; kk++) wgmma_ss_n256_tb1(acc, dsc(pd, R3 + kk * 32, 16), dsc(vd, kk * 2048, 8192), 1);
            wg_commit();
            wg_wait<0>();
            pin(acc);
            PL(j, 2);
            if (w0 && elect1()) {
                if (j == NKV - 5 && mode == 0) flag_wait(&g_sync[3], 2);
                if (atom_inc_s(sb + CNT + 4 * s) & 1) {
                    if (j + 3 < NKV) {
                        mbar_expect_tx(sb + B_KV + s * 8, 65536);
                        tma4(sb + s * 65536, &mp.xa, 0, 64 * (j + 3), 0, b, sb + B_KV + s * 8);
                    } else if (j < NKV - 1) {
                        const int n0 = j == NKV - 3 ? 0 : 8, n1 = j == NKV - 3 ? 8 : 12;
#pragma unroll 1
                        for (int n = n0; n < n1; n++) ring_ld(sb, B_R2, n * 8, &mp.wepi, 16 * (n >> 1), 4 * (n & 1));
                    }
                }
            }
            if (++s == 3) s = 0;
            if (s == 1) ph ^= 1;
        }
        {
            const float i0 = lds_f32(sb + LINV + r0 * 4), i1 = lds_f32(sb + LINV + r0 * 4 + 32);
#pragma unroll
            for (int p = 0; p < 16; p++)
                stsm4(((sb + R0 + h * 32768 + loff) ^ ((p & 3) << 5)) + (p >> 2) * 8192,
                      pack2(acc[8 * p] * i0, acc[8 * p + 1] * i0), pack2(acc[8 * p + 2] * i1, acc[8 * p + 3] * i1),
                      pack2(acc[8 * p + 4] * i0, acc[8 * p + 5] * i0), pack2(acc[8 * p + 6] * i1, acc[8 * p + 7] * i1));
        }
        fence_async();
        fence_async_g();
        bar_sync(2, 256);
        if (tid == 128) {
            mbar_expect_tx(sb + B_UC, 65536);
            tma3(sb + UCT, &mp.uc, 0, 64 * blockIdx.x, 0, sb + B_UC);
        }
        PT(7);
        fresh(acc);
        {
            uint32_t slot8 = 8 * h, par = 0, prev8 = 0;
#pragma unroll 1
            for (int kk = 0; kk < 64; kk++) {
                if (kk == 32) mbar_wait(sb + B_UC, 0);
                mbar_wait(sb + B_R2 + slot8, par);
                wg_fence();
                wgmma_ss_n256_tb1(acc, mkd(sd + (1u << 16) + (kk < 32 ? (R0 >> 4) : (UCT >> 4) - 4096) + (kk >> 2) * 512 + (kk & 3) * 2), mkd(bd2k + slot8 * 64), 1);
                wg_commit();
                wg_wait<1>();
                if (kk > 0 && w0 && elect1()) {
                    if (kk < 59) ring_ld(sb, B_R2, prev8, &mp.wepi, 16 * (kk + 5), 4 * h);
                    if (kk == 32 && (atom_inc_s(sb + CNT + 12) & 1)) {
                        mbar_expect_tx(sb + B_X, 65536);
                        tma4(sb + R0, &mp.x, 0, 62 * ti, 0, b, sb + B_X);
                    }
                }
                prev8 = slot8;
                slot8 += 16;
                if (slot8 >= 96) { slot8 -= 96; par ^= 1; }
            }
        }
        wg_wait<0>();
        pin(acc);
        PT(8);
        mbar_wait(sb + B_X, 0);
        PT(9);
        {
            const uint32_t sr = (lrow + 63) & 63;
            const uint32_t xoff = sr * 128 + ((((lane >> 4) ^ sr) & 7) << 4);
#pragma unroll
            for (int p = 0; p < 16; p++) {
                const uint32_t a = ((sb + R0 + h * 32768 + xoff) ^ ((p & 3) << 5)) + (p >> 2) * 8192;
                uint32_t xv[4];
                ldsm4(a, xv);
#pragma unroll
                for (int e = 0; e < 4; e++)
                    xv[e] = pack2(acc[8 * p + 2 * e] + __uint_as_float(xv[e] << 16), acc[8 * p + 2 * e + 1] + __uint_as_float(xv[e] & 0xffff0000u));
                stsm4(a, xv[0], xv[1], xv[2], xv[3]);
            }
        }
        fence_async();
        bar_sync(3 + h, 128);
        if (el) {
            for (int c = 0; c < 4; c++) tma4_store(&mp.out, sb + R0 + (4 * h + c) * 8192, 0, 62 * ti, 4 * h + c, b);
            asm volatile("cp.async.bulk.commit_group;" ::: "memory");
            PT(10);
            if (h == 0) cta_done(mode);
            asm volatile("cp.async.bulk.wait_group.read 0;" ::: "memory");
        }
        PT(11);
        PDUMP();
    }
}

typedef CUresult (*PFN_enc)(CUtensorMap*, CUtensorMapDataType, cuuint32_t, void*, const cuuint64_t*, const cuuint64_t*,
                            const cuuint32_t*, const cuuint32_t*, CUtensorMapInterleave, CUtensorMapSwizzle,
                            CUtensorMapL2promotion, CUtensorMapFloatOOBfill);

static void enc(PFN_enc f, CUtensorMap* m, void* base, int rank, const cuuint64_t* dims, const cuuint64_t* strides, const cuuint32_t* box) {
    cuuint32_t es[5] = {1, 1, 1, 1, 1};
    f(m, CU_TENSOR_MAP_DATA_TYPE_BFLOAT16, rank, base, dims, strides, box, es, CU_TENSOR_MAP_INTERLEAVE_NONE,
      CU_TENSOR_MAP_SWIZZLE_128B, CU_TENSOR_MAP_L2_PROMOTION_L2_256B, CU_TENSOR_MAP_FLOAT_OOB_FILL_NONE);
}
static void enc_act(PFN_enc f, CUtensorMap* m, void* base, int rows, int chunks, int trows = T_, int pitch = T_) {
    cuuint64_t dims[4] = {64, (cuuint64_t)trows, 8, (cuuint64_t)NB_};
    cuuint64_t st[3] = {1024, 128, (cuuint64_t)pitch * 1024};
    cuuint32_t box[4] = {64, (cuuint32_t)rows, (cuuint32_t)chunks, 1};
    enc(f, m, base, 4, dims, st, box);
}
static void enc_w(PFN_enc f, CUtensorMap* m, void* base, int krows, int ncols, int bk, int bc) {
    cuuint64_t dims[3] = {64, (cuuint64_t)krows, (cuuint64_t)(ncols / 64)};
    cuuint64_t st[2] = {(cuuint64_t)ncols * 2, 128};
    cuuint32_t box[3] = {64, (cuuint32_t)bk, (cuuint32_t)bc};
    enc(f, m, base, 3, dims, st, box);
}

extern "C" void kernel_launch(void* const* d_in, const int* in_sizes, int n_in, void* d_out, int out_size) {
    const bf16* x = (const bf16*)d_in[0];
    static PFN_enc fenc = nullptr;
    static void *p_xa, *p_mqk, *p_wepi, *p_uc, *p_t1;
    static int fused = 0;
    if (!fenc) {
        void* fn = nullptr;
        cudaDriverEntryPointQueryResult qr;
        cudaGetDriverEntryPoint("cuTensorMapEncodeTiled", &fn, cudaEnableDefault, &qr);
        fenc = (PFN_enc)fn;
        cudaGetSymbolAddress(&p_xa, g_xa);
        cudaGetSymbolAddress(&p_mqk, g_mqk);
        cudaGetSymbolAddress(&p_wepi, g_wepi);
        cudaGetSymbolAddress(&p_uc, g_uc);
        cudaGetSymbolAddress(&p_t1, g_t1);
        cudaFuncSetAttribute(main_kernel, cudaFuncAttributeMaxDynamicSharedMemorySize, SMEM_BYTES);
        int dev = 0, sms = 0, occ = 0;
        cudaGetDevice(&dev);
        cudaDeviceGetAttribute(&sms, cudaDevAttrMultiProcessorCount, dev);
        cudaOccupancyMaxActiveBlocksPerMultiprocessor(&occ, main_kernel, 384, SMEM_BYTES);
        fused = sms * occ >= NCTA + 2;
    }
    Maps mp;
    enc_act(fenc, &mp.xa, (char*)p_xa + 1024, 64, 8, T_, T_ + 8);
    enc_act(fenc, &mp.xa2, (char*)p_xa + 1024, 64, 2, T_, T_ + 8);
    enc_act(fenc, &mp.xas, p_xa, 64, 8, T_ + 1, T_ + 8);
    enc_act(fenc, &mp.x, (void*)x, 64, 8);
    enc_act(fenc, &mp.out, d_out, 62, 1);
    enc_w(fenc, &mp.wup4, d_in[5], 512, 1024, 16, 4);
    enc_w(fenc, &mp.wup8, d_in[5], 512, 1024, 16, 8);
    enc_w(fenc, &mp.mqa2, p_mqk, 512, 512, 32, 2);
    enc_w(fenc, &mp.mqa4, p_mqk, 512, 512, 32, 4);
    enc_w(fenc, &mp.mqb1, p_mqk, 512, 512, 64, 1);
    enc_w(fenc, &mp.mqb2, p_mqk, 512, 512, 64, 2);
    enc_w(fenc, &mp.wepi, p_wepi, 1024, 512, 16, 4);
    enc_w(fenc, &mp.uc, p_uc, NCTA * 64, 512, 64, 8);
    enc_w(fenc, &mp.wq, d_in[1], 512, 512, 64, 8);
    enc_w(fenc, &mp.wk, d_in[2], 512, 512, 32, 8);
    enc_w(fenc, &mp.fa[0], d_in[3], 512, 512, 128, 1);
    enc_w(fenc, &mp.fa[1], d_in[7], 512, 512, 128, 1);
    enc_w(fenc, &mp.fa[2], p_t1, 512, 512, 128, 1);
    enc_w(fenc, &mp.fb[0], d_in[4], 512, 512, 64, 4);
    enc_w(fenc, &mp.fb[1], d_in[8], 1024, 512, 64, 4);
    cudaStream_t st = cudaStreamPerThread;
    if (fused) {
        main_kernel<<<NCTA + 2, 384, SMEM_BYTES, st>>>(mp, (const bf16*)d_in[6], 0);
    } else {
        main_kernel<<<NCTA + 2, 384, SMEM_BYTES, st>>>(mp, (const bf16*)d_in[6], 1);
        main_kernel<<<NCTA + 2, 384, SMEM_BYTES, st>>>(mp, (const bf16*)d_in[6], 2);
    }
}
```

```cpp
#include <cuda_runtime.h>
#include <cuda_bf16.h>
#include <cuda.h>
#include <stdint.h>

typedef __nv_bfloat16 bf16;

constexpr int T_ = 4000, D_ = 512, NB_ = 2;
constexpr int TPB = 65;
constexpr int NCTA = TPB * NB_;
constexpr int NKV = 63;

__device__ __align__(1024) bf16 g_xa[NB_ * (T_ + 8) * D_];
__device__ __align__(1024) bf16 g_mqk[D_ * D_];
__device__ __align__(1024) bf16 g_t1[D_ * D_];
__device__ __align__(1024) bf16 g_wepi[2 * D_ * D_];
__device__ __align__(1024) bf16 g_uc[NCTA * 64 * D_];
__device__ unsigned g_sync[8];

#define PT(i)
#define PL(j, q)
#define PDUMP()

constexpr uint32_t R0 = 0, R1 = 65536, R2 = 131072, R3 = 196608, QS = 221184, MISC = 229376;
constexpr uint32_t AT = 147456, DWS = R3 + 16384, UCT = 163840;
constexpr uint32_t SMEM_BYTES = 232448;
constexpr uint32_t B_A = MISC, B_R1 = MISC + 8  , B_MK = MISC + 48, B_LN = MISC + 56, B_MQ = MISC + 64, B_XA = MISC + 72,
                   B_H1 = MISC + 88, B_H2 = MISC + 96, B_H3 = MISC + 104,
                   B_KV = MISC + 112, B_P = MISC + 136, B_GO = MISC + 160, B_R2 = MISC + 184, B_UC = MISC + 280,
                   B_X = MISC + 288, CNT = MISC + 296  , SCL = MISC + 512  ,
                   LINV = MISC + 1280  , STAT = MISC + 1536  ;

__device__ __forceinline__ uint32_t smem_u32(const void* p) { return (uint32_t)__cvta_generic_to_shared(p); }
__device__ __forceinline__ void wg_fence() { asm volatile("wgmma.fence.sync.aligned;" ::: "memory"); }
__device__ __forceinline__ void wg_commit() { asm volatile("wgmma.commit_group.sync.aligned;" ::: "memory"); }
template <int N> __device__ __forceinline__ void wg_wait() { asm volatile("wgmma.wait_group.sync.aligned %0;" ::"n"(N) : "memory"); }
__device__ __forceinline__ uint64_t dsc(uint32_t sd, uint32_t off, uint32_t lbo) {
    uint32_t lo = sd + (off >> 4) + ((lbo >> 4) << 16);
    uint64_t d;
    asm("mov.b64 %0, {%1, %2};" : "=l"(d) : "r"(lo), "r"((1024u >> 4) | (1u << 30)));
    return d;
}
__device__ __forceinline__ bool elect1() {
    uint32_t p;
    asm volatile("{\n.reg .pred p;\nelect.sync _|p, 0xffffffff;\nselp.u32 %0, 1, 0, p;\n}\n" : "=r"(p));
    return p != 0;
}
__device__ __forceinline__ void mbar_init(uint32_t bar, int cnt) { asm volatile("mbarrier.init.shared::cta.b64 [%0], %1;" ::"r"(bar), "r"(cnt) : "memory"); }
__device__ __forceinline__ void mbar_expect_tx(uint32_t bar, uint32_t bytes) { asm volatile("mbarrier.arrive.expect_tx.shared::cta.b64 _, [%0], %1;" ::"r"(bar), "r"(bytes) : "memory"); }
__device__ __forceinline__ void mbar_arrive(uint32_t bar) { asm volatile("mbarrier.arrive.shared::cta.b64 _, [%0];" ::"r"(bar) : "memory"); }
__device__ __forceinline__ void mbar_wait(uint32_t bar, uint32_t parity) {
    uint32_t ok;
#pragma unroll 1
    for (uint32_t it = 0;; ++it) {
        asm volatile("{\n.reg .pred p;\nmbarrier.try_wait.parity.shared::cta.b64 p, [%1], %2;\nselp.u32 %0, 1, 0, p;\n}\n" : "=r"(ok) : "r"(bar), "r"(parity) : "memory");
        if (ok) break;
        if (it > (1u << 20)) __trap();
    }
}
__device__ __forceinline__ void fence_async() { asm volatile("fence.proxy.async.shared::cta;" ::: "memory"); }
__device__ __forceinline__ void fence_async_g() { asm volatile("fence.proxy.async.global;" ::: "memory"); }
__device__ __forceinline__ void bar_sync(int id, int n) { asm volatile("bar.sync %0, %1;" ::"r"(id), "r"(n) : "memory"); }
__device__ __forceinline__ void tma3(uint32_t dst, const CUtensorMap* tm, int c0, int c1, int c2, uint32_t bar) {
    asm volatile("cp.async.bulk.tensor.3d.shared::cluster.global.mbarrier::complete_tx::bytes [%0], [%1, {%3, %4, %5}], [%2];"
                 ::"r"(dst), "l"(tm), "r"(bar), "r"(c0), "r"(c1), "r"(c2) : "memory");
}
__device__ __forceinline__ void tma4(uint32_t dst, const CUtensorMap* tm, int c0, int c1, int c2, int c3, uint32_t bar) {
    asm volatile("cp.async.bulk.tensor.4d.shared::cluster.global.mbarrier::complete_tx::bytes [%0], [%1, {%3, %4, %5, %6}], [%2];"
                 ::"r"(dst), "l"(tm), "r"(bar), "r"(c0), "r"(c1), "r"(c2), "r"(c3) : "memory");
}
__device__ __forceinline__ void tma4_store(const CUtensorMap* tm, uint32_t src, int c0, int c1, int c2, int c3) {
    asm volatile("cp.async.bulk.tensor.4d.global.shared::cta.bulk_group [%0, {%2, %3, %4, %5}], [%1];"
                 ::"l"(tm), "r"(src), "r"(c0), "r"(c1), "r"(c2), "r"(c3) : "memory");
}
__device__ __forceinline__ void stsm4(uint32_t addr, uint32_t a, uint32_t b, uint32_t c, uint32_t d) {
    asm volatile("stmatrix.sync.aligned.m8n8.x4.shared.b16 [%0], {%1, %2, %3, %4};" ::"r"(addr), "r"(a), "r"(b), "r"(c), "r"(d) : "memory");
}
__device__ __forceinline__ void ldsm4(uint32_t addr, uint32_t (&r)[4]) {
    asm volatile("ldmatrix.sync.aligned.m8n8.x4.shared.b16 {%0, %1, %2, %3}, [%4];" : "=r"(r[0]), "=r"(r[1]), "=r"(r[2]), "=r"(r[3]) : "r"(addr) : "memory");
}
__device__ __forceinline__ void ldsm2(uint32_t addr, uint32_t (&r)[2]) {
    asm volatile("ldmatrix.sync.aligned.m8n8.x2.shared.b16 {%0, %1}, [%2];" : "=r"(r[0]), "=r"(r[1]) : "r"(addr) : "memory");
}
__device__ __forceinline__ void stg4(void* p, uint32_t a, uint32_t b, uint32_t c, uint32_t d) {
    asm volatile("st.global.v4.u32 [%0], {%1, %2, %3, %4};" ::"l"(p), "r"(a), "r"(b), "r"(c), "r"(d) : "memory");
}
__device__ __forceinline__ uint32_t pack2(float lo, float hi) {
    uint32_t r;
    asm("cvt.rn.bf16x2.f32 %0, %1, %2;" : "=r"(r) : "f"(hi), "f"(lo));
    return r;
}
__device__ __forceinline__ uint32_t pack2v(float lo, float hi) {
    uint32_t r;
    asm volatile("cvt.rn.bf16x2.f32 %0, %1, %2;" : "=r"(r) : "f"(hi), "f"(lo));
    return r;
}
__device__ __forceinline__ uint32_t bmul2(uint32_t a, uint32_t b) { uint32_t r; asm("mul.rn.bf16x2 %0, %1, %2;" : "=r"(r) : "r"(a), "r"(b)); return r; }
__device__ __forceinline__ uint32_t bfma2(uint32_t a, uint32_t b, uint32_t c) { uint32_t r; asm("fma.rn.bf16x2 %0, %1, %2, %3;" : "=r"(r) : "r"(a), "r"(b), "r"(c)); return r; }
__device__ __forceinline__ float ex2(float x) { float r; asm("ex2.approx.ftz.f32 %0, %1;" : "=f"(r) : "f"(x)); return r; }
__device__ __forceinline__ float rcp(float x) { float r; asm("rcp.approx.ftz.f32 %0, %1;" : "=f"(r) : "f"(x)); return r; }
__device__ __forceinline__ float gelu(float x) {
    float t = fmaf(x * x, 0.044715f * 0.7978845608028654f, 0.7978845608028654f), th;
    asm("tanh.approx.f32 %0, %1;" : "=f"(th) : "f"(x * t));
    float hx = 0.5f * x;
    return fmaf(hx, th, hx);
}
__device__ __forceinline__ uint32_t ldg_v(const uint32_t* p) { uint32_t v; asm volatile("ld.global.nc.u32 %0, [%1];" : "=r"(v) : "l"(p)); return v; }
__device__ __forceinline__ float lds_f32(uint32_t a) { float v; asm volatile("ld.shared.f32 %0, [%1];" : "=f"(v) : "r"(a) : "memory"); return v; }
__device__ __forceinline__ void sts_f32(uint32_t a, float v) { asm volatile("st.shared.f32 [%0], %1;" ::"r"(a), "f"(v) : "memory"); }
__device__ __forceinline__ uint32_t atom_inc_s(uint32_t a) { uint32_t v; asm volatile("atom.relaxed.cta.shared.add.u32 %0, [%1], 1;" : "=r"(v) : "r"(a) : "memory"); return v; }
__device__ __forceinline__ void lds4(uint32_t a, uint32_t* r) {
    asm volatile("ld.shared.v4.u32 {%0, %1, %2, %3}, [%4];" : "=r"(r[0]), "=r"(r[1]), "=r"(r[2]), "=r"(r[3]) : "r"(a) : "memory");
}
__device__ __forceinline__ void sts4(uint32_t a, uint32_t x, uint32_t y, uint32_t z, uint32_t t) {
    asm volatile("st.shared.v4.u32 [%0], {%1, %2, %3, %4};" ::"r"(a), "r"(x), "r"(y), "r"(z), "r"(t) : "memory");
}
__device__ __forceinline__ uint32_t bsub2(uint32_t a, uint32_t b) { uint32_t r; asm("sub.rn.bf16x2 %0, %1, %2;" : "=r"(r) : "r"(a), "r"(b)); return r; }
__device__ __forceinline__ float blo(uint32_t v) { return __uint_as_float(v << 16); }
__device__ __forceinline__ float bhi(uint32_t v) { return __uint_as_float(v & 0xffff0000u); }
__device__ __forceinline__ float bfr(float x) { return __bfloat162float(__float2bfloat16_rn(x)); }
__device__ __forceinline__ void flag_add(unsigned* p) { asm volatile("red.release.gpu.global.add.u32 [%0], 1;" ::"l"(p) : "memory"); }
__device__ __forceinline__ void flag_wait(const unsigned* p, unsigned target) {
#pragma unroll 1
    for (uint32_t it = 0;; ++it) {
        unsigned v;
        asm volatile("ld.acquire.gpu.global.u32 %0, [%1];" : "=r"(v) : "l"(p) : "memory");
        if (v >= target) break;
        if (it > (1u << 20)) __trap();
    }
    fence_async_g();
}
template <int N> __device__ __forceinline__ void pin(float (&a)[N]) {
#pragma unroll
    for (int i = 0; i < N; i++) asm volatile("" : "+f"(a[i])::"memory");
}

template <int N> __device__ __forceinline__ void fresh(float (&a)[N]) {
#pragma unroll
    for (int i = 0; i < N; i++) a[i] = 0.f;
    pin(a);
}

__device__ __forceinline__ void wgmma_rs_n64_tb0(float (&d)[32], uint32_t a0, uint32_t a1, uint32_t a2, uint32_t a3, uint64_t db, int scale_d) {
    asm volatile("{\n.reg .pred p;\nsetp.ne.b32 p, %37, 0;\n"
        "wgmma.mma_async.sync.aligned.m64n64k16.f32.bf16.bf16 {%0, %1, %2, %3, %4, %5, %6, %7, %8, %9, %10, %11, %12, %13, %14, %15, %16, %17, %18, %19, %20, %21, %22, %23, %24, %25, %26, %27, %28, %29, %30, %31}, {%32, %33, %34, %35}, %36, p, 1, 1, 0;\n}\n"
        : "+f"(d[0]), "+f"(d[1]), "+f"(d[2]), "+f"(d[3]), "+f"(d[4]), "+f"(d[5]), "+f"(d[6]), "+f"(d[7]), "+f"(d[8]), "+f"(d[9]), "+f"(d[10]), "+f"(d[11]), "+f"(d[12]), "+f"(d[13]), "+f"(d[14]), "+f"(d[15]), "+f"(d[16]), "+f"(d[17]), "+f"(d[18]), "+f"(d[19]), "+f"(d[20]), "+f"(d[21]), "+f"(d[22]), "+f"(d[23]), "+f"(d[24]), "+f"(d[25]), "+f"(d[26]), "+f"(d[27]), "+f"(d[28]), "+f"(d[29]), "+f"(d[30]), "+f"(d[31])
        : "r"(a0), "r"(a1), "r"(a2), "r"(a3), "l"(db), "r"(scale_d));
}

__device__ __forceinline__ void wgmma_ss_n128_tb1(float (&d)[64], uint64_t da, uint64_t db, int scale_d) {
    asm volatile("{\n.reg .pred p;\nsetp.ne.b32 p, %66, 0;\n"
        "wgmma.mma_async.sync.aligned.m64n128k16.f32.bf16.bf16 {%0, %1, %2, %3, %4, %5, %6, %7, %8, %9, %10, %11, %12, %13, %14, %15, %16, %17, %18, %19, %20, %21, %22, %23, %24, %25, %26, %27, %28, %29, %30, %31, %32, %33, %34, %35, %36, %37, %38, %39, %40, %41, %42, %43, %44, %45, %46, %47, %48, %49, %50, %51, %52, %53, %54, %55, %56, %57, %58, %59, %60, %61, %62, %63}, %64, %65, p, 1, 1, 0, 1;\n}\n"
        : "+f"(d[0]), "+f"(d[1]), "+f"(d[2]), "+f"(d[3]), "+f"(d[4]), "+f"(d[5]), "+f"(d[6]), "+f"(d[7]), "+f"(d[8]), "+f"(d[9]), "+f"(d[10]), "+f"(d[11]), "+f"(d[12]), "+f"(d[13]), "+f"(d[14]), "+f"(d[15]), "+f"(d[16]), "+f"(d[17]), "+f"(d[18]), "+f"(d[19]), "+f"(d[20]), "+f"(d[21]), "+f"(d[22]), "+f"(d[23]), "+f"(d[24]), "+f"(d[25]), "+f"(d[26]), "+f"(d[27]), "+f"(d[28]), "+f"(d[29]), "+f"(d[30]), "+f"(d[31]), "+f"(d[32]), "+f"(d[33]), "+f"(d[34]), "+f"(d[35]), "+f"(d[36]), "+f"(d[37]), "+f"(d[38]), "+f"(d[39]), "+f"(d[40]), "+f"(d[41]), "+f"(d[42]), "+f"(d[43]), "+f"(d[44]), "+f"(d[45]), "+f"(d[46]), "+f"(d[47]), "+f"(d[48]), "+f"(d[49]), "+f"(d[50]), "+f"(d[51]), "+f"(d[52]), "+f"(d[53]), "+f"(d[54]), "+f"(d[55]), "+f"(d[56]), "+f"(d[57]), "+f"(d[58]), "+f"(d[59]), "+f"(d[60]), "+f"(d[61]), "+f"(d[62]), "+f"(d[63])
        : "l"(da), "l"(db), "r"(scale_d));
}

__device__ __forceinline__ void wgmma_ss_n256_tb1(float (&d)[128], uint64_t da, uint64_t db, int scale_d) {
    asm volatile("{\n.reg .pred p;\nsetp.ne.b32 p, %130, 0;\n"
        "wgmma.mma_async.sync.aligned.m64n256k16.f32.bf16.bf16 {%0, %1, %2, %3, %4, %5, %6, %7, %8, %9, %10, %11, %12, %13, %14, %15, %16, %17, %18, %19, %20, %21, %22, %23, %24, %25, %26, %27, %28, %29, %30, %31, %32, %33, %34, %35, %36, %37, %38, %39, %40, %41, %42, %43, %44, %45, %46, %47, %48, %49, %50, %51, %52, %53, %54, %55, %56, %57, %58, %59, %60, %61, %62, %63, %64, %65, %66, %67, %68, %69, %70, %71, %72, %73, %74, %75, %76, %77, %78, %79, %80, %81, %82, %83, %84, %85, %86, %87, %88, %89, %90, %91, %92, %93, %94, %95, %96, %97, %98, %99, %100, %101, %102, %103, %104, %105, %106, %107, %108, %109, %110, %111, %112, %113, %114, %115, %116, %117, %118, %119, %120, %121, %122, %123, %124, %125, %126, %127}, %128, %129, p, 1, 1, 0, 1;\n}\n"
        : "+f"(d[0]), "+f"(d[1]), "+f"(d[2]), "+f"(d[3]), "+f"(d[4]), "+f"(d[5]), "+f"(d[6]), "+f"(d[7]), "+f"(d[8]), "+f"(d[9]), "+f"(d[10]), "+f"(d[11]), "+f"(d[12]), "+f"(d[13]), "+f"(d[14]), "+f"(d[15]), "+f"(d[16]), "+f"(d[17]), "+f"(d[18]), "+f"(d[19]), "+f"(d[20]), "+f"(d[21]), "+f"(d[22]), "+f"(d[23]), "+f"(d[24]), "+f"(d[25]), "+f"(d[26]), "+f"(d[27]), "+f"(d[28]), "+f"(d[29]), "+f"(d[30]), "+f"(d[31]), "+f"(d[32]), "+f"(d[33]), "+f"(d[34]), "+f"(d[35]), "+f"(d[36]), "+f"(d[37]), "+f"(d[38]), "+f"(d[39]), "+f"(d[40]), "+f"(d[41]), "+f"(d[42]), "+f"(d[43]), "+f"(d[44]), "+f"(d[45]), "+f"(d[46]), "+f"(d[47]), "+f"(d[48]), "+f"(d[49]), "+f"(d[50]), "+f"(d[51]), "+f"(d[52]), "+f"(d[53]), "+f"(d[54]), "+f"(d[55]), "+f"(d[56]), "+f"(d[57]), "+f"(d[58]), "+f"(d[59]), "+f"(d[60]), "+f"(d[61]), "+f"(d[62]), "+f"(d[63]), "+f"(d[64]), "+f"(d[65]), "+f"(d[66]), "+f"(d[67]), "+f"(d[68]), "+f"(d[69]), "+f"(d[70]), "+f"(d[71]), "+f"(d[72]), "+f"(d[73]), "+f"(d[74]), "+f"(d[75]), "+f"(d[76]), "+f"(d[77]), "+f"(d[78]), "+f"(d[79]), "+f"(d[80]), "+f"(d[81]), "+f"(d[82]), "+f"(d[83]), "+f"(d[84]), "+f"(d[85]), "+f"(d[86]), "+f"(d[87]), "+f"(d[88]), "+f"(d[89]), "+f"(d[90]), "+f"(d[91]), "+f"(d[92]), "+f"(d[93]), "+f"(d[94]), "+f"(d[95]), "+f"(d[96]), "+f"(d[97]), "+f"(d[98]), "+f"(d[99]), "+f"(d[100]), "+f"(d[101]), "+f"(d[102]), "+f"(d[103]), "+f"(d[104]), "+f"(d[105]), "+f"(d[106]), "+f"(d[107]), "+f"(d[108]), "+f"(d[109]), "+f"(d[110]), "+f"(d[111]), "+f"(d[112]), "+f"(d[113]), "+f"(d[114]), "+f"(d[115]), "+f"(d[116]), "+f"(d[117]), "+f"(d[118]), "+f"(d[119]), "+f"(d[120]), "+f"(d[121]), "+f"(d[122]), "+f"(d[123]), "+f"(d[124]), "+f"(d[125]), "+f"(d[126]), "+f"(d[127])
        : "l"(da), "l"(db), "r"(scale_d));
}

__device__ __forceinline__ void wgmma_ss_n32_tb0(float (&d)[16], uint64_t da, uint64_t db, int scale_d) {
    asm volatile("{\n.reg .pred p;\nsetp.ne.b32 p, %18, 0;\n"
        "wgmma.mma_async.sync.aligned.m64n32k16.f32.bf16.bf16 {%0, %1, %2, %3, %4, %5, %6, %7, %8, %9, %10, %11, %12, %13, %14, %15}, %16, %17, p, 1, 1, 0, 0;\n}\n"
        : "+f"(d[0]), "+f"(d[1]), "+f"(d[2]), "+f"(d[3]), "+f"(d[4]), "+f"(d[5]), "+f"(d[6]), "+f"(d[7]), "+f"(d[8]), "+f"(d[9]), "+f"(d[10]), "+f"(d[11]), "+f"(d[12]), "+f"(d[13]), "+f"(d[14]), "+f"(d[15])
        : "l"(da), "l"(db), "r"(scale_d));
}

__device__ __forceinline__ void wgmma_ss_n64_tb0(float (&d)[32], uint64_t da, uint64_t db, int scale_d) {
    asm volatile("{\n.reg .pred p;\nsetp.ne.b32 p, %34, 0;\n"
        "wgmma.mma_async.sync.aligned.m64n64k16.f32.bf16.bf16 {%0, %1, %2, %3, %4, %5, %6, %7, %8, %9, %10, %11, %12, %13, %14, %15, %16, %17, %18, %19, %20, %21, %22, %23, %24, %25, %26, %27, %28, %29, %30, %31}, %32, %33, p, 1, 1, 0, 0;\n}\n"
        : "+f"(d[0]), "+f"(d[1]), "+f"(d[2]), "+f"(d[3]), "+f"(d[4]), "+f"(d[5]), "+f"(d[6]), "+f"(d[7]), "+f"(d[8]), "+f"(d[9]), "+f"(d[10]), "+f"(d[11]), "+f"(d[12]), "+f"(d[13]), "+f"(d[14]), "+f"(d[15]), "+f"(d[16]), "+f"(d[17]), "+f"(d[18]), "+f"(d[19]), "+f"(d[20]), "+f"(d[21]), "+f"(d[22]), "+f"(d[23]), "+f"(d[24]), "+f"(d[25]), "+f"(d[26]), "+f"(d[27]), "+f"(d[28]), "+f"(d[29]), "+f"(d[30]), "+f"(d[31])
        : "l"(da), "l"(db), "r"(scale_d));
}

struct Maps {
    CUtensorMap xa, xa2, xas, wup4, wup8, mqa2, mqa4, mqb1, mqb2, wepi, uc, x, out, wq, wk, fa[3], fb[2];
};

__device__ __forceinline__ uint64_t mkd(uint32_t lo) {
    uint64_t d;
    asm("mov.b64 %0, {%1, %2};" : "=l"(d) : "r"(lo), "r"((1024u >> 4) | (1u << 30)));
    return d;
}
__device__ __forceinline__ void ring_ld(uint32_t sb, uint32_t barbase, uint32_t slot8, const CUtensorMap* tm, int c1, int c2) {
    mbar_expect_tx(sb + barbase + slot8, 8192);
    tma3(sb + R1 + slot8 * 1024, tm, 0, c1, c2, sb + barbase + slot8);
}

__device__ __forceinline__ void ring_half(uint32_t sb, uint32_t slot8, uint32_t hoff, const CUtensorMap* tm, int c1, int c2) {
    mbar_expect_tx(sb + B_R1 + slot8, 8192);
    tma3(sb + R1 + slot8 * 2048 + hoff, tm, 0, c1, c2, sb + B_R1 + slot8);
}
__device__ __forceinline__ void ring_full(uint32_t sb, uint32_t slot8, const CUtensorMap* tm, int c1, int c2) {
    mbar_expect_tx(sb + B_R1 + slot8, 16384);
    mbar_arrive(sb + B_R1 + slot8);
    tma3(sb + R1 + slot8 * 2048, tm, 0, c1, c2, sb + B_R1 + slot8);
}
__device__ __forceinline__ void cta_done(int mode) {
    if (mode == 0 && atomicAdd(&g_sync[4], 1) == NCTA + 1) {
#pragma unroll
        for (int i = 0; i < 5; i++) g_sync[i] = 0;
    }
}

__device__ __forceinline__ void fold_cta(const Maps& mp, uint32_t sb, int mode) {
    constexpr uint32_t F_FULL = MISC, F_EMPTY = MISC + 32, F_T1 = MISC + 64, STG = 49152;
    const int tid = threadIdx.x, f = blockIdx.x - NCTA;
    if (mode == 2) return;
    if (tid == 0) {
        for (int i = 0; i < 4; i++) { mbar_init(sb + F_FULL + 8 * i, 1); mbar_init(sb + F_EMPTY + 8 * i, 2); }
        mbar_init(sb + F_T1, 256);
        asm volatile("fence.mbarrier_init.release.cluster;" ::: "memory");
        fence_async();
    }
    __syncthreads();
    const int wg = __shfl_sync(0xffffffffu, tid >> 7, 0);
    if (wg == 0) {
        if (tid == 0) {
#pragma unroll 1
            for (int it = 0; it < 96; it++) {
                const int p = it >> 3, kc = it & 7, job = p >> 2, st = it & 3;
                if (it == 64) mbar_wait(sb + F_T1, 0);
                if (it >= 4) mbar_wait(sb + F_EMPTY + 8 * st, ((it >> 2) - 1) & 1);
                mbar_expect_tx(sb + F_FULL + 8 * st, STG);
                tma3(sb + st * STG, &mp.fa[job], 0, 256 * f + 128 * ((p >> 1) & 1), kc, sb + F_FULL + 8 * st);
                tma3(sb + st * STG + 16384, &mp.fb[job != 0], 0, 64 * kc + (job == 1 ? 512 : 0), 4 * (p & 1), sb + F_FULL + 8 * st);
            }
        }
        return;
    }
    const int h = wg - 1, lane = tid & 31, w = (tid >> 5) & 3;
    const uint32_t sd = (sb & 0x3FFFF) >> 4;
#pragma unroll 1
    for (int p = 0; p < 12; p++) {
        float acc[128];
        fresh(acc);
#pragma unroll 1
        for (int kc = 0; kc < 8; kc++) {
            const int st = kc & 3;
            mbar_wait(sb + F_FULL + 8 * st, (kc >> 2) & 1);
            wg_fence();
#pragma unroll
            for (int kk = 0; kk < 4; kk++)
                wgmma_ss_n256_tb1(acc, dsc(sd, st * STG + h * 8192 + kk * 32, 16), dsc(sd, st * STG + 16384 + kk * 2048, 8192), 1);
            wg_commit();
            wg_wait<0>();
            if ((tid & 127) == 0) mbar_arrive(sb + F_EMPTY + 8 * st);
        }
        pin(acc);
        const int job = p >> 2;
#pragma unroll
        for (int e = 0; e < 2; e++) {
            int r = 256 * f + 128 * ((p >> 1) & 1) + 64 * h + 16 * w + (lane >> 2) + 8 * e;
            if (job == 1) r = 512 + ((r & ~31) | (((r >> 1) & 3) << 3) | (((r >> 3) & 3) << 1) | (r & 1));
            uint32_t* c = reinterpret_cast<uint32_t*>((job == 0 ? g_t1 : g_wepi) + r * D_ + 256 * (p & 1) + 2 * (lane & 3));
#pragma unroll
            for (int n = 0; n < 32; n++) c[4 * n] = pack2(acc[4 * n + 2 * e], acc[4 * n + 2 * e + 1]);
        }
        if (p == 3) { fence_async_g(); mbar_arrive(sb + F_T1); }
    }
    fence_async_g();
    bar_sync(2, 256);
    if (tid == 128) {
        if (mode == 0) flag_add(&g_sync[3]);
        cta_done(mode);
    }
}

__global__ void __launch_bounds__(384, 1) main_kernel(const __grid_constant__ Maps mp, const bf16* __restrict__ dw, const int mode) {
    extern __shared__ __align__(1024) uint8_t smem[];
    const uint32_t sb = smem_u32(smem);
    const int tid = threadIdx.x;
    if (blockIdx.x >= NCTA) { fold_cta(mp, sb, mode); return; }
    const int b = blockIdx.x / TPB, ti = blockIdx.x % TPB;
    const int piece = blockIdx.x & 127;
    if (tid == 0) {
        mbar_init(sb + B_A, 1); mbar_init(sb + B_MK, 1);
        for (int i = 0; i < 5; i++) mbar_init(sb + B_R1 + 8 * i, 2);
        asm volatile("fence.mbarrier_init.release.cluster;" ::: "memory");
        fence_async();
        mbar_expect_tx(sb + B_A, 65536 + 3072);
        tma4(sb + AT, &mp.x, 0, 62 * ti - 1, 0, b, sb + B_A);
        mbar_expect_tx(sb + B_MK, 65536 + 32768);
        tma3(sb + R0, &mp.wq, 0, 64 * (piece >> 4), 0, sb + B_MK);
        tma3(sb + R1 + 32768, &mp.wk, 0, 32 * (piece & 15), 0, sb + B_MK);
        asm volatile("cp.async.bulk.shared::cluster.global.mbarrier::complete_tx::bytes [%0], [%1], 3072, [%2];" ::"r"(sb + DWS), "l"(dw), "r"(sb + B_A) : "memory");
        for (int i = 0; i < 8; i++) mbar_arrive(sb + B_R1 + 8 * (i >> 1));
        if (mode != 1) {
            ring_full(sb, 32, &mp.wup8, 0, 8);
            ring_full(sb, 0, &mp.wup8, 16, 8);
            ring_full(sb, 8, &mp.wup8, 32, 8);
        }
    } else if (tid == 32) {
        mbar_init(sb + B_LN, 1); mbar_init(sb + B_MQ, 1); mbar_init(sb + B_XA, 1);
        mbar_init(sb + B_H1, 2); mbar_init(sb + B_H2, 1); mbar_init(sb + B_H3, 2);
        for (int i = 0; i < 3; i++) { mbar_init(sb + B_KV + 8 * i, 1); mbar_init(sb + B_P + 8 * i, 4); mbar_init(sb + B_GO + 8 * i, 4); }
        for (int i = 0; i < 12; i++) mbar_init(sb + B_R2 + 8 * i, 1);
        mbar_init(sb + B_UC, 1); mbar_init(sb + B_X, 1);
        for (int i = 0; i < 4; i++) asm volatile("st.shared.u32 [%0], 0;" ::"r"(sb + CNT + 4 * i) : "memory");
        asm volatile("fence.mbarrier_init.release.cluster;" ::: "memory");
        fence_async();
    }
    __syncthreads();
    const int wg = __shfl_sync(0xffffffffu, tid >> 7, 0);
    const int lane = tid & 31, w = (tid >> 5) & 3;
    const bool w0 = __shfl_sync(0xffffffffu, w, 0) == 0;
    const uint32_t sd = (sb & 0x3FFFF) >> 4;
    const uint32_t adA = sd + (AT >> 4) + (1u << 16);
    const uint32_t bd0 = sd + (R1 >> 4);
    const uint32_t bd2k = bd0 + ((2048u >> 4) << 16);
    const bool el = (tid & 127) == 0;
    const uint32_t lrow = 16 * w + (lane & 7) + ((lane >> 3) & 1) * 8;
    const uint32_t loff = lrow * 128 + ((((lane >> 4) ^ lrow) & 7) << 4);
    const int r0 = 16 * w + (lane >> 2);

    if (wg == 0) {
        asm volatile("setmaxnreg.inc.sync.aligned.u32 184;");
        uint32_t q[112];
        PT(0);
        {
            float mq[16];
            fresh(mq);
            mbar_wait(sb + B_MK, 0);
            PT(1);
            wg_fence();
#pragma unroll 1
            for (int c = 0; c < 8; c++)
#pragma unroll
                for (int kk = 0; kk < 4; kk++)
                    wgmma_ss_n32_tb0(mq, dsc(sd, R0 + c * 8192 + kk * 32, 16), dsc(sd, R1 + 32768 + c * 4096 + kk * 32, 16), 1);
            wg_commit();
            wg_wait<0>();
            if (mode != 1 && w0 && elect1()) { ring_full(sb, 16, &mp.wup8, 48, 8); ring_full(sb, 24, &mp.wup8, 64, 8); }
            pin(mq);
            uint32_t* c = reinterpret_cast<uint32_t*>(g_mqk + (64 * (piece >> 4) + r0) * D_ + 32 * (piece & 15) + 2 * (lane & 3));
#pragma unroll
            for (int n = 0; n < 4; n++) { c[4 * n] = pack2(mq[4 * n], mq[4 * n + 1]); c[4 * n + 4 * D_] = pack2(mq[4 * n + 2], mq[4 * n + 3]); }
            fence_async_g();
            bar_sync(1, 128);
            if (el) {
                if (mode == 0) flag_add(&g_sync[2]);
                mbar_wait(sb + B_LN, 0);
                tma4_store(&mp.xas, sb + AT, 0, 62 * ti, 0, b);
                asm volatile("cp.async.bulk.commit_group;" ::: "memory");
                asm volatile("cp.async.bulk.wait_group 0;" ::: "memory");
                if (mode == 0) {
                    fence_async_g();
                    flag_add(&g_sync[b]);
                    PT(12);
                    flag_wait(&g_sync[2], NCTA);
                }
                mbar_arrive(sb + B_MQ);
            }
            PT(13);
            if (mode == 1) return;
        }
        mbar_wait(sb + B_H1, 0);
        PT(2);
        uint32_t slot8 = 8, par = 1, prev8 = 0;
        auto adv = [&]() { prev8 = slot8; slot8 += 8; if (slot8 == 40) { slot8 = 0; par ^= 1; } };
        {
            float acc[128];
            fresh(acc);
            auto step = [&](int i) {
                const uint32_t aa = adA + (i >> 1) * 512 + (i & 1) * 4, bb = bd0 + ((4096u >> 4) << 16) + slot8 * 128;
                wg_fence();
                wgmma_ss_n256_tb1(acc, mkd(aa), mkd(bb), 1);
                wgmma_ss_n256_tb1(acc, mkd(aa + 2), mkd(bb + 128), 1);
                wg_commit();
                wg_wait<1>();
            };
#pragma unroll 1
            for (int i = 0; i < 12; i++) {
                mbar_wait(sb + B_R1 + slot8, par);
                step(i);
                if (i > 0 && w0 && elect1()) ring_full(sb, prev8, &mp.mqa4, 32 * i + 128, 4);
                adv();
            }
#pragma unroll 1
            for (int i = 12; i < 16; i++) {
                mbar_wait(sb + B_R1 + slot8, par);
                if (i == 15 && el) mbar_arrive(sb + B_H2);
                step(i);
                if (w0 && elect1()) ring_full(sb, prev8, &mp.wup8, 16 * i - 192, 0);
                adv();
            }
            wg_wait<0>();
            if (w0 && elect1()) ring_full(sb, prev8, &mp.wup8, 64, 0);
            pin(acc);
            PT(3);
#pragma unroll
            for (int kk = 0; kk < 4; kk++)
                stsm4((sb + QS + loff) ^ (kk << 5), pack2(acc[96 + 8 * kk], acc[97 + 8 * kk]), pack2(acc[98 + 8 * kk], acc[99 + 8 * kk]),
                      pack2(acc[100 + 8 * kk], acc[101 + 8 * kk]), pack2(acc[102 + 8 * kk], acc[103 + 8 * kk]));
            fence_async();
#pragma unroll
            for (int i = 47; i >= 0; i--) q[64 + i] = pack2v(acc[2 * i], acc[2 * i + 1]);
        }
        if (el) {
            if (mode == 0) flag_wait(&g_sync[b], TPB);
            mbar_arrive(sb + B_XA);
        }
        __syncwarp();
        mbar_wait(sb + B_H3, 0);
        PT(4);
        slot8 = 32; par = 0;
#pragma unroll
        for (int half = 0; half < 2; half++) {
            float acc[64];
            fresh(acc);
            auto step = [&](int m) {
                const uint32_t aa = adA + m * 512, bb = bd0 + ((8192u >> 4) << 16) + slot8 * 128;
                mbar_wait(sb + B_R1 + slot8, par);
                wg_fence();
#pragma unroll
                for (int kk = 0; kk < 4; kk++) wgmma_ss_n128_tb1(acc, mkd(aa + 2 * kk), mkd(bb + 128 * kk), 1);
                wg_commit();
                wg_wait<1>();
            };
            if (half == 0) {
#pragma unroll 1
                for (int m = 0; m < 8; m++) {
                    step(m);
                    if (m > 0 && w0 && elect1()) ring_full(sb, prev8, &mp.mqb2, (64 * m + 256) & 511, (m + 4) >> 3 << 1);
                    adv();
                }
            } else {
#pragma unroll 1
                for (int m = 0; m < 4; m++) {
                    step(m);
                    if (m > 0 && w0 && elect1()) ring_full(sb, prev8, &mp.mqb2, 64 * m + 256, 2);
                    adv();
                }
#pragma unroll 1
                for (int m = 4; m < 8; m++) {
                    step(m);
                    if (w0 && elect1()) {
                        if (m == 4) mbar_expect_tx(sb + B_KV + 8, 65536);
                        tma4(sb + R1 + prev8 * 2048, &mp.xa2, 0, 0, 2 * m - 8, b, sb + B_KV + 8);
                    }
                    adv();
                }
            }
            wg_wait<0>();
            if (w0 && elect1()) {
                if (half == 0) ring_full(sb, prev8, &mp.mqb2, 256, 2);
                else {
                    mbar_expect_tx(sb + B_KV + 16, 65536);
                    tma4(sb + R2, &mp.xa, 0, 64, 0, b, sb + B_KV + 16);
                }
            }
            pin(acc);
#pragma unroll
            for (int i = 31; i >= 0; i--) q[32 * half + i] = pack2v(acc[2 * i], acc[2 * i + 1]);
        }
        bar_sync(1, 128);
        PT(5);

        const float CS = 0.04419417382415922f * 1.4426950408889634f;
        float m0 = -INFINITY, m1 = -INFINITY, l0 = 0.f, l1 = 0.f;
        int s = 0, sn = 1, ph = 0;
        float S[32];
        const bool l0w = lane == 0, q0 = (lane & 3) == 0;
#pragma unroll 1
        for (int j = -1;; j++) {
            if (j >= 0) {
                PL(j, 1);
                if (j == NKV - 1) {
#pragma unroll
                    for (int i = (T_ - 64 * (NKV - 1)) / 2; i < 32; i++) asm volatile("mov.b32 %0, 0xff800000;" : "=f"(S[i]));
                }
                float y[8], z[8];
#pragma unroll
                for (int n = 0; n < 8; n++) { y[n] = fmaxf(S[4 * n], S[4 * n + 1]); z[n] = fmaxf(S[4 * n + 2], S[4 * n + 3]); }
#pragma unroll
                for (int n = 0; n < 4; n++) { y[n] = fmaxf(y[n], y[n + 4]); z[n] = fmaxf(z[n], z[n + 4]); }
                float x0 = fmaxf(fmaxf(y[0], y[1]), fmaxf(fmaxf(y[2], y[3]), m0)), x1 = fmaxf(fmaxf(z[0], z[1]), fmaxf(fmaxf(z[2], z[3]), m1));
                x0 = fmaxf(x0, __shfl_xor_sync(0xffffffffu, x0, 1));
                x1 = fmaxf(x1, __shfl_xor_sync(0xffffffffu, x1, 1));
                x0 = fmaxf(x0, __shfl_xor_sync(0xffffffffu, x0, 2));
                x1 = fmaxf(x1, __shfl_xor_sync(0xffffffffu, x1, 2));
                const float sc0 = ex2((m0 - x0) * CS), sc1 = ex2((m1 - x1) * CS);
                m0 = x0; m1 = x1;
                const float n0 = -x0 * CS, n1 = -x1 * CS;
                if (q0) { sts_f32(sb + SCL + s * 256 + r0 * 4, sc0); sts_f32(sb + SCL + s * 256 + r0 * 4 + 32, sc1); }
                __syncwarp();
                if (l0w) mbar_arrive(sb + B_P + s * 8);
                if (j < NKV - 1) mbar_wait(sb + B_KV + sn * 8, ph);
                float a0 = 0.f, a1 = 0.f;
                const uint32_t pb = sb + R3 + (s == 0 ? 2 : s - 1) * 8192;
#pragma unroll
                for (int kk = 0; kk < 4; kk++) {
                    float p[8];
#pragma unroll
                    for (int e = 0; e < 8; e++) p[e] = ex2(fmaf(S[8 * kk + e], CS, (e & 2) ? n1 : n0));
                    a0 += (p[0] + p[1]) + (p[4] + p[5]);
                    a1 += (p[2] + p[3]) + (p[6] + p[7]);
                    stsm4((pb + loff) ^ (kk << 5), pack2(p[0], p[1]), pack2(p[2], p[3]), pack2(p[4], p[5]), pack2(p[6], p[7]));
                }
                l0 = fmaf(l0, sc0, a0); l1 = fmaf(l1, sc1, a1);
                PL(j, 2);
                if (j == NKV - 1) break;
            } else {
                mbar_wait(sb + B_KV + 8, 0);
            }
            float Sn[32];
            const uint32_t kd = sd + sn * 4096;
            wg_fence();
#pragma unroll
            for (int kk = 0; kk < 28; kk++)
                wgmma_rs_n64_tb0(Sn, q[4 * kk], q[4 * kk + 1], q[4 * kk + 2], q[4 * kk + 3], dsc(kd, (kk >> 2) * 8192 + (kk & 3) * 32, 16), kk > 0);
            wg_commit();
#pragma unroll
            for (int kk = 0; kk < 4; kk++)
                wgmma_ss_n64_tb0(Sn, dsc(sd, QS + kk * 32, 16), dsc(kd, 7 * 8192 + kk * 32, 16), 1);
            wg_commit();
            PL(j, 3);
            fence_async();
            __syncwarp();
            wg_wait<1>();
            if (j >= 0 && l0w) mbar_arrive(sb + B_GO + s * 8);
            PL(j, 0);
            wg_wait<0>();
            pin(Sn);
#pragma unroll
            for (int i = 0; i < 32; i++) S[i] = Sn[i];
            s = sn;
            if (++sn == 3) sn = 0;
            if (sn == 1) ph ^= 1;
        }
        l0 += __shfl_xor_sync(0xffffffffu, l0, 1); l1 += __shfl_xor_sync(0xffffffffu, l1, 1);
        l0 += __shfl_xor_sync(0xffffffffu, l0, 2); l1 += __shfl_xor_sync(0xffffffffu, l1, 2);
        if (q0) { sts_f32(sb + LINV + r0 * 4, rcp(l0)); sts_f32(sb + LINV + r0 * 4 + 32, rcp(l1)); }
        fence_async();
        __syncwarp();
        if (l0w) mbar_arrive(sb + B_GO + s * 8);
        PDUMP();
    } else {
        asm volatile("setmaxnreg.dec.sync.aligned.u32 160;");
        const int h = wg - 1;
        mbar_wait(sb + B_A, 0);
        PT(0);
#pragma unroll 1
        for (int bt = 0; bt < 2; bt++) {
            uint32_t v[4][8];
            float mu[4], vr[4];
            const uint32_t la = sb + AT + (lane >> 3) * 8192 + (32 * h + 8 * w + 4 * bt) * 128 + (((lane & 7) ^ (4 * bt)) << 4);
#pragma unroll
            for (int r = 0; r < 4; r++) { lds4((la ^ (r << 4)) + r * 128, v[r]); lds4((la ^ (r << 4)) + r * 128 + 32768, v[r] + 4); }
#pragma unroll
            for (int r = 0; r < 4; r++) {
                float s0 = 0.f, s1 = 0.f;
#pragma unroll
                for (int i = 0; i < 8; i++) { s0 += blo(v[r][i]); s1 += bhi(v[r][i]); }
                mu[r] = s0 + s1;
            }
#pragma unroll
            for (int o = 16; o; o >>= 1)
#pragma unroll
                for (int r = 0; r < 4; r++) mu[r] += __shfl_xor_sync(0xffffffffu, mu[r], o);
#pragma unroll
            for (int r = 0; r < 4; r++) {
                mu[r] *= (1.f / D_);
                float s0 = 0.f, s1 = 0.f;
#pragma unroll
                for (int i = 0; i < 8; i++) { const float d0 = blo(v[r][i]) - mu[r], d1 = bhi(v[r][i]) - mu[r]; s0 = fmaf(d0, d0, s0); s1 = fmaf(d1, d1, s1); }
                vr[r] = s0 + s1;
            }
#pragma unroll
            for (int o = 16; o; o >>= 1)
#pragma unroll
                for (int r = 0; r < 4; r++) vr[r] += __shfl_xor_sync(0xffffffffu, vr[r], o);
#pragma unroll
            for (int r = 0; r < 4; r++) {
                const uint32_t m2 = pack2(mu[r], mu[r]);
                const float rinv = 1.f / bfr(sqrtf(bfr(bfr(vr[r] * (1.f / D_)) + 1e-5f)));
#pragma unroll
                for (int i = 0; i < 8; i++) { const uint32_t d = bsub2(v[r][i], m2); v[r][i] = pack2(blo(d) * rinv, bhi(d) * rinv); }
                sts4((la ^ (r << 4)) + r * 128, v[r][0], v[r][1], v[r][2], v[r][3]);
                sts4((la ^ (r << 4)) + r * 128 + 32768, v[r][4], v[r][5], v[r][6], v[r][7]);
            }
        }
        fence_async();
        bar_sync(2, 256);
        if (tid == 128) mbar_arrive(sb + B_LN);
        if (mode == 1) return;
        float acc[128];
#pragma unroll
        for (int pass = 0; pass < 2; pass++) {
            if (pass == 1) mbar_wait(sb + B_H2, 0);
            PT(1 + 3 * pass);
            fresh(acc);
            uint32_t slot8 = pass ? 16 : 32, par = 0, prev8 = 0;
            auto adv = [&]() { prev8 = slot8; slot8 += 8; if (slot8 == 40) { slot8 = 0; par ^= 1; } };
            auto step = [&](int kk) {
                wg_fence();
                wgmma_ss_n256_tb1(acc, mkd(adA + (kk >> 2) * 512 + (kk & 3) * 2), mkd(bd2k + h * 512 + slot8 * 128), 1);
                wg_commit();
                wg_wait<1>();
            };
#pragma unroll 1
            for (int kk = 0; kk < 28; kk++) {
                mbar_wait(sb + B_R1 + slot8, par);
                step(kk);
                if (kk > 0 && w0 && elect1()) ring_half(sb, prev8, h * 8192, &mp.wup4, 16 * kk + 64, (pass ? 0 : 8) + 4 * h);
                adv();
            }
            if (pass == 0 && w0) mbar_wait(sb + B_MQ, 0);
#pragma unroll 1
            for (int kk = 28; kk < 32; kk++) {
                mbar_wait(sb + B_R1 + slot8, par);
                if (kk == 31 && el) mbar_arrive(sb + (pass ? B_H3 : B_H1));
                step(kk);
                if (w0 && elect1()) ring_half(sb, prev8, h * 8192, pass ? &mp.mqb1 : &mp.mqa2, (pass ? 64 : 32) * (kk - 28), pass ? h : 4 + 2 * h);
                adv();
            }
            wg_wait<0>();
            if (w0 && elect1()) ring_half(sb, prev8, h * 8192, pass ? &mp.mqb1 : &mp.mqa2, pass ? 256 : 128, pass ? h : 4 + 2 * h);
            pin(acc);
            PT(2 + 3 * pass);
            if (pass == 0) {
#pragma unroll
                for (int i = 0; i < 128; i++) acc[i] = gelu(acc[i]);
                float s0 = 0.f, s1 = 0.f;
#pragma unroll
                for (int n = 0; n < 32; n++) { s0 += acc[4 * n] + acc[4 * n + 1]; s1 += acc[4 * n + 2] + acc[4 * n + 3]; }
                s0 += __shfl_xor_sync(0xffffffffu, s0, 1); s1 += __shfl_xor_sync(0xffffffffu, s1, 1);
                s0 += __shfl_xor_sync(0xffffffffu, s0, 2); s1 += __shfl_xor_sync(0xffffffffu, s1, 2);
                s0 *= (1.f / 256.f); s1 *= (1.f / 256.f);
                float v0 = 0.f, v1 = 0.f;
#pragma unroll
                for (int n = 0; n < 32; n++) {
                    float d0 = acc[4 * n] - s0, d1 = acc[4 * n + 1] - s0, d2 = acc[4 * n + 2] - s1, d3 = acc[4 * n + 3] - s1;
                    v0 = fmaf(d0, d0, v0); v0 = fmaf(d1, d1, v0); v1 = fmaf(d2, d2, v1); v1 = fmaf(d3, d3, v1);
                }
                v0 += __shfl_xor_sync(0xffffffffu, v0, 1); v1 += __shfl_xor_sync(0xffffffffu, v1, 1);
                v0 += __shfl_xor_sync(0xffffffffu, v0, 2); v1 += __shfl_xor_sync(0xffffffffu, v1, 2);
                if ((lane & 3) == 0) {
                    uint32_t a = sb + STAT + h * 512 + r0 * 8;
                    sts_f32(a, s0); sts_f32(a + 4, v0); sts_f32(a + 64, s1); sts_f32(a + 68, v1);
                }
                bar_sync(2, 256);
                {
                    uint32_t a = sb + STAT + (h ^ 1) * 512 + r0 * 8;
                    float t0 = lds_f32(a), u0 = lds_f32(a + 4), t1 = lds_f32(a + 64), u1 = lds_f32(a + 68);
                    v0 = (v0 + u0 + (s0 - t0) * (s0 - t0) * 128.f) * (1.f / 512.f);
                    v1 = (v1 + u1 + (s1 - t1) * (s1 - t1) * 128.f) * (1.f / 512.f);
                    s0 = 0.5f * (s0 + t0); s1 = 0.5f * (s1 + t1);
                }
                v0 = rsqrtf(v0 + 1e-5f); v1 = rsqrtf(v1 + 1e-5f);
                s0 = -s0 * v0; s1 = -s1 * v1;
#pragma unroll
                for (int p = 0; p < 16; p++)
                    stsm4(((sb + R0 + h * 32768 + loff) ^ ((p & 3) << 5)) + (p >> 2) * 8192,
                          pack2(fmaf(acc[8 * p], v0, s0), fmaf(acc[8 * p + 1], v0, s0)), pack2(fmaf(acc[8 * p + 2], v1, s1), fmaf(acc[8 * p + 3], v1, s1)),
                          pack2(fmaf(acc[8 * p + 4], v0, s0), fmaf(acc[8 * p + 5], v0, s0)), pack2(fmaf(acc[8 * p + 6], v1, s1), fmaf(acc[8 * p + 7], v1, s1)));
            } else {
                bar_sync(3 + h, 128);
                const uint32_t rm = lrow == 0 ? 0 : lrow - 1, rp = lrow == 63 ? 63 : lrow + 1;
                const uint32_t gb = sb + R0 + h * 32768;
                const uint32_t am = gb + rm * 128 + ((((lane >> 4) ^ rm) & 7) << 4), ap = gb + rp * 128 + ((((lane >> 4) ^ rp) & 7) << 4), ac = gb + loff;
                const uint32_t dwa = sb + DWS + 512 * h + ((lane >> 3) & 1) * 16 + (lane >> 4) * 1024;
                bf16* ucp = g_uc + ((size_t)blockIdx.x * 64 + r0) * D_ + 256 * h + 8 * (lane & 3);
#pragma unroll
                for (int m = 7; m >= 0; m--) {
                    uint32_t o[8];
#pragma unroll
                    for (int pp = 1; pp >= 0; pp--) {
                        const int p = 2 * m + pp;
                        const uint32_t co = (p >> 2) * 8192, cx = (p & 3) << 5;
                        uint32_t u[4], g[4], cv[4], d[4], d2[2];
#pragma unroll
                        for (int e = 3; e >= 0; e--) u[e] = pack2v(gelu(acc[8 * p + 2 * e]), gelu(acc[8 * p + 2 * e + 1]));
                        ldsm4(dwa + 32 * p, d);
                        ldsm2(dwa + 32 * p + 2048, d2);
                        ldsm4((am ^ cx) + co, g);
#pragma unroll
                        for (int e = 0; e < 4; e++) cv[e] = bmul2(g[e], d[e >> 1]);
                        ldsm4((ac ^ cx) + co, g);
#pragma unroll
                        for (int e = 0; e < 4; e++) cv[e] = bfma2(g[e], d[2 + (e >> 1)], cv[e]);
                        ldsm4((ap ^ cx) + co, g);
#pragma unroll
                        for (int e = 0; e < 4; e++) o[4 * (e & 1) + 2 * pp + (e >> 1)] = bmul2(u[e], bfma2(g[e], d2[e >> 1], cv[e]));
                    }
                    stg4(ucp + 32 * m, o[0], o[1], o[2], o[3]);
                    stg4(ucp + 32 * m + 8 * D_, o[4], o[5], o[6], o[7]);
                }
                bar_sync(2, 256);
                if (tid == 128) {
                    mbar_wait(sb + B_XA, 0);
                    mbar_expect_tx(sb + B_KV, 65536);
                    tma4(sb + R0, &mp.xa, 0, 128, 0, b, sb + B_KV);
                }
            }
            PT(3 + 3 * pass);
        }
        int s = 1, ph = 0;
        fresh(acc);
#pragma unroll 1
        for (int j = 0; j < NKV; j++) {
            mbar_wait(sb + B_P + s * 8, ph);
            PL(j, 0);
            if (j > 0) {
                const float sc0 = lds_f32(sb + SCL + s * 256 + r0 * 4), sc1 = lds_f32(sb + SCL + s * 256 + r0 * 4 + 32);
                if (__any_sync(0xffffffffu, sc0 != 1.f || sc1 != 1.f)) {
#pragma unroll
                    for (int n = 0; n < 32; n++) { acc[4 * n] *= sc0; acc[4 * n + 1] *= sc0; acc[4 * n + 2] *= sc1; acc[4 * n + 3] *= sc1; }
                }
            }
            mbar_wait(sb + B_GO + s * 8, ph);
            PL(j, 1);
            const uint32_t vd = sd + s * 4096 + h * 2048, pd = sd + (s == 0 ? 2 : s - 1) * 512;
            pin(acc);
            wg_fence();
#pragma unroll
            for (int kk = 0; kk < 4; kk++) wgmma_ss_n256_tb1(acc, dsc(pd, R3 + kk * 32, 16), dsc(vd, kk * 2048, 8192), 1);
            wg_commit();
            wg_wait<0>();
            pin(acc);
            PL(j, 2);
            if (w0 && elect1()) {
                if (j == NKV - 5 && mode == 0) flag_wait(&g_sync[3], 2);
                if (atom_inc_s(sb + CNT + 4 * s) & 1) {
                    if (j + 3 < NKV) {
                        mbar_expect_tx(sb + B_KV + s * 8, 65536);
                        tma4(sb + s * 65536, &mp.xa, 0, 64 * (j + 3), 0, b, sb + B_KV + s * 8);
                    } else if (j < NKV - 1) {
                        const int n0 = j == NKV - 3 ? 0 : 8, n1 = j == NKV - 3 ? 8 : 12;
#pragma unroll 1
                        for (int n = n0; n < n1; n++) ring_ld(sb, B_R2, n * 8, &mp.wepi, 16 * (n >> 1), 4 * (n & 1));
                    }
                }
            }
            if (++s == 3) s = 0;
            if (s == 1) ph ^= 1;
        }
        {
            const float i0 = lds_f32(sb + LINV + r0 * 4), i1 = lds_f32(sb + LINV + r0 * 4 + 32);
#pragma unroll
            for (int p = 0; p < 16; p++)
                stsm4(((sb + R0 + h * 32768 + loff) ^ ((p & 3) << 5)) + (p >> 2) * 8192,
                      pack2(acc[8 * p] * i0, acc[8 * p + 1] * i0), pack2(acc[8 * p + 2] * i1, acc[8 * p + 3] * i1),
                      pack2(acc[8 * p + 4] * i0, acc[8 * p + 5] * i0), pack2(acc[8 * p + 6] * i1, acc[8 * p + 7] * i1));
        }
        fence_async();
        fence_async_g();
        bar_sync(2, 256);
        if (tid == 128) {
            mbar_expect_tx(sb + B_UC, 65536);
            tma3(sb + UCT, &mp.uc, 0, 64 * blockIdx.x, 0, sb + B_UC);
        }
        PT(7);
        fresh(acc);
        {
            uint32_t slot8 = 8 * h, par = 0, prev8 = 0;
#pragma unroll 1
            for (int kk = 0; kk < 64; kk++) {
                if (kk == 32) mbar_wait(sb + B_UC, 0);
                mbar_wait(sb + B_R2 + slot8, par);
                wg_fence();
                wgmma_ss_n256_tb1(acc, mkd(sd + (1u << 16) + (kk < 32 ? (R0 >> 4) : (UCT >> 4) - 4096) + (kk >> 2) * 512 + (kk & 3) * 2), mkd(bd2k + slot8 * 64), 1);
                wg_commit();
                wg_wait<1>();
                if (kk > 0 && w0 && elect1()) {
                    if (kk < 59) ring_ld(sb, B_R2, prev8, &mp.wepi, 16 * (kk + 5), 4 * h);
                    if (kk == 32 && (atom_inc_s(sb + CNT + 12) & 1)) {
                        mbar_expect_tx(sb + B_X, 65536);
                        tma4(sb + R0, &mp.x, 0, 62 * ti, 0, b, sb + B_X);
                    }
                }
                prev8 = slot8;
                slot8 += 16;
                if (slot8 >= 96) { slot8 -= 96; par ^= 1; }
            }
        }
        wg_wait<0>();
        pin(acc);
        PT(8);
        mbar_wait(sb + B_X, 0);
        PT(9);
        {
            const uint32_t sr = (lrow + 63) & 63;
            const uint32_t xoff = sr * 128 + ((((lane >> 4) ^ sr) & 7) << 4);
#pragma unroll
            for (int p = 0; p < 16; p++) {
                const uint32_t a = ((sb + R0 + h * 32768 + xoff) ^ ((p & 3) << 5)) + (p >> 2) * 8192;
                uint32_t xv[4];
                ldsm4(a, xv);
#pragma unroll
                for (int e = 0; e < 4; e++)
                    xv[e] = pack2(acc[8 * p + 2 * e] + __uint_as_float(xv[e] << 16), acc[8 * p + 2 * e + 1] + __uint_as_float(xv[e] & 0xffff0000u));
                stsm4(a, xv[0], xv[1], xv[2], xv[3]);
            }
        }
        fence_async();
        bar_sync(3 + h, 128);
        if (el) {
            for (int c = 0; c < 4; c++) tma4_store(&mp.out, sb + R0 + (4 * h + c) * 8192, 0, 62 * ti, 4 * h + c, b);
            asm volatile("cp.async.bulk.commit_group;" ::: "memory");
            PT(10);
            if (h == 0) cta_done(mode);
            asm volatile("cp.async.bulk.wait_group.read 0;" ::: "memory");
        }
        PT(11);
        PDUMP();
    }
}

typedef CUresult (*PFN_enc)(CUtensorMap*, CUtensorMapDataType, cuuint32_t, void*, const cuuint64_t*, const cuuint64_t*,
                            const cuuint32_t*, const cuuint32_t*, CUtensorMapInterleave, CUtensorMapSwizzle,
                            CUtensorMapL2promotion, CUtensorMapFloatOOBfill);

static void enc(PFN_enc f, CUtensorMap* m, void* base, int rank, const cuuint64_t* dims, const cuuint64_t* strides, const cuuint32_t* box) {
    cuuint32_t es[5] = {1, 1, 1, 1, 1};
    f(m, CU_TENSOR_MAP_DATA_TYPE_BFLOAT16, rank, base, dims, strides, box, es, CU_TENSOR_MAP_INTERLEAVE_NONE,
      CU_TENSOR_MAP_SWIZZLE_128B, CU_TENSOR_MAP_L2_PROMOTION_L2_256B, CU_TENSOR_MAP_FLOAT_OOB_FILL_NONE);
}
static void enc_act(PFN_enc f, CUtensorMap* m, void* base, int rows, int chunks, int trows = T_, int pitch = T_) {
    cuuint64_t dims[4] = {64, (cuuint64_t)trows, 8, (cuuint64_t)NB_};
    cuuint64_t st[3] = {1024, 128, (cuuint64_t)pitch * 1024};
    cuuint32_t box[4] = {64, (cuuint32_t)rows, (cuuint32_t)chunks, 1};
    enc(f, m, base, 4, dims, st, box);
}
static void enc_w(PFN_enc f, CUtensorMap* m, void* base, int krows, int ncols, int bk, int bc) {
    cuuint64_t dims[3] = {64, (cuuint64_t)krows, (cuuint64_t)(ncols / 64)};
    cuuint64_t st[2] = {(cuuint64_t)ncols * 2, 128};
    cuuint32_t box[3] = {64, (cuuint32_t)bk, (cuuint32_t)bc};
    enc(f, m, base, 3, dims, st, box);
}

extern "C" void kernel_launch(void* const* d_in, const int* in_sizes, int n_in, void* d_out, int out_size) {
    const bf16* x = (const bf16*)d_in[0];
    static PFN_enc fenc = nullptr;
    static void *p_xa, *p_mqk, *p_wepi, *p_uc, *p_t1;
    static int fused = 0;
    if (!fenc) {
        void* fn = nullptr;
        cudaDriverEntryPointQueryResult qr;
        cudaGetDriverEntryPoint("cuTensorMapEncodeTiled", &fn, cudaEnableDefault, &qr);
        fenc = (PFN_enc)fn;
        cudaGetSymbolAddress(&p_xa, g_xa);
        cudaGetSymbolAddress(&p_mqk, g_mqk);
        cudaGetSymbolAddress(&p_wepi, g_wepi);
        cudaGetSymbolAddress(&p_uc, g_uc);
        cudaGetSymbolAddress(&p_t1, g_t1);
        cudaFuncSetAttribute(main_kernel, cudaFuncAttributeMaxDynamicSharedMemorySize, SMEM_BYTES);
        int dev = 0, sms = 0, occ = 0;
        cudaGetDevice(&dev);
        cudaDeviceGetAttribute(&sms, cudaDevAttrMultiProcessorCount, dev);
        cudaOccupancyMaxActiveBlocksPerMultiprocessor(&occ, main_kernel, 384, SMEM_BYTES);
        fused = sms * occ >= NCTA + 2;
    }
    Maps mp;
    enc_act(fenc, &mp.xa, (char*)p_xa + 1024, 64, 8, T_, T_ + 8);
    enc_act(fenc, &mp.xa2, (char*)p_xa + 1024, 64, 2, T_, T_ + 8);
    enc_act(fenc, &mp.xas, p_xa, 64, 8, T_ + 1, T_ + 8);
    enc_act(fenc, &mp.x, (void*)x, 64, 8);
    enc_act(fenc, &mp.out, d_out, 62, 1);
    enc_w(fenc, &mp.wup4, d_in[5], 512, 1024, 16, 4);
    enc_w(fenc, &mp.wup8, d_in[5], 512, 1024, 16, 8);
    enc_w(fenc, &mp.mqa2, p_mqk, 512, 512, 32, 2);
    enc_w(fenc, &mp.mqa4, p_mqk, 512, 512, 32, 4);
    enc_w(fenc, &mp.mqb1, p_mqk, 512, 512, 64, 1);
    enc_w(fenc, &mp.mqb2, p_mqk, 512, 512, 64, 2);
    enc_w(fenc, &mp.wepi, p_wepi, 1024, 512, 16, 4);
    enc_w(fenc, &mp.uc, p_uc, NCTA * 64, 512, 64, 8);
    enc_w(fenc, &mp.wq, d_in[1], 512, 512, 64, 8);
    enc_w(fenc, &mp.wk, d_in[2], 512, 512, 32, 8);
    enc_w(fenc, &mp.fa[0], d_in[3], 512, 512, 128, 1);
    enc_w(fenc, &mp.fa[1], d_in[7], 512, 512, 128, 1);
    enc_w(fenc, &mp.fa[2], p_t1, 512, 512, 128, 1);
    enc_w(fenc, &mp.fb[0], d_in[4], 512, 512, 64, 4);
    enc_w(fenc, &mp.fb[1], d_in[8], 1024, 512, 64, 4);
    cudaStream_t st = cudaStreamPerThread;
    if (fused) {
        main_kernel<<<NCTA + 2, 384, SMEM_BYTES, st>>>(mp, (const bf16*)d_in[6], 0);
    } else {
        main_kernel<<<NCTA + 2, 384, SMEM_BYTES, st>>>(mp, (const bf16*)d_in[6], 1);
        main_kernel<<<NCTA + 2, 384, SMEM_BYTES, st>>>(mp, (const bf16*)d_in[6], 2);
    }
}
```

```cpp
#include <cuda_runtime.h>
#include <cuda_bf16.h>
#include <cuda.h>
#include <stdint.h>

typedef __nv_bfloat16 bf16;

constexpr int T_ = 4000, D_ = 512, NB_ = 2;
constexpr int TPB = 65;
constexpr int NCTA = TPB * NB_;
constexpr int NKV = 63;

__device__ __align__(1024) bf16 g_xa[NB_ * (T_ + 8) * D_];
__device__ __align__(1024) bf16 g_mqk[D_ * D_];
__device__ __align__(1024) bf16 g_t1[D_ * D_];
__device__ __align__(1024) bf16 g_wepi[2 * D_ * D_];
__device__ __align__(1024) bf16 g_uc[NCTA * 64 * D_];
__device__ unsigned g_sync[8];

#define PT(i)
#define PL(j, q)
#define PDUMP()

#define FENCE_AT 1
#define GO_AT 25
constexpr uint32_t R0 = 0, R1 = 65536, R2 = 131072, R3 = 196608, QS = 221184, MISC = 229376;
constexpr uint32_t AT = 147456, DWS = R3 + 16384, UCT = 163840;
constexpr uint32_t SMEM_BYTES = 232448;
constexpr uint32_t B_A = MISC, B_R1 = MISC + 8  , B_MK = MISC + 48, B_LN = MISC + 56, B_MQ = MISC + 64, B_XA = MISC + 72,
                   B_H1 = MISC + 88, B_H2 = MISC + 96, B_H3 = MISC + 104,
                   B_KV = MISC + 112, B_P = MISC + 136, B_GO = MISC + 160, B_R2 = MISC + 184, B_UC = MISC + 280,
                   B_X = MISC + 288, CNT = MISC + 296  , SCL = MISC + 512  ,
                   LINV = MISC + 1280  , STAT = MISC + 1536  ;

__device__ __forceinline__ uint32_t smem_u32(const void* p) { return (uint32_t)__cvta_generic_to_shared(p); }
__device__ __forceinline__ void wg_fence() { asm volatile("wgmma.fence.sync.aligned;" ::: "memory"); }
__device__ __forceinline__ void wg_commit() { asm volatile("wgmma.commit_group.sync.aligned;" ::: "memory"); }
template <int N> __device__ __forceinline__ void wg_wait() { asm volatile("wgmma.wait_group.sync.aligned %0;" ::"n"(N) : "memory"); }
__device__ __forceinline__ uint64_t dsc(uint32_t sd, uint32_t off, uint32_t lbo) {
    uint32_t lo = sd + (off >> 4) + ((lbo >> 4) << 16);
    uint64_t d;
    asm("mov.b64 %0, {%1, %2};" : "=l"(d) : "r"(lo), "r"((1024u >> 4) | (1u << 30)));
    return d;
}
__device__ __forceinline__ bool elect1() {
    uint32_t p;
    asm volatile("{\n.reg .pred p;\nelect.sync _|p, 0xffffffff;\nselp.u32 %0, 1, 0, p;\n}\n" : "=r"(p));
    return p != 0;
}
__device__ __forceinline__ void mbar_init(uint32_t bar, int cnt) { asm volatile("mbarrier.init.shared::cta.b64 [%0], %1;" ::"r"(bar), "r"(cnt) : "memory"); }
__device__ __forceinline__ void mbar_expect_tx(uint32_t bar, uint32_t bytes) { asm volatile("mbarrier.arrive.expect_tx.shared::cta.b64 _, [%0], %1;" ::"r"(bar), "r"(bytes) : "memory"); }
__device__ __forceinline__ void mbar_arrive(uint32_t bar) { asm volatile("mbarrier.arrive.shared::cta.b64 _, [%0];" ::"r"(bar) : "memory"); }
__device__ __forceinline__ void mbar_wait(uint32_t bar, uint32_t parity) {
    uint32_t ok;
#pragma unroll 1
    for (uint32_t it = 0;; ++it) {
        asm volatile("{\n.reg .pred p;\nmbarrier.try_wait.parity.shared::cta.b64 p, [%1], %2;\nselp.u32 %0, 1, 0, p;\n}\n" : "=r"(ok) : "r"(bar), "r"(parity) : "memory");
        if (ok) break;
        if (it > (1u << 20)) __trap();
    }
}
__device__ __forceinline__ void fence_async() { asm volatile("fence.proxy.async.shared::cta;" ::: "memory"); }
__device__ __forceinline__ void fence_async_g() { asm volatile("fence.proxy.async.global;" ::: "memory"); }
__device__ __forceinline__ void bar_sync(int id, int n) { asm volatile("bar.sync %0, %1;" ::"r"(id), "r"(n) : "memory"); }
__device__ __forceinline__ void tma3(uint32_t dst, const CUtensorMap* tm, int c0, int c1, int c2, uint32_t bar) {
    asm volatile("cp.async.bulk.tensor.3d.shared::cluster.global.mbarrier::complete_tx::bytes [%0], [%1, {%3, %4, %5}], [%2];"
                 ::"r"(dst), "l"(tm), "r"(bar), "r"(c0), "r"(c1), "r"(c2) : "memory");
}
__device__ __forceinline__ void tma4(uint32_t dst, const CUtensorMap* tm, int c0, int c1, int c2, int c3, uint32_t bar) {
    asm volatile("cp.async.bulk.tensor.4d.shared::cluster.global.mbarrier::complete_tx::bytes [%0], [%1, {%3, %4, %5, %6}], [%2];"
                 ::"r"(dst), "l"(tm), "r"(bar), "r"(c0), "r"(c1), "r"(c2), "r"(c3) : "memory");
}
__device__ __forceinline__ void tma4_store(const CUtensorMap* tm, uint32_t src, int c0, int c1, int c2, int c3) {
    asm volatile("cp.async.bulk.tensor.4d.global.shared::cta.bulk_group [%0, {%2, %3, %4, %5}], [%1];"
                 ::"l"(tm), "r"(src), "r"(c0), "r"(c1), "r"(c2), "r"(c3) : "memory");
}
__device__ __forceinline__ void tma3_store(const CUtensorMap* tm, uint32_t src, int c0, int c1, int c2) {
    asm volatile("cp.async.bulk.tensor.3d.global.shared::cta.bulk_group [%0, {%2, %3, %4}], [%1];"
                 ::"l"(tm), "r"(src), "r"(c0), "r"(c1), "r"(c2) : "memory");
}
__device__ __forceinline__ void stsm4(uint32_t addr, uint32_t a, uint32_t b, uint32_t c, uint32_t d) {
    asm volatile("stmatrix.sync.aligned.m8n8.x4.shared.b16 [%0], {%1, %2, %3, %4};" ::"r"(addr), "r"(a), "r"(b), "r"(c), "r"(d) : "memory");
}
__device__ __forceinline__ void ldsm4(uint32_t addr, uint32_t (&r)[4]) {
    asm volatile("ldmatrix.sync.aligned.m8n8.x4.shared.b16 {%0, %1, %2, %3}, [%4];" : "=r"(r[0]), "=r"(r[1]), "=r"(r[2]), "=r"(r[3]) : "r"(addr) : "memory");
}
__device__ __forceinline__ void ldsm2(uint32_t addr, uint32_t (&r)[2]) {
    asm volatile("ldmatrix.sync.aligned.m8n8.x2.shared.b16 {%0, %1}, [%2];" : "=r"(r[0]), "=r"(r[1]) : "r"(addr) : "memory");
}
__device__ __forceinline__ void stg4(void* p, uint32_t a, uint32_t b, uint32_t c, uint32_t d) {
    asm volatile("st.global.v4.u32 [%0], {%1, %2, %3, %4};" ::"l"(p), "r"(a), "r"(b), "r"(c), "r"(d) : "memory");
}
__device__ __forceinline__ uint32_t pack2(float lo, float hi) {
    uint32_t r;
    asm("cvt.rn.bf16x2.f32 %0, %1, %2;" : "=r"(r) : "f"(hi), "f"(lo));
    return r;
}
__device__ __forceinline__ uint32_t pack2v(float lo, float hi) {
    uint32_t r;
    asm volatile("cvt.rn.bf16x2.f32 %0, %1, %2;" : "=r"(r) : "f"(hi), "f"(lo));
    return r;
}
__device__ __forceinline__ uint32_t bmul2(uint32_t a, uint32_t b) { uint32_t r; asm("mul.rn.bf16x2 %0, %1, %2;" : "=r"(r) : "r"(a), "r"(b)); return r; }
__device__ __forceinline__ uint32_t bfma2(uint32_t a, uint32_t b, uint32_t c) { uint32_t r; asm("fma.rn.bf16x2 %0, %1, %2, %3;" : "=r"(r) : "r"(a), "r"(b), "r"(c)); return r; }
__device__ __forceinline__ float ex2(float x) { float r; asm("ex2.approx.ftz.f32 %0, %1;" : "=f"(r) : "f"(x)); return r; }
__device__ __forceinline__ float rcp(float x) { float r; asm("rcp.approx.ftz.f32 %0, %1;" : "=f"(r) : "f"(x)); return r; }
__device__ __forceinline__ float gelu(float x) {
    float t = fmaf(x * x, 0.044715f * 0.7978845608028654f, 0.7978845608028654f), th;
    asm("tanh.approx.f32 %0, %1;" : "=f"(th) : "f"(x * t));
    float hx = 0.5f * x;
    return fmaf(hx, th, hx);
}
__device__ __forceinline__ uint32_t ldg_v(const uint32_t* p) { uint32_t v; asm volatile("ld.global.nc.u32 %0, [%1];" : "=r"(v) : "l"(p)); return v; }
__device__ __forceinline__ float lds_f32(uint32_t a) { float v; asm volatile("ld.shared.f32 %0, [%1];" : "=f"(v) : "r"(a) : "memory"); return v; }
__device__ __forceinline__ void sts_f32(uint32_t a, float v) { asm volatile("st.shared.f32 [%0], %1;" ::"r"(a), "f"(v) : "memory"); }
__device__ __forceinline__ uint32_t atom_inc_s(uint32_t a) { uint32_t v; asm volatile("atom.relaxed.cta.shared.add.u32 %0, [%1], 1;" : "=r"(v) : "r"(a) : "memory"); return v; }
__device__ __forceinline__ void lds4(uint32_t a, uint32_t* r) {
    asm volatile("ld.shared.v4.u32 {%0, %1, %2, %3}, [%4];" : "=r"(r[0]), "=r"(r[1]), "=r"(r[2]), "=r"(r[3]) : "r"(a) : "memory");
}
__device__ __forceinline__ void sts4(uint32_t a, uint32_t x, uint32_t y, uint32_t z, uint32_t t) {
    asm volatile("st.shared.v4.u32 [%0], {%1, %2, %3, %4};" ::"r"(a), "r"(x), "r"(y), "r"(z), "r"(t) : "memory");
}
__device__ __forceinline__ uint32_t bsub2(uint32_t a, uint32_t b) { uint32_t r; asm("sub.rn.bf16x2 %0, %1, %2;" : "=r"(r) : "r"(a), "r"(b)); return r; }
__device__ __forceinline__ float blo(uint32_t v) { return __uint_as_float(v << 16); }
__device__ __forceinline__ float bhi(uint32_t v) { return __uint_as_float(v & 0xffff0000u); }
__device__ __forceinline__ float bfr(float x) { return __bfloat162float(__float2bfloat16_rn(x)); }
__device__ __forceinline__ void l2_prefetch(const void* p, uint32_t bytes) { asm volatile("cp.async.bulk.prefetch.L2.global [%0], %1;" ::"l"(p), "r"(bytes) : "memory"); }
__device__ __forceinline__ void flag_add(unsigned* p) { asm volatile("red.release.gpu.global.add.u32 [%0], 1;" ::"l"(p) : "memory"); }
__device__ __forceinline__ void flag_wait(const unsigned* p, unsigned target) {
#pragma unroll 1
    for (uint32_t it = 0;; ++it) {
        unsigned v;
        asm volatile("ld.acquire.gpu.global.u32 %0, [%1];" : "=r"(v) : "l"(p) : "memory");
        if (v >= target) break;
        if (it > (1u << 20)) __trap();
    }
    fence_async_g();
}
template <int N> __device__ __forceinline__ void pin(float (&a)[N]) {
#pragma unroll
    for (int i = 0; i < N; i++) asm volatile("" : "+f"(a[i])::"memory");
}

template <int N> __device__ __forceinline__ void fresh(float (&a)[N]) {
#pragma unroll
    for (int i = 0; i < N; i++) a[i] = 0.f;
    pin(a);
}

__device__ __forceinline__ void wgmma_rs_n64_tb0(float (&d)[32], uint32_t a0, uint32_t a1, uint32_t a2, uint32_t a3, uint64_t db, int scale_d) {
    asm volatile("{\n.reg .pred p;\nsetp.ne.b32 p, %37, 0;\n"
        "wgmma.mma_async.sync.aligned.m64n64k16.f32.bf16.bf16 {%0, %1, %2, %3, %4, %5, %6, %7, %8, %9, %10, %11, %12, %13, %14, %15, %16, %17, %18, %19, %20, %21, %22, %23, %24, %25, %26, %27, %28, %29, %30, %31}, {%32, %33, %34, %35}, %36, p, 1, 1, 0;\n}\n"
        : "+f"(d[0]), "+f"(d[1]), "+f"(d[2]), "+f"(d[3]), "+f"(d[4]), "+f"(d[5]), "+f"(d[6]), "+f"(d[7]), "+f"(d[8]), "+f"(d[9]), "+f"(d[10]), "+f"(d[11]), "+f"(d[12]), "+f"(d[13]), "+f"(d[14]), "+f"(d[15]), "+f"(d[16]), "+f"(d[17]), "+f"(d[18]), "+f"(d[19]), "+f"(d[20]), "+f"(d[21]), "+f"(d[22]), "+f"(d[23]), "+f"(d[24]), "+f"(d[25]), "+f"(d[26]), "+f"(d[27]), "+f"(d[28]), "+f"(d[29]), "+f"(d[30]), "+f"(d[31])
        : "r"(a0), "r"(a1), "r"(a2), "r"(a3), "l"(db), "r"(scale_d));
}

__device__ __forceinline__ void wgmma_ss_n128_tb1(float (&d)[64], uint64_t da, uint64_t db, int scale_d) {
    asm volatile("{\n.reg .pred p;\nsetp.ne.b32 p, %66, 0;\n"
        "wgmma.mma_async.sync.aligned.m64n128k16.f32.bf16.bf16 {%0, %1, %2, %3, %4, %5, %6, %7, %8, %9, %10, %11, %12, %13, %14, %15, %16, %17, %18, %19, %20, %21, %22, %23, %24, %25, %26, %27, %28, %29, %30, %31, %32, %33, %34, %35, %36, %37, %38, %39, %40, %41, %42, %43, %44, %45, %46, %47, %48, %49, %50, %51, %52, %53, %54, %55, %56, %57, %58, %59, %60, %61, %62, %63}, %64, %65, p, 1, 1, 0, 1;\n}\n"
        : "+f"(d[0]), "+f"(d[1]), "+f"(d[2]), "+f"(d[3]), "+f"(d[4]), "+f"(d[5]), "+f"(d[6]), "+f"(d[7]), "+f"(d[8]), "+f"(d[9]), "+f"(d[10]), "+f"(d[11]), "+f"(d[12]), "+f"(d[13]), "+f"(d[14]), "+f"(d[15]), "+f"(d[16]), "+f"(d[17]), "+f"(d[18]), "+f"(d[19]), "+f"(d[20]), "+f"(d[21]), "+f"(d[22]), "+f"(d[23]), "+f"(d[24]), "+f"(d[25]), "+f"(d[26]), "+f"(d[27]), "+f"(d[28]), "+f"(d[29]), "+f"(d[30]), "+f"(d[31]), "+f"(d[32]), "+f"(d[33]), "+f"(d[34]), "+f"(d[35]), "+f"(d[36]), "+f"(d[37]), "+f"(d[38]), "+f"(d[39]), "+f"(d[40]), "+f"(d[41]), "+f"(d[42]), "+f"(d[43]), "+f"(d[44]), "+f"(d[45]), "+f"(d[46]), "+f"(d[47]), "+f"(d[48]), "+f"(d[49]), "+f"(d[50]), "+f"(d[51]), "+f"(d[52]), "+f"(d[53]), "+f"(d[54]), "+f"(d[55]), "+f"(d[56]), "+f"(d[57]), "+f"(d[58]), "+f"(d[59]), "+f"(d[60]), "+f"(d[61]), "+f"(d[62]), "+f"(d[63])
        : "l"(da), "l"(db), "r"(scale_d));
}

__device__ __forceinline__ void wgmma_ss_n256_tb1(float (&d)[128], uint64_t da, uint64_t db, int scale_d) {
    asm volatile("{\n.reg .pred p;\nsetp.ne.b32 p, %130, 0;\n"
        "wgmma.mma_async.sync.aligned.m64n256k16.f32.bf16.bf16 {%0, %1, %2, %3, %4, %5, %6, %7, %8, %9, %10, %11, %12, %13, %14, %15, %16, %17, %18, %19, %20, %21, %22, %23, %24, %25, %26, %27, %28, %29, %30, %31, %32, %33, %34, %35, %36, %37, %38, %39, %40, %41, %42, %43, %44, %45, %46, %47, %48, %49, %50, %51, %52, %53, %54, %55, %56, %57, %58, %59, %60, %61, %62, %63, %64, %65, %66, %67, %68, %69, %70, %71, %72, %73, %74, %75, %76, %77, %78, %79, %80, %81, %82, %83, %84, %85, %86, %87, %88, %89, %90, %91, %92, %93, %94, %95, %96, %97, %98, %99, %100, %101, %102, %103, %104, %105, %106, %107, %108, %109, %110, %111, %112, %113, %114, %115, %116, %117, %118, %119, %120, %121, %122, %123, %124, %125, %126, %127}, %128, %129, p, 1, 1, 0, 1;\n}\n"
        : "+f"(d[0]), "+f"(d[1]), "+f"(d[2]), "+f"(d[3]), "+f"(d[4]), "+f"(d[5]), "+f"(d[6]), "+f"(d[7]), "+f"(d[8]), "+f"(d[9]), "+f"(d[10]), "+f"(d[11]), "+f"(d[12]), "+f"(d[13]), "+f"(d[14]), "+f"(d[15]), "+f"(d[16]), "+f"(d[17]), "+f"(d[18]), "+f"(d[19]), "+f"(d[20]), "+f"(d[21]), "+f"(d[22]), "+f"(d[23]), "+f"(d[24]), "+f"(d[25]), "+f"(d[26]), "+f"(d[27]), "+f"(d[28]), "+f"(d[29]), "+f"(d[30]), "+f"(d[31]), "+f"(d[32]), "+f"(d[33]), "+f"(d[34]), "+f"(d[35]), "+f"(d[36]), "+f"(d[37]), "+f"(d[38]), "+f"(d[39]), "+f"(d[40]), "+f"(d[41]), "+f"(d[42]), "+f"(d[43]), "+f"(d[44]), "+f"(d[45]), "+f"(d[46]), "+f"(d[47]), "+f"(d[48]), "+f"(d[49]), "+f"(d[50]), "+f"(d[51]), "+f"(d[52]), "+f"(d[53]), "+f"(d[54]), "+f"(d[55]), "+f"(d[56]), "+f"(d[57]), "+f"(d[58]), "+f"(d[59]), "+f"(d[60]), "+f"(d[61]), "+f"(d[62]), "+f"(d[63]), "+f"(d[64]), "+f"(d[65]), "+f"(d[66]), "+f"(d[67]), "+f"(d[68]), "+f"(d[69]), "+f"(d[70]), "+f"(d[71]), "+f"(d[72]), "+f"(d[73]), "+f"(d[74]), "+f"(d[75]), "+f"(d[76]), "+f"(d[77]), "+f"(d[78]), "+f"(d[79]), "+f"(d[80]), "+f"(d[81]), "+f"(d[82]), "+f"(d[83]), "+f"(d[84]), "+f"(d[85]), "+f"(d[86]), "+f"(d[87]), "+f"(d[88]), "+f"(d[89]), "+f"(d[90]), "+f"(d[91]), "+f"(d[92]), "+f"(d[93]), "+f"(d[94]), "+f"(d[95]), "+f"(d[96]), "+f"(d[97]), "+f"(d[98]), "+f"(d[99]), "+f"(d[100]), "+f"(d[101]), "+f"(d[102]), "+f"(d[103]), "+f"(d[104]), "+f"(d[105]), "+f"(d[106]), "+f"(d[107]), "+f"(d[108]), "+f"(d[109]), "+f"(d[110]), "+f"(d[111]), "+f"(d[112]), "+f"(d[113]), "+f"(d[114]), "+f"(d[115]), "+f"(d[116]), "+f"(d[117]), "+f"(d[118]), "+f"(d[119]), "+f"(d[120]), "+f"(d[121]), "+f"(d[122]), "+f"(d[123]), "+f"(d[124]), "+f"(d[125]), "+f"(d[126]), "+f"(d[127])
        : "l"(da), "l"(db), "r"(scale_d));
}

__device__ __forceinline__ void wgmma_ss_n32_tb0(float (&d)[16], uint64_t da, uint64_t db, int scale_d) {
    asm volatile("{\n.reg .pred p;\nsetp.ne.b32 p, %18, 0;\n"
        "wgmma.mma_async.sync.aligned.m64n32k16.f32.bf16.bf16 {%0, %1, %2, %3, %4, %5, %6, %7, %8, %9, %10, %11, %12, %13, %14, %15}, %16, %17, p, 1, 1, 0, 0;\n}\n"
        : "+f"(d[0]), "+f"(d[1]), "+f"(d[2]), "+f"(d[3]), "+f"(d[4]), "+f"(d[5]), "+f"(d[6]), "+f"(d[7]), "+f"(d[8]), "+f"(d[9]), "+f"(d[10]), "+f"(d[11]), "+f"(d[12]), "+f"(d[13]), "+f"(d[14]), "+f"(d[15])
        : "l"(da), "l"(db), "r"(scale_d));
}

__device__ __forceinline__ void wgmma_ss_n64_tb0(float (&d)[32], uint64_t da, uint64_t db, int scale_d) {
    asm volatile("{\n.reg .pred p;\nsetp.ne.b32 p, %34, 0;\n"
        "wgmma.mma_async.sync.aligned.m64n64k16.f32.bf16.bf16 {%0, %1, %2, %3, %4, %5, %6, %7, %8, %9, %10, %11, %12, %13, %14, %15, %16, %17, %18, %19, %20, %21, %22, %23, %24, %25, %26, %27, %28, %29, %30, %31}, %32, %33, p, 1, 1, 0, 0;\n}\n"
        : "+f"(d[0]), "+f"(d[1]), "+f"(d[2]), "+f"(d[3]), "+f"(d[4]), "+f"(d[5]), "+f"(d[6]), "+f"(d[7]), "+f"(d[8]), "+f"(d[9]), "+f"(d[10]), "+f"(d[11]), "+f"(d[12]), "+f"(d[13]), "+f"(d[14]), "+f"(d[15]), "+f"(d[16]), "+f"(d[17]), "+f"(d[18]), "+f"(d[19]), "+f"(d[20]), "+f"(d[21]), "+f"(d[22]), "+f"(d[23]), "+f"(d[24]), "+f"(d[25]), "+f"(d[26]), "+f"(d[27]), "+f"(d[28]), "+f"(d[29]), "+f"(d[30]), "+f"(d[31])
        : "l"(da), "l"(db), "r"(scale_d));
}

struct Maps {
    CUtensorMap xa, xa2, xas, wup4, wup8, mqa2, mqa4, mqb1, mqb2, wepi, uc, x, out, wq, wk, fa[3], fb[2], fc[2];
};

__device__ __forceinline__ uint64_t mkd(uint32_t lo) {
    uint64_t d;
    asm("mov.b64 %0, {%1, %2};" : "=l"(d) : "r"(lo), "r"((1024u >> 4) | (1u << 30)));
    return d;
}
__device__ __forceinline__ void ring_ld(uint32_t sb, uint32_t barbase, uint32_t slot8, const CUtensorMap* tm, int c1, int c2) {
    mbar_expect_tx(sb + barbase + slot8, 8192);
    tma3(sb + R1 + slot8 * 1024, tm, 0, c1, c2, sb + barbase + slot8);
}

__device__ __forceinline__ void ring_half(uint32_t sb, uint32_t slot8, uint32_t hoff, const CUtensorMap* tm, int c1, int c2) {
    mbar_expect_tx(sb + B_R1 + slot8, 8192);
    tma3(sb + R1 + slot8 * 2048 + hoff, tm, 0, c1, c2, sb + B_R1 + slot8);
}
__device__ __forceinline__ void ring_full(uint32_t sb, uint32_t slot8, const CUtensorMap* tm, int c1, int c2) {
    mbar_expect_tx(sb + B_R1 + slot8, 16384);
    mbar_arrive(sb + B_R1 + slot8);
    tma3(sb + R1 + slot8 * 2048, tm, 0, c1, c2, sb + B_R1 + slot8);
}
__device__ __forceinline__ void cta_done(int mode) {
    if (mode == 0 && atomicAdd(&g_sync[4], 1) == NCTA + 1) {
#pragma unroll
        for (int i = 0; i < 5; i++) g_sync[i] = 0;
    }
}

__device__ __forceinline__ void fold_cta(const Maps& mp, uint32_t sb, int mode) {
    constexpr uint32_t F_FULL = MISC, F_EMPTY = MISC + 32, F_T1 = MISC + 64, STG = 49152, FOUT = 3 * STG;
    const int tid = threadIdx.x, f = blockIdx.x - NCTA;
    if (mode == 2) return;
    if (tid == 0) {
        for (int i = 0; i < 3; i++) { mbar_init(sb + F_FULL + 8 * i, 1); mbar_init(sb + F_EMPTY + 8 * i, 2); }
        mbar_init(sb + F_T1, 2);
        asm volatile("fence.mbarrier_init.release.cluster;" ::: "memory");
        fence_async();
    }
    __syncthreads();
    const int wg = __shfl_sync(0xffffffffu, tid >> 7, 0);
    int st = 0, ph = 0;
    if (wg == 0) {
        if (tid == 0) {
#pragma unroll 1
            for (int it = 0; it < 96; it++) {
                const int p = it >> 3, kc = it & 7, job = p >> 2;
                if (it == 64) mbar_wait(sb + F_T1, 0);
                mbar_wait(sb + F_EMPTY + 8 * st, ph ^ 1);
                mbar_expect_tx(sb + F_FULL + 8 * st, STG);
                tma3(sb + st * STG, &mp.fa[job], 0, 256 * f + 128 * ((p >> 1) & 1), kc, sb + F_FULL + 8 * st);
                tma3(sb + st * STG + 16384, &mp.fb[job != 0], 0, 64 * kc + (job == 1 ? 512 : 0), 4 * (p & 1), sb + F_FULL + 8 * st);
                if (++st == 3) { st = 0; ph ^= 1; }
            }
        }
        return;
    }
    const int h = wg - 1, lane = tid & 31, w = (tid >> 5) & 3;
    const uint32_t sd = (sb & 0x3FFFF) >> 4;
    const bool el = (tid & 127) == 0;
#pragma unroll 1
    for (int p = 0; p < 12; p++) {
        float acc[128];
        fresh(acc);
#pragma unroll 1
        for (int kc = 0; kc < 8; kc++) {
            mbar_wait(sb + F_FULL + 8 * st, ph);
            wg_fence();
#pragma unroll
            for (int kk = 0; kk < 4; kk++)
                wgmma_ss_n256_tb1(acc, dsc(sd, st * STG + h * 8192 + kk * 32, 16), dsc(sd, st * STG + 16384 + kk * 2048, 8192), 1);
            wg_commit();
            wg_wait<0>();
            if (el) mbar_arrive(sb + F_EMPTY + 8 * st);
            if (++st == 3) { st = 0; ph ^= 1; }
        }
        pin(acc);
        const int job = p >> 2;
        if (el) {
            asm volatile("cp.async.bulk.wait_group 0;" ::: "memory");
            if (p == 4) { fence_async_g(); mbar_arrive(sb + F_T1); }
        }
        bar_sync(3 + h, 128);
        uint32_t r = 16 * w + (lane & 7) + ((lane >> 3) & 1) * 8;
        if (job == 1) r = (r & ~31) | (((r >> 1) & 3) << 3) | (((r >> 3) & 3) << 1) | (r & 1);
        const uint32_t oa = sb + FOUT + h * 32768 + r * 128 + ((((lane >> 4) ^ r) & 7) << 4);
#pragma unroll
        for (int i = 0; i < 16; i++)
            stsm4((oa ^ ((i & 3) << 5)) + (i >> 2) * 8192, pack2(acc[8 * i], acc[8 * i + 1]), pack2(acc[8 * i + 2], acc[8 * i + 3]),
                  pack2(acc[8 * i + 4], acc[8 * i + 5]), pack2(acc[8 * i + 6], acc[8 * i + 7]));
        fence_async();
        bar_sync(3 + h, 128);
        if (el) {
            tma3_store(&mp.fc[job != 0], sb + FOUT + h * 32768, 0, 256 * f + 128 * ((p >> 1) & 1) + 64 * h + (job == 1 ? 512 : 0), 4 * (p & 1));
            asm volatile("cp.async.bulk.commit_group;" ::: "memory");
        }
    }
    if (el) {
        asm volatile("cp.async.bulk.wait_group 0;" ::: "memory");
        fence_async_g();
        if (mode == 0) flag_add(&g_sync[3]);
    }
    bar_sync(2, 256);
    if (tid == 128) cta_done(mode);
}

__global__ void __launch_bounds__(384, 1) main_kernel(const __grid_constant__ Maps mp, const bf16* __restrict__ dw, const bf16* wup, const bf16* wm, const int mode) {
    extern __shared__ __align__(1024) uint8_t smem[];
    const uint32_t sb = smem_u32(smem);
    const int tid = threadIdx.x;
    if (blockIdx.x >= NCTA) { fold_cta(mp, sb, mode); return; }
    const int b = blockIdx.x / TPB, ti = blockIdx.x % TPB;
    const int piece = blockIdx.x & 127;
    if (tid == 0) {
        mbar_init(sb + B_A, 1); mbar_init(sb + B_MK, 1);
        for (int i = 0; i < 5; i++) mbar_init(sb + B_R1 + 8 * i, 2);
        asm volatile("fence.mbarrier_init.release.cluster;" ::: "memory");
        fence_async();
        mbar_expect_tx(sb + B_A, 65536 + 3072);
        tma4(sb + AT, &mp.x, 0, 62 * ti - 1, 0, b, sb + B_A);
        mbar_expect_tx(sb + B_MK, 65536 + 32768);
        tma3(sb + R0, &mp.wq, 0, 64 * (piece >> 4), 0, sb + B_MK);
        tma3(sb + R1 + 32768, &mp.wk, 0, 32 * (piece & 15), 0, sb + B_MK);
        asm volatile("cp.async.bulk.shared::cluster.global.mbarrier::complete_tx::bytes [%0], [%1], 3072, [%2];" ::"r"(sb + DWS), "l"(dw), "r"(sb + B_A) : "memory");
        for (int i = 0; i < 8; i++) mbar_arrive(sb + B_R1 + 8 * (i >> 1));
        if (mode != 1) {
            ring_full(sb, 32, &mp.wup8, 0, 8);
            ring_full(sb, 0, &mp.wup8, 16, 8);
            ring_full(sb, 8, &mp.wup8, 32, 8);
        }
    } else if (tid == 64) {
        l2_prefetch((const char*)wup + piece * 8192, 8192);
        l2_prefetch((const char*)wm + piece * 8192, 8192);
    } else if (tid == 32) {
        mbar_init(sb + B_LN, 1); mbar_init(sb + B_MQ, 1); mbar_init(sb + B_XA, 1);
        mbar_init(sb + B_H1, 2); mbar_init(sb + B_H2, 1); mbar_init(sb + B_H3, 2);
        for (int i = 0; i < 3; i++) { mbar_init(sb + B_KV + 8 * i, 1); mbar_init(sb + B_P + 8 * i, 4); mbar_init(sb + B_GO + 8 * i, 4); }
        for (int i = 0; i < 12; i++) mbar_init(sb + B_R2 + 8 * i, 1);
        mbar_init(sb + B_UC, 1); mbar_init(sb + B_X, 1);
        for (int i = 0; i < 4; i++) asm volatile("st.shared.u32 [%0], 0;" ::"r"(sb + CNT + 4 * i) : "memory");
        asm volatile("fence.mbarrier_init.release.cluster;" ::: "memory");
        fence_async();
    }
    __syncthreads();
    const int wg = __shfl_sync(0xffffffffu, tid >> 7, 0);
    const int lane = tid & 31, w = (tid >> 5) & 3;
    const bool w0 = __shfl_sync(0xffffffffu, w, 0) == 0;
    const uint32_t sd = (sb & 0x3FFFF) >> 4;
    const uint32_t adA = sd + (AT >> 4) + (1u << 16);
    const uint32_t bd0 = sd + (R1 >> 4);
    const uint32_t bd2k = bd0 + ((2048u >> 4) << 16);
    const bool el = (tid & 127) == 0;
    const uint32_t lrow = 16 * w + (lane & 7) + ((lane >> 3) & 1) * 8;
    const uint32_t loff = lrow * 128 + ((((lane >> 4) ^ lrow) & 7) << 4);
    const int r0 = 16 * w + (lane >> 2);

    if (wg == 0) {
        asm volatile("setmaxnreg.inc.sync.aligned.u32 184;");
        uint32_t q[112];
        PT(0);
        {
            float mq[16];
            fresh(mq);
            mbar_wait(sb + B_MK, 0);
            PT(1);
            wg_fence();
#pragma unroll 1
            for (int c = 0; c < 8; c++)
#pragma unroll
                for (int kk = 0; kk < 4; kk++)
                    wgmma_ss_n32_tb0(mq, dsc(sd, R0 + c * 8192 + kk * 32, 16), dsc(sd, R1 + 32768 + c * 4096 + kk * 32, 16), 1);
            wg_commit();
            wg_wait<0>();
            if (mode != 1 && w0 && elect1()) { ring_full(sb, 16, &mp.wup8, 48, 8); ring_full(sb, 24, &mp.wup8, 64, 8); }
            pin(mq);
            uint32_t* c = reinterpret_cast<uint32_t*>(g_mqk + (64 * (piece >> 4) + r0) * D_ + 32 * (piece & 15) + 2 * (lane & 3));
#pragma unroll
            for (int n = 0; n < 4; n++) { c[4 * n] = pack2(mq[4 * n], mq[4 * n + 1]); c[4 * n + 4 * D_] = pack2(mq[4 * n + 2], mq[4 * n + 3]); }
            fence_async_g();
            bar_sync(1, 128);
            if (el) {
                if (mode == 0) flag_add(&g_sync[2]);
                mbar_wait(sb + B_LN, 0);
                tma4_store(&mp.xas, sb + AT, 0, 62 * ti, 0, b);
                asm volatile("cp.async.bulk.commit_group;" ::: "memory");
                asm volatile("cp.async.bulk.wait_group 0;" ::: "memory");
                if (mode == 0) {
                    fence_async_g();
                    flag_add(&g_sync[b]);
                    PT(12);
                    flag_wait(&g_sync[2], NCTA);
                }
                mbar_arrive(sb + B_MQ);
            }
            PT(13);
            if (mode == 1) return;
        }
        mbar_wait(sb + B_H1, 0);
        PT(2);
        uint32_t slot8 = 8, par = 1, prev8 = 0;
        auto adv = [&]() { prev8 = slot8; slot8 += 8; if (slot8 == 40) { slot8 = 0; par ^= 1; } };
        {
            float acc[128];
            fresh(acc);
            auto step = [&](int i) {
                const uint32_t aa = adA + (i >> 1) * 512 + (i & 1) * 4, bb = bd0 + ((4096u >> 4) << 16) + slot8 * 128;
                wg_fence();
                wgmma_ss_n256_tb1(acc, mkd(aa), mkd(bb), 1);
                wgmma_ss_n256_tb1(acc, mkd(aa + 2), mkd(bb + 128), 1);
                wg_commit();
                wg_wait<1>();
            };
#pragma unroll 1
            for (int i = 0; i < 12; i++) {
                mbar_wait(sb + B_R1 + slot8, par);
                step(i);
                if (i > 0 && w0 && elect1()) ring_full(sb, prev8, &mp.mqa4, 32 * i + 128, 4);
                adv();
            }
#pragma unroll 1
            for (int i = 12; i < 16; i++) {
                mbar_wait(sb + B_R1 + slot8, par);
                if (i == 15 && el) mbar_arrive(sb + B_H2);
                step(i);
                if (w0 && elect1()) ring_full(sb, prev8, &mp.wup8, 16 * i - 192, 0);
                adv();
            }
            wg_wait<0>();
            if (w0 && elect1()) ring_full(sb, prev8, &mp.wup8, 64, 0);
            pin(acc);
            PT(3);
#pragma unroll
            for (int kk = 0; kk < 4; kk++)
                stsm4((sb + QS + loff) ^ (kk << 5), pack2(acc[96 + 8 * kk], acc[97 + 8 * kk]), pack2(acc[98 + 8 * kk], acc[99 + 8 * kk]),
                      pack2(acc[100 + 8 * kk], acc[101 + 8 * kk]), pack2(acc[102 + 8 * kk], acc[103 + 8 * kk]));
            fence_async();
#pragma unroll
            for (int i = 47; i >= 0; i--) q[64 + i] = pack2v(acc[2 * i], acc[2 * i + 1]);
        }
        if (el) {
            if (mode == 0) flag_wait(&g_sync[b], TPB);
            mbar_arrive(sb + B_XA);
        }
        __syncwarp();
        mbar_wait(sb + B_H3, 0);
        PT(4);
        slot8 = 32; par = 0;
#pragma unroll
        for (int half = 0; half < 2; half++) {
            float acc[64];
            fresh(acc);
            auto step = [&](int m) {
                const uint32_t aa = adA + m * 512, bb = bd0 + ((8192u >> 4) << 16) + slot8 * 128;
                mbar_wait(sb + B_R1 + slot8, par);
                wg_fence();
#pragma unroll
                for (int kk = 0; kk < 4; kk++) wgmma_ss_n128_tb1(acc, mkd(aa + 2 * kk), mkd(bb + 128 * kk), 1);
                wg_commit();
                wg_wait<1>();
            };
            if (half == 0) {
#pragma unroll 1
                for (int m = 0; m < 8; m++) {
                    step(m);
                    if (m > 0 && w0 && elect1()) ring_full(sb, prev8, &mp.mqb2, (64 * m + 256) & 511, (m + 4) >> 3 << 1);
                    adv();
                }
            } else {
#pragma unroll 1
                for (int m = 0; m < 4; m++) {
                    step(m);
                    if (m > 0 && w0 && elect1()) ring_full(sb, prev8, &mp.mqb2, 64 * m + 256, 2);
                    adv();
                }
#pragma unroll 1
                for (int m = 4; m < 8; m++) {
                    step(m);
                    if (w0 && elect1()) {
                        if (m == 4) mbar_expect_tx(sb + B_KV + 8, 65536);
                        tma4(sb + R1 + prev8 * 2048, &mp.xa2, 0, 0, 2 * m - 8, b, sb + B_KV + 8);
                    }
                    adv();
                }
            }
            wg_wait<0>();
            if (w0 && elect1()) {
                if (half == 0) ring_full(sb, prev8, &mp.mqb2, 256, 2);
                else {
                    mbar_expect_tx(sb + B_KV + 16, 65536);
                    tma4(sb + R2, &mp.xa, 0, 64, 0, b, sb + B_KV + 16);
                }
            }
            pin(acc);
#pragma unroll
            for (int i = 31; i >= 0; i--) q[32 * half + i] = pack2v(acc[2 * i], acc[2 * i + 1]);
        }
        bar_sync(1, 128);
        PT(5);

        const float CS = 0.04419417382415922f * 1.4426950408889634f;
        float m0 = -INFINITY, m1 = -INFINITY, l0 = 0.f, l1 = 0.f;
        int s = 0, sn = 1, ph = 0;
        float S[32];
        const bool l0w = lane == 0, q0 = (lane & 3) == 0;
#pragma unroll 1
        for (int j = -1;; j++) {
            if (j >= 0) {
                PL(j, 1);
                if (j == NKV - 1) {
#pragma unroll
                    for (int i = (T_ - 64 * (NKV - 1)) / 2; i < 32; i++) asm volatile("mov.b32 %0, 0xff800000;" : "=f"(S[i]));
                }
                float y[8], z[8];
#pragma unroll
                for (int n = 0; n < 8; n++) { y[n] = fmaxf(S[4 * n], S[4 * n + 1]); z[n] = fmaxf(S[4 * n + 2], S[4 * n + 3]); }
#pragma unroll
                for (int n = 0; n < 4; n++) { y[n] = fmaxf(y[n], y[n + 4]); z[n] = fmaxf(z[n], z[n + 4]); }
                float x0 = fmaxf(fmaxf(y[0], y[1]), fmaxf(fmaxf(y[2], y[3]), m0)), x1 = fmaxf(fmaxf(z[0], z[1]), fmaxf(fmaxf(z[2], z[3]), m1));
                x0 = fmaxf(x0, __shfl_xor_sync(0xffffffffu, x0, 1));
                x1 = fmaxf(x1, __shfl_xor_sync(0xffffffffu, x1, 1));
                x0 = fmaxf(x0, __shfl_xor_sync(0xffffffffu, x0, 2));
                x1 = fmaxf(x1, __shfl_xor_sync(0xffffffffu, x1, 2));
                const float sc0 = ex2((m0 - x0) * CS), sc1 = ex2((m1 - x1) * CS);
                m0 = x0; m1 = x1;
                const float n0 = -x0 * CS, n1 = -x1 * CS;
                if (q0) { sts_f32(sb + SCL + s * 256 + r0 * 4, sc0); sts_f32(sb + SCL + s * 256 + r0 * 4 + 32, sc1); }
                __syncwarp();
                if (l0w) mbar_arrive(sb + B_P + s * 8);
                if (j < NKV - 1) mbar_wait(sb + B_KV + sn * 8, ph);
                float a0 = 0.f, a1 = 0.f;
                const uint32_t pb = sb + R3 + (s == 0 ? 2 : s - 1) * 8192;
#pragma unroll
                for (int kk = 0; kk < 4; kk++) {
                    float p[8];
#pragma unroll
                    for (int e = 0; e < 8; e++) p[e] = ex2(fmaf(S[8 * kk + e], CS, (e & 2) ? n1 : n0));
                    a0 += (p[0] + p[1]) + (p[4] + p[5]);
                    a1 += (p[2] + p[3]) + (p[6] + p[7]);
                    stsm4((pb + loff) ^ (kk << 5), pack2(p[0], p[1]), pack2(p[2], p[3]), pack2(p[4], p[5]), pack2(p[6], p[7]));
                }
                l0 = fmaf(l0, sc0, a0); l1 = fmaf(l1, sc1, a1);
                PL(j, 2);
                if (j == NKV - 1) break;
            } else {
                mbar_wait(sb + B_KV + 8, 0);
            }
            float Sn[32];
            const uint32_t kd = sd + sn * 4096;
            wg_fence();
#pragma unroll
            for (int kk = 0; kk < 28; kk++) {
                wgmma_rs_n64_tb0(Sn, q[4 * kk], q[4 * kk + 1], q[4 * kk + 2], q[4 * kk + 3], dsc(kd, (kk >> 2) * 8192 + (kk & 3) * 32, 16), kk > 0);
                if (kk == FENCE_AT) { fence_async(); __syncwarp(); }
                if (kk == GO_AT) { PL(j, 3); if (j >= 0 && l0w) mbar_arrive(sb + B_GO + s * 8); }
            }
#pragma unroll
            for (int kk = 0; kk < 4; kk++)
                wgmma_ss_n64_tb0(Sn, dsc(sd, QS + kk * 32, 16), dsc(kd, 7 * 8192 + kk * 32, 16), 1);
            wg_commit();
            PL(j, 0);
            wg_wait<0>();
            pin(Sn);
#pragma unroll
            for (int i = 0; i < 32; i++) S[i] = Sn[i];
            s = sn;
            if (++sn == 3) sn = 0;
            if (sn == 1) ph ^= 1;
        }
        l0 += __shfl_xor_sync(0xffffffffu, l0, 1); l1 += __shfl_xor_sync(0xffffffffu, l1, 1);
        l0 += __shfl_xor_sync(0xffffffffu, l0, 2); l1 += __shfl_xor_sync(0xffffffffu, l1, 2);
        if (q0) { sts_f32(sb + LINV + r0 * 4, rcp(l0)); sts_f32(sb + LINV + r0 * 4 + 32, rcp(l1)); }
        fence_async();
        __syncwarp();
        if (l0w) mbar_arrive(sb + B_GO + s * 8);
        PDUMP();
    } else {
        asm volatile("setmaxnreg.dec.sync.aligned.u32 160;");
        const int h = wg - 1;
        mbar_wait(sb + B_A, 0);
        PT(0);
#pragma unroll 1
        for (int bt = 0; bt < 2; bt++) {
            uint32_t v[4][8];
            float mu[4], vr[4];
            const uint32_t la = sb + AT + (lane >> 3) * 8192 + (32 * h + 8 * w + 4 * bt) * 128 + (((lane & 7) ^ (4 * bt)) << 4);
#pragma unroll
            for (int r = 0; r < 4; r++) { lds4((la ^ (r << 4)) + r * 128, v[r]); lds4((la ^ (r << 4)) + r * 128 + 32768, v[r] + 4); }
#pragma unroll
            for (int r = 0; r < 4; r++) {
                float s0 = 0.f, s1 = 0.f;
#pragma unroll
                for (int i = 0; i < 8; i++) { s0 += blo(v[r][i]); s1 += bhi(v[r][i]); }
                mu[r] = s0 + s1;
            }
#pragma unroll
            for (int o = 16; o; o >>= 1)
#pragma unroll
                for (int r = 0; r < 4; r++) mu[r] += __shfl_xor_sync(0xffffffffu, mu[r], o);
#pragma unroll
            for (int r = 0; r < 4; r++) {
                mu[r] *= (1.f / D_);
                float s0 = 0.f, s1 = 0.f;
#pragma unroll
                for (int i = 0; i < 8; i++) { const float d0 = blo(v[r][i]) - mu[r], d1 = bhi(v[r][i]) - mu[r]; s0 = fmaf(d0, d0, s0); s1 = fmaf(d1, d1, s1); }
                vr[r] = s0 + s1;
            }
#pragma unroll
            for (int o = 16; o; o >>= 1)
#pragma unroll
                for (int r = 0; r < 4; r++) vr[r] += __shfl_xor_sync(0xffffffffu, vr[r], o);
#pragma unroll
            for (int r = 0; r < 4; r++) {
                const uint32_t m2 = pack2(mu[r], mu[r]);
                const float rinv = 1.f / bfr(sqrtf(bfr(bfr(vr[r] * (1.f / D_)) + 1e-5f)));
#pragma unroll
                for (int i = 0; i < 8; i++) { const uint32_t d = bsub2(v[r][i], m2); v[r][i] = pack2(blo(d) * rinv, bhi(d) * rinv); }
                sts4((la ^ (r << 4)) + r * 128, v[r][0], v[r][1], v[r][2], v[r][3]);
                sts4((la ^ (r << 4)) + r * 128 + 32768, v[r][4], v[r][5], v[r][6], v[r][7]);
            }
        }
        fence_async();
        bar_sync(2, 256);
        if (tid == 128) mbar_arrive(sb + B_LN);
        if (mode == 1) return;
        float acc[128];
#pragma unroll
        for (int pass = 0; pass < 2; pass++) {
            if (pass == 1) mbar_wait(sb + B_H2, 0);
            PT(1 + 3 * pass);
            fresh(acc);
            uint32_t slot8 = pass ? 16 : 32, par = 0, prev8 = 0;
            auto adv = [&]() { prev8 = slot8; slot8 += 8; if (slot8 == 40) { slot8 = 0; par ^= 1; } };
            auto step = [&](int kk) {
                wg_fence();
                wgmma_ss_n256_tb1(acc, mkd(adA + (kk >> 2) * 512 + (kk & 3) * 2), mkd(bd2k + h * 512 + slot8 * 128), 1);
                wg_commit();
                wg_wait<1>();
            };
#pragma unroll 1
            for (int kk = 0; kk < 28; kk++) {
                mbar_wait(sb + B_R1 + slot8, par);
                step(kk);
                if (kk > 0 && w0 && elect1()) ring_half(sb, prev8, h * 8192, &mp.wup4, 16 * kk + 64, (pass ? 0 : 8) + 4 * h);
                adv();
            }
            if (pass == 0 && w0) mbar_wait(sb + B_MQ, 0);
#pragma unroll 1
            for (int kk = 28; kk < 32; kk++) {
                mbar_wait(sb + B_R1 + slot8, par);
                if (kk == 31 && el) mbar_arrive(sb + (pass ? B_H3 : B_H1));
                step(kk);
                if (w0 && elect1()) ring_half(sb, prev8, h * 8192, pass ? &mp.mqb1 : &mp.mqa2, (pass ? 64 : 32) * (kk - 28), pass ? h : 4 + 2 * h);
                adv();
            }
            wg_wait<0>();
            if (w0 && elect1()) ring_half(sb, prev8, h * 8192, pass ? &mp.mqb1 : &mp.mqa2, pass ? 256 : 128, pass ? h : 4 + 2 * h);
            pin(acc);
            PT(2 + 3 * pass);
            if (pass == 0) {
#pragma unroll
                for (int i = 0; i < 128; i++) acc[i] = gelu(acc[i]);
                float s0 = 0.f, s1 = 0.f;
#pragma unroll
                for (int n = 0; n < 32; n++) { s0 += acc[4 * n] + acc[4 * n + 1]; s1 += acc[4 * n + 2] + acc[4 * n + 3]; }
                s0 += __shfl_xor_sync(0xffffffffu, s0, 1); s1 += __shfl_xor_sync(0xffffffffu, s1, 1);
                s0 += __shfl_xor_sync(0xffffffffu, s0, 2); s1 += __shfl_xor_sync(0xffffffffu, s1, 2);
                s0 *= (1.f / 256.f); s1 *= (1.f / 256.f);
                float v0 = 0.f, v1 = 0.f;
#pragma unroll
                for (int n = 0; n < 32; n++) {
                    float d0 = acc[4 * n] - s0, d1 = acc[4 * n + 1] - s0, d2 = acc[4 * n + 2] - s1, d3 = acc[4 * n + 3] - s1;
                    v0 = fmaf(d0, d0, v0); v0 = fmaf(d1, d1, v0); v1 = fmaf(d2, d2, v1); v1 = fmaf(d3, d3, v1);
                }
                v0 += __shfl_xor_sync(0xffffffffu, v0, 1); v1 += __shfl_xor_sync(0xffffffffu, v1, 1);
                v0 += __shfl_xor_sync(0xffffffffu, v0, 2); v1 += __shfl_xor_sync(0xffffffffu, v1, 2);
                if ((lane & 3) == 0) {
                    uint32_t a = sb + STAT + h * 512 + r0 * 8;
                    sts_f32(a, s0); sts_f32(a + 4, v0); sts_f32(a + 64, s1); sts_f32(a + 68, v1);
                }
                bar_sync(2, 256);
                {
                    uint32_t a = sb + STAT + (h ^ 1) * 512 + r0 * 8;
                    float t0 = lds_f32(a), u0 = lds_f32(a + 4), t1 = lds_f32(a + 64), u1 = lds_f32(a + 68);
                    v0 = (v0 + u0 + (s0 - t0) * (s0 - t0) * 128.f) * (1.f / 512.f);
                    v1 = (v1 + u1 + (s1 - t1) * (s1 - t1) * 128.f) * (1.f / 512.f);
                    s0 = 0.5f * (s0 + t0); s1 = 0.5f * (s1 + t1);
                }
                v0 = rsqrtf(v0 + 1e-5f); v1 = rsqrtf(v1 + 1e-5f);
                s0 = -s0 * v0; s1 = -s1 * v1;
#pragma unroll
                for (int p = 0; p < 16; p++)
                    stsm4(((sb + R0 + h * 32768 + loff) ^ ((p & 3) << 5)) + (p >> 2) * 8192,
                          pack2(fmaf(acc[8 * p], v0, s0), fmaf(acc[8 * p + 1], v0, s0)), pack2(fmaf(acc[8 * p + 2], v1, s1), fmaf(acc[8 * p + 3], v1, s1)),
                          pack2(fmaf(acc[8 * p + 4], v0, s0), fmaf(acc[8 * p + 5], v0, s0)), pack2(fmaf(acc[8 * p + 6], v1, s1), fmaf(acc[8 * p + 7], v1, s1)));
            } else {
                bar_sync(3 + h, 128);
                const uint32_t rm = lrow == 0 ? 0 : lrow - 1, rp = lrow == 63 ? 63 : lrow + 1;
                const uint32_t gb = sb + R0 + h * 32768;
                const uint32_t am = gb + rm * 128 + ((((lane >> 4) ^ rm) & 7) << 4), ap = gb + rp * 128 + ((((lane >> 4) ^ rp) & 7) << 4), ac = gb + loff;
                const uint32_t dwa = sb + DWS + 512 * h + ((lane >> 3) & 1) * 16 + (lane >> 4) * 1024;
                bf16* ucp = g_uc + ((size_t)blockIdx.x * 64 + r0) * D_ + 256 * h + 8 * (lane & 3);
#pragma unroll
                for (int m = 7; m >= 0; m--) {
                    uint32_t o[8];
#pragma unroll
                    for (int pp = 1; pp >= 0; pp--) {
                        const int p = 2 * m + pp;
                        const uint32_t co = (p >> 2) * 8192, cx = (p & 3) << 5;
                        uint32_t u[4], g[4], cv[4], d[4], d2[2];
#pragma unroll
                        for (int e = 3; e >= 0; e--) u[e] = pack2v(gelu(acc[8 * p + 2 * e]), gelu(acc[8 * p + 2 * e + 1]));
                        ldsm4(dwa + 32 * p, d);
                        ldsm2(dwa + 32 * p + 2048, d2);
                        ldsm4((am ^ cx) + co, g);
#pragma unroll
                        for (int e = 0; e < 4; e++) cv[e] = bmul2(g[e], d[e >> 1]);
                        ldsm4((ac ^ cx) + co, g);
#pragma unroll
                        for (int e = 0; e < 4; e++) cv[e] = bfma2(g[e], d[2 + (e >> 1)], cv[e]);
                        ldsm4((ap ^ cx) + co, g);
#pragma unroll
                        for (int e = 0; e < 4; e++) o[4 * (e & 1) + 2 * pp + (e >> 1)] = bmul2(u[e], bfma2(g[e], d2[e >> 1], cv[e]));
                    }
                    stg4(ucp + 32 * m, o[0], o[1], o[2], o[3]);
                    stg4(ucp + 32 * m + 8 * D_, o[4], o[5], o[6], o[7]);
                }
                bar_sync(2, 256);
                if (tid == 128) {
                    mbar_wait(sb + B_XA, 0);
                    mbar_expect_tx(sb + B_KV, 65536);
                    tma4(sb + R0, &mp.xa, 0, 128, 0, b, sb + B_KV);
                }
            }
            PT(3 + 3 * pass);
        }
        int s = 1, ph = 0;
        fresh(acc);
#pragma unroll 1
        for (int j = 0; j < NKV; j++) {
            mbar_wait(sb + B_P + s * 8, ph);
            PL(j, 0);
            if (j > 0) {
                const float sc0 = lds_f32(sb + SCL + s * 256 + r0 * 4), sc1 = lds_f32(sb + SCL + s * 256 + r0 * 4 + 32);
                if (__any_sync(0xffffffffu, sc0 != 1.f || sc1 != 1.f)) {
#pragma unroll
                    for (int n = 0; n < 32; n++) { acc[4 * n] *= sc0; acc[4 * n + 1] *= sc0; acc[4 * n + 2] *= sc1; acc[4 * n + 3] *= sc1; }
                }
            }
            mbar_wait(sb + B_GO + s * 8, ph);
            PL(j, 1);
            const uint32_t vd = sd + s * 4096 + h * 2048, pd = sd + (s == 0 ? 2 : s - 1) * 512;
            pin(acc);
            wg_fence();
#pragma unroll
            for (int kk = 0; kk < 4; kk++) wgmma_ss_n256_tb1(acc, dsc(pd, R3 + kk * 32, 16), dsc(vd, kk * 2048, 8192), 1);
            wg_commit();
            wg_wait<0>();
            pin(acc);
            PL(j, 2);
            if (w0 && elect1()) {
                if (j == NKV - 5 && mode == 0) flag_wait(&g_sync[3], 4);
                if (atom_inc_s(sb + CNT + 4 * s) & 1) {
                    if (j + 3 < NKV) {
                        mbar_expect_tx(sb + B_KV + s * 8, 65536);
                        tma4(sb + s * 65536, &mp.xa, 0, 64 * (j + 3), 0, b, sb + B_KV + s * 8);
                    } else if (j < NKV - 1) {
                        const int n0 = j == NKV - 3 ? 0 : 8, n1 = j == NKV - 3 ? 8 : 12;
#pragma unroll 1
                        for (int n = n0; n < n1; n++) ring_ld(sb, B_R2, n * 8, &mp.wepi, 16 * (n >> 1), 4 * (n & 1));
                    }
                }
            }
            if (++s == 3) s = 0;
            if (s == 1) ph ^= 1;
        }
        {
            const float i0 = lds_f32(sb + LINV + r0 * 4), i1 = lds_f32(sb + LINV + r0 * 4 + 32);
#pragma unroll
            for (int p = 0; p < 16; p++)
                stsm4(((sb + R0 + h * 32768 + loff) ^ ((p & 3) << 5)) + (p >> 2) * 8192,
                      pack2(acc[8 * p] * i0, acc[8 * p + 1] * i0), pack2(acc[8 * p + 2] * i1, acc[8 * p + 3] * i1),
                      pack2(acc[8 * p + 4] * i0, acc[8 * p + 5] * i0), pack2(acc[8 * p + 6] * i1, acc[8 * p + 7] * i1));
        }
        fence_async();
        fence_async_g();
        bar_sync(2, 256);
        if (tid == 128) {
            mbar_expect_tx(sb + B_UC, 65536);
            tma3(sb + UCT, &mp.uc, 0, 64 * blockIdx.x, 0, sb + B_UC);
        }
        PT(7);
        fresh(acc);
        {
            uint32_t slot8 = 8 * h, par = 0, prev8 = 0;
#pragma unroll 1
            for (int kk = 0; kk < 64; kk++) {
                if (kk == 32) mbar_wait(sb + B_UC, 0);
                mbar_wait(sb + B_R2 + slot8, par);
                wg_fence();
                wgmma_ss_n256_tb1(acc, mkd(sd + (1u << 16) + (kk < 32 ? (R0 >> 4) : (UCT >> 4) - 4096) + (kk >> 2) * 512 + (kk & 3) * 2), mkd(bd2k + slot8 * 64), 1);
                wg_commit();
                wg_wait<1>();
                if (kk > 0 && w0 && elect1()) {
                    if (kk < 59) ring_ld(sb, B_R2, prev8, &mp.wepi, 16 * (kk + 5), 4 * h);
                    if (kk == 32 && (atom_inc_s(sb + CNT + 12) & 1)) {
                        mbar_expect_tx(sb + B_X, 65536);
                        tma4(sb + R0, &mp.x, 0, 62 * ti, 0, b, sb + B_X);
                    }
                }
                prev8 = slot8;
                slot8 += 16;
                if (slot8 >= 96) { slot8 -= 96; par ^= 1; }
            }
        }
        wg_wait<0>();
        pin(acc);
        PT(8);
        mbar_wait(sb + B_X, 0);
        PT(9);
        {
            const uint32_t sr = (lrow + 63) & 63;
            const uint32_t xoff = sr * 128 + ((((lane >> 4) ^ sr) & 7) << 4);
#pragma unroll
            for (int p = 0; p < 16; p++) {
                const uint32_t a = ((sb + R0 + h * 32768 + xoff) ^ ((p & 3) << 5)) + (p >> 2) * 8192;
                uint32_t xv[4];
                ldsm4(a, xv);
#pragma unroll
                for (int e = 0; e < 4; e++)
                    xv[e] = pack2(acc[8 * p + 2 * e] + __uint_as_float(xv[e] << 16), acc[8 * p + 2 * e + 1] + __uint_as_float(xv[e] & 0xffff0000u));
                stsm4(a, xv[0], xv[1], xv[2], xv[3]);
            }
        }
        fence_async();
        bar_sync(3 + h, 128);
        if (el) {
            for (int c = 0; c < 4; c++) tma4_store(&mp.out, sb + R0 + (4 * h + c) * 8192, 0, 62 * ti, 4 * h + c, b);
            asm volatile("cp.async.bulk.commit_group;" ::: "memory");
            PT(10);
            if (h == 0) cta_done(mode);
            asm volatile("cp.async.bulk.wait_group.read 0;" ::: "memory");
        }
        PT(11);
        PDUMP();
    }
}

typedef CUresult (*PFN_enc)(CUtensorMap*, CUtensorMapDataType, cuuint32_t, void*, const cuuint64_t*, const cuuint64_t*,
                            const cuuint32_t*, const cuuint32_t*, CUtensorMapInterleave, CUtensorMapSwizzle,
                            CUtensorMapL2promotion, CUtensorMapFloatOOBfill);

static void enc(PFN_enc f, CUtensorMap* m, void* base, int rank, const cuuint64_t* dims, const cuuint64_t* strides, const cuuint32_t* box) {
    cuuint32_t es[5] = {1, 1, 1, 1, 1};
    f(m, CU_TENSOR_MAP_DATA_TYPE_BFLOAT16, rank, base, dims, strides, box, es, CU_TENSOR_MAP_INTERLEAVE_NONE,
      CU_TENSOR_MAP_SWIZZLE_128B, CU_TENSOR_MAP_L2_PROMOTION_L2_256B, CU_TENSOR_MAP_FLOAT_OOB_FILL_NONE);
}
static void enc_act(PFN_enc f, CUtensorMap* m, void* base, int rows, int chunks, int trows = T_, int pitch = T_) {
    cuuint64_t dims[4] = {64, (cuuint64_t)trows, 8, (cuuint64_t)NB_};
    cuuint64_t st[3] = {1024, 128, (cuuint64_t)pitch * 1024};
    cuuint32_t box[4] = {64, (cuuint32_t)rows, (cuuint32_t)chunks, 1};
    enc(f, m, base, 4, dims, st, box);
}
static void enc_w(PFN_enc f, CUtensorMap* m, void* base, int krows, int ncols, int bk, int bc) {
    cuuint64_t dims[3] = {64, (cuuint64_t)krows, (cuuint64_t)(ncols / 64)};
    cuuint64_t st[2] = {(cuuint64_t)ncols * 2, 128};
    cuuint32_t box[3] = {64, (cuuint32_t)bk, (cuuint32_t)bc};
    enc(f, m, base, 3, dims, st, box);
}

extern "C" void kernel_launch(void* const* d_in, const int* in_sizes, int n_in, void* d_out, int out_size) {
    const bf16* x = (const bf16*)d_in[0];
    static PFN_enc fenc = nullptr;
    static void *p_xa, *p_mqk, *p_wepi, *p_uc, *p_t1;
    static int fused = 0;
    if (!fenc) {
        void* fn = nullptr;
        cudaDriverEntryPointQueryResult qr;
        cudaGetDriverEntryPoint("cuTensorMapEncodeTiled", &fn, cudaEnableDefault, &qr);
        fenc = (PFN_enc)fn;
        cudaGetSymbolAddress(&p_xa, g_xa);
        cudaGetSymbolAddress(&p_mqk, g_mqk);
        cudaGetSymbolAddress(&p_wepi, g_wepi);
        cudaGetSymbolAddress(&p_uc, g_uc);
        cudaGetSymbolAddress(&p_t1, g_t1);
        cudaFuncSetAttribute(main_kernel, cudaFuncAttributeMaxDynamicSharedMemorySize, SMEM_BYTES);
        int dev = 0, sms = 0, occ = 0;
        cudaGetDevice(&dev);
        cudaDeviceGetAttribute(&sms, cudaDevAttrMultiProcessorCount, dev);
        cudaOccupancyMaxActiveBlocksPerMultiprocessor(&occ, main_kernel, 384, SMEM_BYTES);
        fused = sms * occ >= NCTA + 2;
    }
    Maps mp;
    enc_act(fenc, &mp.xa, (char*)p_xa + 1024, 64, 8, T_, T_ + 8);
    enc_act(fenc, &mp.xa2, (char*)p_xa + 1024, 64, 2, T_, T_ + 8);
    enc_act(fenc, &mp.xas, p_xa, 64, 8, T_ + 1, T_ + 8);
    enc_act(fenc, &mp.x, (void*)x, 64, 8);
    enc_act(fenc, &mp.out, d_out, 62, 1);
    enc_w(fenc, &mp.wup4, d_in[5], 512, 1024, 16, 4);
    enc_w(fenc, &mp.wup8, d_in[5], 512, 1024, 16, 8);
    enc_w(fenc, &mp.mqa2, p_mqk, 512, 512, 32, 2);
    enc_w(fenc, &mp.mqa4, p_mqk, 512, 512, 32, 4);
    enc_w(fenc, &mp.mqb1, p_mqk, 512, 512, 64, 1);
    enc_w(fenc, &mp.mqb2, p_mqk, 512, 512, 64, 2);
    enc_w(fenc, &mp.wepi, p_wepi, 1024, 512, 16, 4);
    enc_w(fenc, &mp.uc, p_uc, NCTA * 64, 512, 64, 8);
    enc_w(fenc, &mp.wq, d_in[1], 512, 512, 64, 8);
    enc_w(fenc, &mp.wk, d_in[2], 512, 512, 32, 8);
    enc_w(fenc, &mp.fa[0], d_in[3], 512, 512, 128, 1);
    enc_w(fenc, &mp.fa[1], d_in[7], 512, 512, 128, 1);
    enc_w(fenc, &mp.fa[2], p_t1, 512, 512, 128, 1);
    enc_w(fenc, &mp.fb[0], d_in[4], 512, 512, 64, 4);
    enc_w(fenc, &mp.fb[1], d_in[8], 1024, 512, 64, 4);
    enc_w(fenc, &mp.fc[0], p_t1, 512, 512, 64, 4);
    enc_w(fenc, &mp.fc[1], p_wepi, 1024, 512, 64, 4);
    cudaStream_t st = cudaStreamPerThread;
    if (fused) {
        main_kernel<<<NCTA + 2, 384, SMEM_BYTES, st>>>(mp, (const bf16*)d_in[6], (const bf16*)d_in[5], (const bf16*)d_in[8], 0);
    } else {
        main_kernel<<<NCTA + 2, 384, SMEM_BYTES, st>>>(mp, (const bf16*)d_in[6], (const bf16*)d_in[5], (const bf16*)d_in[8], 1);
        main_kernel<<<NCTA + 2, 384, SMEM_BYTES, st>>>(mp, (const bf16*)d_in[6], (const bf16*)d_in[5], (const bf16*)d_in[8], 2);
    }
}
```

```cpp
#include <cuda_runtime.h>
#include <cuda_bf16.h>
#include <cuda.h>
#include <stdint.h>

typedef __nv_bfloat16 bf16;

constexpr int T_ = 4000, D_ = 512, NB_ = 2;
constexpr int TPB = 65;
constexpr int NCTA = TPB * NB_;
constexpr int NKV = 63;

__device__ __align__(1024) bf16 g_xa[NB_ * (T_ + 8) * D_];
__device__ __align__(1024) bf16 g_mqk[D_ * D_];
__device__ __align__(1024) bf16 g_t1[D_ * D_];
__device__ __align__(1024) bf16 g_wepi[2 * D_ * D_];
__device__ __align__(1024) bf16 g_uc[NCTA * 64 * D_];
__device__ unsigned g_sync[8];

#define PT(i)
#define PL(j, q)
#define PDUMP()

#define FENCE_AT 1
#define GO_AT 25
#define XS_GAP 800
#define PFW 1
constexpr uint32_t R0 = 0, R1 = 65536, R2 = 131072, R3 = 196608, QS = 221184, MISC = 229376;
constexpr uint32_t AT = 147456, DWS = R3 + 16384, UCT = 163840;
constexpr uint32_t SMEM_BYTES = 232448;
constexpr uint32_t B_A = MISC, B_R1 = MISC + 8  , B_MK = MISC + 48, B_LN = MISC + 56, B_MQ = MISC + 64, B_XA = MISC + 72,
                   B_H1 = MISC + 88, B_H2 = MISC + 96, B_H3 = MISC + 104,
                   B_KV = MISC + 112, B_P = MISC + 136, B_GO = MISC + 160, B_R2 = MISC + 184, B_UC = MISC + 280,
                   B_X = MISC + 288, CNT = MISC + 296  , SCL = MISC + 512  ,
                   LINV = MISC + 1280  , STAT = MISC + 1536  ;

__device__ __forceinline__ uint32_t smem_u32(const void* p) { return (uint32_t)__cvta_generic_to_shared(p); }
__device__ __forceinline__ void wg_fence() { asm volatile("wgmma.fence.sync.aligned;" ::: "memory"); }
__device__ __forceinline__ void wg_commit() { asm volatile("wgmma.commit_group.sync.aligned;" ::: "memory"); }
template <int N> __device__ __forceinline__ void wg_wait() { asm volatile("wgmma.wait_group.sync.aligned %0;" ::"n"(N) : "memory"); }
__device__ __forceinline__ uint64_t dsc(uint32_t sd, uint32_t off, uint32_t lbo) {
    uint32_t lo = sd + (off >> 4) + ((lbo >> 4) << 16);
    uint64_t d;
    asm("mov.b64 %0, {%1, %2};" : "=l"(d) : "r"(lo), "r"((1024u >> 4) | (1u << 30)));
    return d;
}
__device__ __forceinline__ bool elect1() {
    uint32_t p;
    asm volatile("{\n.reg .pred p;\nelect.sync _|p, 0xffffffff;\nselp.u32 %0, 1, 0, p;\n}\n" : "=r"(p));
    return p != 0;
}
__device__ __forceinline__ void mbar_init(uint32_t bar, int cnt) { asm volatile("mbarrier.init.shared::cta.b64 [%0], %1;" ::"r"(bar), "r"(cnt) : "memory"); }
__device__ __forceinline__ void mbar_expect_tx(uint32_t bar, uint32_t bytes) { asm volatile("mbarrier.arrive.expect_tx.shared::cta.b64 _, [%0], %1;" ::"r"(bar), "r"(bytes) : "memory"); }
__device__ __forceinline__ void mbar_arrive(uint32_t bar) { asm volatile("mbarrier.arrive.shared::cta.b64 _, [%0];" ::"r"(bar) : "memory"); }
__device__ __forceinline__ void mbar_wait(uint32_t bar, uint32_t parity) {
    uint32_t ok;
#pragma unroll 1
    for (uint32_t it = 0;; ++it) {
        asm volatile("{\n.reg .pred p;\nmbarrier.try_wait.parity.shared::cta.b64 p, [%1], %2;\nselp.u32 %0, 1, 0, p;\n}\n" : "=r"(ok) : "r"(bar), "r"(parity) : "memory");
        if (ok) break;
        if (it > (1u << 20)) __trap();
    }
}
__device__ __forceinline__ void fence_async() { asm volatile("fence.proxy.async.shared::cta;" ::: "memory"); }
__device__ __forceinline__ void fence_async_g() { asm volatile("fence.proxy.async.global;" ::: "memory"); }
__device__ __forceinline__ void bar_sync(int id, int n) { asm volatile("bar.sync %0, %1;" ::"r"(id), "r"(n) : "memory"); }
__device__ __forceinline__ void tma3(uint32_t dst, const CUtensorMap* tm, int c0, int c1, int c2, uint32_t bar) {
    asm volatile("cp.async.bulk.tensor.3d.shared::cluster.global.mbarrier::complete_tx::bytes [%0], [%1, {%3, %4, %5}], [%2];"
                 ::"r"(dst), "l"(tm), "r"(bar), "r"(c0), "r"(c1), "r"(c2) : "memory");
}
__device__ __forceinline__ void tma4(uint32_t dst, const CUtensorMap* tm, int c0, int c1, int c2, int c3, uint32_t bar) {
    asm volatile("cp.async.bulk.tensor.4d.shared::cluster.global.mbarrier::complete_tx::bytes [%0], [%1, {%3, %4, %5, %6}], [%2];"
                 ::"r"(dst), "l"(tm), "r"(bar), "r"(c0), "r"(c1), "r"(c2), "r"(c3) : "memory");
}
__device__ __forceinline__ void tma4_store(const CUtensorMap* tm, uint32_t src, int c0, int c1, int c2, int c3) {
    asm volatile("cp.async.bulk.tensor.4d.global.shared::cta.bulk_group [%0, {%2, %3, %4, %5}], [%1];"
                 ::"l"(tm), "r"(src), "r"(c0), "r"(c1), "r"(c2), "r"(c3) : "memory");
}
__device__ __forceinline__ void tma3_store(const CUtensorMap* tm, uint32_t src, int c0, int c1, int c2) {
    asm volatile("cp.async.bulk.tensor.3d.global.shared::cta.bulk_group [%0, {%2, %3, %4}], [%1];"
                 ::"l"(tm), "r"(src), "r"(c0), "r"(c1), "r"(c2) : "memory");
}
__device__ __forceinline__ void stsm4(uint32_t addr, uint32_t a, uint32_t b, uint32_t c, uint32_t d) {
    asm volatile("stmatrix.sync.aligned.m8n8.x4.shared.b16 [%0], {%1, %2, %3, %4};" ::"r"(addr), "r"(a), "r"(b), "r"(c), "r"(d) : "memory");
}
__device__ __forceinline__ void ldsm4(uint32_t addr, uint32_t (&r)[4]) {
    asm volatile("ldmatrix.sync.aligned.m8n8.x4.shared.b16 {%0, %1, %2, %3}, [%4];" : "=r"(r[0]), "=r"(r[1]), "=r"(r[2]), "=r"(r[3]) : "r"(addr) : "memory");
}
__device__ __forceinline__ void ldsm2(uint32_t addr, uint32_t (&r)[2]) {
    asm volatile("ldmatrix.sync.aligned.m8n8.x2.shared.b16 {%0, %1}, [%2];" : "=r"(r[0]), "=r"(r[1]) : "r"(addr) : "memory");
}
__device__ __forceinline__ void stg4(void* p, uint32_t a, uint32_t b, uint32_t c, uint32_t d) {
    asm volatile("st.global.v4.u32 [%0], {%1, %2, %3, %4};" ::"l"(p), "r"(a), "r"(b), "r"(c), "r"(d) : "memory");
}
__device__ __forceinline__ uint32_t pack2(float lo, float hi) {
    uint32_t r;
    asm("cvt.rn.bf16x2.f32 %0, %1, %2;" : "=r"(r) : "f"(hi), "f"(lo));
    return r;
}
__device__ __forceinline__ uint32_t pack2v(float lo, float hi) {
    uint32_t r;
    asm volatile("cvt.rn.bf16x2.f32 %0, %1, %2;" : "=r"(r) : "f"(hi), "f"(lo));
    return r;
}
__device__ __forceinline__ uint32_t bmul2(uint32_t a, uint32_t b) { uint32_t r; asm("mul.rn.bf16x2 %0, %1, %2;" : "=r"(r) : "r"(a), "r"(b)); return r; }
__device__ __forceinline__ uint32_t bfma2(uint32_t a, uint32_t b, uint32_t c) { uint32_t r; asm("fma.rn.bf16x2 %0, %1, %2, %3;" : "=r"(r) : "r"(a), "r"(b), "r"(c)); return r; }
__device__ __forceinline__ float ex2(float x) { float r; asm("ex2.approx.ftz.f32 %0, %1;" : "=f"(r) : "f"(x)); return r; }
__device__ __forceinline__ float rcp(float x) { float r; asm("rcp.approx.ftz.f32 %0, %1;" : "=f"(r) : "f"(x)); return r; }
__device__ __forceinline__ float gelu(float x) {
    float t = fmaf(x * x, 0.044715f * 0.7978845608028654f, 0.7978845608028654f), th;
    asm("tanh.approx.f32 %0, %1;" : "=f"(th) : "f"(x * t));
    float hx = 0.5f * x;
    return fmaf(hx, th, hx);
}
__device__ __forceinline__ uint32_t ldg_v(const uint32_t* p) { uint32_t v; asm volatile("ld.global.nc.u32 %0, [%1];" : "=r"(v) : "l"(p)); return v; }
__device__ __forceinline__ float lds_f32(uint32_t a) { float v; asm volatile("ld.shared.f32 %0, [%1];" : "=f"(v) : "r"(a) : "memory"); return v; }
__device__ __forceinline__ void sts_f32(uint32_t a, float v) { asm volatile("st.shared.f32 [%0], %1;" ::"r"(a), "f"(v) : "memory"); }
__device__ __forceinline__ uint32_t atom_inc_s(uint32_t a) { uint32_t v; asm volatile("atom.relaxed.cta.shared.add.u32 %0, [%1], 1;" : "=r"(v) : "r"(a) : "memory"); return v; }
__device__ __forceinline__ void lds4(uint32_t a, uint32_t* r) {
    asm volatile("ld.shared.v4.u32 {%0, %1, %2, %3}, [%4];" : "=r"(r[0]), "=r"(r[1]), "=r"(r[2]), "=r"(r[3]) : "r"(a) : "memory");
}
__device__ __forceinline__ void sts4(uint32_t a, uint32_t x, uint32_t y, uint32_t z, uint32_t t) {
    asm volatile("st.shared.v4.u32 [%0], {%1, %2, %3, %4};" ::"r"(a), "r"(x), "r"(y), "r"(z), "r"(t) : "memory");
}
__device__ __forceinline__ uint32_t bsub2(uint32_t a, uint32_t b) { uint32_t r; asm("sub.rn.bf16x2 %0, %1, %2;" : "=r"(r) : "r"(a), "r"(b)); return r; }
__device__ __forceinline__ float blo(uint32_t v) { return __uint_as_float(v << 16); }
__device__ __forceinline__ float bhi(uint32_t v) { return __uint_as_float(v & 0xffff0000u); }
__device__ __forceinline__ float bfr(float x) { return __bfloat162float(__float2bfloat16_rn(x)); }
__device__ __forceinline__ void l2_prefetch(const void* p, uint32_t bytes) { asm volatile("cp.async.bulk.prefetch.L2.global [%0], %1;" ::"l"(p), "r"(bytes) : "memory"); }
__device__ __forceinline__ void flag_add(unsigned* p) { asm volatile("red.release.gpu.global.add.u32 [%0], 1;" ::"l"(p) : "memory"); }
__device__ __forceinline__ void flag_wait(const unsigned* p, unsigned target) {
#pragma unroll 1
    for (uint32_t it = 0;; ++it) {
        unsigned v;
        asm volatile("ld.acquire.gpu.global.u32 %0, [%1];" : "=r"(v) : "l"(p) : "memory");
        if (v >= target) break;
        if (it > (1u << 20)) __trap();
    }
    fence_async_g();
}
template <int N> __device__ __forceinline__ void pin(float (&a)[N]) {
#pragma unroll
    for (int i = 0; i < N; i++) asm volatile("" : "+f"(a[i])::"memory");
}

template <int N> __device__ __forceinline__ void fresh(float (&a)[N]) {
#pragma unroll
    for (int i = 0; i < N; i++) a[i] = 0.f;
    pin(a);
}

__device__ __forceinline__ void wgmma_rs_n64_tb0(float (&d)[32], uint32_t a0, uint32_t a1, uint32_t a2, uint32_t a3, uint64_t db, int scale_d) {
    asm volatile("{\n.reg .pred p;\nsetp.ne.b32 p, %37, 0;\n"
        "wgmma.mma_async.sync.aligned.m64n64k16.f32.bf16.bf16 {%0, %1, %2, %3, %4, %5, %6, %7, %8, %9, %10, %11, %12, %13, %14, %15, %16, %17, %18, %19, %20, %21, %22, %23, %24, %25, %26, %27, %28, %29, %30, %31}, {%32, %33, %34, %35}, %36, p, 1, 1, 0;\n}\n"
        : "+f"(d[0]), "+f"(d[1]), "+f"(d[2]), "+f"(d[3]), "+f"(d[4]), "+f"(d[5]), "+f"(d[6]), "+f"(d[7]), "+f"(d[8]), "+f"(d[9]), "+f"(d[10]), "+f"(d[11]), "+f"(d[12]), "+f"(d[13]), "+f"(d[14]), "+f"(d[15]), "+f"(d[16]), "+f"(d[17]), "+f"(d[18]), "+f"(d[19]), "+f"(d[20]), "+f"(d[21]), "+f"(d[22]), "+f"(d[23]), "+f"(d[24]), "+f"(d[25]), "+f"(d[26]), "+f"(d[27]), "+f"(d[28]), "+f"(d[29]), "+f"(d[30]), "+f"(d[31])
        : "r"(a0), "r"(a1), "r"(a2), "r"(a3), "l"(db), "r"(scale_d));
}

__device__ __forceinline__ void wgmma_ss_n128_tb1(float (&d)[64], uint64_t da, uint64_t db, int scale_d) {
    asm volatile("{\n.reg .pred p;\nsetp.ne.b32 p, %66, 0;\n"
        "wgmma.mma_async.sync.aligned.m64n128k16.f32.bf16.bf16 {%0, %1, %2, %3, %4, %5, %6, %7, %8, %9, %10, %11, %12, %13, %14, %15, %16, %17, %18, %19, %20, %21, %22, %23, %24, %25, %26, %27, %28, %29, %30, %31, %32, %33, %34, %35, %36, %37, %38, %39, %40, %41, %42, %43, %44, %45, %46, %47, %48, %49, %50, %51, %52, %53, %54, %55, %56, %57, %58, %59, %60, %61, %62, %63}, %64, %65, p, 1, 1, 0, 1;\n}\n"
        : "+f"(d[0]), "+f"(d[1]), "+f"(d[2]), "+f"(d[3]), "+f"(d[4]), "+f"(d[5]), "+f"(d[6]), "+f"(d[7]), "+f"(d[8]), "+f"(d[9]), "+f"(d[10]), "+f"(d[11]), "+f"(d[12]), "+f"(d[13]), "+f"(d[14]), "+f"(d[15]), "+f"(d[16]), "+f"(d[17]), "+f"(d[18]), "+f"(d[19]), "+f"(d[20]), "+f"(d[21]), "+f"(d[22]), "+f"(d[23]), "+f"(d[24]), "+f"(d[25]), "+f"(d[26]), "+f"(d[27]), "+f"(d[28]), "+f"(d[29]), "+f"(d[30]), "+f"(d[31]), "+f"(d[32]), "+f"(d[33]), "+f"(d[34]), "+f"(d[35]), "+f"(d[36]), "+f"(d[37]), "+f"(d[38]), "+f"(d[39]), "+f"(d[40]), "+f"(d[41]), "+f"(d[42]), "+f"(d[43]), "+f"(d[44]), "+f"(d[45]), "+f"(d[46]), "+f"(d[47]), "+f"(d[48]), "+f"(d[49]), "+f"(d[50]), "+f"(d[51]), "+f"(d[52]), "+f"(d[53]), "+f"(d[54]), "+f"(d[55]), "+f"(d[56]), "+f"(d[57]), "+f"(d[58]), "+f"(d[59]), "+f"(d[60]), "+f"(d[61]), "+f"(d[62]), "+f"(d[63])
        : "l"(da), "l"(db), "r"(scale_d));
}

__device__ __forceinline__ void wgmma_ss_n256_tb1(float (&d)[128], uint64_t da, uint64_t db, int scale_d) {
    asm volatile("{\n.reg .pred p;\nsetp.ne.b32 p, %130, 0;\n"
        "wgmma.mma_async.sync.aligned.m64n256k16.f32.bf16.bf16 {%0, %1, %2, %3, %4, %5, %6, %7, %8, %9, %10, %11, %12, %13, %14, %15, %16, %17, %18, %19, %20, %21, %22, %23, %24, %25, %26, %27, %28, %29, %30, %31, %32, %33, %34, %35, %36, %37, %38, %39, %40, %41, %42, %43, %44, %45, %46, %47, %48, %49, %50, %51, %52, %53, %54, %55, %56, %57, %58, %59, %60, %61, %62, %63, %64, %65, %66, %67, %68, %69, %70, %71, %72, %73, %74, %75, %76, %77, %78, %79, %80, %81, %82, %83, %84, %85, %86, %87, %88, %89, %90, %91, %92, %93, %94, %95, %96, %97, %98, %99, %100, %101, %102, %103, %104, %105, %106, %107, %108, %109, %110, %111, %112, %113, %114, %115, %116, %117, %118, %119, %120, %121, %122, %123, %124, %125, %126, %127}, %128, %129, p, 1, 1, 0, 1;\n}\n"
        : "+f"(d[0]), "+f"(d[1]), "+f"(d[2]), "+f"(d[3]), "+f"(d[4]), "+f"(d[5]), "+f"(d[6]), "+f"(d[7]), "+f"(d[8]), "+f"(d[9]), "+f"(d[10]), "+f"(d[11]), "+f"(d[12]), "+f"(d[13]), "+f"(d[14]), "+f"(d[15]), "+f"(d[16]), "+f"(d[17]), "+f"(d[18]), "+f"(d[19]), "+f"(d[20]), "+f"(d[21]), "+f"(d[22]), "+f"(d[23]), "+f"(d[24]), "+f"(d[25]), "+f"(d[26]), "+f"(d[27]), "+f"(d[28]), "+f"(d[29]), "+f"(d[30]), "+f"(d[31]), "+f"(d[32]), "+f"(d[33]), "+f"(d[34]), "+f"(d[35]), "+f"(d[36]), "+f"(d[37]), "+f"(d[38]), "+f"(d[39]), "+f"(d[40]), "+f"(d[41]), "+f"(d[42]), "+f"(d[43]), "+f"(d[44]), "+f"(d[45]), "+f"(d[46]), "+f"(d[47]), "+f"(d[48]), "+f"(d[49]), "+f"(d[50]), "+f"(d[51]), "+f"(d[52]), "+f"(d[53]), "+f"(d[54]), "+f"(d[55]), "+f"(d[56]), "+f"(d[57]), "+f"(d[58]), "+f"(d[59]), "+f"(d[60]), "+f"(d[61]), "+f"(d[62]), "+f"(d[63]), "+f"(d[64]), "+f"(d[65]), "+f"(d[66]), "+f"(d[67]), "+f"(d[68]), "+f"(d[69]), "+f"(d[70]), "+f"(d[71]), "+f"(d[72]), "+f"(d[73]), "+f"(d[74]), "+f"(d[75]), "+f"(d[76]), "+f"(d[77]), "+f"(d[78]), "+f"(d[79]), "+f"(d[80]), "+f"(d[81]), "+f"(d[82]), "+f"(d[83]), "+f"(d[84]), "+f"(d[85]), "+f"(d[86]), "+f"(d[87]), "+f"(d[88]), "+f"(d[89]), "+f"(d[90]), "+f"(d[91]), "+f"(d[92]), "+f"(d[93]), "+f"(d[94]), "+f"(d[95]), "+f"(d[96]), "+f"(d[97]), "+f"(d[98]), "+f"(d[99]), "+f"(d[100]), "+f"(d[101]), "+f"(d[102]), "+f"(d[103]), "+f"(d[104]), "+f"(d[105]), "+f"(d[106]), "+f"(d[107]), "+f"(d[108]), "+f"(d[109]), "+f"(d[110]), "+f"(d[111]), "+f"(d[112]), "+f"(d[113]), "+f"(d[114]), "+f"(d[115]), "+f"(d[116]), "+f"(d[117]), "+f"(d[118]), "+f"(d[119]), "+f"(d[120]), "+f"(d[121]), "+f"(d[122]), "+f"(d[123]), "+f"(d[124]), "+f"(d[125]), "+f"(d[126]), "+f"(d[127])
        : "l"(da), "l"(db), "r"(scale_d));
}

__device__ __forceinline__ void wgmma_ss_n32_tb0(float (&d)[16], uint64_t da, uint64_t db, int scale_d) {
    asm volatile("{\n.reg .pred p;\nsetp.ne.b32 p, %18, 0;\n"
        "wgmma.mma_async.sync.aligned.m64n32k16.f32.bf16.bf16 {%0, %1, %2, %3, %4, %5, %6, %7, %8, %9, %10, %11, %12, %13, %14, %15}, %16, %17, p, 1, 1, 0, 0;\n}\n"
        : "+f"(d[0]), "+f"(d[1]), "+f"(d[2]), "+f"(d[3]), "+f"(d[4]), "+f"(d[5]), "+f"(d[6]), "+f"(d[7]), "+f"(d[8]), "+f"(d[9]), "+f"(d[10]), "+f"(d[11]), "+f"(d[12]), "+f"(d[13]), "+f"(d[14]), "+f"(d[15])
        : "l"(da), "l"(db), "r"(scale_d));
}

__device__ __forceinline__ void wgmma_ss_n64_tb0(float (&d)[32], uint64_t da, uint64_t db, int scale_d) {
    asm volatile("{\n.reg .pred p;\nsetp.ne.b32 p, %34, 0;\n"
        "wgmma.mma_async.sync.aligned.m64n64k16.f32.bf16.bf16 {%0, %1, %2, %3, %4, %5, %6, %7, %8, %9, %10, %11, %12, %13, %14, %15, %16, %17, %18, %19, %20, %21, %22, %23, %24, %25, %26, %27, %28, %29, %30, %31}, %32, %33, p, 1, 1, 0, 0;\n}\n"
        : "+f"(d[0]), "+f"(d[1]), "+f"(d[2]), "+f"(d[3]), "+f"(d[4]), "+f"(d[5]), "+f"(d[6]), "+f"(d[7]), "+f"(d[8]), "+f"(d[9]), "+f"(d[10]), "+f"(d[11]), "+f"(d[12]), "+f"(d[13]), "+f"(d[14]), "+f"(d[15]), "+f"(d[16]), "+f"(d[17]), "+f"(d[18]), "+f"(d[19]), "+f"(d[20]), "+f"(d[21]), "+f"(d[22]), "+f"(d[23]), "+f"(d[24]), "+f"(d[25]), "+f"(d[26]), "+f"(d[27]), "+f"(d[28]), "+f"(d[29]), "+f"(d[30]), "+f"(d[31])
        : "l"(da), "l"(db), "r"(scale_d));
}

struct Maps {
    CUtensorMap xa, xa2, xas, wup4, wup8, mqa2, mqa4, mqb1, mqb2, wepi, uc, x, out, wq, wk, fa[3], fb[2], fc[2];
};

__device__ __forceinline__ uint64_t mkd(uint32_t lo) {
    uint64_t d;
    asm("mov.b64 %0, {%1, %2};" : "=l"(d) : "r"(lo), "r"((1024u >> 4) | (1u << 30)));
    return d;
}
__device__ __forceinline__ void ring_ld(uint32_t sb, uint32_t barbase, uint32_t slot8, const CUtensorMap* tm, int c1, int c2) {
    mbar_expect_tx(sb + barbase + slot8, 8192);
    tma3(sb + R1 + slot8 * 1024, tm, 0, c1, c2, sb + barbase + slot8);
}

__device__ __forceinline__ void ring_half(uint32_t sb, uint32_t slot8, uint32_t hoff, const CUtensorMap* tm, int c1, int c2) {
    mbar_expect_tx(sb + B_R1 + slot8, 8192);
    tma3(sb + R1 + slot8 * 2048 + hoff, tm, 0, c1, c2, sb + B_R1 + slot8);
}
__device__ __forceinline__ void ring_full(uint32_t sb, uint32_t slot8, const CUtensorMap* tm, int c1, int c2) {
    mbar_expect_tx(sb + B_R1 + slot8, 16384);
    mbar_arrive(sb + B_R1 + slot8);
    tma3(sb + R1 + slot8 * 2048, tm, 0, c1, c2, sb + B_R1 + slot8);
}
__device__ __forceinline__ void cta_done(int mode) {
    if (mode == 0 && atomicAdd(&g_sync[4], 1) == NCTA + 1) {
#pragma unroll
        for (int i = 0; i < 5; i++) g_sync[i] = 0;
    }
}

__device__ __forceinline__ void fold_cta(const Maps& mp, uint32_t sb, int mode) {
    constexpr uint32_t F_FULL = MISC, F_EMPTY = MISC + 32, F_T1 = MISC + 64, STG = 49152, FOUT = 3 * STG;
    const int tid = threadIdx.x, f = blockIdx.x - NCTA;
    if (mode == 2) return;
    if (tid == 0) {
        for (int i = 0; i < 3; i++) { mbar_init(sb + F_FULL + 8 * i, 1); mbar_init(sb + F_EMPTY + 8 * i, 2); }
        mbar_init(sb + F_T1, 2);
        asm volatile("fence.mbarrier_init.release.cluster;" ::: "memory");
        fence_async();
    }
    __syncthreads();
    const int wg = __shfl_sync(0xffffffffu, tid >> 7, 0);
    int st = 0, ph = 0;
    if (wg == 0) {
        if (tid == 0) {
#pragma unroll 1
            for (int it = 0; it < 96; it++) {
                const int p = it >> 3, kc = it & 7, job = p >> 2;
                if (it == 64) mbar_wait(sb + F_T1, 0);
                mbar_wait(sb + F_EMPTY + 8 * st, ph ^ 1);
                mbar_expect_tx(sb + F_FULL + 8 * st, STG);
                tma3(sb + st * STG, &mp.fa[job], 0, 256 * f + 128 * ((p >> 1) & 1), kc, sb + F_FULL + 8 * st);
                tma3(sb + st * STG + 16384, &mp.fb[job != 0], 0, 64 * kc + (job == 1 ? 512 : 0), 4 * (p & 1), sb + F_FULL + 8 * st);
                if (++st == 3) { st = 0; ph ^= 1; }
            }
        }
        return;
    }
    const int h = wg - 1, lane = tid & 31, w = (tid >> 5) & 3;
    const uint32_t sd = (sb & 0x3FFFF) >> 4;
    const bool el = (tid & 127) == 0;
#pragma unroll 1
    for (int p = 0; p < 12; p++) {
        float acc[128];
        fresh(acc);
#pragma unroll 1
        for (int kc = 0; kc < 8; kc++) {
            mbar_wait(sb + F_FULL + 8 * st, ph);
            wg_fence();
#pragma unroll
            for (int kk = 0; kk < 4; kk++)
                wgmma_ss_n256_tb1(acc, dsc(sd, st * STG + h * 8192 + kk * 32, 16), dsc(sd, st * STG + 16384 + kk * 2048, 8192), 1);
            wg_commit();
            wg_wait<0>();
            if (el) mbar_arrive(sb + F_EMPTY + 8 * st);
            if (++st == 3) { st = 0; ph ^= 1; }
        }
        pin(acc);
        const int job = p >> 2;
        if (el) {
            asm volatile("cp.async.bulk.wait_group 0;" ::: "memory");
            if (p == 4) { fence_async_g(); mbar_arrive(sb + F_T1); }
        }
        bar_sync(3 + h, 128);
        uint32_t r = 16 * w + (lane & 7) + ((lane >> 3) & 1) * 8;
        if (job == 1) r = (r & ~31) | (((r >> 1) & 3) << 3) | (((r >> 3) & 3) << 1) | (r & 1);
        const uint32_t oa = sb + FOUT + h * 32768 + r * 128 + ((((lane >> 4) ^ r) & 7) << 4);
#pragma unroll
        for (int i = 0; i < 16; i++)
            stsm4((oa ^ ((i & 3) << 5)) + (i >> 2) * 8192, pack2(acc[8 * i], acc[8 * i + 1]), pack2(acc[8 * i + 2], acc[8 * i + 3]),
                  pack2(acc[8 * i + 4], acc[8 * i + 5]), pack2(acc[8 * i + 6], acc[8 * i + 7]));
        fence_async();
        bar_sync(3 + h, 128);
        if (el) {
            tma3_store(&mp.fc[job != 0], sb + FOUT + h * 32768, 0, 256 * f + 128 * ((p >> 1) & 1) + 64 * h + (job == 1 ? 512 : 0), 4 * (p & 1));
            asm volatile("cp.async.bulk.commit_group;" ::: "memory");
        }
    }
    if (el) {
        asm volatile("cp.async.bulk.wait_group 0;" ::: "memory");
        fence_async_g();
        if (mode == 0) flag_add(&g_sync[3]);
    }
    bar_sync(2, 256);
    if (tid == 128) cta_done(mode);
}

__global__ void __launch_bounds__(384, 1) main_kernel(const __grid_constant__ Maps mp, const bf16* __restrict__ dw, const bf16* wup, const int mode) {
    extern __shared__ __align__(1024) uint8_t smem[];
    const uint32_t sb = smem_u32(smem);
    const int tid = threadIdx.x;
    if (blockIdx.x >= NCTA) { fold_cta(mp, sb, mode); return; }
    const int b = blockIdx.x / TPB, ti = blockIdx.x % TPB;
    const int piece = blockIdx.x & 127;
    if (tid == 0) {
        mbar_init(sb + B_A, 1); mbar_init(sb + B_MK, 1);
        for (int i = 0; i < 5; i++) mbar_init(sb + B_R1 + 8 * i, 2);
        asm volatile("fence.mbarrier_init.release.cluster;" ::: "memory");
        fence_async();
        mbar_expect_tx(sb + B_A, 65536 + 3072);
        tma4(sb + AT, &mp.x, 0, 62 * ti - 1, 0, b, sb + B_A);
        mbar_expect_tx(sb + B_MK, 65536 + 32768);
        tma3(sb + R0, &mp.wq, 0, 64 * (piece >> 4), 0, sb + B_MK);
        tma3(sb + R1 + 32768, &mp.wk, 0, 32 * (piece & 15), 0, sb + B_MK);
        asm volatile("cp.async.bulk.shared::cluster.global.mbarrier::complete_tx::bytes [%0], [%1], 3072, [%2];" ::"r"(sb + DWS), "l"(dw), "r"(sb + B_A) : "memory");
        for (int i = 0; i < 8; i++) mbar_arrive(sb + B_R1 + 8 * (i >> 1));
        if (mode != 1) {
            ring_full(sb, 32, &mp.wup8, 0, 8);
            ring_full(sb, 0, &mp.wup8, 16, 8);
            ring_full(sb, 8, &mp.wup8, 32, 8);
        }
    } else if (tid == 32) {
        mbar_init(sb + B_LN, 1); mbar_init(sb + B_MQ, 1); mbar_init(sb + B_XA, 1);
        mbar_init(sb + B_H1, 2); mbar_init(sb + B_H2, 1); mbar_init(sb + B_H3, 2);
        for (int i = 0; i < 3; i++) { mbar_init(sb + B_KV + 8 * i, 1); mbar_init(sb + B_P + 8 * i, 4); mbar_init(sb + B_GO + 8 * i, 4); }
        for (int i = 0; i < 12; i++) mbar_init(sb + B_R2 + 8 * i, 1);
        mbar_init(sb + B_UC, 1); mbar_init(sb + B_X, 1);
        for (int i = 0; i < 4; i++) asm volatile("st.shared.u32 [%0], 0;" ::"r"(sb + CNT + 4 * i) : "memory");
        asm volatile("fence.mbarrier_init.release.cluster;" ::: "memory");
        fence_async();
    }
    __syncthreads();
    const int wg = __shfl_sync(0xffffffffu, tid >> 7, 0);
    const int lane = tid & 31, w = (tid >> 5) & 3;
    const bool w0 = __shfl_sync(0xffffffffu, w, 0) == 0;
    const uint32_t sd = (sb & 0x3FFFF) >> 4;
    const uint32_t adA = sd + (AT >> 4) + (1u << 16);
    const uint32_t bd0 = sd + (R1 >> 4);
    const uint32_t bd2k = bd0 + ((2048u >> 4) << 16);
    const bool el = (tid & 127) == 0;
    const uint32_t lrow = 16 * w + (lane & 7) + ((lane >> 3) & 1) * 8;
    const uint32_t loff = lrow * 128 + ((((lane >> 4) ^ lrow) & 7) << 4);
    const int r0 = 16 * w + (lane >> 2);

    if (wg == 0) {
        asm volatile("setmaxnreg.inc.sync.aligned.u32 184;");
        uint32_t q[112];
        PT(0);
        {
            float mq[16];
            fresh(mq);
            mbar_wait(sb + B_MK, 0);
            PT(1);
            if (PFW && tid == 32) l2_prefetch((const char*)wup + piece * 8192, 8192);
            wg_fence();
#pragma unroll 1
            for (int c = 0; c < 8; c++)
#pragma unroll
                for (int kk = 0; kk < 4; kk++)
                    wgmma_ss_n32_tb0(mq, dsc(sd, R0 + c * 8192 + kk * 32, 16), dsc(sd, R1 + 32768 + c * 4096 + kk * 32, 16), 1);
            wg_commit();
            wg_wait<0>();
            if (mode != 1 && w0 && elect1()) { ring_full(sb, 16, &mp.wup8, 48, 8); ring_full(sb, 24, &mp.wup8, 64, 8); }
            pin(mq);
            uint32_t* c = reinterpret_cast<uint32_t*>(g_mqk + (64 * (piece >> 4) + r0) * D_ + 32 * (piece & 15) + 2 * (lane & 3));
#pragma unroll
            for (int n = 0; n < 4; n++) { c[4 * n] = pack2(mq[4 * n], mq[4 * n + 1]); c[4 * n + 4 * D_] = pack2(mq[4 * n + 2], mq[4 * n + 3]); }
            fence_async_g();
            bar_sync(1, 128);
            if (el) {
                if (mode == 0) flag_add(&g_sync[2]);
                if (mode == 0) flag_wait(&g_sync[2], NCTA);
                mbar_arrive(sb + B_MQ);
                PT(12);
                mbar_wait(sb + B_LN, 0);
#pragma unroll 1
                for (int c = 0; c < 8; c++) {
                    tma4_store(&mp.xas, sb + AT + c * 8192, 0, 62 * ti, c, b);
                    const unsigned t0 = (unsigned)clock();
                    while (c < 7 && (unsigned)clock() - t0 < XS_GAP) __nanosleep(20);
                }
                asm volatile("cp.async.bulk.commit_group;" ::: "memory");
                if (mode == 1) asm volatile("cp.async.bulk.wait_group 0;" ::: "memory");
            }
            PT(13);
            if (mode == 1) return;
        }
        mbar_wait(sb + B_H1, 0);
        PT(2);
        uint32_t slot8 = 8, par = 1, prev8 = 0;
        auto adv = [&]() { prev8 = slot8; slot8 += 8; if (slot8 == 40) { slot8 = 0; par ^= 1; } };
        {
            float acc[128];
            fresh(acc);
            auto step = [&](int i) {
                const uint32_t aa = adA + (i >> 1) * 512 + (i & 1) * 4, bb = bd0 + ((4096u >> 4) << 16) + slot8 * 128;
                wg_fence();
                wgmma_ss_n256_tb1(acc, mkd(aa), mkd(bb), 1);
                wgmma_ss_n256_tb1(acc, mkd(aa + 2), mkd(bb + 128), 1);
                wg_commit();
                wg_wait<1>();
            };
#pragma unroll 1
            for (int i = 0; i < 12; i++) {
                mbar_wait(sb + B_R1 + slot8, par);
                step(i);
                if (i > 0 && w0 && elect1()) ring_full(sb, prev8, &mp.mqa4, 32 * i + 128, 4);
                adv();
            }
#pragma unroll 1
            for (int i = 12; i < 16; i++) {
                mbar_wait(sb + B_R1 + slot8, par);
                if (i == 15 && el) mbar_arrive(sb + B_H2);
                step(i);
                if (w0 && elect1()) ring_full(sb, prev8, &mp.wup8, 16 * i - 192, 0);
                adv();
            }
            wg_wait<0>();
            if (w0 && elect1()) ring_full(sb, prev8, &mp.wup8, 64, 0);
            pin(acc);
            PT(3);
#pragma unroll
            for (int kk = 0; kk < 4; kk++)
                stsm4((sb + QS + loff) ^ (kk << 5), pack2(acc[96 + 8 * kk], acc[97 + 8 * kk]), pack2(acc[98 + 8 * kk], acc[99 + 8 * kk]),
                      pack2(acc[100 + 8 * kk], acc[101 + 8 * kk]), pack2(acc[102 + 8 * kk], acc[103 + 8 * kk]));
            fence_async();
#pragma unroll
            for (int i = 47; i >= 0; i--) q[64 + i] = pack2v(acc[2 * i], acc[2 * i + 1]);
        }
        if (el) {
            asm volatile("cp.async.bulk.wait_group 0;" ::: "memory");
            if (mode == 0) {
                fence_async_g();
                flag_add(&g_sync[b]);
                flag_wait(&g_sync[b], TPB);
            }
            mbar_arrive(sb + B_XA);
        }
        __syncwarp();
        mbar_wait(sb + B_H3, 0);
        PT(4);
        slot8 = 32; par = 0;
#pragma unroll
        for (int half = 0; half < 2; half++) {
            float acc[64];
            fresh(acc);
            auto step = [&](int m) {
                const uint32_t aa = adA + m * 512, bb = bd0 + ((8192u >> 4) << 16) + slot8 * 128;
                mbar_wait(sb + B_R1 + slot8, par);
                wg_fence();
#pragma unroll
                for (int kk = 0; kk < 4; kk++) wgmma_ss_n128_tb1(acc, mkd(aa + 2 * kk), mkd(bb + 128 * kk), 1);
                wg_commit();
                wg_wait<1>();
            };
            if (half == 0) {
#pragma unroll 1
                for (int m = 0; m < 8; m++) {
                    step(m);
                    if (m > 0 && w0 && elect1()) ring_full(sb, prev8, &mp.mqb2, (64 * m + 256) & 511, (m + 4) >> 3 << 1);
                    adv();
                }
            } else {
#pragma unroll 1
                for (int m = 0; m < 4; m++) {
                    step(m);
                    if (m > 0 && w0 && elect1()) ring_full(sb, prev8, &mp.mqb2, 64 * m + 256, 2);
                    adv();
                }
#pragma unroll 1
                for (int m = 4; m < 8; m++) {
                    step(m);
                    if (w0 && elect1()) {
                        if (m == 4) mbar_expect_tx(sb + B_KV + 8, 65536);
                        tma4(sb + R1 + prev8 * 2048, &mp.xa2, 0, 0, 2 * m - 8, b, sb + B_KV + 8);
                    }
                    adv();
                }
            }
            wg_wait<0>();
            if (w0 && elect1()) {
                if (half == 0) ring_full(sb, prev8, &mp.mqb2, 256, 2);
                else {
                    mbar_expect_tx(sb + B_KV + 16, 65536);
                    tma4(sb + R2, &mp.xa, 0, 64, 0, b, sb + B_KV + 16);
                }
            }
            pin(acc);
#pragma unroll
            for (int i = 31; i >= 0; i--) q[32 * half + i] = pack2v(acc[2 * i], acc[2 * i + 1]);
        }
        bar_sync(1, 128);
        PT(5);

        const float CS = 0.04419417382415922f * 1.4426950408889634f;
        float m0 = -INFINITY, m1 = -INFINITY, l0 = 0.f, l1 = 0.f;
        int s = 0, sn = 1, ph = 0;
        float S[32];
        const bool l0w = lane == 0, q0 = (lane & 3) == 0;
#pragma unroll 1
        for (int j = -1;; j++) {
            if (j >= 0) {
                PL(j, 1);
                if (j == NKV - 1) {
#pragma unroll
                    for (int i = (T_ - 64 * (NKV - 1)) / 2; i < 32; i++) asm volatile("mov.b32 %0, 0xff800000;" : "=f"(S[i]));
                }
                float y[8], z[8];
#pragma unroll
                for (int n = 0; n < 8; n++) { y[n] = fmaxf(S[4 * n], S[4 * n + 1]); z[n] = fmaxf(S[4 * n + 2], S[4 * n + 3]); }
#pragma unroll
                for (int n = 0; n < 4; n++) { y[n] = fmaxf(y[n], y[n + 4]); z[n] = fmaxf(z[n], z[n + 4]); }
                float x0 = fmaxf(fmaxf(y[0], y[1]), fmaxf(fmaxf(y[2], y[3]), m0)), x1 = fmaxf(fmaxf(z[0], z[1]), fmaxf(fmaxf(z[2], z[3]), m1));
                x0 = fmaxf(x0, __shfl_xor_sync(0xffffffffu, x0, 1));
                x1 = fmaxf(x1, __shfl_xor_sync(0xffffffffu, x1, 1));
                x0 = fmaxf(x0, __shfl_xor_sync(0xffffffffu, x0, 2));
                x1 = fmaxf(x1, __shfl_xor_sync(0xffffffffu, x1, 2));
                const float sc0 = ex2((m0 - x0) * CS), sc1 = ex2((m1 - x1) * CS);
                m0 = x0; m1 = x1;
                const float n0 = -x0 * CS, n1 = -x1 * CS;
                if (q0) { sts_f32(sb + SCL + s * 256 + r0 * 4, sc0); sts_f32(sb + SCL + s * 256 + r0 * 4 + 32, sc1); }
                __syncwarp();
                if (l0w) mbar_arrive(sb + B_P + s * 8);
                if (j < NKV - 1) mbar_wait(sb + B_KV + sn * 8, ph);
                float a0 = 0.f, a1 = 0.f;
                const uint32_t pb = sb + R3 + (s == 0 ? 2 : s - 1) * 8192;
#pragma unroll
                for (int kk = 0; kk < 4; kk++) {
                    float p[8];
#pragma unroll
                    for (int e = 0; e < 8; e++) p[e] = ex2(fmaf(S[8 * kk + e], CS, (e & 2) ? n1 : n0));
                    a0 += (p[0] + p[1]) + (p[4] + p[5]);
                    a1 += (p[2] + p[3]) + (p[6] + p[7]);
                    stsm4((pb + loff) ^ (kk << 5), pack2(p[0], p[1]), pack2(p[2], p[3]), pack2(p[4], p[5]), pack2(p[6], p[7]));
                }
                l0 = fmaf(l0, sc0, a0); l1 = fmaf(l1, sc1, a1);
                PL(j, 2);
                if (j == NKV - 1) break;
            } else {
                mbar_wait(sb + B_KV + 8, 0);
            }
            float Sn[32];
            const uint32_t kd = sd + sn * 4096;
            wg_fence();
#pragma unroll
            for (int kk = 0; kk < 28; kk++) {
                wgmma_rs_n64_tb0(Sn, q[4 * kk], q[4 * kk + 1], q[4 * kk + 2], q[4 * kk + 3], dsc(kd, (kk >> 2) * 8192 + (kk & 3) * 32, 16), kk > 0);
                if (kk == FENCE_AT) { fence_async(); __syncwarp(); }
                if (kk == GO_AT) { PL(j, 3); if (j >= 0 && l0w) mbar_arrive(sb + B_GO + s * 8); }
            }
#pragma unroll
            for (int kk = 0; kk < 4; kk++)
                wgmma_ss_n64_tb0(Sn, dsc(sd, QS + kk * 32, 16), dsc(kd, 7 * 8192 + kk * 32, 16), 1);
            wg_commit();
            PL(j, 0);
            wg_wait<0>();
            pin(Sn);
#pragma unroll
            for (int i = 0; i < 32; i++) S[i] = Sn[i];
            s = sn;
            if (++sn == 3) sn = 0;
            if (sn == 1) ph ^= 1;
        }
        l0 += __shfl_xor_sync(0xffffffffu, l0, 1); l1 += __shfl_xor_sync(0xffffffffu, l1, 1);
        l0 += __shfl_xor_sync(0xffffffffu, l0, 2); l1 += __shfl_xor_sync(0xffffffffu, l1, 2);
        if (q0) { sts_f32(sb + LINV + r0 * 4, rcp(l0)); sts_f32(sb + LINV + r0 * 4 + 32, rcp(l1)); }
        fence_async();
        __syncwarp();
        if (l0w) mbar_arrive(sb + B_GO + s * 8);
        PDUMP();
    } else {
        asm volatile("setmaxnreg.dec.sync.aligned.u32 160;");
        const int h = wg - 1;
        auto red4 = [&](float (&a)[4]) {
            const bool b4 = lane & 16, b3 = lane & 8;
            const float k0 = (b4 ? a[2] : a[0]) + __shfl_xor_sync(0xffffffffu, b4 ? a[0] : a[2], 16);
            const float k1 = (b4 ? a[3] : a[1]) + __shfl_xor_sync(0xffffffffu, b4 ? a[1] : a[3], 16);
            float k = (b3 ? k1 : k0) + __shfl_xor_sync(0xffffffffu, b3 ? k0 : k1, 8);
            k += __shfl_xor_sync(0xffffffffu, k, 4);
            k += __shfl_xor_sync(0xffffffffu, k, 2);
            k += __shfl_xor_sync(0xffffffffu, k, 1);
            return k;
        };
#pragma unroll 1
        for (int bt = -1; bt < 2; bt++) {
            if (bt == 0) { mbar_wait(sb + B_A, 0); PT(0); }
            uint32_t v[4][8];
            float a[4], f[4][16];
            const uint32_t la = sb + AT + (lane >> 3) * 8192 + (32 * h + 8 * w + (bt & 1) * 4) * 128 + (((lane & 7) ^ ((bt & 1) * 4)) << 4);
#pragma unroll
            for (int r = 0; r < 4; r++) { lds4((la ^ (r << 4)) + r * 128, v[r]); lds4((la ^ (r << 4)) + r * 128 + 32768, v[r] + 4); }
#pragma unroll
            for (int r = 0; r < 4; r++) {
                float s0 = blo(v[r][0]), s1 = bhi(v[r][0]);
#pragma unroll
                for (int i = 1; i < 8; i++) { s0 += blo(v[r][i]); s1 += bhi(v[r][i]); }
                a[r] = s0 + s1;
            }
            const float mu = red4(a) * (1.f / D_);
            const uint32_t mp2 = pack2(mu, mu);
#pragma unroll
            for (int r = 0; r < 4; r++) {
                const uint32_t m2 = __shfl_sync(0xffffffffu, mp2, 8 * r);
                float s0 = 0.f, s1 = 0.f;
#pragma unroll
                for (int i = 0; i < 8; i++) {
                    const uint32_t d = bsub2(v[r][i], m2);
                    f[r][2 * i] = blo(d); f[r][2 * i + 1] = bhi(d);
                    s0 = fmaf(f[r][2 * i], f[r][2 * i], s0); s1 = fmaf(f[r][2 * i + 1], f[r][2 * i + 1], s1);
                }
                a[r] = s0 + s1;
            }
            const float dm = mu - blo(mp2);
            float sd_ = bfr(bfr(fmaxf(fmaf(red4(a), 1.f / D_, -dm * dm), 0.f)) + 1e-5f);
            asm("sqrt.approx.f32 %0, %0;" : "+f"(sd_));
            const float ri = rcp(bfr(sd_));
#pragma unroll
            for (int r = 0; r < 4; r++) {
                const float rinv = __shfl_sync(0xffffffffu, ri, 8 * r);
#pragma unroll
                for (int i = 0; i < 8; i++) v[r][i] = pack2(f[r][2 * i] * rinv, f[r][2 * i + 1] * rinv);
                if (bt >= 0) {
                    sts4((la ^ (r << 4)) + r * 128, v[r][0], v[r][1], v[r][2], v[r][3]);
                    sts4((la ^ (r << 4)) + r * 128 + 32768, v[r][4], v[r][5], v[r][6], v[r][7]);
                }
            }
        }
        fence_async();
        bar_sync(2, 256);
        if (tid == 128) mbar_arrive(sb + B_LN);
        if (mode == 1) return;
        float acc[128];
#pragma unroll
        for (int pass = 0; pass < 2; pass++) {
            if (pass == 1) mbar_wait(sb + B_H2, 0);
            PT(1 + 3 * pass);
            fresh(acc);
            uint32_t slot8 = pass ? 16 : 32, par = 0, prev8 = 0;
            auto adv = [&]() { prev8 = slot8; slot8 += 8; if (slot8 == 40) { slot8 = 0; par ^= 1; } };
            auto step = [&](int kk) {
                wg_fence();
                wgmma_ss_n256_tb1(acc, mkd(adA + (kk >> 2) * 512 + (kk & 3) * 2), mkd(bd2k + h * 512 + slot8 * 128), 1);
                wg_commit();
                wg_wait<1>();
            };
#pragma unroll 1
            for (int kk = 0; kk < 28; kk++) {
                mbar_wait(sb + B_R1 + slot8, par);
                step(kk);
                if (kk > 0 && w0 && elect1()) ring_half(sb, prev8, h * 8192, &mp.wup4, 16 * kk + 64, (pass ? 0 : 8) + 4 * h);
                adv();
            }
            if (pass == 0 && w0) mbar_wait(sb + B_MQ, 0);
#pragma unroll 1
            for (int kk = 28; kk < 32; kk++) {
                mbar_wait(sb + B_R1 + slot8, par);
                if (kk == 31 && el) mbar_arrive(sb + (pass ? B_H3 : B_H1));
                step(kk);
                if (w0 && elect1()) ring_half(sb, prev8, h * 8192, pass ? &mp.mqb1 : &mp.mqa2, (pass ? 64 : 32) * (kk - 28), pass ? h : 4 + 2 * h);
                adv();
            }
            wg_wait<0>();
            if (w0 && elect1()) ring_half(sb, prev8, h * 8192, pass ? &mp.mqb1 : &mp.mqa2, pass ? 256 : 128, pass ? h : 4 + 2 * h);
            pin(acc);
            PT(2 + 3 * pass);
            if (pass == 0) {
#pragma unroll
                for (int i = 0; i < 128; i++) acc[i] = gelu(acc[i]);
                float s0 = 0.f, s1 = 0.f;
#pragma unroll
                for (int n = 0; n < 32; n++) { s0 += acc[4 * n] + acc[4 * n + 1]; s1 += acc[4 * n + 2] + acc[4 * n + 3]; }
                s0 += __shfl_xor_sync(0xffffffffu, s0, 1); s1 += __shfl_xor_sync(0xffffffffu, s1, 1);
                s0 += __shfl_xor_sync(0xffffffffu, s0, 2); s1 += __shfl_xor_sync(0xffffffffu, s1, 2);
                s0 *= (1.f / 256.f); s1 *= (1.f / 256.f);
                float v0 = 0.f, v1 = 0.f;
#pragma unroll
                for (int n = 0; n < 32; n++) {
                    float d0 = acc[4 * n] - s0, d1 = acc[4 * n + 1] - s0, d2 = acc[4 * n + 2] - s1, d3 = acc[4 * n + 3] - s1;
                    v0 = fmaf(d0, d0, v0); v0 = fmaf(d1, d1, v0); v1 = fmaf(d2, d2, v1); v1 = fmaf(d3, d3, v1);
                }
                v0 += __shfl_xor_sync(0xffffffffu, v0, 1); v1 += __shfl_xor_sync(0xffffffffu, v1, 1);
                v0 += __shfl_xor_sync(0xffffffffu, v0, 2); v1 += __shfl_xor_sync(0xffffffffu, v1, 2);
                if ((lane & 3) == 0) {
                    uint32_t a = sb + STAT + h * 512 + r0 * 8;
                    sts_f32(a, s0); sts_f32(a + 4, v0); sts_f32(a + 64, s1); sts_f32(a + 68, v1);
                }
                bar_sync(2, 256);
                {
                    uint32_t a = sb + STAT + (h ^ 1) * 512 + r0 * 8;
                    float t0 = lds_f32(a), u0 = lds_f32(a + 4), t1 = lds_f32(a + 64), u1 = lds_f32(a + 68);
                    v0 = (v0 + u0 + (s0 - t0) * (s0 - t0) * 128.f) * (1.f / 512.f);
                    v1 = (v1 + u1 + (s1 - t1) * (s1 - t1) * 128.f) * (1.f / 512.f);
                    s0 = 0.5f * (s0 + t0); s1 = 0.5f * (s1 + t1);
                }
                v0 = rsqrtf(v0 + 1e-5f); v1 = rsqrtf(v1 + 1e-5f);
                s0 = -s0 * v0; s1 = -s1 * v1;
#pragma unroll
                for (int p = 0; p < 16; p++)
                    stsm4(((sb + R0 + h * 32768 + loff) ^ ((p & 3) << 5)) + (p >> 2) * 8192,
                          pack2(fmaf(acc[8 * p], v0, s0), fmaf(acc[8 * p + 1], v0, s0)), pack2(fmaf(acc[8 * p + 2], v1, s1), fmaf(acc[8 * p + 3], v1, s1)),
                          pack2(fmaf(acc[8 * p + 4], v0, s0), fmaf(acc[8 * p + 5], v0, s0)), pack2(fmaf(acc[8 * p + 6], v1, s1), fmaf(acc[8 * p + 7], v1, s1)));
            } else {
                bar_sync(3 + h, 128);
                const uint32_t rm = lrow == 0 ? 0 : lrow - 1, rp = lrow == 63 ? 63 : lrow + 1;
                const uint32_t gb = sb + R0 + h * 32768;
                const uint32_t am = gb + rm * 128 + ((((lane >> 4) ^ rm) & 7) << 4), ap = gb + rp * 128 + ((((lane >> 4) ^ rp) & 7) << 4), ac = gb + loff;
                const uint32_t dwa = sb + DWS + 512 * h + ((lane >> 3) & 1) * 16 + (lane >> 4) * 1024;
                bf16* ucp = g_uc + ((size_t)blockIdx.x * 64 + r0) * D_ + 256 * h + 8 * (lane & 3);
#pragma unroll
                for (int m = 7; m >= 0; m--) {
                    uint32_t o[8];
#pragma unroll
                    for (int pp = 1; pp >= 0; pp--) {
                        const int p = 2 * m + pp;
                        const uint32_t co = (p >> 2) * 8192, cx = (p & 3) << 5;
                        uint32_t u[4], g[4], cv[4], d[4], d2[2];
#pragma unroll
                        for (int e = 3; e >= 0; e--) u[e] = pack2v(gelu(acc[8 * p + 2 * e]), gelu(acc[8 * p + 2 * e + 1]));
                        ldsm4(dwa + 32 * p, d);
                        ldsm2(dwa + 32 * p + 2048, d2);
                        ldsm4((am ^ cx) + co, g);
#pragma unroll
                        for (int e = 0; e < 4; e++) cv[e] = bmul2(g[e], d[e >> 1]);
                        ldsm4((ac ^ cx) + co, g);
#pragma unroll
                        for (int e = 0; e < 4; e++) cv[e] = bfma2(g[e], d[2 + (e >> 1)], cv[e]);
                        ldsm4((ap ^ cx) + co, g);
#pragma unroll
                        for (int e = 0; e < 4; e++) o[4 * (e & 1) + 2 * pp + (e >> 1)] = bmul2(u[e], bfma2(g[e], d2[e >> 1], cv[e]));
                    }
                    stg4(ucp + 32 * m, o[0], o[1], o[2], o[3]);
                    stg4(ucp + 32 * m + 8 * D_, o[4], o[5], o[6], o[7]);
                }
                bar_sync(2, 256);
                if (tid == 128) {
                    mbar_wait(sb + B_XA, 0);
                    mbar_expect_tx(sb + B_KV, 65536);
                    tma4(sb + R0, &mp.xa, 0, 128, 0, b, sb + B_KV);
                }
            }
            PT(3 + 3 * pass);
        }
        int s = 1, ph = 0;
        fresh(acc);
#pragma unroll 1
        for (int j = 0; j < NKV; j++) {
            mbar_wait(sb + B_P + s * 8, ph);
            PL(j, 0);
            if (j > 0) {
                const float sc0 = lds_f32(sb + SCL + s * 256 + r0 * 4), sc1 = lds_f32(sb + SCL + s * 256 + r0 * 4 + 32);
                if (__any_sync(0xffffffffu, sc0 != 1.f || sc1 != 1.f)) {
#pragma unroll
                    for (int n = 0; n < 32; n++) { acc[4 * n] *= sc0; acc[4 * n + 1] *= sc0; acc[4 * n + 2] *= sc1; acc[4 * n + 3] *= sc1; }
                }
            }
            mbar_wait(sb + B_GO + s * 8, ph);
            PL(j, 1);
            const uint32_t vd = sd + s * 4096 + h * 2048, pd = sd + (s == 0 ? 2 : s - 1) * 512;
            pin(acc);
            wg_fence();
#pragma unroll
            for (int kk = 0; kk < 4; kk++) wgmma_ss_n256_tb1(acc, dsc(pd, R3 + kk * 32, 16), dsc(vd, kk * 2048, 8192), 1);
            wg_commit();
            wg_wait<0>();
            pin(acc);
            PL(j, 2);
            if (w0 && elect1()) {
                if (j == NKV - 5 && mode == 0) flag_wait(&g_sync[3], 4);
                if (atom_inc_s(sb + CNT + 4 * s) & 1) {
                    if (j + 3 < NKV) {
                        mbar_expect_tx(sb + B_KV + s * 8, 65536);
                        tma4(sb + s * 65536, &mp.xa, 0, 64 * (j + 3), 0, b, sb + B_KV + s * 8);
                    } else if (j < NKV - 1) {
                        const int n0 = j == NKV - 3 ? 0 : 8, n1 = j == NKV - 3 ? 8 : 12;
#pragma unroll 1
                        for (int n = n0; n < n1; n++) ring_ld(sb, B_R2, n * 8, &mp.wepi, 16 * (n >> 1), 4 * (n & 1));
                    }
                }
            }
            if (++s == 3) s = 0;
            if (s == 1) ph ^= 1;
        }
        {
            const float i0 = lds_f32(sb + LINV + r0 * 4), i1 = lds_f32(sb + LINV + r0 * 4 + 32);
#pragma unroll
            for (int p = 0; p < 16; p++)
                stsm4(((sb + R0 + h * 32768 + loff) ^ ((p & 3) << 5)) + (p >> 2) * 8192,
                      pack2(acc[8 * p] * i0, acc[8 * p + 1] * i0), pack2(acc[8 * p + 2] * i1, acc[8 * p + 3] * i1),
                      pack2(acc[8 * p + 4] * i0, acc[8 * p + 5] * i0), pack2(acc[8 * p + 6] * i1, acc[8 * p + 7] * i1));
        }
        fence_async();
        fence_async_g();
        bar_sync(2, 256);
        if (tid == 128) {
            mbar_expect_tx(sb + B_UC, 65536);
            tma3(sb + UCT, &mp.uc, 0, 64 * blockIdx.x, 0, sb + B_UC);
        }
        PT(7);
        fresh(acc);
        {
            uint32_t slot8 = 8 * h, par = 0, prev8 = 0;
#pragma unroll 1
            for (int kk = 0; kk < 64; kk++) {
                if (kk == 32) mbar_wait(sb + B_UC, 0);
                mbar_wait(sb + B_R2 + slot8, par);
                wg_fence();
                wgmma_ss_n256_tb1(acc, mkd(sd + (1u << 16) + (kk < 32 ? (R0 >> 4) : (UCT >> 4) - 4096) + (kk >> 2) * 512 + (kk & 3) * 2), mkd(bd2k + slot8 * 64), 1);
                wg_commit();
                wg_wait<1>();
                if (kk > 0 && w0 && elect1()) {
                    if (kk < 59) ring_ld(sb, B_R2, prev8, &mp.wepi, 16 * (kk + 5), 4 * h);
                    if (kk == 32 && (atom_inc_s(sb + CNT + 12) & 1)) {
                        mbar_expect_tx(sb + B_X, 65536);
                        tma4(sb + R0, &mp.x, 0, 62 * ti, 0, b, sb + B_X);
                    }
                }
                prev8 = slot8;
                slot8 += 16;
                if (slot8 >= 96) { slot8 -= 96; par ^= 1; }
            }
        }
        wg_wait<0>();
        pin(acc);
        PT(8);
        mbar_wait(sb + B_X, 0);
        PT(9);
        {
            const uint32_t sr = (lrow + 63) & 63;
            const uint32_t xoff = sr * 128 + ((((lane >> 4) ^ sr) & 7) << 4);
#pragma unroll
            for (int p = 0; p < 16; p++) {
                const uint32_t a = ((sb + R0 + h * 32768 + xoff) ^ ((p & 3) << 5)) + (p >> 2) * 8192;
                uint32_t xv[4];
                ldsm4(a, xv);
#pragma unroll
                for (int e = 0; e < 4; e++)
                    xv[e] = pack2(acc[8 * p + 2 * e] + __uint_as_float(xv[e] << 16), acc[8 * p + 2 * e + 1] + __uint_as_float(xv[e] & 0xffff0000u));
                stsm4(a, xv[0], xv[1], xv[2], xv[3]);
            }
        }
        fence_async();
        bar_sync(3 + h, 128);
        if (el) {
            for (int c = 0; c < 4; c++) tma4_store(&mp.out, sb + R0 + (4 * h + c) * 8192, 0, 62 * ti, 4 * h + c, b);
            asm volatile("cp.async.bulk.commit_group;" ::: "memory");
            PT(10);
            if (h == 0) cta_done(mode);
            asm volatile("cp.async.bulk.wait_group.read 0;" ::: "memory");
        }
        PT(11);
        PDUMP();
    }
}

typedef CUresult (*PFN_enc)(CUtensorMap*, CUtensorMapDataType, cuuint32_t, void*, const cuuint64_t*, const cuuint64_t*,
                            const cuuint32_t*, const cuuint32_t*, CUtensorMapInterleave, CUtensorMapSwizzle,
                            CUtensorMapL2promotion, CUtensorMapFloatOOBfill);

static void enc(PFN_enc f, CUtensorMap* m, void* base, int rank, const cuuint64_t* dims, const cuuint64_t* strides, const cuuint32_t* box) {
    cuuint32_t es[5] = {1, 1, 1, 1, 1};
    f(m, CU_TENSOR_MAP_DATA_TYPE_BFLOAT16, rank, base, dims, strides, box, es, CU_TENSOR_MAP_INTERLEAVE_NONE,
      CU_TENSOR_MAP_SWIZZLE_128B, CU_TENSOR_MAP_L2_PROMOTION_L2_256B, CU_TENSOR_MAP_FLOAT_OOB_FILL_NONE);
}
static void enc_act(PFN_enc f, CUtensorMap* m, void* base, int rows, int chunks, int trows = T_, int pitch = T_) {
    cuuint64_t dims[4] = {64, (cuuint64_t)trows, 8, (cuuint64_t)NB_};
    cuuint64_t st[3] = {1024, 128, (cuuint64_t)pitch * 1024};
    cuuint32_t box[4] = {64, (cuuint32_t)rows, (cuuint32_t)chunks, 1};
    enc(f, m, base, 4, dims, st, box);
}
static void enc_w(PFN_enc f, CUtensorMap* m, void* base, int krows, int ncols, int bk, int bc) {
    cuuint64_t dims[3] = {64, (cuuint64_t)krows, (cuuint64_t)(ncols / 64)};
    cuuint64_t st[2] = {(cuuint64_t)ncols * 2, 128};
    cuuint32_t box[3] = {64, (cuuint32_t)bk, (cuuint32_t)bc};
    enc(f, m, base, 3, dims, st, box);
}

extern "C" void kernel_launch(void* const* d_in, const int* in_sizes, int n_in, void* d_out, int out_size) {
    const bf16* x = (const bf16*)d_in[0];
    static PFN_enc fenc = nullptr;
    static void *p_xa, *p_mqk, *p_wepi, *p_uc, *p_t1;
    static int fused = 0;
    if (!fenc) {
        void* fn = nullptr;
        cudaDriverEntryPointQueryResult qr;
        cudaGetDriverEntryPoint("cuTensorMapEncodeTiled", &fn, cudaEnableDefault, &qr);
        fenc = (PFN_enc)fn;
        cudaGetSymbolAddress(&p_xa, g_xa);
        cudaGetSymbolAddress(&p_mqk, g_mqk);
        cudaGetSymbolAddress(&p_wepi, g_wepi);
        cudaGetSymbolAddress(&p_uc, g_uc);
        cudaGetSymbolAddress(&p_t1, g_t1);
        cudaFuncSetAttribute(main_kernel, cudaFuncAttributeMaxDynamicSharedMemorySize, SMEM_BYTES);
        int dev = 0, sms = 0, occ = 0;
        cudaGetDevice(&dev);
        cudaDeviceGetAttribute(&sms, cudaDevAttrMultiProcessorCount, dev);
        cudaOccupancyMaxActiveBlocksPerMultiprocessor(&occ, main_kernel, 384, SMEM_BYTES);
        fused = sms * occ >= NCTA + 2;
    }
    Maps mp;
    enc_act(fenc, &mp.xa, (char*)p_xa + 1024, 64, 8, T_, T_ + 8);
    enc_act(fenc, &mp.xa2, (char*)p_xa + 1024, 64, 2, T_, T_ + 8);
    enc_act(fenc, &mp.xas, p_xa, 64, 1, T_ + 1, T_ + 8);
    enc_act(fenc, &mp.x, (void*)x, 64, 8);
    enc_act(fenc, &mp.out, d_out, 62, 1);
    enc_w(fenc, &mp.wup4, d_in[5], 512, 1024, 16, 4);
    enc_w(fenc, &mp.wup8, d_in[5], 512, 1024, 16, 8);
    enc_w(fenc, &mp.mqa2, p_mqk, 512, 512, 32, 2);
    enc_w(fenc, &mp.mqa4, p_mqk, 512, 512, 32, 4);
    enc_w(fenc, &mp.mqb1, p_mqk, 512, 512, 64, 1);
    enc_w(fenc, &mp.mqb2, p_mqk, 512, 512, 64, 2);
    enc_w(fenc, &mp.wepi, p_wepi, 1024, 512, 16, 4);
    enc_w(fenc, &mp.uc, p_uc, NCTA * 64, 512, 64, 8);
    enc_w(fenc, &mp.wq, d_in[1], 512, 512, 64, 8);
    enc_w(fenc, &mp.wk, d_in[2], 512, 512, 32, 8);
    enc_w(fenc, &mp.fa[0], d_in[3], 512, 512, 128, 1);
    enc_w(fenc, &mp.fa[1], d_in[7], 512, 512, 128, 1);
    enc_w(fenc, &mp.fa[2], p_t1, 512, 512, 128, 1);
    enc_w(fenc, &mp.fb[0], d_in[4], 512, 512, 64, 4);
    enc_w(fenc, &mp.fb[1], d_in[8], 1024, 512, 64, 4);
    enc_w(fenc, &mp.fc[0], p_t1, 512, 512, 64, 4);
    enc_w(fenc, &mp.fc[1], p_wepi, 1024, 512, 64, 4);
    cudaStream_t st = cudaStreamPerThread;
    if (fused) {
        main_kernel<<<NCTA + 2, 384, SMEM_BYTES, st>>>(mp, (const bf16*)d_in[6], (const bf16*)d_in[5], 0);
    } else {
        main_kernel<<<NCTA + 2, 384, SMEM_BYTES, st>>>(mp, (const bf16*)d_in[6], (const bf16*)d_in[5], 1);
        main_kernel<<<NCTA + 2, 384, SMEM_BYTES, st>>>(mp, (const bf16*)d_in[6], (const bf16*)d_in[5], 2);
    }
}
```

```cpp
#include <cuda_runtime.h>
#include <cuda_bf16.h>
#include <cuda.h>
#include <stdint.h>

typedef __nv_bfloat16 bf16;

constexpr int T_ = 4000, D_ = 512, NB_ = 2;
constexpr int TPB = 65;
constexpr int NCTA = TPB * NB_;
constexpr int NKV = 63;

__device__ __align__(1024) bf16 g_xa[NB_ * (T_ + 8) * D_];
__device__ __align__(1024) bf16 g_mqk[D_ * D_];
__device__ __align__(1024) bf16 g_t1[D_ * D_];
__device__ __align__(1024) bf16 g_wepi[2 * D_ * D_];
__device__ __align__(1024) bf16 g_uc[NCTA * 64 * D_];
__device__ unsigned g_sync[8];

#define PT(i)
#define PG(i)
#define PL(j, q)
#define PDUMP()

#define FENCE_AT 1
#define GO_AT 25
#define XS_GAP 800
#define PFW 1
constexpr uint32_t R0 = 0, R1 = 65536, R2 = 131072, R3 = 196608, QS = 221184, MISC = 229376;
constexpr uint32_t AT = 147456, DWS = R3 + 16384, UCT = 163840;
constexpr uint32_t SMEM_BYTES = 232448;
constexpr uint32_t B_A = MISC, B_R1 = MISC + 8  , B_MK = MISC + 48, B_LN = MISC + 56, B_MQ = MISC + 64, B_XA = MISC + 72, B_A2 = MISC + 80,
                   B_H1 = MISC + 88, B_H2 = MISC + 96, B_H3 = MISC + 104,
                   B_KV = MISC + 112, B_P = MISC + 136, B_GO = MISC + 160, B_R2 = MISC + 184, B_UC = MISC + 280,
                   B_X = MISC + 288, CNT = MISC + 296  , SCL = MISC + 512  ,
                   LINV = MISC + 1280  , STAT = MISC + 1536  ;

__device__ __forceinline__ uint32_t smem_u32(const void* p) { return (uint32_t)__cvta_generic_to_shared(p); }
__device__ __forceinline__ void wg_fence() { asm volatile("wgmma.fence.sync.aligned;" ::: "memory"); }
__device__ __forceinline__ void wg_commit() { asm volatile("wgmma.commit_group.sync.aligned;" ::: "memory"); }
template <int N> __device__ __forceinline__ void wg_wait() { asm volatile("wgmma.wait_group.sync.aligned %0;" ::"n"(N) : "memory"); }
__device__ __forceinline__ uint64_t dsc(uint32_t sd, uint32_t off, uint32_t lbo) {
    uint32_t lo = sd + (off >> 4) + ((lbo >> 4) << 16);
    uint64_t d;
    asm("mov.b64 %0, {%1, %2};" : "=l"(d) : "r"(lo), "r"((1024u >> 4) | (1u << 30)));
    return d;
}
__device__ __forceinline__ bool elect1() {
    uint32_t p;
    asm volatile("{\n.reg .pred p;\nelect.sync _|p, 0xffffffff;\nselp.u32 %0, 1, 0, p;\n}\n" : "=r"(p));
    return p != 0;
}
__device__ __forceinline__ void mbar_init(uint32_t bar, int cnt) { asm volatile("mbarrier.init.shared::cta.b64 [%0], %1;" ::"r"(bar), "r"(cnt) : "memory"); }
__device__ __forceinline__ void mbar_expect_tx(uint32_t bar, uint32_t bytes) { asm volatile("mbarrier.arrive.expect_tx.shared::cta.b64 _, [%0], %1;" ::"r"(bar), "r"(bytes) : "memory"); }
__device__ __forceinline__ void mbar_arrive(uint32_t bar) { asm volatile("mbarrier.arrive.shared::cta.b64 _, [%0];" ::"r"(bar) : "memory"); }
__device__ __forceinline__ void mbar_wait(uint32_t bar, uint32_t parity) {
    uint32_t ok;
#pragma unroll 1
    for (uint32_t it = 0;; ++it) {
        asm volatile("{\n.reg .pred p;\nmbarrier.try_wait.parity.shared::cta.b64 p, [%1], %2;\nselp.u32 %0, 1, 0, p;\n}\n" : "=r"(ok) : "r"(bar), "r"(parity) : "memory");
        if (ok) break;
        if (it > (1u << 20)) __trap();
    }
}
__device__ __forceinline__ void fence_async() { asm volatile("fence.proxy.async.shared::cta;" ::: "memory"); }
__device__ __forceinline__ void fence_async_g() { asm volatile("fence.proxy.async.global;" ::: "memory"); }
__device__ __forceinline__ void bar_sync(int id, int n) { asm volatile("bar.sync %0, %1;" ::"r"(id), "r"(n) : "memory"); }
__device__ __forceinline__ void tma3(uint32_t dst, const CUtensorMap* tm, int c0, int c1, int c2, uint32_t bar) {
    asm volatile("cp.async.bulk.tensor.3d.shared::cluster.global.mbarrier::complete_tx::bytes [%0], [%1, {%3, %4, %5}], [%2];"
                 ::"r"(dst), "l"(tm), "r"(bar), "r"(c0), "r"(c1), "r"(c2) : "memory");
}
__device__ __forceinline__ void tma4(uint32_t dst, const CUtensorMap* tm, int c0, int c1, int c2, int c3, uint32_t bar) {
    asm volatile("cp.async.bulk.tensor.4d.shared::cluster.global.mbarrier::complete_tx::bytes [%0], [%1, {%3, %4, %5, %6}], [%2];"
                 ::"r"(dst), "l"(tm), "r"(bar), "r"(c0), "r"(c1), "r"(c2), "r"(c3) : "memory");
}
__device__ __forceinline__ void tma4_store(const CUtensorMap* tm, uint32_t src, int c0, int c1, int c2, int c3) {
    asm volatile("cp.async.bulk.tensor.4d.global.shared::cta.bulk_group [%0, {%2, %3, %4, %5}], [%1];"
                 ::"l"(tm), "r"(src), "r"(c0), "r"(c1), "r"(c2), "r"(c3) : "memory");
}
__device__ __forceinline__ void tma3_store(const CUtensorMap* tm, uint32_t src, int c0, int c1, int c2) {
    asm volatile("cp.async.bulk.tensor.3d.global.shared::cta.bulk_group [%0, {%2, %3, %4}], [%1];"
                 ::"l"(tm), "r"(src), "r"(c0), "r"(c1), "r"(c2) : "memory");
}
__device__ __forceinline__ void stsm4(uint32_t addr, uint32_t a, uint32_t b, uint32_t c, uint32_t d) {
    asm volatile("stmatrix.sync.aligned.m8n8.x4.shared.b16 [%0], {%1, %2, %3, %4};" ::"r"(addr), "r"(a), "r"(b), "r"(c), "r"(d) : "memory");
}
__device__ __forceinline__ void ldsm4(uint32_t addr, uint32_t (&r)[4]) {
    asm volatile("ldmatrix.sync.aligned.m8n8.x4.shared.b16 {%0, %1, %2, %3}, [%4];" : "=r"(r[0]), "=r"(r[1]), "=r"(r[2]), "=r"(r[3]) : "r"(addr) : "memory");
}
__device__ __forceinline__ void ldsm2(uint32_t addr, uint32_t (&r)[2]) {
    asm volatile("ldmatrix.sync.aligned.m8n8.x2.shared.b16 {%0, %1}, [%2];" : "=r"(r[0]), "=r"(r[1]) : "r"(addr) : "memory");
}
__device__ __forceinline__ void stg4(void* p, uint32_t a, uint32_t b, uint32_t c, uint32_t d) {
    asm volatile("st.global.v4.u32 [%0], {%1, %2, %3, %4};" ::"l"(p), "r"(a), "r"(b), "r"(c), "r"(d) : "memory");
}
__device__ __forceinline__ uint32_t pack2(float lo, float hi) {
    uint32_t r;
    asm("cvt.rn.bf16x2.f32 %0, %1, %2;" : "=r"(r) : "f"(hi), "f"(lo));
    return r;
}
__device__ __forceinline__ uint32_t pack2v(float lo, float hi) {
    uint32_t r;
    asm volatile("cvt.rn.bf16x2.f32 %0, %1, %2;" : "=r"(r) : "f"(hi), "f"(lo));
    return r;
}
__device__ __forceinline__ uint32_t bmul2(uint32_t a, uint32_t b) { uint32_t r; asm("mul.rn.bf16x2 %0, %1, %2;" : "=r"(r) : "r"(a), "r"(b)); return r; }
__device__ __forceinline__ uint32_t bfma2(uint32_t a, uint32_t b, uint32_t c) { uint32_t r; asm("fma.rn.bf16x2 %0, %1, %2, %3;" : "=r"(r) : "r"(a), "r"(b), "r"(c)); return r; }
__device__ __forceinline__ float ex2(float x) { float r; asm("ex2.approx.ftz.f32 %0, %1;" : "=f"(r) : "f"(x)); return r; }
__device__ __forceinline__ float rcp(float x) { float r; asm("rcp.approx.ftz.f32 %0, %1;" : "=f"(r) : "f"(x)); return r; }
__device__ __forceinline__ float gelu2(float x) {
    float t = fmaf(x * x, 0.044715f * 0.7978845608028654f, 0.7978845608028654f), th;
    asm("tanh.approx.f32 %0, %1;" : "=f"(th) : "f"(x * t));
    return fmaf(x, th, x);
}
__device__ __forceinline__ uint32_t ldg_v(const uint32_t* p) { uint32_t v; asm volatile("ld.global.nc.u32 %0, [%1];" : "=r"(v) : "l"(p)); return v; }
__device__ __forceinline__ float lds_f32(uint32_t a) { float v; asm volatile("ld.shared.f32 %0, [%1];" : "=f"(v) : "r"(a) : "memory"); return v; }
__device__ __forceinline__ void sts_f32(uint32_t a, float v) { asm volatile("st.shared.f32 [%0], %1;" ::"r"(a), "f"(v) : "memory"); }
__device__ __forceinline__ uint32_t atom_inc_s(uint32_t a) { uint32_t v; asm volatile("atom.relaxed.cta.shared.add.u32 %0, [%1], 1;" : "=r"(v) : "r"(a) : "memory"); return v; }
__device__ __forceinline__ void lds4(uint32_t a, uint32_t* r) {
    asm volatile("ld.shared.v4.u32 {%0, %1, %2, %3}, [%4];" : "=r"(r[0]), "=r"(r[1]), "=r"(r[2]), "=r"(r[3]) : "r"(a) : "memory");
}
__device__ __forceinline__ void sts4(uint32_t a, uint32_t x, uint32_t y, uint32_t z, uint32_t t) {
    asm volatile("st.shared.v4.u32 [%0], {%1, %2, %3, %4};" ::"r"(a), "r"(x), "r"(y), "r"(z), "r"(t) : "memory");
}
__device__ __forceinline__ uint32_t bsub2(uint32_t a, uint32_t b) { uint32_t r; asm("sub.rn.bf16x2 %0, %1, %2;" : "=r"(r) : "r"(a), "r"(b)); return r; }
__device__ __forceinline__ float blo(uint32_t v) { return __uint_as_float(v << 16); }
__device__ __forceinline__ float bhi(uint32_t v) { return __uint_as_float(v & 0xffff0000u); }
__device__ __forceinline__ float bfr(float x) { return __bfloat162float(__float2bfloat16_rn(x)); }
__device__ __forceinline__ void l2_prefetch(const void* p, uint32_t bytes) { asm volatile("cp.async.bulk.prefetch.L2.global [%0], %1;" ::"l"(p), "r"(bytes) : "memory"); }
__device__ __forceinline__ void flag_add(unsigned* p) { asm volatile("red.release.gpu.global.add.u32 [%0], 1;" ::"l"(p) : "memory"); }
__device__ __forceinline__ void flag_wait(const unsigned* p, unsigned target) {
#pragma unroll 1
    for (uint32_t it = 0;; ++it) {
        unsigned v;
        asm volatile("ld.acquire.gpu.global.u32 %0, [%1];" : "=r"(v) : "l"(p) : "memory");
        if (v >= target) break;
        if (it > (1u << 20)) __trap();
    }
    fence_async_g();
}
template <int N> __device__ __forceinline__ void pin(float (&a)[N]) {
#pragma unroll
    for (int i = 0; i < N; i++) asm volatile("" : "+f"(a[i])::"memory");
}

template <int N> __device__ __forceinline__ void fresh(float (&a)[N]) {
#pragma unroll
    for (int i = 0; i < N; i++) a[i] = 0.f;
    pin(a);
}

__device__ __forceinline__ void wgmma_rs_n64_tb0(float (&d)[32], uint32_t a0, uint32_t a1, uint32_t a2, uint32_t a3, uint64_t db, int scale_d) {
    asm volatile("{\n.reg .pred p;\nsetp.ne.b32 p, %37, 0;\n"
        "wgmma.mma_async.sync.aligned.m64n64k16.f32.bf16.bf16 {%0, %1, %2, %3, %4, %5, %6, %7, %8, %9, %10, %11, %12, %13, %14, %15, %16, %17, %18, %19, %20, %21, %22, %23, %24, %25, %26, %27, %28, %29, %30, %31}, {%32, %33, %34, %35}, %36, p, 1, 1, 0;\n}\n"
        : "+f"(d[0]), "+f"(d[1]), "+f"(d[2]), "+f"(d[3]), "+f"(d[4]), "+f"(d[5]), "+f"(d[6]), "+f"(d[7]), "+f"(d[8]), "+f"(d[9]), "+f"(d[10]), "+f"(d[11]), "+f"(d[12]), "+f"(d[13]), "+f"(d[14]), "+f"(d[15]), "+f"(d[16]), "+f"(d[17]), "+f"(d[18]), "+f"(d[19]), "+f"(d[20]), "+f"(d[21]), "+f"(d[22]), "+f"(d[23]), "+f"(d[24]), "+f"(d[25]), "+f"(d[26]), "+f"(d[27]), "+f"(d[28]), "+f"(d[29]), "+f"(d[30]), "+f"(d[31])
        : "r"(a0), "r"(a1), "r"(a2), "r"(a3), "l"(db), "r"(scale_d));
}

__device__ __forceinline__ void wgmma_ss_n128_tb1(float (&d)[64], uint64_t da, uint64_t db, int scale_d) {
    asm volatile("{\n.reg .pred p;\nsetp.ne.b32 p, %66, 0;\n"
        "wgmma.mma_async.sync.aligned.m64n128k16.f32.bf16.bf16 {%0, %1, %2, %3, %4, %5, %6, %7, %8, %9, %10, %11, %12, %13, %14, %15, %16, %17, %18, %19, %20, %21, %22, %23, %24, %25, %26, %27, %28, %29, %30, %31, %32, %33, %34, %35, %36, %37, %38, %39, %40, %41, %42, %43, %44, %45, %46, %47, %48, %49, %50, %51, %52, %53, %54, %55, %56, %57, %58, %59, %60, %61, %62, %63}, %64, %65, p, 1, 1, 0, 1;\n}\n"
        : "+f"(d[0]), "+f"(d[1]), "+f"(d[2]), "+f"(d[3]), "+f"(d[4]), "+f"(d[5]), "+f"(d[6]), "+f"(d[7]), "+f"(d[8]), "+f"(d[9]), "+f"(d[10]), "+f"(d[11]), "+f"(d[12]), "+f"(d[13]), "+f"(d[14]), "+f"(d[15]), "+f"(d[16]), "+f"(d[17]), "+f"(d[18]), "+f"(d[19]), "+f"(d[20]), "+f"(d[21]), "+f"(d[22]), "+f"(d[23]), "+f"(d[24]), "+f"(d[25]), "+f"(d[26]), "+f"(d[27]), "+f"(d[28]), "+f"(d[29]), "+f"(d[30]), "+f"(d[31]), "+f"(d[32]), "+f"(d[33]), "+f"(d[34]), "+f"(d[35]), "+f"(d[36]), "+f"(d[37]), "+f"(d[38]), "+f"(d[39]), "+f"(d[40]), "+f"(d[41]), "+f"(d[42]), "+f"(d[43]), "+f"(d[44]), "+f"(d[45]), "+f"(d[46]), "+f"(d[47]), "+f"(d[48]), "+f"(d[49]), "+f"(d[50]), "+f"(d[51]), "+f"(d[52]), "+f"(d[53]), "+f"(d[54]), "+f"(d[55]), "+f"(d[56]), "+f"(d[57]), "+f"(d[58]), "+f"(d[59]), "+f"(d[60]), "+f"(d[61]), "+f"(d[62]), "+f"(d[63])
        : "l"(da), "l"(db), "r"(scale_d));
}

__device__ __forceinline__ void wgmma_ss_n256_tb1(float (&d)[128], uint64_t da, uint64_t db, int scale_d) {
    asm volatile("{\n.reg .pred p;\nsetp.ne.b32 p, %130, 0;\n"
        "wgmma.mma_async.sync.aligned.m64n256k16.f32.bf16.bf16 {%0, %1, %2, %3, %4, %5, %6, %7, %8, %9, %10, %11, %12, %13, %14, %15, %16, %17, %18, %19, %20, %21, %22, %23, %24, %25, %26, %27, %28, %29, %30, %31, %32, %33, %34, %35, %36, %37, %38, %39, %40, %41, %42, %43, %44, %45, %46, %47, %48, %49, %50, %51, %52, %53, %54, %55, %56, %57, %58, %59, %60, %61, %62, %63, %64, %65, %66, %67, %68, %69, %70, %71, %72, %73, %74, %75, %76, %77, %78, %79, %80, %81, %82, %83, %84, %85, %86, %87, %88, %89, %90, %91, %92, %93, %94, %95, %96, %97, %98, %99, %100, %101, %102, %103, %104, %105, %106, %107, %108, %109, %110, %111, %112, %113, %114, %115, %116, %117, %118, %119, %120, %121, %122, %123, %124, %125, %126, %127}, %128, %129, p, 1, 1, 0, 1;\n}\n"
        : "+f"(d[0]), "+f"(d[1]), "+f"(d[2]), "+f"(d[3]), "+f"(d[4]), "+f"(d[5]), "+f"(d[6]), "+f"(d[7]), "+f"(d[8]), "+f"(d[9]), "+f"(d[10]), "+f"(d[11]), "+f"(d[12]), "+f"(d[13]), "+f"(d[14]), "+f"(d[15]), "+f"(d[16]), "+f"(d[17]), "+f"(d[18]), "+f"(d[19]), "+f"(d[20]), "+f"(d[21]), "+f"(d[22]), "+f"(d[23]), "+f"(d[24]), "+f"(d[25]), "+f"(d[26]), "+f"(d[27]), "+f"(d[28]), "+f"(d[29]), "+f"(d[30]), "+f"(d[31]), "+f"(d[32]), "+f"(d[33]), "+f"(d[34]), "+f"(d[35]), "+f"(d[36]), "+f"(d[37]), "+f"(d[38]), "+f"(d[39]), "+f"(d[40]), "+f"(d[41]), "+f"(d[42]), "+f"(d[43]), "+f"(d[44]), "+f"(d[45]), "+f"(d[46]), "+f"(d[47]), "+f"(d[48]), "+f"(d[49]), "+f"(d[50]), "+f"(d[51]), "+f"(d[52]), "+f"(d[53]), "+f"(d[54]), "+f"(d[55]), "+f"(d[56]), "+f"(d[57]), "+f"(d[58]), "+f"(d[59]), "+f"(d[60]), "+f"(d[61]), "+f"(d[62]), "+f"(d[63]), "+f"(d[64]), "+f"(d[65]), "+f"(d[66]), "+f"(d[67]), "+f"(d[68]), "+f"(d[69]), "+f"(d[70]), "+f"(d[71]), "+f"(d[72]), "+f"(d[73]), "+f"(d[74]), "+f"(d[75]), "+f"(d[76]), "+f"(d[77]), "+f"(d[78]), "+f"(d[79]), "+f"(d[80]), "+f"(d[81]), "+f"(d[82]), "+f"(d[83]), "+f"(d[84]), "+f"(d[85]), "+f"(d[86]), "+f"(d[87]), "+f"(d[88]), "+f"(d[89]), "+f"(d[90]), "+f"(d[91]), "+f"(d[92]), "+f"(d[93]), "+f"(d[94]), "+f"(d[95]), "+f"(d[96]), "+f"(d[97]), "+f"(d[98]), "+f"(d[99]), "+f"(d[100]), "+f"(d[101]), "+f"(d[102]), "+f"(d[103]), "+f"(d[104]), "+f"(d[105]), "+f"(d[106]), "+f"(d[107]), "+f"(d[108]), "+f"(d[109]), "+f"(d[110]), "+f"(d[111]), "+f"(d[112]), "+f"(d[113]), "+f"(d[114]), "+f"(d[115]), "+f"(d[116]), "+f"(d[117]), "+f"(d[118]), "+f"(d[119]), "+f"(d[120]), "+f"(d[121]), "+f"(d[122]), "+f"(d[123]), "+f"(d[124]), "+f"(d[125]), "+f"(d[126]), "+f"(d[127])
        : "l"(da), "l"(db), "r"(scale_d));
}

__device__ __forceinline__ void wgmma_ss_n32_tb0(float (&d)[16], uint64_t da, uint64_t db, int scale_d) {
    asm volatile("{\n.reg .pred p;\nsetp.ne.b32 p, %18, 0;\n"
        "wgmma.mma_async.sync.aligned.m64n32k16.f32.bf16.bf16 {%0, %1, %2, %3, %4, %5, %6, %7, %8, %9, %10, %11, %12, %13, %14, %15}, %16, %17, p, 1, 1, 0, 0;\n}\n"
        : "+f"(d[0]), "+f"(d[1]), "+f"(d[2]), "+f"(d[3]), "+f"(d[4]), "+f"(d[5]), "+f"(d[6]), "+f"(d[7]), "+f"(d[8]), "+f"(d[9]), "+f"(d[10]), "+f"(d[11]), "+f"(d[12]), "+f"(d[13]), "+f"(d[14]), "+f"(d[15])
        : "l"(da), "l"(db), "r"(scale_d));
}

__device__ __forceinline__ void wgmma_ss_n64_tb0(float (&d)[32], uint64_t da, uint64_t db, int scale_d) {
    asm volatile("{\n.reg .pred p;\nsetp.ne.b32 p, %34, 0;\n"
        "wgmma.mma_async.sync.aligned.m64n64k16.f32.bf16.bf16 {%0, %1, %2, %3, %4, %5, %6, %7, %8, %9, %10, %11, %12, %13, %14, %15, %16, %17, %18, %19, %20, %21, %22, %23, %24, %25, %26, %27, %28, %29, %30, %31}, %32, %33, p, 1, 1, 0, 0;\n}\n"
        : "+f"(d[0]), "+f"(d[1]), "+f"(d[2]), "+f"(d[3]), "+f"(d[4]), "+f"(d[5]), "+f"(d[6]), "+f"(d[7]), "+f"(d[8]), "+f"(d[9]), "+f"(d[10]), "+f"(d[11]), "+f"(d[12]), "+f"(d[13]), "+f"(d[14]), "+f"(d[15]), "+f"(d[16]), "+f"(d[17]), "+f"(d[18]), "+f"(d[19]), "+f"(d[20]), "+f"(d[21]), "+f"(d[22]), "+f"(d[23]), "+f"(d[24]), "+f"(d[25]), "+f"(d[26]), "+f"(d[27]), "+f"(d[28]), "+f"(d[29]), "+f"(d[30]), "+f"(d[31])
        : "l"(da), "l"(db), "r"(scale_d));
}

struct Maps {
    CUtensorMap xa, xa2, xas, xh, wup4, wup8, mqa2, mqa4, mqb1, mqb2, wepi, uc, x, out, wq, wk, fa[3], fb[2], fc[2];
};

__device__ __forceinline__ uint64_t mkd(uint32_t lo) {
    uint64_t d;
    asm("mov.b64 %0, {%1, %2};" : "=l"(d) : "r"(lo), "r"((1024u >> 4) | (1u << 30)));
    return d;
}
__device__ __forceinline__ void ring_ld(uint32_t sb, uint32_t barbase, uint32_t slot8, const CUtensorMap* tm, int c1, int c2) {
    mbar_expect_tx(sb + barbase + slot8, 8192);
    tma3(sb + R1 + slot8 * 1024, tm, 0, c1, c2, sb + barbase + slot8);
}

__device__ __forceinline__ void ring_half(uint32_t sb, uint32_t slot8, uint32_t hoff, const CUtensorMap* tm, int c1, int c2) {
    mbar_expect_tx(sb + B_R1 + slot8, 8192);
    tma3(sb + R1 + slot8 * 2048 + hoff, tm, 0, c1, c2, sb + B_R1 + slot8);
}
__device__ __forceinline__ void ring_full(uint32_t sb, uint32_t slot8, const CUtensorMap* tm, int c1, int c2) {
    mbar_expect_tx(sb + B_R1 + slot8, 16384);
    mbar_arrive(sb + B_R1 + slot8);
    tma3(sb + R1 + slot8 * 2048, tm, 0, c1, c2, sb + B_R1 + slot8);
}
__device__ __forceinline__ void cta_done(int mode) {
    if (mode == 0 && atomicAdd(&g_sync[4], 1) == NCTA + 1) {
#pragma unroll
        for (int i = 0; i < 5; i++) g_sync[i] = 0;
    }
}

__device__ __forceinline__ void fold_cta(const Maps& mp, uint32_t sb, int mode) {
    constexpr uint32_t F_FULL = MISC, F_EMPTY = MISC + 32, F_T1 = MISC + 64, STG = 49152, FOUT = 3 * STG;
    const int tid = threadIdx.x, f = blockIdx.x - NCTA;
    if (mode == 2) return;
    if (tid == 0) {
        for (int i = 0; i < 3; i++) { mbar_init(sb + F_FULL + 8 * i, 1); mbar_init(sb + F_EMPTY + 8 * i, 2); }
        mbar_init(sb + F_T1, 2);
        asm volatile("fence.mbarrier_init.release.cluster;" ::: "memory");
        fence_async();
    }
    __syncthreads();
    const int wg = __shfl_sync(0xffffffffu, tid >> 7, 0);
    int st = 0, ph = 0;
    if (wg == 0) {
        if (tid == 0) {
#pragma unroll 1
            for (int it = 0; it < 96; it++) {
                const int p = it >> 3, kc = it & 7, job = p >> 2;
                if (it == 64) mbar_wait(sb + F_T1, 0);
                mbar_wait(sb + F_EMPTY + 8 * st, ph ^ 1);
                mbar_expect_tx(sb + F_FULL + 8 * st, STG);
                tma3(sb + st * STG, &mp.fa[job], 0, 256 * f + 128 * ((p >> 1) & 1), kc, sb + F_FULL + 8 * st);
                tma3(sb + st * STG + 16384, &mp.fb[job != 0], 0, 64 * kc + (job == 1 ? 512 : 0), 4 * (p & 1), sb + F_FULL + 8 * st);
                if (++st == 3) { st = 0; ph ^= 1; }
            }
        }
        return;
    }
    const int h = wg - 1, lane = tid & 31, w = (tid >> 5) & 3;
    const uint32_t sd = (sb & 0x3FFFF) >> 4;
    const bool el = (tid & 127) == 0;
#pragma unroll 1
    for (int p = 0; p < 12; p++) {
        float acc[128];
        fresh(acc);
#pragma unroll 1
        for (int kc = 0; kc < 8; kc++) {
            mbar_wait(sb + F_FULL + 8 * st, ph);
            wg_fence();
#pragma unroll
            for (int kk = 0; kk < 4; kk++)
                wgmma_ss_n256_tb1(acc, dsc(sd, st * STG + h * 8192 + kk * 32, 16), dsc(sd, st * STG + 16384 + kk * 2048, 8192), 1);
            wg_commit();
            wg_wait<0>();
            if (el) mbar_arrive(sb + F_EMPTY + 8 * st);
            if (++st == 3) { st = 0; ph ^= 1; }
        }
        pin(acc);
        const int job = p >> 2;
        if (el) {
            asm volatile("cp.async.bulk.wait_group 0;" ::: "memory");
            if (p == 4) { fence_async_g(); mbar_arrive(sb + F_T1); }
        }
        bar_sync(3 + h, 128);
        uint32_t r = 16 * w + (lane & 7) + ((lane >> 3) & 1) * 8;
        const float fs = job == 1 ? 0.5f : 1.f;
        if (job == 1) r = (r & ~31) | (((r >> 1) & 3) << 3) | (((r >> 3) & 3) << 1) | (r & 1);
        const uint32_t oa = sb + FOUT + h * 32768 + r * 128 + ((((lane >> 4) ^ r) & 7) << 4);
#pragma unroll
        for (int i = 0; i < 16; i++)
            stsm4((oa ^ ((i & 3) << 5)) + (i >> 2) * 8192, pack2(acc[8 * i] * fs, acc[8 * i + 1] * fs), pack2(acc[8 * i + 2] * fs, acc[8 * i + 3] * fs),
                  pack2(acc[8 * i + 4] * fs, acc[8 * i + 5] * fs), pack2(acc[8 * i + 6] * fs, acc[8 * i + 7] * fs));
        fence_async();
        bar_sync(3 + h, 128);
        if (el) {
            tma3_store(&mp.fc[job != 0], sb + FOUT + h * 32768, 0, 256 * f + 128 * ((p >> 1) & 1) + 64 * h + (job == 1 ? 512 : 0), 4 * (p & 1));
            asm volatile("cp.async.bulk.commit_group;" ::: "memory");
        }
    }
    if (el) {
        asm volatile("cp.async.bulk.wait_group 0;" ::: "memory");
        fence_async_g();
        if (mode == 0) flag_add(&g_sync[3]);
    }
    bar_sync(2, 256);
    if (tid == 128) cta_done(mode);
}

__global__ void __launch_bounds__(384, 1) main_kernel(const __grid_constant__ Maps mp, const bf16* __restrict__ dw, const bf16* wup, const int mode) {
    extern __shared__ __align__(1024) uint8_t smem[];
    const uint32_t sb = smem_u32(smem);
    const int tid = threadIdx.x;
    if (blockIdx.x >= NCTA) { fold_cta(mp, sb, mode); return; }
    const int b = blockIdx.x / TPB, ti = blockIdx.x % TPB;
    const int piece = blockIdx.x & 127;
    if (tid == 0) {
        mbar_init(sb + B_A, 1); mbar_init(sb + B_A2, 1); mbar_init(sb + B_MK, 1);
        for (int i = 0; i < 5; i++) mbar_init(sb + B_R1 + 8 * i, 2);
        asm volatile("fence.mbarrier_init.release.cluster;" ::: "memory");
        fence_async();
        mbar_expect_tx(sb + B_MK, 65536 + 32768);
        tma3(sb + R0, &mp.wq, 0, 64 * (piece >> 4), 0, sb + B_MK);
        tma3(sb + R1 + 32768, &mp.wk, 0, 32 * (piece & 15), 0, sb + B_MK);
        mbar_expect_tx(sb + B_A, 32768);
        mbar_expect_tx(sb + B_A2, 32768 + 3072);
#pragma unroll 1
        for (int i = 0; i < 16; i++) tma4(sb + AT + (i & 7) * 8192 + (i >> 3) * 4096, &mp.xh, 0, 62 * ti - 1 + 32 * (i >> 3), i & 7, b, sb + (i < 8 ? B_A : B_A2));
        asm volatile("cp.async.bulk.shared::cluster.global.mbarrier::complete_tx::bytes [%0], [%1], 3072, [%2];" ::"r"(sb + DWS), "l"(dw), "r"(sb + B_A2) : "memory");
        for (int i = 0; i < 8; i++) mbar_arrive(sb + B_R1 + 8 * (i >> 1));
        if (mode != 1) {
            ring_full(sb, 32, &mp.wup8, 0, 8);
            ring_full(sb, 0, &mp.wup8, 16, 8);
            ring_full(sb, 8, &mp.wup8, 32, 8);
        }
    } else if (tid == 32) {
        mbar_init(sb + B_LN, 1); mbar_init(sb + B_MQ, 1); mbar_init(sb + B_XA, 1);
        mbar_init(sb + B_H1, 2); mbar_init(sb + B_H2, 1); mbar_init(sb + B_H3, 2);
        for (int i = 0; i < 3; i++) { mbar_init(sb + B_KV + 8 * i, 1); mbar_init(sb + B_P + 8 * i, 4); mbar_init(sb + B_GO + 8 * i, 4); }
        for (int i = 0; i < 12; i++) mbar_init(sb + B_R2 + 8 * i, 1);
        mbar_init(sb + B_UC, 1); mbar_init(sb + B_X, 1);
        for (int i = 0; i < 4; i++) asm volatile("st.shared.u32 [%0], 0;" ::"r"(sb + CNT + 4 * i) : "memory");
        asm volatile("fence.mbarrier_init.release.cluster;" ::: "memory");
        fence_async();
    }
    __syncthreads();
    const int wg = __shfl_sync(0xffffffffu, tid >> 7, 0);
    const int lane = tid & 31, w = (tid >> 5) & 3;
    const bool w0 = __shfl_sync(0xffffffffu, w, 0) == 0;
    const uint32_t sd = (sb & 0x3FFFF) >> 4;
    const uint32_t adA = sd + (AT >> 4) + (1u << 16);
    const uint32_t bd0 = sd + (R1 >> 4);
    const uint32_t bd2k = bd0 + ((2048u >> 4) << 16);
    const bool el = (tid & 127) == 0;
    const uint32_t lrow = 16 * w + (lane & 7) + ((lane >> 3) & 1) * 8;
    const uint32_t loff = lrow * 128 + ((((lane >> 4) ^ lrow) & 7) << 4);
    const int r0 = 16 * w + (lane >> 2);

    if (wg == 0) {
        asm volatile("setmaxnreg.inc.sync.aligned.u32 184;");
        uint32_t q[112];
        PT(0);
        PG(200);
        {
            float mq[16];
            fresh(mq);
            mbar_wait(sb + B_MK, 0);
            PT(1);
            if (PFW && tid == 32) l2_prefetch((const char*)wup + piece * 8192, 8192);
            wg_fence();
#pragma unroll 1
            for (int c = 0; c < 8; c++)
#pragma unroll
                for (int kk = 0; kk < 4; kk++)
                    wgmma_ss_n32_tb0(mq, dsc(sd, R0 + c * 8192 + kk * 32, 16), dsc(sd, R1 + 32768 + c * 4096 + kk * 32, 16), 1);
            wg_commit();
            wg_wait<0>();
            if (mode != 1 && w0 && elect1()) { ring_full(sb, 16, &mp.wup8, 48, 8); ring_full(sb, 24, &mp.wup8, 64, 8); }
            pin(mq);
            uint32_t* c = reinterpret_cast<uint32_t*>(g_mqk + (64 * (piece >> 4) + r0) * D_ + 32 * (piece & 15) + 2 * (lane & 3));
#pragma unroll
            for (int n = 0; n < 4; n++) { c[4 * n] = pack2(mq[4 * n], mq[4 * n + 1]); c[4 * n + 4 * D_] = pack2(mq[4 * n + 2], mq[4 * n + 3]); }
            fence_async_g();
            bar_sync(1, 128);
            if (el) {
                if (mode == 0) flag_add(&g_sync[2]);
                if (mode == 0) flag_wait(&g_sync[2], NCTA);
                mbar_arrive(sb + B_MQ);
                PT(12);
                mbar_wait(sb + B_LN, 0);
#pragma unroll 1
                for (int c = 0; c < 8; c++) {
                    tma4_store(&mp.xas, sb + AT + c * 8192, 0, 62 * ti, c, b);
                    const unsigned t0 = (unsigned)clock();
                    while (c < 7 && (unsigned)clock() - t0 < XS_GAP) __nanosleep(20);
                }
                asm volatile("cp.async.bulk.commit_group;" ::: "memory");
                if (mode == 1) asm volatile("cp.async.bulk.wait_group 0;" ::: "memory");
            }
            PT(13);
            if (mode == 1) return;
        }
        mbar_wait(sb + B_H1, 0);
        PT(2);
        uint32_t slot8 = 8, par = 1, prev8 = 0;
        auto adv = [&]() { prev8 = slot8; slot8 += 8; if (slot8 == 40) { slot8 = 0; par ^= 1; } };
        {
            float acc[128];
            fresh(acc);
            auto step = [&](int i) {
                const uint32_t aa = adA + (i >> 1) * 512 + (i & 1) * 4, bb = bd0 + ((4096u >> 4) << 16) + slot8 * 128;
                wg_fence();
                wgmma_ss_n256_tb1(acc, mkd(aa), mkd(bb), 1);
                wgmma_ss_n256_tb1(acc, mkd(aa + 2), mkd(bb + 128), 1);
                wg_commit();
                wg_wait<1>();
            };
#pragma unroll 1
            for (int i = 0; i < 12; i++) {
                mbar_wait(sb + B_R1 + slot8, par);
                step(i);
                if (i > 0 && w0 && elect1()) ring_full(sb, prev8, &mp.mqa4, 32 * i + 128, 4);
                adv();
            }
#pragma unroll 1
            for (int i = 12; i < 16; i++) {
                mbar_wait(sb + B_R1 + slot8, par);
                if (i == 15 && el) mbar_arrive(sb + B_H2);
                step(i);
                if (w0 && elect1()) ring_full(sb, prev8, &mp.wup8, 16 * i - 192, 0);
                adv();
            }
            wg_wait<0>();
            if (w0 && elect1()) ring_full(sb, prev8, &mp.wup8, 64, 0);
            pin(acc);
            PT(3);
#pragma unroll
            for (int kk = 0; kk < 4; kk++)
                stsm4((sb + QS + loff) ^ (kk << 5), pack2(acc[96 + 8 * kk], acc[97 + 8 * kk]), pack2(acc[98 + 8 * kk], acc[99 + 8 * kk]),
                      pack2(acc[100 + 8 * kk], acc[101 + 8 * kk]), pack2(acc[102 + 8 * kk], acc[103 + 8 * kk]));
            fence_async();
#pragma unroll
            for (int i = 47; i >= 0; i--) q[64 + i] = pack2v(acc[2 * i], acc[2 * i + 1]);
        }
        if (el) {
            asm volatile("cp.async.bulk.wait_group 0;" ::: "memory");
            if (mode == 0) {
                fence_async_g();
                flag_add(&g_sync[b]);
                flag_wait(&g_sync[b], TPB);
            }
            mbar_arrive(sb + B_XA);
        }
        __syncwarp();
        mbar_wait(sb + B_H3, 0);
        PT(4);
        slot8 = 32; par = 0;
#pragma unroll
        for (int half = 0; half < 2; half++) {
            float acc[64];
            fresh(acc);
            auto step = [&](int m) {
                const uint32_t aa = adA + m * 512, bb = bd0 + ((8192u >> 4) << 16) + slot8 * 128;
                mbar_wait(sb + B_R1 + slot8, par);
                wg_fence();
#pragma unroll
                for (int kk = 0; kk < 4; kk++) wgmma_ss_n128_tb1(acc, mkd(aa + 2 * kk), mkd(bb + 128 * kk), 1);
                wg_commit();
                wg_wait<1>();
            };
            if (half == 0) {
#pragma unroll 1
                for (int m = 0; m < 8; m++) {
                    step(m);
                    if (m > 0 && w0 && elect1()) ring_full(sb, prev8, &mp.mqb2, (64 * m + 256) & 511, (m + 4) >> 3 << 1);
                    adv();
                }
            } else {
#pragma unroll 1
                for (int m = 0; m < 4; m++) {
                    step(m);
                    if (m > 0 && w0 && elect1()) ring_full(sb, prev8, &mp.mqb2, 64 * m + 256, 2);
                    adv();
                }
#pragma unroll 1
                for (int m = 4; m < 8; m++) {
                    step(m);
                    if (w0 && elect1()) {
                        if (m == 4) mbar_expect_tx(sb + B_KV + 8, 65536);
                        tma4(sb + R1 + prev8 * 2048, &mp.xa2, 0, 0, 2 * m - 8, b, sb + B_KV + 8);
                    }
                    adv();
                }
            }
            wg_wait<0>();
            if (w0 && elect1()) {
                if (half == 0) ring_full(sb, prev8, &mp.mqb2, 256, 2);
                else {
                    mbar_expect_tx(sb + B_KV + 16, 65536);
                    tma4(sb + R2, &mp.xa, 0, 64, 0, b, sb + B_KV + 16);
                }
            }
            pin(acc);
#pragma unroll
            for (int i = 31; i >= 0; i--) q[32 * half + i] = pack2v(acc[2 * i], acc[2 * i + 1]);
        }
        bar_sync(1, 128);
        PT(5);

        const float CS = 0.04419417382415922f * 1.4426950408889634f;
        float m0 = -INFINITY, m1 = -INFINITY, l0 = 0.f, l1 = 0.f;
        int s = 0, sn = 1, ph = 0;
        float S[32];
        const bool l0w = lane == 0, q0 = (lane & 3) == 0;
#pragma unroll 1
        for (int j = -1;; j++) {
            if (j >= 0) {
                PL(j, 1);
                if (j == NKV - 1) {
#pragma unroll
                    for (int i = (T_ - 64 * (NKV - 1)) / 2; i < 32; i++) asm volatile("mov.b32 %0, 0xff800000;" : "=f"(S[i]));
                }
                float y[8], z[8];
#pragma unroll
                for (int n = 0; n < 8; n++) { y[n] = fmaxf(S[4 * n], S[4 * n + 1]); z[n] = fmaxf(S[4 * n + 2], S[4 * n + 3]); }
#pragma unroll
                for (int n = 0; n < 4; n++) { y[n] = fmaxf(y[n], y[n + 4]); z[n] = fmaxf(z[n], z[n + 4]); }
                float x0 = fmaxf(fmaxf(y[0], y[1]), fmaxf(fmaxf(y[2], y[3]), m0)), x1 = fmaxf(fmaxf(z[0], z[1]), fmaxf(fmaxf(z[2], z[3]), m1));
                x0 = fmaxf(x0, __shfl_xor_sync(0xffffffffu, x0, 1));
                x1 = fmaxf(x1, __shfl_xor_sync(0xffffffffu, x1, 1));
                x0 = fmaxf(x0, __shfl_xor_sync(0xffffffffu, x0, 2));
                x1 = fmaxf(x1, __shfl_xor_sync(0xffffffffu, x1, 2));
                const float sc0 = ex2((m0 - x0) * CS), sc1 = ex2((m1 - x1) * CS);
                m0 = x0; m1 = x1;
                const float n0 = -x0 * CS, n1 = -x1 * CS;
                if (q0) { sts_f32(sb + SCL + s * 256 + r0 * 4, sc0); sts_f32(sb + SCL + s * 256 + r0 * 4 + 32, sc1); }
                __syncwarp();
                if (l0w) mbar_arrive(sb + B_P + s * 8);
                if (j < NKV - 1) mbar_wait(sb + B_KV + sn * 8, ph);
                float a0 = 0.f, a1 = 0.f;
                const uint32_t pb = sb + R3 + (s == 0 ? 2 : s - 1) * 8192;
#pragma unroll
                for (int kk = 0; kk < 4; kk++) {
                    float p[8];
#pragma unroll
                    for (int e = 0; e < 8; e++) p[e] = ex2(fmaf(S[8 * kk + e], CS, (e & 2) ? n1 : n0));
                    a0 += (p[0] + p[1]) + (p[4] + p[5]);
                    a1 += (p[2] + p[3]) + (p[6] + p[7]);
                    stsm4((pb + loff) ^ (kk << 5), pack2(p[0], p[1]), pack2(p[2], p[3]), pack2(p[4], p[5]), pack2(p[6], p[7]));
                }
                l0 = fmaf(l0, sc0, a0); l1 = fmaf(l1, sc1, a1);
                PL(j, 2);
                if (j == NKV - 1) break;
            } else {
                mbar_wait(sb + B_KV + 8, 0);
            }
            float Sn[32];
            const uint32_t kd = sd + sn * 4096;
            wg_fence();
#pragma unroll
            for (int kk = 0; kk < 28; kk++) {
                wgmma_rs_n64_tb0(Sn, q[4 * kk], q[4 * kk + 1], q[4 * kk + 2], q[4 * kk + 3], dsc(kd, (kk >> 2) * 8192 + (kk & 3) * 32, 16), kk > 0);
                if (kk == FENCE_AT) { fence_async(); __syncwarp(); }
                if (kk == GO_AT) { PL(j, 3); if (j >= 0 && l0w) mbar_arrive(sb + B_GO + s * 8); }
            }
#pragma unroll
            for (int kk = 0; kk < 4; kk++)
                wgmma_ss_n64_tb0(Sn, dsc(sd, QS + kk * 32, 16), dsc(kd, 7 * 8192 + kk * 32, 16), 1);
            wg_commit();
            PL(j, 0);
            wg_wait<0>();
            pin(Sn);
#pragma unroll
            for (int i = 0; i < 32; i++) S[i] = Sn[i];
            s = sn;
            if (++sn == 3) sn = 0;
            if (sn == 1) ph ^= 1;
        }
        l0 += __shfl_xor_sync(0xffffffffu, l0, 1); l1 += __shfl_xor_sync(0xffffffffu, l1, 1);
        l0 += __shfl_xor_sync(0xffffffffu, l0, 2); l1 += __shfl_xor_sync(0xffffffffu, l1, 2);
        if (q0) { sts_f32(sb + LINV + r0 * 4, rcp(l0)); sts_f32(sb + LINV + r0 * 4 + 32, rcp(l1)); }
        fence_async();
        __syncwarp();
        if (l0w) mbar_arrive(sb + B_GO + s * 8);
        PDUMP();
    } else {
        asm volatile("setmaxnreg.dec.sync.aligned.u32 160;");
        const int h = wg - 1;
        auto red4 = [&](float (&a)[4]) {
            const bool b4 = lane & 16, b3 = lane & 8;
            const float k0 = (b4 ? a[2] : a[0]) + __shfl_xor_sync(0xffffffffu, b4 ? a[0] : a[2], 16);
            const float k1 = (b4 ? a[3] : a[1]) + __shfl_xor_sync(0xffffffffu, b4 ? a[1] : a[3], 16);
            float k = (b3 ? k1 : k0) + __shfl_xor_sync(0xffffffffu, b3 ? k0 : k1, 8);
            k += __shfl_xor_sync(0xffffffffu, k, 4);
            k += __shfl_xor_sync(0xffffffffu, k, 2);
            k += __shfl_xor_sync(0xffffffffu, k, 1);
            return k;
        };
#pragma unroll 1
        for (int bt = 0; bt < 2; bt++) {
            mbar_wait(sb + (bt ? B_A2 : B_A), 0);
            PT(bt ? 13 : 0);
            uint32_t v[4][8];
            float a[4], f[4][16];
            const uint32_t la = sb + AT + (lane >> 3) * 8192 + (32 * bt + 16 * h + 4 * w) * 128 + (((lane & 7) ^ ((w & 1) * 4)) << 4);
#pragma unroll
            for (int r = 0; r < 4; r++) { lds4((la ^ (r << 4)) + r * 128, v[r]); lds4((la ^ (r << 4)) + r * 128 + 32768, v[r] + 4); }
#pragma unroll
            for (int r = 0; r < 4; r++) {
                float s0 = blo(v[r][0]), s1 = bhi(v[r][0]);
#pragma unroll
                for (int i = 1; i < 8; i++) { s0 += blo(v[r][i]); s1 += bhi(v[r][i]); }
                a[r] = s0 + s1;
            }
            const float mu = red4(a) * (1.f / D_);
            const uint32_t mp2 = pack2(mu, mu);
#pragma unroll
            for (int r = 0; r < 4; r++) {
                const uint32_t m2 = __shfl_sync(0xffffffffu, mp2, 8 * r);
                float s0 = 0.f, s1 = 0.f;
#pragma unroll
                for (int i = 0; i < 8; i++) {
                    const uint32_t d = bsub2(v[r][i], m2);
                    f[r][2 * i] = blo(d); f[r][2 * i + 1] = bhi(d);
                    s0 = fmaf(f[r][2 * i], f[r][2 * i], s0); s1 = fmaf(f[r][2 * i + 1], f[r][2 * i + 1], s1);
                }
                a[r] = s0 + s1;
            }
            const float dm = mu - blo(mp2);
            float sd_ = bfr(bfr(fmaxf(fmaf(red4(a), 1.f / D_, -dm * dm), 0.f)) + 1e-5f);
            asm("sqrt.approx.f32 %0, %0;" : "+f"(sd_));
            const float ri = rcp(bfr(sd_));
#pragma unroll
            for (int r = 0; r < 4; r++) {
                const float rinv = __shfl_sync(0xffffffffu, ri, 8 * r);
#pragma unroll
                for (int i = 0; i < 8; i++) v[r][i] = pack2(f[r][2 * i] * rinv, f[r][2 * i + 1] * rinv);
                sts4((la ^ (r << 4)) + r * 128, v[r][0], v[r][1], v[r][2], v[r][3]);
                sts4((la ^ (r << 4)) + r * 128 + 32768, v[r][4], v[r][5], v[r][6], v[r][7]);
            }
        }
        fence_async();
        bar_sync(2, 256);
        if (tid == 128) mbar_arrive(sb + B_LN);
        if (mode == 1) return;
        float acc[128];
#pragma unroll
        for (int pass = 0; pass < 2; pass++) {
            if (pass == 1) mbar_wait(sb + B_H2, 0);
            PT(1 + 3 * pass);
            fresh(acc);
            uint32_t slot8 = pass ? 16 : 32, par = 0, prev8 = 0;
            auto adv = [&]() { prev8 = slot8; slot8 += 8; if (slot8 == 40) { slot8 = 0; par ^= 1; } };
            auto step = [&](int kk) {
                wg_fence();
                wgmma_ss_n256_tb1(acc, mkd(adA + (kk >> 2) * 512 + (kk & 3) * 2), mkd(bd2k + h * 512 + slot8 * 128), 1);
                wg_commit();
                wg_wait<1>();
            };
#pragma unroll 1
            for (int kk = 0; kk < 28; kk++) {
                mbar_wait(sb + B_R1 + slot8, par);
                step(kk);
                if (kk > 0 && w0 && elect1()) ring_half(sb, prev8, h * 8192, &mp.wup4, 16 * kk + 64, (pass ? 0 : 8) + 4 * h);
                adv();
            }
            if (pass == 0 && w0) mbar_wait(sb + B_MQ, 0);
#pragma unroll 1
            for (int kk = 28; kk < 32; kk++) {
                mbar_wait(sb + B_R1 + slot8, par);
                if (kk == 31 && el) mbar_arrive(sb + (pass ? B_H3 : B_H1));
                step(kk);
                if (w0 && elect1()) ring_half(sb, prev8, h * 8192, pass ? &mp.mqb1 : &mp.mqa2, (pass ? 64 : 32) * (kk - 28), pass ? h : 4 + 2 * h);
                adv();
            }
            wg_wait<0>();
            if (w0 && elect1()) ring_half(sb, prev8, h * 8192, pass ? &mp.mqb1 : &mp.mqa2, pass ? 256 : 128, pass ? h : 4 + 2 * h);
            pin(acc);
            PT(2 + 3 * pass);
            if (pass == 0) {
                float s0 = 0.f, s1 = 0.f, v0 = 0.f, v1 = 0.f;
#pragma unroll
                for (int n = 0; n < 32; n++) {
#pragma unroll
                    for (int e = 0; e < 4; e++) acc[4 * n + e] = gelu2(acc[4 * n + e]);
                    s0 += acc[4 * n] + acc[4 * n + 1]; s1 += acc[4 * n + 2] + acc[4 * n + 3];
                    v0 = fmaf(acc[4 * n], acc[4 * n], v0); v0 = fmaf(acc[4 * n + 1], acc[4 * n + 1], v0);
                    v1 = fmaf(acc[4 * n + 2], acc[4 * n + 2], v1); v1 = fmaf(acc[4 * n + 3], acc[4 * n + 3], v1);
                }
#pragma unroll
                for (int o = 1; o < 4; o <<= 1) {
                    s0 += __shfl_xor_sync(0xffffffffu, s0, o); s1 += __shfl_xor_sync(0xffffffffu, s1, o);
                    v0 += __shfl_xor_sync(0xffffffffu, v0, o); v1 += __shfl_xor_sync(0xffffffffu, v1, o);
                }
                if ((lane & 3) == 0) {
                    uint32_t a = sb + STAT + h * 512 + r0 * 8;
                    sts_f32(a, s0); sts_f32(a + 4, v0); sts_f32(a + 64, s1); sts_f32(a + 68, v1);
                }
                bar_sync(2, 256);
                {
                    uint32_t a = sb + STAT + (h ^ 1) * 512 + r0 * 8;
                    s0 = (s0 + lds_f32(a)) * (1.f / 512.f); v0 = (v0 + lds_f32(a + 4)) * (1.f / 512.f);
                    s1 = (s1 + lds_f32(a + 64)) * (1.f / 512.f); v1 = (v1 + lds_f32(a + 68)) * (1.f / 512.f);
                }
                v0 = rsqrtf(fmaxf(fmaf(-s0, s0, v0), 0.f) + 4e-5f); v1 = rsqrtf(fmaxf(fmaf(-s1, s1, v1), 0.f) + 4e-5f);
                s0 = -s0 * v0; s1 = -s1 * v1;
#pragma unroll
                for (int p = 0; p < 16; p++)
                    stsm4(((sb + R0 + h * 32768 + loff) ^ ((p & 3) << 5)) + (p >> 2) * 8192,
                          pack2(fmaf(acc[8 * p], v0, s0), fmaf(acc[8 * p + 1], v0, s0)), pack2(fmaf(acc[8 * p + 2], v1, s1), fmaf(acc[8 * p + 3], v1, s1)),
                          pack2(fmaf(acc[8 * p + 4], v0, s0), fmaf(acc[8 * p + 5], v0, s0)), pack2(fmaf(acc[8 * p + 6], v1, s1), fmaf(acc[8 * p + 7], v1, s1)));
            } else {
                uint32_t u[64];
#pragma unroll
                for (int i = 63; i >= 0; i--) u[i] = pack2v(gelu2(acc[2 * i]), gelu2(acc[2 * i + 1]));
                PT(12);
                bar_sync(3 + h, 128);
                const uint32_t rm = lrow == 0 ? 0 : lrow - 1, rp = lrow == 63 ? 63 : lrow + 1;
                const uint32_t gb = sb + R0 + h * 32768;
                const uint32_t am = gb + rm * 128 + ((((lane >> 4) ^ rm) & 7) << 4), ap = gb + rp * 128 + ((((lane >> 4) ^ rp) & 7) << 4), ac = gb + loff;
                const uint32_t dwa = sb + DWS + 512 * h + ((lane >> 3) & 1) * 16 + (lane >> 4) * 1024;
                bf16* ucp = g_uc + ((size_t)blockIdx.x * 64 + r0) * D_ + 256 * h + 8 * (lane & 3);
#pragma unroll
                for (int m = 0; m < 8; m++) {
                    uint32_t o[8], g0[2][4], g1[2][4], g2[2][4], d[2][4], d2[2][2];
#pragma unroll
                    for (int pp = 0; pp < 2; pp++) {
                        const int p = 2 * m + pp;
                        const uint32_t co = (p >> 2) * 8192, cx = (p & 3) << 5;
                        ldsm4(dwa + 32 * p, d[pp]);
                        ldsm2(dwa + 32 * p + 2048, d2[pp]);
                        ldsm4((am ^ cx) + co, g0[pp]);
                        ldsm4((ac ^ cx) + co, g1[pp]);
                        ldsm4((ap ^ cx) + co, g2[pp]);
                    }
#pragma unroll
                    for (int pp = 0; pp < 2; pp++)
#pragma unroll
                        for (int e = 0; e < 4; e++)
                            o[4 * (e & 1) + 2 * pp + (e >> 1)] =
                                bmul2(u[8 * m + 4 * pp + e], bfma2(g2[pp][e], d2[pp][e >> 1], bfma2(g1[pp][e], d[pp][2 + (e >> 1)], bmul2(g0[pp][e], d[pp][e >> 1]))));
                    stg4(ucp + 32 * m, o[0], o[1], o[2], o[3]);
                    stg4(ucp + 32 * m + 8 * D_, o[4], o[5], o[6], o[7]);
                }
                bar_sync(2, 256);
                if (tid == 128) {
                    mbar_wait(sb + B_XA, 0);
                    mbar_expect_tx(sb + B_KV, 65536);
                    tma4(sb + R0, &mp.xa, 0, 128, 0, b, sb + B_KV);
                }
            }
            PT(3 + 3 * pass);
        }
        int s = 1, ph = 0;
        fresh(acc);
#pragma unroll 1
        for (int j = 0; j < NKV; j++) {
            mbar_wait(sb + B_P + s * 8, ph);
            PL(j, 0);
            if (j > 0) {
                const float sc0 = lds_f32(sb + SCL + s * 256 + r0 * 4), sc1 = lds_f32(sb + SCL + s * 256 + r0 * 4 + 32);
                if (__any_sync(0xffffffffu, sc0 != 1.f || sc1 != 1.f)) {
#pragma unroll
                    for (int n = 0; n < 32; n++) { acc[4 * n] *= sc0; acc[4 * n + 1] *= sc0; acc[4 * n + 2] *= sc1; acc[4 * n + 3] *= sc1; }
                }
            }
            mbar_wait(sb + B_GO + s * 8, ph);
            PL(j, 1);
            const uint32_t vd = sd + s * 4096 + h * 2048, pd = sd + (s == 0 ? 2 : s - 1) * 512;
            pin(acc);
            wg_fence();
#pragma unroll
            for (int kk = 0; kk < 4; kk++) wgmma_ss_n256_tb1(acc, dsc(pd, R3 + kk * 32, 16), dsc(vd, kk * 2048, 8192), 1);
            wg_commit();
            wg_wait<0>();
            pin(acc);
            PL(j, 2);
            if (w0 && elect1()) {
                if (j == NKV - 5 && mode == 0) flag_wait(&g_sync[3], 4);
                if (atom_inc_s(sb + CNT + 4 * s) & 1) {
                    if (j + 3 < NKV) {
                        mbar_expect_tx(sb + B_KV + s * 8, 65536);
                        tma4(sb + s * 65536, &mp.xa, 0, 64 * (j + 3), 0, b, sb + B_KV + s * 8);
                    } else if (j < NKV - 1) {
                        const int n0 = j == NKV - 3 ? 0 : 8, n1 = j == NKV - 3 ? 8 : 12;
#pragma unroll 1
                        for (int n = n0; n < n1; n++) ring_ld(sb, B_R2, n * 8, &mp.wepi, 16 * (n >> 1), 4 * (n & 1));
                    }
                }
            }
            if (++s == 3) s = 0;
            if (s == 1) ph ^= 1;
        }
        {
            const float i0 = lds_f32(sb + LINV + r0 * 4), i1 = lds_f32(sb + LINV + r0 * 4 + 32);
#pragma unroll
            for (int p = 0; p < 16; p++)
                stsm4(((sb + R0 + h * 32768 + loff) ^ ((p & 3) << 5)) + (p >> 2) * 8192,
                      pack2(acc[8 * p] * i0, acc[8 * p + 1] * i0), pack2(acc[8 * p + 2] * i1, acc[8 * p + 3] * i1),
                      pack2(acc[8 * p + 4] * i0, acc[8 * p + 5] * i0), pack2(acc[8 * p + 6] * i1, acc[8 * p + 7] * i1));
        }
        fence_async();
        fence_async_g();
        bar_sync(2, 256);
        if (tid == 128) {
            mbar_expect_tx(sb + B_UC, 65536);
            tma3(sb + UCT, &mp.uc, 0, 64 * blockIdx.x, 0, sb + B_UC);
        }
        PT(7);
        fresh(acc);
        {
            uint32_t slot8 = 8 * h, par = 0, prev8 = 0;
#pragma unroll 1
            for (int kk = 0; kk < 64; kk++) {
                if (kk == 32) mbar_wait(sb + B_UC, 0);
                mbar_wait(sb + B_R2 + slot8, par);
                wg_fence();
                wgmma_ss_n256_tb1(acc, mkd(sd + (1u << 16) + (kk < 32 ? (R0 >> 4) : (UCT >> 4) - 4096) + (kk >> 2) * 512 + (kk & 3) * 2), mkd(bd2k + slot8 * 64), 1);
                wg_commit();
                wg_wait<1>();
                if (kk > 0 && w0 && elect1()) {
                    if (kk < 59) ring_ld(sb, B_R2, prev8, &mp.wepi, 16 * (kk + 5), 4 * h);
                    if (kk == 32 && (atom_inc_s(sb + CNT + 12) & 1)) {
                        mbar_expect_tx(sb + B_X, 65536);
                        tma4(sb + R0, &mp.x, 0, 62 * ti, 0, b, sb + B_X);
                    }
                }
                prev8 = slot8;
                slot8 += 16;
                if (slot8 >= 96) { slot8 -= 96; par ^= 1; }
            }
        }
        wg_wait<0>();
        pin(acc);
        PT(8);
        mbar_wait(sb + B_X, 0);
        PT(9);
        {
            const uint32_t sr = (lrow + 63) & 63;
            const uint32_t xoff = sr * 128 + ((((lane >> 4) ^ sr) & 7) << 4);
#pragma unroll
            for (int p = 0; p < 16; p++) {
                const uint32_t a = ((sb + R0 + h * 32768 + xoff) ^ ((p & 3) << 5)) + (p >> 2) * 8192;
                uint32_t xv[4];
                ldsm4(a, xv);
#pragma unroll
                for (int e = 0; e < 4; e++)
                    xv[e] = pack2(acc[8 * p + 2 * e] + __uint_as_float(xv[e] << 16), acc[8 * p + 2 * e + 1] + __uint_as_float(xv[e] & 0xffff0000u));
                stsm4(a, xv[0], xv[1], xv[2], xv[3]);
            }
        }
        fence_async();
        bar_sync(3 + h, 128);
        if (el) {
            for (int c = 0; c < 4; c++) tma4_store(&mp.out, sb + R0 + (4 * h + c) * 8192, 0, 62 * ti, 4 * h + c, b);
            asm volatile("cp.async.bulk.commit_group;" ::: "memory");
            PT(10);
            if (h == 0) cta_done(mode);
            asm volatile("cp.async.bulk.wait_group.read 0;" ::: "memory");
        }
        PT(11);
        PG(201);
        PDUMP();
    }
}

typedef CUresult (*PFN_enc)(CUtensorMap*, CUtensorMapDataType, cuuint32_t, void*, const cuuint64_t*, const cuuint64_t*,
                            const cuuint32_t*, const cuuint32_t*, CUtensorMapInterleave, CUtensorMapSwizzle,
                            CUtensorMapL2promotion, CUtensorMapFloatOOBfill);

static void enc(PFN_enc f, CUtensorMap* m, void* base, int rank, const cuuint64_t* dims, const cuuint64_t* strides, const cuuint32_t* box) {
    cuuint32_t es[5] = {1, 1, 1, 1, 1};
    f(m, CU_TENSOR_MAP_DATA_TYPE_BFLOAT16, rank, base, dims, strides, box, es, CU_TENSOR_MAP_INTERLEAVE_NONE,
      CU_TENSOR_MAP_SWIZZLE_128B, CU_TENSOR_MAP_L2_PROMOTION_L2_256B, CU_TENSOR_MAP_FLOAT_OOB_FILL_NONE);
}
static void enc_act(PFN_enc f, CUtensorMap* m, void* base, int rows, int chunks, int trows = T_, int pitch = T_) {
    cuuint64_t dims[4] = {64, (cuuint64_t)trows, 8, (cuuint64_t)NB_};
    cuuint64_t st[3] = {1024, 128, (cuuint64_t)pitch * 1024};
    cuuint32_t box[4] = {64, (cuuint32_t)rows, (cuuint32_t)chunks, 1};
    enc(f, m, base, 4, dims, st, box);
}
static void enc_w(PFN_enc f, CUtensorMap* m, void* base, int krows, int ncols, int bk, int bc) {
    cuuint64_t dims[3] = {64, (cuuint64_t)krows, (cuuint64_t)(ncols / 64)};
    cuuint64_t st[2] = {(cuuint64_t)ncols * 2, 128};
    cuuint32_t box[3] = {64, (cuuint32_t)bk, (cuuint32_t)bc};
    enc(f, m, base, 3, dims, st, box);
}

extern "C" void kernel_launch(void* const* d_in, const int* in_sizes, int n_in, void* d_out, int out_size) {
    const bf16* x = (const bf16*)d_in[0];
    static PFN_enc fenc = nullptr;
    static void *p_xa, *p_mqk, *p_wepi, *p_uc, *p_t1;
    static int fused = 0;
    if (!fenc) {
        void* fn = nullptr;
        cudaDriverEntryPointQueryResult qr;
        cudaGetDriverEntryPoint("cuTensorMapEncodeTiled", &fn, cudaEnableDefault, &qr);
        fenc = (PFN_enc)fn;
        cudaGetSymbolAddress(&p_xa, g_xa);
        cudaGetSymbolAddress(&p_mqk, g_mqk);
        cudaGetSymbolAddress(&p_wepi, g_wepi);
        cudaGetSymbolAddress(&p_uc, g_uc);
        cudaGetSymbolAddress(&p_t1, g_t1);
        cudaFuncSetAttribute(main_kernel, cudaFuncAttributeMaxDynamicSharedMemorySize, SMEM_BYTES);
        int dev = 0, sms = 0, occ = 0;
        cudaGetDevice(&dev);
        cudaDeviceGetAttribute(&sms, cudaDevAttrMultiProcessorCount, dev);
        cudaOccupancyMaxActiveBlocksPerMultiprocessor(&occ, main_kernel, 384, SMEM_BYTES);
        fused = sms * occ >= NCTA + 2;
    }
    Maps mp;
    enc_act(fenc, &mp.xa, (char*)p_xa + 1024, 64, 8, T_, T_ + 8);
    enc_act(fenc, &mp.xa2, (char*)p_xa + 1024, 64, 2, T_, T_ + 8);
    enc_act(fenc, &mp.xas, p_xa, 64, 1, T_ + 1, T_ + 8);
    enc_act(fenc, &mp.x, (void*)x, 64, 8);
    enc_act(fenc, &mp.xh, (void*)x, 32, 1);
    enc_act(fenc, &mp.out, d_out, 62, 1);
    enc_w(fenc, &mp.wup4, d_in[5], 512, 1024, 16, 4);
    enc_w(fenc, &mp.wup8, d_in[5], 512, 1024, 16, 8);
    enc_w(fenc, &mp.mqa2, p_mqk, 512, 512, 32, 2);
    enc_w(fenc, &mp.mqa4, p_mqk, 512, 512, 32, 4);
    enc_w(fenc, &mp.mqb1, p_mqk, 512, 512, 64, 1);
    enc_w(fenc, &mp.mqb2, p_mqk, 512, 512, 64, 2);
    enc_w(fenc, &mp.wepi, p_wepi, 1024, 512, 16, 4);
    enc_w(fenc, &mp.uc, p_uc, NCTA * 64, 512, 64, 8);
    enc_w(fenc, &mp.wq, d_in[1], 512, 512, 64, 8);
    enc_w(fenc, &mp.wk, d_in[2], 512, 512, 32, 8);
    enc_w(fenc, &mp.fa[0], d_in[3], 512, 512, 128, 1);
    enc_w(fenc, &mp.fa[1], d_in[7], 512, 512, 128, 1);
    enc_w(fenc, &mp.fa[2], p_t1, 512, 512, 128, 1);
    enc_w(fenc, &mp.fb[0], d_in[4], 512, 512, 64, 4);
    enc_w(fenc, &mp.fb[1], d_in[8], 1024, 512, 64, 4);
    enc_w(fenc, &mp.fc[0], p_t1, 512, 512, 64, 4);
    enc_w(fenc, &mp.fc[1], p_wepi, 1024, 512, 64, 4);
    cudaStream_t st = cudaStreamPerThread;
    if (fused) {
        main_kernel<<<NCTA + 2, 384, SMEM_BYTES, st>>>(mp, (const bf16*)d_in[6], (const bf16*)d_in[5], 0);
    } else {
        main_kernel<<<NCTA + 2, 384, SMEM_BYTES, st>>>(mp, (const bf16*)d_in[6], (const bf16*)d_in[5], 1);
        main_kernel<<<NCTA + 2, 384, SMEM_BYTES, st>>>(mp, (const bf16*)d_in[6], (const bf16*)d_in[5], 2);
    }
}
```

```cpp
#include <cuda_runtime.h>
#include <cuda_bf16.h>
#include <cuda.h>
#include <stdint.h>

typedef __nv_bfloat16 bf16;

constexpr int T_ = 4000, D_ = 512, NB_ = 2;
constexpr int TPB = 65;
constexpr int NCTA = TPB * NB_;
constexpr int NKV = 63;

__device__ __align__(1024) bf16 g_xa[NB_ * (T_ + 8) * D_];
__device__ __align__(1024) bf16 g_mqk[D_ * D_];
__device__ __align__(1024) bf16 g_t1[D_ * D_];
__device__ __align__(1024) bf16 g_wepi[2 * D_ * D_];
__device__ __align__(1024) bf16 g_uc[NCTA * 64 * D_];
__device__ unsigned g_sync[8];

#define PT(i) do { if (el) asm volatile("st.shared.u32 [%0], %1;" ::"r"(sb + MISC + 2560), "r"((unsigned)clock())); } while (0)
#define PG(i)
#define PL(j, q)
#define PDUMP()

#define FENCE_AT 1
#define GO_AT 25
#define LAZY 8.f
#define XS_GAP 800
#define PFW 1
constexpr uint32_t R0 = 0, R1 = 65536, R2 = 131072, R3 = 196608, QS = 221184, MISC = 229376;
constexpr uint32_t AT = 147456, DWS = R3 + 16384, UCT = 163840;
constexpr uint32_t SMEM_BYTES = 232448;
constexpr uint32_t B_A = MISC, B_R1 = MISC + 8  , B_MK = MISC + 48, B_LN = MISC + 56, B_MQ = MISC + 64, B_XA = MISC + 72, B_A2 = MISC + 80,
                   B_H1 = MISC + 88, B_H2 = MISC + 96, B_H3 = MISC + 104,
                   B_KV = MISC + 112, B_P = MISC + 136, B_GO = MISC + 160, B_R2 = MISC + 184, B_UC = MISC + 280,
                   B_X = MISC + 288, CNT = MISC + 296  , SCL = MISC + 512  ,
                   LINV = MISC + 1280  , STAT = MISC + 1536  ;

__device__ __forceinline__ uint32_t smem_u32(const void* p) { return (uint32_t)__cvta_generic_to_shared(p); }
__device__ __forceinline__ void wg_fence() { asm volatile("wgmma.fence.sync.aligned;" ::: "memory"); }
__device__ __forceinline__ void wg_commit() { asm volatile("wgmma.commit_group.sync.aligned;" ::: "memory"); }
template <int N> __device__ __forceinline__ void wg_wait() { asm volatile("wgmma.wait_group.sync.aligned %0;" ::"n"(N) : "memory"); }
__device__ __forceinline__ uint64_t dsc(uint32_t sd, uint32_t off, uint32_t lbo) {
    uint32_t lo = sd + (off >> 4) + ((lbo >> 4) << 16);
    uint64_t d;
    asm("mov.b64 %0, {%1, %2};" : "=l"(d) : "r"(lo), "r"((1024u >> 4) | (1u << 30)));
    return d;
}
__device__ __forceinline__ bool elect1() {
    uint32_t p;
    asm volatile("{\n.reg .pred p;\nelect.sync _|p, 0xffffffff;\nselp.u32 %0, 1, 0, p;\n}\n" : "=r"(p));
    return p != 0;
}
__device__ __forceinline__ void mbar_init(uint32_t bar, int cnt) { asm volatile("mbarrier.init.shared::cta.b64 [%0], %1;" ::"r"(bar), "r"(cnt) : "memory"); }
__device__ __forceinline__ void mbar_expect_tx(uint32_t bar, uint32_t bytes) { asm volatile("mbarrier.arrive.expect_tx.shared::cta.b64 _, [%0], %1;" ::"r"(bar), "r"(bytes) : "memory"); }
__device__ __forceinline__ void mbar_arrive(uint32_t bar) { asm volatile("mbarrier.arrive.shared::cta.b64 _, [%0];" ::"r"(bar) : "memory"); }
__device__ __forceinline__ void mbar_wait(uint32_t bar, uint32_t parity) {
    uint32_t ok;
#pragma unroll 1
    for (uint32_t it = 0;; ++it) {
        asm volatile("{\n.reg .pred p;\nmbarrier.try_wait.parity.shared::cta.b64 p, [%1], %2;\nselp.u32 %0, 1, 0, p;\n}\n" : "=r"(ok) : "r"(bar), "r"(parity) : "memory");
        if (ok) break;
        if (it > (1u << 20)) __trap();
    }
}
__device__ __forceinline__ void fence_async() { asm volatile("fence.proxy.async.shared::cta;" ::: "memory"); }
__device__ __forceinline__ void fence_async_g() { asm volatile("fence.proxy.async.global;" ::: "memory"); }
__device__ __forceinline__ void bar_sync(int id, int n) { asm volatile("bar.sync %0, %1;" ::"r"(id), "r"(n) : "memory"); }
__device__ __forceinline__ void tma3(uint32_t dst, const CUtensorMap* tm, int c0, int c1, int c2, uint32_t bar) {
    asm volatile("cp.async.bulk.tensor.3d.shared::cluster.global.mbarrier::complete_tx::bytes [%0], [%1, {%3, %4, %5}], [%2];"
                 ::"r"(dst), "l"(tm), "r"(bar), "r"(c0), "r"(c1), "r"(c2) : "memory");
}
__device__ __forceinline__ void tma4(uint32_t dst, const CUtensorMap* tm, int c0, int c1, int c2, int c3, uint32_t bar) {
    asm volatile("cp.async.bulk.tensor.4d.shared::cluster.global.mbarrier::complete_tx::bytes [%0], [%1, {%3, %4, %5, %6}], [%2];"
                 ::"r"(dst), "l"(tm), "r"(bar), "r"(c0), "r"(c1), "r"(c2), "r"(c3) : "memory");
}
__device__ __forceinline__ void tma4_store(const CUtensorMap* tm, uint32_t src, int c0, int c1, int c2, int c3) {
    asm volatile("cp.async.bulk.tensor.4d.global.shared::cta.bulk_group [%0, {%2, %3, %4, %5}], [%1];"
                 ::"l"(tm), "r"(src), "r"(c0), "r"(c1), "r"(c2), "r"(c3) : "memory");
}
__device__ __forceinline__ void tma3_store(const CUtensorMap* tm, uint32_t src, int c0, int c1, int c2) {
    asm volatile("cp.async.bulk.tensor.3d.global.shared::cta.bulk_group [%0, {%2, %3, %4}], [%1];"
                 ::"l"(tm), "r"(src), "r"(c0), "r"(c1), "r"(c2) : "memory");
}
__device__ __forceinline__ void stsm4(uint32_t addr, uint32_t a, uint32_t b, uint32_t c, uint32_t d) {
    asm volatile("stmatrix.sync.aligned.m8n8.x4.shared.b16 [%0], {%1, %2, %3, %4};" ::"r"(addr), "r"(a), "r"(b), "r"(c), "r"(d) : "memory");
}
__device__ __forceinline__ void ldsm4(uint32_t addr, uint32_t (&r)[4]) {
    asm volatile("ldmatrix.sync.aligned.m8n8.x4.shared.b16 {%0, %1, %2, %3}, [%4];" : "=r"(r[0]), "=r"(r[1]), "=r"(r[2]), "=r"(r[3]) : "r"(addr) : "memory");
}
__device__ __forceinline__ void ldsm2(uint32_t addr, uint32_t (&r)[2]) {
    asm volatile("ldmatrix.sync.aligned.m8n8.x2.shared.b16 {%0, %1}, [%2];" : "=r"(r[0]), "=r"(r[1]) : "r"(addr) : "memory");
}
__device__ __forceinline__ void stg4(void* p, uint32_t a, uint32_t b, uint32_t c, uint32_t d) {
    asm volatile("st.global.v4.u32 [%0], {%1, %2, %3, %4};" ::"l"(p), "r"(a), "r"(b), "r"(c), "r"(d) : "memory");
}
__device__ __forceinline__ uint32_t pack2(float lo, float hi) {
    uint32_t r;
    asm("cvt.rn.bf16x2.f32 %0, %1, %2;" : "=r"(r) : "f"(hi), "f"(lo));
    return r;
}
__device__ __forceinline__ uint32_t pack2v(float lo, float hi) {
    uint32_t r;
    asm volatile("cvt.rn.bf16x2.f32 %0, %1, %2;" : "=r"(r) : "f"(hi), "f"(lo));
    return r;
}
__device__ __forceinline__ uint32_t bmul2(uint32_t a, uint32_t b) { uint32_t r; asm("mul.rn.bf16x2 %0, %1, %2;" : "=r"(r) : "r"(a), "r"(b)); return r; }
__device__ __forceinline__ uint32_t bfma2(uint32_t a, uint32_t b, uint32_t c) { uint32_t r; asm("fma.rn.bf16x2 %0, %1, %2, %3;" : "=r"(r) : "r"(a), "r"(b), "r"(c)); return r; }
__device__ __forceinline__ float ex2(float x) { float r; asm("ex2.approx.ftz.f32 %0, %1;" : "=f"(r) : "f"(x)); return r; }
__device__ __forceinline__ float rcp(float x) { float r; asm("rcp.approx.ftz.f32 %0, %1;" : "=f"(r) : "f"(x)); return r; }
__device__ __forceinline__ float gelu2(float x) {
    float t = fmaf(x * x, 0.044715f * 0.7978845608028654f, 0.7978845608028654f), th;
    asm("tanh.approx.f32 %0, %1;" : "=f"(th) : "f"(x * t));
    return fmaf(x, th, x);
}
__device__ __forceinline__ uint32_t ldg_v(const uint32_t* p) { uint32_t v; asm volatile("ld.global.nc.u32 %0, [%1];" : "=r"(v) : "l"(p)); return v; }
__device__ __forceinline__ float lds_f32(uint32_t a) { float v; asm volatile("ld.shared.f32 %0, [%1];" : "=f"(v) : "r"(a) : "memory"); return v; }
__device__ __forceinline__ void sts_f32(uint32_t a, float v) { asm volatile("st.shared.f32 [%0], %1;" ::"r"(a), "f"(v) : "memory"); }
__device__ __forceinline__ uint32_t atom_inc_s(uint32_t a) { uint32_t v; asm volatile("atom.relaxed.cta.shared.add.u32 %0, [%1], 1;" : "=r"(v) : "r"(a) : "memory"); return v; }
__device__ __forceinline__ void lds4(uint32_t a, uint32_t* r) {
    asm volatile("ld.shared.v4.u32 {%0, %1, %2, %3}, [%4];" : "=r"(r[0]), "=r"(r[1]), "=r"(r[2]), "=r"(r[3]) : "r"(a) : "memory");
}
__device__ __forceinline__ void sts4(uint32_t a, uint32_t x, uint32_t y, uint32_t z, uint32_t t) {
    asm volatile("st.shared.v4.u32 [%0], {%1, %2, %3, %4};" ::"r"(a), "r"(x), "r"(y), "r"(z), "r"(t) : "memory");
}
__device__ __forceinline__ uint32_t bsub2(uint32_t a, uint32_t b) { uint32_t r; asm("sub.rn.bf16x2 %0, %1, %2;" : "=r"(r) : "r"(a), "r"(b)); return r; }
__device__ __forceinline__ float blo(uint32_t v) { return __uint_as_float(v << 16); }
__device__ __forceinline__ float bhi(uint32_t v) { return __uint_as_float(v & 0xffff0000u); }
__device__ __forceinline__ float bfr(float x) { return __bfloat162float(__float2bfloat16_rn(x)); }
__device__ __forceinline__ void l2_prefetch(const void* p, uint32_t bytes) { asm volatile("cp.async.bulk.prefetch.L2.global [%0], %1;" ::"l"(p), "r"(bytes) : "memory"); }
__device__ __forceinline__ void flag_add(unsigned* p) { asm volatile("red.release.gpu.global.add.u32 [%0], 1;" ::"l"(p) : "memory"); }
__device__ __forceinline__ void flag_wait(const unsigned* p, unsigned target) {
#pragma unroll 1
    for (uint32_t it = 0;; ++it) {
        unsigned v;
        asm volatile("ld.acquire.gpu.global.u32 %0, [%1];" : "=r"(v) : "l"(p) : "memory");
        if (v >= target) break;
        if (it > (1u << 20)) __trap();
    }
    fence_async_g();
}
template <int N> __device__ __forceinline__ void pin(float (&a)[N]) {
#pragma unroll
    for (int i = 0; i < N; i++) asm volatile("" : "+f"(a[i])::"memory");
}

template <int N> __device__ __forceinline__ void fresh(float (&a)[N]) {
#pragma unroll
    for (int i = 0; i < N; i++) a[i] = 0.f;
    pin(a);
}

__device__ __forceinline__ void wgmma_rs_n64_tb0(float (&d)[32], uint32_t a0, uint32_t a1, uint32_t a2, uint32_t a3, uint64_t db, int scale_d) {
    asm volatile("{\n.reg .pred p;\nsetp.ne.b32 p, %37, 0;\n"
        "wgmma.mma_async.sync.aligned.m64n64k16.f32.bf16.bf16 {%0, %1, %2, %3, %4, %5, %6, %7, %8, %9, %10, %11, %12, %13, %14, %15, %16, %17, %18, %19, %20, %21, %22, %23, %24, %25, %26, %27, %28, %29, %30, %31}, {%32, %33, %34, %35}, %36, p, 1, 1, 0;\n}\n"
        : "+f"(d[0]), "+f"(d[1]), "+f"(d[2]), "+f"(d[3]), "+f"(d[4]), "+f"(d[5]), "+f"(d[6]), "+f"(d[7]), "+f"(d[8]), "+f"(d[9]), "+f"(d[10]), "+f"(d[11]), "+f"(d[12]), "+f"(d[13]), "+f"(d[14]), "+f"(d[15]), "+f"(d[16]), "+f"(d[17]), "+f"(d[18]), "+f"(d[19]), "+f"(d[20]), "+f"(d[21]), "+f"(d[22]), "+f"(d[23]), "+f"(d[24]), "+f"(d[25]), "+f"(d[26]), "+f"(d[27]), "+f"(d[28]), "+f"(d[29]), "+f"(d[30]), "+f"(d[31])
        : "r"(a0), "r"(a1), "r"(a2), "r"(a3), "l"(db), "r"(scale_d));
}

__device__ __forceinline__ void wgmma_ss_n128_tb1(float (&d)[64], uint64_t da, uint64_t db, int scale_d) {
    asm volatile("{\n.reg .pred p;\nsetp.ne.b32 p, %66, 0;\n"
        "wgmma.mma_async.sync.aligned.m64n128k16.f32.bf16.bf16 {%0, %1, %2, %3, %4, %5, %6, %7, %8, %9, %10, %11, %12, %13, %14, %15, %16, %17, %18, %19, %20, %21, %22, %23, %24, %25, %26, %27, %28, %29, %30, %31, %32, %33, %34, %35, %36, %37, %38, %39, %40, %41, %42, %43, %44, %45, %46, %47, %48, %49, %50, %51, %52, %53, %54, %55, %56, %57, %58, %59, %60, %61, %62, %63}, %64, %65, p, 1, 1, 0, 1;\n}\n"
        : "+f"(d[0]), "+f"(d[1]), "+f"(d[2]), "+f"(d[3]), "+f"(d[4]), "+f"(d[5]), "+f"(d[6]), "+f"(d[7]), "+f"(d[8]), "+f"(d[9]), "+f"(d[10]), "+f"(d[11]), "+f"(d[12]), "+f"(d[13]), "+f"(d[14]), "+f"(d[15]), "+f"(d[16]), "+f"(d[17]), "+f"(d[18]), "+f"(d[19]), "+f"(d[20]), "+f"(d[21]), "+f"(d[22]), "+f"(d[23]), "+f"(d[24]), "+f"(d[25]), "+f"(d[26]), "+f"(d[27]), "+f"(d[28]), "+f"(d[29]), "+f"(d[30]), "+f"(d[31]), "+f"(d[32]), "+f"(d[33]), "+f"(d[34]), "+f"(d[35]), "+f"(d[36]), "+f"(d[37]), "+f"(d[38]), "+f"(d[39]), "+f"(d[40]), "+f"(d[41]), "+f"(d[42]), "+f"(d[43]), "+f"(d[44]), "+f"(d[45]), "+f"(d[46]), "+f"(d[47]), "+f"(d[48]), "+f"(d[49]), "+f"(d[50]), "+f"(d[51]), "+f"(d[52]), "+f"(d[53]), "+f"(d[54]), "+f"(d[55]), "+f"(d[56]), "+f"(d[57]), "+f"(d[58]), "+f"(d[59]), "+f"(d[60]), "+f"(d[61]), "+f"(d[62]), "+f"(d[63])
        : "l"(da), "l"(db), "r"(scale_d));
}

__device__ __forceinline__ void wgmma_ss_n256_tb1(float (&d)[128], uint64_t da, uint64_t db, int scale_d) {
    asm volatile("{\n.reg .pred p;\nsetp.ne.b32 p, %130, 0;\n"
        "wgmma.mma_async.sync.aligned.m64n256k16.f32.bf16.bf16 {%0, %1, %2, %3, %4, %5, %6, %7, %8, %9, %10, %11, %12, %13, %14, %15, %16, %17, %18, %19, %20, %21, %22, %23, %24, %25, %26, %27, %28, %29, %30, %31, %32, %33, %34, %35, %36, %37, %38, %39, %40, %41, %42, %43, %44, %45, %46, %47, %48, %49, %50, %51, %52, %53, %54, %55, %56, %57, %58, %59, %60, %61, %62, %63, %64, %65, %66, %67, %68, %69, %70, %71, %72, %73, %74, %75, %76, %77, %78, %79, %80, %81, %82, %83, %84, %85, %86, %87, %88, %89, %90, %91, %92, %93, %94, %95, %96, %97, %98, %99, %100, %101, %102, %103, %104, %105, %106, %107, %108, %109, %110, %111, %112, %113, %114, %115, %116, %117, %118, %119, %120, %121, %122, %123, %124, %125, %126, %127}, %128, %129, p, 1, 1, 0, 1;\n}\n"
        : "+f"(d[0]), "+f"(d[1]), "+f"(d[2]), "+f"(d[3]), "+f"(d[4]), "+f"(d[5]), "+f"(d[6]), "+f"(d[7]), "+f"(d[8]), "+f"(d[9]), "+f"(d[10]), "+f"(d[11]), "+f"(d[12]), "+f"(d[13]), "+f"(d[14]), "+f"(d[15]), "+f"(d[16]), "+f"(d[17]), "+f"(d[18]), "+f"(d[19]), "+f"(d[20]), "+f"(d[21]), "+f"(d[22]), "+f"(d[23]), "+f"(d[24]), "+f"(d[25]), "+f"(d[26]), "+f"(d[27]), "+f"(d[28]), "+f"(d[29]), "+f"(d[30]), "+f"(d[31]), "+f"(d[32]), "+f"(d[33]), "+f"(d[34]), "+f"(d[35]), "+f"(d[36]), "+f"(d[37]), "+f"(d[38]), "+f"(d[39]), "+f"(d[40]), "+f"(d[41]), "+f"(d[42]), "+f"(d[43]), "+f"(d[44]), "+f"(d[45]), "+f"(d[46]), "+f"(d[47]), "+f"(d[48]), "+f"(d[49]), "+f"(d[50]), "+f"(d[51]), "+f"(d[52]), "+f"(d[53]), "+f"(d[54]), "+f"(d[55]), "+f"(d[56]), "+f"(d[57]), "+f"(d[58]), "+f"(d[59]), "+f"(d[60]), "+f"(d[61]), "+f"(d[62]), "+f"(d[63]), "+f"(d[64]), "+f"(d[65]), "+f"(d[66]), "+f"(d[67]), "+f"(d[68]), "+f"(d[69]), "+f"(d[70]), "+f"(d[71]), "+f"(d[72]), "+f"(d[73]), "+f"(d[74]), "+f"(d[75]), "+f"(d[76]), "+f"(d[77]), "+f"(d[78]), "+f"(d[79]), "+f"(d[80]), "+f"(d[81]), "+f"(d[82]), "+f"(d[83]), "+f"(d[84]), "+f"(d[85]), "+f"(d[86]), "+f"(d[87]), "+f"(d[88]), "+f"(d[89]), "+f"(d[90]), "+f"(d[91]), "+f"(d[92]), "+f"(d[93]), "+f"(d[94]), "+f"(d[95]), "+f"(d[96]), "+f"(d[97]), "+f"(d[98]), "+f"(d[99]), "+f"(d[100]), "+f"(d[101]), "+f"(d[102]), "+f"(d[103]), "+f"(d[104]), "+f"(d[105]), "+f"(d[106]), "+f"(d[107]), "+f"(d[108]), "+f"(d[109]), "+f"(d[110]), "+f"(d[111]), "+f"(d[112]), "+f"(d[113]), "+f"(d[114]), "+f"(d[115]), "+f"(d[116]), "+f"(d[117]), "+f"(d[118]), "+f"(d[119]), "+f"(d[120]), "+f"(d[121]), "+f"(d[122]), "+f"(d[123]), "+f"(d[124]), "+f"(d[125]), "+f"(d[126]), "+f"(d[127])
        : "l"(da), "l"(db), "r"(scale_d));
}

__device__ __forceinline__ void wgmma_ss_n32_tb0(float (&d)[16], uint64_t da, uint64_t db, int scale_d) {
    asm volatile("{\n.reg .pred p;\nsetp.ne.b32 p, %18, 0;\n"
        "wgmma.mma_async.sync.aligned.m64n32k16.f32.bf16.bf16 {%0, %1, %2, %3, %4, %5, %6, %7, %8, %9, %10, %11, %12, %13, %14, %15}, %16, %17, p, 1, 1, 0, 0;\n}\n"
        : "+f"(d[0]), "+f"(d[1]), "+f"(d[2]), "+f"(d[3]), "+f"(d[4]), "+f"(d[5]), "+f"(d[6]), "+f"(d[7]), "+f"(d[8]), "+f"(d[9]), "+f"(d[10]), "+f"(d[11]), "+f"(d[12]), "+f"(d[13]), "+f"(d[14]), "+f"(d[15])
        : "l"(da), "l"(db), "r"(scale_d));
}

__device__ __forceinline__ void wgmma_ss_n64_tb0(float (&d)[32], uint64_t da, uint64_t db, int scale_d) {
    asm volatile("{\n.reg .pred p;\nsetp.ne.b32 p, %34, 0;\n"
        "wgmma.mma_async.sync.aligned.m64n64k16.f32.bf16.bf16 {%0, %1, %2, %3, %4, %5, %6, %7, %8, %9, %10, %11, %12, %13, %14, %15, %16, %17, %18, %19, %20, %21, %22, %23, %24, %25, %26, %27, %28, %29, %30, %31}, %32, %33, p, 1, 1, 0, 0;\n}\n"
        : "+f"(d[0]), "+f"(d[1]), "+f"(d[2]), "+f"(d[3]), "+f"(d[4]), "+f"(d[5]), "+f"(d[6]), "+f"(d[7]), "+f"(d[8]), "+f"(d[9]), "+f"(d[10]), "+f"(d[11]), "+f"(d[12]), "+f"(d[13]), "+f"(d[14]), "+f"(d[15]), "+f"(d[16]), "+f"(d[17]), "+f"(d[18]), "+f"(d[19]), "+f"(d[20]), "+f"(d[21]), "+f"(d[22]), "+f"(d[23]), "+f"(d[24]), "+f"(d[25]), "+f"(d[26]), "+f"(d[27]), "+f"(d[28]), "+f"(d[29]), "+f"(d[30]), "+f"(d[31])
        : "l"(da), "l"(db), "r"(scale_d));
}

struct Maps {
    CUtensorMap xa, xa2, xas, xh, wup4, wup8, mqa2, mqa4, mqb1, mqb2, wepi, uc, x, out, wq, wk, fa[3], fb[2], fc[2];
};

__device__ __forceinline__ uint64_t mkd(uint32_t lo) {
    uint64_t d;
    asm("mov.b64 %0, {%1, %2};" : "=l"(d) : "r"(lo), "r"((1024u >> 4) | (1u << 30)));
    return d;
}
__device__ __forceinline__ void ring_ld(uint32_t sb, uint32_t barbase, uint32_t slot8, const CUtensorMap* tm, int c1, int c2) {
    mbar_expect_tx(sb + barbase + slot8, 8192);
    tma3(sb + R1 + slot8 * 1024, tm, 0, c1, c2, sb + barbase + slot8);
}

__device__ __forceinline__ void ring_half(uint32_t sb, uint32_t slot8, uint32_t hoff, const CUtensorMap* tm, int c1, int c2) {
    mbar_expect_tx(sb + B_R1 + slot8, 8192);
    tma3(sb + R1 + slot8 * 2048 + hoff, tm, 0, c1, c2, sb + B_R1 + slot8);
}
__device__ __forceinline__ void ring_full(uint32_t sb, uint32_t slot8, const CUtensorMap* tm, int c1, int c2) {
    mbar_expect_tx(sb + B_R1 + slot8, 16384);
    mbar_arrive(sb + B_R1 + slot8);
    tma3(sb + R1 + slot8 * 2048, tm, 0, c1, c2, sb + B_R1 + slot8);
}
__device__ __forceinline__ void cta_done(int mode) {
    if (mode == 0 && atomicAdd(&g_sync[4], 1) == NCTA + 1) {
#pragma unroll
        for (int i = 0; i < 5; i++) g_sync[i] = 0;
    }
}

__device__ __forceinline__ void fold_cta(const Maps& mp, uint32_t sb, int mode) {
    constexpr uint32_t F_FULL = MISC, F_EMPTY = MISC + 32, F_T1 = MISC + 64, STG = 49152, FOUT = 3 * STG;
    const int tid = threadIdx.x, f = blockIdx.x - NCTA;
    if (mode == 2) return;
    if (tid == 0) {
        for (int i = 0; i < 3; i++) { mbar_init(sb + F_FULL + 8 * i, 1); mbar_init(sb + F_EMPTY + 8 * i, 2); }
        mbar_init(sb + F_T1, 2);
        asm volatile("fence.mbarrier_init.release.cluster;" ::: "memory");
        fence_async();
    }
    __syncthreads();
    const int wg = __shfl_sync(0xffffffffu, tid >> 7, 0);
    int st = 0, ph = 0;
    if (wg == 0) {
        if (tid == 0) {
#pragma unroll 1
            for (int it = 0; it < 96; it++) {
                const int p = it >> 3, kc = it & 7, job = p >> 2;
                if (it == 64) mbar_wait(sb + F_T1, 0);
                mbar_wait(sb + F_EMPTY + 8 * st, ph ^ 1);
                mbar_expect_tx(sb + F_FULL + 8 * st, STG);
                tma3(sb + st * STG, &mp.fa[job], 0, 256 * f + 128 * ((p >> 1) & 1), kc, sb + F_FULL + 8 * st);
                tma3(sb + st * STG + 16384, &mp.fb[job != 0], 0, 64 * kc + (job == 1 ? 512 : 0), 4 * (p & 1), sb + F_FULL + 8 * st);
                if (++st == 3) { st = 0; ph ^= 1; }
            }
        }
        return;
    }
    const int h = wg - 1, lane = tid & 31, w = (tid >> 5) & 3;
    const uint32_t sd = (sb & 0x3FFFF) >> 4;
    const bool el = (tid & 127) == 0;
#pragma unroll 1
    for (int p = 0; p < 12; p++) {
        float acc[128];
        fresh(acc);
#pragma unroll 1
        for (int kc = 0; kc < 8; kc++) {
            mbar_wait(sb + F_FULL + 8 * st, ph);
            wg_fence();
#pragma unroll
            for (int kk = 0; kk < 4; kk++)
                wgmma_ss_n256_tb1(acc, dsc(sd, st * STG + h * 8192 + kk * 32, 16), dsc(sd, st * STG + 16384 + kk * 2048, 8192), 1);
            wg_commit();
            wg_wait<0>();
            if (el) mbar_arrive(sb + F_EMPTY + 8 * st);
            if (++st == 3) { st = 0; ph ^= 1; }
        }
        pin(acc);
        const int job = p >> 2;
        if (el) {
            asm volatile("cp.async.bulk.wait_group 0;" ::: "memory");
            if (p == 4) { fence_async_g(); mbar_arrive(sb + F_T1); }
        }
        bar_sync(3 + h, 128);
        uint32_t r = 16 * w + (lane & 7) + ((lane >> 3) & 1) * 8;
        const float fs = job == 1 ? 0.5f : 1.f;
        if (job == 1) r = (r & ~31) | (((r >> 1) & 3) << 3) | (((r >> 3) & 3) << 1) | (r & 1);
        const uint32_t oa = sb + FOUT + h * 32768 + r * 128 + ((((lane >> 4) ^ r) & 7) << 4);
#pragma unroll
        for (int i = 0; i < 16; i++)
            stsm4((oa ^ ((i & 3) << 5)) + (i >> 2) * 8192, pack2(acc[8 * i] * fs, acc[8 * i + 1] * fs), pack2(acc[8 * i + 2] * fs, acc[8 * i + 3] * fs),
                  pack2(acc[8 * i + 4] * fs, acc[8 * i + 5] * fs), pack2(acc[8 * i + 6] * fs, acc[8 * i + 7] * fs));
        fence_async();
        bar_sync(3 + h, 128);
        if (el) {
            tma3_store(&mp.fc[job != 0], sb + FOUT + h * 32768, 0, 256 * f + 128 * ((p >> 1) & 1) + 64 * h + (job == 1 ? 512 : 0), 4 * (p & 1));
            asm volatile("cp.async.bulk.commit_group;" ::: "memory");
        }
    }
    if (el) {
        asm volatile("cp.async.bulk.wait_group 0;" ::: "memory");
        fence_async_g();
        if (mode == 0) flag_add(&g_sync[3]);
    }
    bar_sync(2, 256);
    if (tid == 128) cta_done(mode);
}

__global__ void __launch_bounds__(384, 1) main_kernel(const __grid_constant__ Maps mp, const bf16* __restrict__ dw, const bf16* wup, const int mode) {
    extern __shared__ __align__(1024) uint8_t smem[];
    const uint32_t sb = smem_u32(smem);
    const int tid = threadIdx.x;
    if (blockIdx.x >= NCTA) { fold_cta(mp, sb, mode); return; }
    const int b = blockIdx.x / TPB, ti = blockIdx.x % TPB;
    const int piece = blockIdx.x & 127;
    if (tid == 0) {
        mbar_init(sb + B_A, 1); mbar_init(sb + B_A2, 1); mbar_init(sb + B_MK, 1);
        for (int i = 0; i < 5; i++) mbar_init(sb + B_R1 + 8 * i, 2);
        asm volatile("fence.mbarrier_init.release.cluster;" ::: "memory");
        fence_async();
        mbar_expect_tx(sb + B_MK, 65536 + 32768);
        tma3(sb + R0, &mp.wq, 0, 64 * (piece >> 4), 0, sb + B_MK);
        tma3(sb + R1 + 32768, &mp.wk, 0, 32 * (piece & 15), 0, sb + B_MK);
        mbar_expect_tx(sb + B_A, 32768);
        mbar_expect_tx(sb + B_A2, 32768 + 3072);
#pragma unroll 1
        for (int i = 0; i < 16; i++) tma4(sb + AT + (i & 7) * 8192 + (i >> 3) * 4096, &mp.xh, 0, 62 * ti - 1 + 32 * (i >> 3), i & 7, b, sb + (i < 8 ? B_A : B_A2));
        asm volatile("cp.async.bulk.shared::cluster.global.mbarrier::complete_tx::bytes [%0], [%1], 3072, [%2];" ::"r"(sb + DWS), "l"(dw), "r"(sb + B_A2) : "memory");
        for (int i = 0; i < 8; i++) mbar_arrive(sb + B_R1 + 8 * (i >> 1));
        if (mode != 1) {
            ring_full(sb, 32, &mp.wup8, 0, 8);
            ring_full(sb, 0, &mp.wup8, 16, 8);
            ring_full(sb, 8, &mp.wup8, 32, 8);
        }
    } else if (tid == 32) {
        mbar_init(sb + B_LN, 1); mbar_init(sb + B_MQ, 1); mbar_init(sb + B_XA, 1);
        mbar_init(sb + B_H1, 2); mbar_init(sb + B_H2, 1); mbar_init(sb + B_H3, 2);
        for (int i = 0; i < 3; i++) { mbar_init(sb + B_KV + 8 * i, 1); mbar_init(sb + B_P + 8 * i, 4); mbar_init(sb + B_GO + 8 * i, 4); }
        for (int i = 0; i < 12; i++) mbar_init(sb + B_R2 + 8 * i, 1);
        mbar_init(sb + B_UC, 1); mbar_init(sb + B_X, 1);
        for (int i = 0; i < 4; i++) asm volatile("st.shared.u32 [%0], 0;" ::"r"(sb + CNT + 4 * i) : "memory");
        asm volatile("fence.mbarrier_init.release.cluster;" ::: "memory");
        fence_async();
    }
    __syncthreads();
    const int wg = __shfl_sync(0xffffffffu, tid >> 7, 0);
    const int lane = tid & 31, w = (tid >> 5) & 3;
    const bool w0 = __shfl_sync(0xffffffffu, w, 0) == 0;
    const uint32_t sd = (sb & 0x3FFFF) >> 4;
    const uint32_t adA = sd + (AT >> 4) + (1u << 16);
    const uint32_t bd0 = sd + (R1 >> 4);
    const uint32_t bd2k = bd0 + ((2048u >> 4) << 16);
    const bool el = (tid & 127) == 0;
    const uint32_t lrow = 16 * w + (lane & 7) + ((lane >> 3) & 1) * 8;
    const uint32_t loff = lrow * 128 + ((((lane >> 4) ^ lrow) & 7) << 4);
    const int r0 = 16 * w + (lane >> 2);

    if (wg == 0) {
        asm volatile("setmaxnreg.inc.sync.aligned.u32 184;");
        uint32_t q[112];
        PT(0);
        PG(200);
        {
            float mq[16];
            fresh(mq);
            mbar_wait(sb + B_MK, 0);
            PT(1);
            if (PFW && tid == 32) l2_prefetch((const char*)wup + piece * 8192, 8192);
            wg_fence();
#pragma unroll 1
            for (int c = 0; c < 8; c++)
#pragma unroll
                for (int kk = 0; kk < 4; kk++)
                    wgmma_ss_n32_tb0(mq, dsc(sd, R0 + c * 8192 + kk * 32, 16), dsc(sd, R1 + 32768 + c * 4096 + kk * 32, 16), 1);
            wg_commit();
            wg_wait<0>();
            if (mode != 1 && w0 && elect1()) { ring_full(sb, 16, &mp.wup8, 48, 8); ring_full(sb, 24, &mp.wup8, 64, 8); }
            pin(mq);
            uint32_t* c = reinterpret_cast<uint32_t*>(g_mqk + (64 * (piece >> 4) + r0) * D_ + 32 * (piece & 15) + 2 * (lane & 3));
#pragma unroll
            for (int n = 0; n < 4; n++) { c[4 * n] = pack2(mq[4 * n], mq[4 * n + 1]); c[4 * n + 4 * D_] = pack2(mq[4 * n + 2], mq[4 * n + 3]); }
            fence_async_g();
            bar_sync(1, 128);
            if (el) {
                if (mode == 0) flag_add(&g_sync[2]);
                if (mode == 0) flag_wait(&g_sync[2], NCTA);
                mbar_arrive(sb + B_MQ);
                PT(12);
                mbar_wait(sb + B_LN, 0);
#pragma unroll 1
                for (int c = 0; c < 8; c++) {
                    tma4_store(&mp.xas, sb + AT + c * 8192, 0, 62 * ti, c, b);
                    const unsigned t0 = (unsigned)clock();
                    while (c < 7 && (unsigned)clock() - t0 < XS_GAP) __nanosleep(20);
                }
                asm volatile("cp.async.bulk.commit_group;" ::: "memory");
                if (mode == 1) asm volatile("cp.async.bulk.wait_group 0;" ::: "memory");
            }
            PT(13);
            if (mode == 1) return;
        }
        mbar_wait(sb + B_H1, 0);
        PT(2);
        uint32_t slot8 = 8, par = 1, prev8 = 0;
        auto adv = [&]() { prev8 = slot8; slot8 += 8; if (slot8 == 40) { slot8 = 0; par ^= 1; } };
        {
            float acc[128];
            fresh(acc);
            auto step = [&](int i) {
                const uint32_t aa = adA + (i >> 1) * 512 + (i & 1) * 4, bb = bd0 + ((4096u >> 4) << 16) + slot8 * 128;
                wg_fence();
                wgmma_ss_n256_tb1(acc, mkd(aa), mkd(bb), 1);
                wgmma_ss_n256_tb1(acc, mkd(aa + 2), mkd(bb + 128), 1);
                wg_commit();
                wg_wait<1>();
            };
#pragma unroll 1
            for (int i = 0; i < 12; i++) {
                mbar_wait(sb + B_R1 + slot8, par);
                step(i);
                if (i > 0 && w0 && elect1()) ring_full(sb, prev8, &mp.mqa4, 32 * i + 128, 4);
                adv();
            }
#pragma unroll 1
            for (int i = 12; i < 16; i++) {
                mbar_wait(sb + B_R1 + slot8, par);
                if (i == 15 && el) mbar_arrive(sb + B_H2);
                step(i);
                if (w0 && elect1()) ring_full(sb, prev8, &mp.wup8, 16 * i - 192, 0);
                adv();
            }
            wg_wait<0>();
            if (w0 && elect1()) ring_full(sb, prev8, &mp.wup8, 64, 0);
            pin(acc);
            PT(3);
#pragma unroll
            for (int kk = 0; kk < 4; kk++)
                stsm4((sb + QS + loff) ^ (kk << 5), pack2(acc[96 + 8 * kk], acc[97 + 8 * kk]), pack2(acc[98 + 8 * kk], acc[99 + 8 * kk]),
                      pack2(acc[100 + 8 * kk], acc[101 + 8 * kk]), pack2(acc[102 + 8 * kk], acc[103 + 8 * kk]));
            fence_async();
#pragma unroll
            for (int i = 47; i >= 0; i--) q[64 + i] = pack2v(acc[2 * i], acc[2 * i + 1]);
        }
        if (el) {
            asm volatile("cp.async.bulk.wait_group 0;" ::: "memory");
            if (mode == 0) {
                fence_async_g();
                flag_add(&g_sync[b]);
                flag_wait(&g_sync[b], TPB);
            }
            mbar_arrive(sb + B_XA);
        }
        __syncwarp();
        mbar_wait(sb + B_H3, 0);
        PT(4);
        slot8 = 32; par = 0;
#pragma unroll
        for (int half = 0; half < 2; half++) {
            float acc[64];
            fresh(acc);
            auto step = [&](int m) {
                const uint32_t aa = adA + m * 512, bb = bd0 + ((8192u >> 4) << 16) + slot8 * 128;
                mbar_wait(sb + B_R1 + slot8, par);
                wg_fence();
#pragma unroll
                for (int kk = 0; kk < 4; kk++) wgmma_ss_n128_tb1(acc, mkd(aa + 2 * kk), mkd(bb + 128 * kk), 1);
                wg_commit();
                wg_wait<1>();
            };
            if (half == 0) {
#pragma unroll 1
                for (int m = 0; m < 8; m++) {
                    step(m);
                    if (m > 0 && w0 && elect1()) ring_full(sb, prev8, &mp.mqb2, (64 * m + 256) & 511, (m + 4) >> 3 << 1);
                    adv();
                }
            } else {
#pragma unroll 1
                for (int m = 0; m < 4; m++) {
                    step(m);
                    if (m > 0 && w0 && elect1()) ring_full(sb, prev8, &mp.mqb2, 64 * m + 256, 2);
                    adv();
                }
#pragma unroll 1
                for (int m = 4; m < 8; m++) {
                    step(m);
                    if (w0 && elect1()) {
                        if (m == 4) mbar_expect_tx(sb + B_KV + 8, 65536);
                        tma4(sb + R1 + prev8 * 2048, &mp.xa2, 0, 0, 2 * m - 8, b, sb + B_KV + 8);
                    }
                    adv();
                }
            }
            wg_wait<0>();
            if (w0 && elect1()) {
                if (half == 0) ring_full(sb, prev8, &mp.mqb2, 256, 2);
                else {
                    mbar_expect_tx(sb + B_KV + 16, 65536);
                    tma4(sb + R2, &mp.xa, 0, 64, 0, b, sb + B_KV + 16);
                }
            }
            pin(acc);
#pragma unroll
            for (int i = 31; i >= 0; i--) q[32 * half + i] = pack2v(acc[2 * i], acc[2 * i + 1]);
        }
        bar_sync(1, 128);
        PT(5);

        const float CS = 0.04419417382415922f * 1.4426950408889634f;
        float m0 = -INFINITY, m1 = -INFINITY, l0 = 0.f, l1 = 0.f;
        int s = 0, sn = 1, ph = 0;
        float S[32];
        const bool l0w = lane == 0, q0 = (lane & 3) == 0;
#pragma unroll 1
        for (int j = -1;; j++) {
            if (j >= 0) {
                PL(j, 1);
                if (j == NKV - 1) {
#pragma unroll
                    for (int i = (T_ - 64 * (NKV - 1)) / 2; i < 32; i++) asm volatile("mov.b32 %0, 0xff800000;" : "=f"(S[i]));
                }
                float y[8], z[8];
#pragma unroll
                for (int n = 0; n < 8; n++) { y[n] = fmaxf(S[4 * n], S[4 * n + 1]); z[n] = fmaxf(S[4 * n + 2], S[4 * n + 3]); }
#pragma unroll
                for (int n = 0; n < 4; n++) { y[n] = fmaxf(y[n], y[n + 4]); z[n] = fmaxf(z[n], z[n + 4]); }
                float x0 = fmaxf(fmaxf(y[0], y[1]), fmaxf(fmaxf(y[2], y[3]), m0)), x1 = fmaxf(fmaxf(z[0], z[1]), fmaxf(fmaxf(z[2], z[3]), m1));
                x0 = fmaxf(x0, __shfl_xor_sync(0xffffffffu, x0, 1));
                x1 = fmaxf(x1, __shfl_xor_sync(0xffffffffu, x1, 1));
                x0 = fmaxf(x0, __shfl_xor_sync(0xffffffffu, x0, 2));
                x1 = fmaxf(x1, __shfl_xor_sync(0xffffffffu, x1, 2));
                if ((x0 - m0) * CS <= LAZY) x0 = m0;
                if ((x1 - m1) * CS <= LAZY) x1 = m1;
                const float sc0 = ex2((m0 - x0) * CS), sc1 = ex2((m1 - x1) * CS);
                m0 = x0; m1 = x1;
                const float n0 = -x0 * CS, n1 = -x1 * CS;
                if (q0) { sts_f32(sb + SCL + s * 256 + r0 * 4, sc0); sts_f32(sb + SCL + s * 256 + r0 * 4 + 32, sc1); }
                __syncwarp();
                if (l0w) mbar_arrive(sb + B_P + s * 8);
                if (j < NKV - 1) mbar_wait(sb + B_KV + sn * 8, ph);
                float a0 = 0.f, a1 = 0.f;
                const uint32_t pb = sb + R3 + (s == 0 ? 2 : s - 1) * 8192;
#pragma unroll
                for (int kk = 0; kk < 4; kk++) {
                    float p[8];
#pragma unroll
                    for (int e = 0; e < 8; e++) p[e] = ex2(fmaf(S[8 * kk + e], CS, (e & 2) ? n1 : n0));
                    a0 += (p[0] + p[1]) + (p[4] + p[5]);
                    a1 += (p[2] + p[3]) + (p[6] + p[7]);
                    stsm4((pb + loff) ^ (kk << 5), pack2(p[0], p[1]), pack2(p[2], p[3]), pack2(p[4], p[5]), pack2(p[6], p[7]));
                }
                l0 = fmaf(l0, sc0, a0); l1 = fmaf(l1, sc1, a1);
                PL(j, 2);
                if (j == NKV - 1) break;
            } else {
                mbar_wait(sb + B_KV + 8, 0);
            }
            float Sn[32];
            const uint32_t kd = sd + sn * 4096;
            wg_fence();
#pragma unroll
            for (int kk = 0; kk < 28; kk++) {
                wgmma_rs_n64_tb0(Sn, q[4 * kk], q[4 * kk + 1], q[4 * kk + 2], q[4 * kk + 3], dsc(kd, (kk >> 2) * 8192 + (kk & 3) * 32, 16), kk > 0);
                if (kk == FENCE_AT) { fence_async(); __syncwarp(); }
                if (kk == GO_AT) { PL(j, 3); if (j >= 0 && l0w) mbar_arrive(sb + B_GO + s * 8); }
            }
#pragma unroll
            for (int kk = 0; kk < 4; kk++)
                wgmma_ss_n64_tb0(Sn, dsc(sd, QS + kk * 32, 16), dsc(kd, 7 * 8192 + kk * 32, 16), 1);
            wg_commit();
            PL(j, 0);
            wg_wait<0>();
            pin(Sn);
#pragma unroll
            for (int i = 0; i < 32; i++) S[i] = Sn[i];
            s = sn;
            if (++sn == 3) sn = 0;
            if (sn == 1) ph ^= 1;
        }
        l0 += __shfl_xor_sync(0xffffffffu, l0, 1); l1 += __shfl_xor_sync(0xffffffffu, l1, 1);
        l0 += __shfl_xor_sync(0xffffffffu, l0, 2); l1 += __shfl_xor_sync(0xffffffffu, l1, 2);
        if (q0) { sts_f32(sb + LINV + r0 * 4, rcp(l0)); sts_f32(sb + LINV + r0 * 4 + 32, rcp(l1)); }
        fence_async();
        __syncwarp();
        if (l0w) mbar_arrive(sb + B_GO + s * 8);
        PDUMP();
    } else {
        asm volatile("setmaxnreg.dec.sync.aligned.u32 160;");
        const int h = wg - 1;
        auto red4 = [&](float (&a)[4]) {
            const bool b4 = lane & 16, b3 = lane & 8;
            const float k0 = (b4 ? a[2] : a[0]) + __shfl_xor_sync(0xffffffffu, b4 ? a[0] : a[2], 16);
            const float k1 = (b4 ? a[3] : a[1]) + __shfl_xor_sync(0xffffffffu, b4 ? a[1] : a[3], 16);
            float k = (b3 ? k1 : k0) + __shfl_xor_sync(0xffffffffu, b3 ? k0 : k1, 8);
            k += __shfl_xor_sync(0xffffffffu, k, 4);
            k += __shfl_xor_sync(0xffffffffu, k, 2);
            k += __shfl_xor_sync(0xffffffffu, k, 1);
            return k;
        };
#pragma unroll 1
        for (int bt = 0; bt < 2; bt++) {
            mbar_wait(sb + (bt ? B_A2 : B_A), 0);
            PT(bt ? 13 : 0);
            uint32_t v[4][8];
            float a[4], f[4][16];
            const uint32_t la = sb + AT + (lane >> 3) * 8192 + (32 * bt + 16 * h + 4 * w) * 128 + (((lane & 7) ^ ((w & 1) * 4)) << 4);
#pragma unroll
            for (int r = 0; r < 4; r++) { lds4((la ^ (r << 4)) + r * 128, v[r]); lds4((la ^ (r << 4)) + r * 128 + 32768, v[r] + 4); }
#pragma unroll
            for (int r = 0; r < 4; r++) {
                float s0 = blo(v[r][0]), s1 = bhi(v[r][0]);
#pragma unroll
                for (int i = 1; i < 8; i++) { s0 += blo(v[r][i]); s1 += bhi(v[r][i]); }
                a[r] = s0 + s1;
            }
            const float mu = red4(a) * (1.f / D_);
            const uint32_t mp2 = pack2(mu, mu);
#pragma unroll
            for (int r = 0; r < 4; r++) {
                const uint32_t m2 = __shfl_sync(0xffffffffu, mp2, 8 * r);
                float s0 = 0.f, s1 = 0.f;
#pragma unroll
                for (int i = 0; i < 8; i++) {
                    const uint32_t d = bsub2(v[r][i], m2);
                    f[r][2 * i] = blo(d); f[r][2 * i + 1] = bhi(d);
                    s0 = fmaf(f[r][2 * i], f[r][2 * i], s0); s1 = fmaf(f[r][2 * i + 1], f[r][2 * i + 1], s1);
                }
                a[r] = s0 + s1;
            }
            const float dm = mu - blo(mp2);
            float sd_ = bfr(bfr(fmaxf(fmaf(red4(a), 1.f / D_, -dm * dm), 0.f)) + 1e-5f);
            asm("sqrt.approx.f32 %0, %0;" : "+f"(sd_));
            const float ri = rcp(bfr(sd_));
#pragma unroll
            for (int r = 0; r < 4; r++) {
                const float rinv = __shfl_sync(0xffffffffu, ri, 8 * r);
#pragma unroll
                for (int i = 0; i < 8; i++) v[r][i] = pack2(f[r][2 * i] * rinv, f[r][2 * i + 1] * rinv);
                sts4((la ^ (r << 4)) + r * 128, v[r][0], v[r][1], v[r][2], v[r][3]);
                sts4((la ^ (r << 4)) + r * 128 + 32768, v[r][4], v[r][5], v[r][6], v[r][7]);
            }
        }
        fence_async();
        bar_sync(2, 256);
        if (tid == 128) mbar_arrive(sb + B_LN);
        if (mode == 1) return;
        float acc[128];
#pragma unroll
        for (int pass = 0; pass < 2; pass++) {
            if (pass == 1) mbar_wait(sb + B_H2, 0);
            PT(1 + 3 * pass);
            fresh(acc);
            uint32_t slot8 = pass ? 16 : 32, par = 0, prev8 = 0;
            auto adv = [&]() { prev8 = slot8; slot8 += 8; if (slot8 == 40) { slot8 = 0; par ^= 1; } };
            auto step = [&](int kk) {
                wg_fence();
                wgmma_ss_n256_tb1(acc, mkd(adA + (kk >> 2) * 512 + (kk & 3) * 2), mkd(bd2k + h * 512 + slot8 * 128), 1);
                wg_commit();
                wg_wait<1>();
            };
#pragma unroll 1
            for (int kk = 0; kk < 28; kk++) {
                mbar_wait(sb + B_R1 + slot8, par);
                step(kk);
                if (kk > 0 && w0 && elect1()) ring_half(sb, prev8, h * 8192, &mp.wup4, 16 * kk + 64, (pass ? 0 : 8) + 4 * h);
                adv();
            }
            if (pass == 0 && w0) mbar_wait(sb + B_MQ, 0);
#pragma unroll 1
            for (int kk = 28; kk < 32; kk++) {
                mbar_wait(sb + B_R1 + slot8, par);
                if (kk == 31 && el) mbar_arrive(sb + (pass ? B_H3 : B_H1));
                step(kk);
                if (w0 && elect1()) ring_half(sb, prev8, h * 8192, pass ? &mp.mqb1 : &mp.mqa2, (pass ? 64 : 32) * (kk - 28), pass ? h : 4 + 2 * h);
                adv();
            }
            wg_wait<0>();
            if (w0 && elect1()) ring_half(sb, prev8, h * 8192, pass ? &mp.mqb1 : &mp.mqa2, pass ? 256 : 128, pass ? h : 4 + 2 * h);
            pin(acc);
            PT(2 + 3 * pass);
            if (pass == 0) {
                float s0 = 0.f, s1 = 0.f, v0 = 0.f, v1 = 0.f;
#pragma unroll
                for (int n = 0; n < 32; n++) {
#pragma unroll
                    for (int e = 0; e < 4; e++) acc[4 * n + e] = gelu2(acc[4 * n + e]);
                    s0 += acc[4 * n] + acc[4 * n + 1]; s1 += acc[4 * n + 2] + acc[4 * n + 3];
                    v0 = fmaf(acc[4 * n], acc[4 * n], v0); v0 = fmaf(acc[4 * n + 1], acc[4 * n + 1], v0);
                    v1 = fmaf(acc[4 * n + 2], acc[4 * n + 2], v1); v1 = fmaf(acc[4 * n + 3], acc[4 * n + 3], v1);
                }
#pragma unroll
                for (int o = 1; o < 4; o <<= 1) {
                    s0 += __shfl_xor_sync(0xffffffffu, s0, o); s1 += __shfl_xor_sync(0xffffffffu, s1, o);
                    v0 += __shfl_xor_sync(0xffffffffu, v0, o); v1 += __shfl_xor_sync(0xffffffffu, v1, o);
                }
                if ((lane & 3) == 0) {
                    uint32_t a = sb + STAT + h * 512 + r0 * 8;
                    sts_f32(a, s0); sts_f32(a + 4, v0); sts_f32(a + 64, s1); sts_f32(a + 68, v1);
                }
                bar_sync(2, 256);
                {
                    uint32_t a = sb + STAT + (h ^ 1) * 512 + r0 * 8;
                    s0 = (s0 + lds_f32(a)) * (1.f / 512.f); v0 = (v0 + lds_f32(a + 4)) * (1.f / 512.f);
                    s1 = (s1 + lds_f32(a + 64)) * (1.f / 512.f); v1 = (v1 + lds_f32(a + 68)) * (1.f / 512.f);
                }
                v0 = rsqrtf(fmaxf(fmaf(-s0, s0, v0), 0.f) + 4e-5f); v1 = rsqrtf(fmaxf(fmaf(-s1, s1, v1), 0.f) + 4e-5f);
                s0 = -s0 * v0; s1 = -s1 * v1;
#pragma unroll
                for (int p = 0; p < 16; p++)
                    stsm4(((sb + R0 + h * 32768 + loff) ^ ((p & 3) << 5)) + (p >> 2) * 8192,
                          pack2(fmaf(acc[8 * p], v0, s0), fmaf(acc[8 * p + 1], v0, s0)), pack2(fmaf(acc[8 * p + 2], v1, s1), fmaf(acc[8 * p + 3], v1, s1)),
                          pack2(fmaf(acc[8 * p + 4], v0, s0), fmaf(acc[8 * p + 5], v0, s0)), pack2(fmaf(acc[8 * p + 6], v1, s1), fmaf(acc[8 * p + 7], v1, s1)));
            } else {
                uint32_t u[64];
#pragma unroll
                for (int i = 63; i >= 0; i--) u[i] = pack2v(gelu2(acc[2 * i]), gelu2(acc[2 * i + 1]));
                PT(12);
                bar_sync(3 + h, 128);
                const uint32_t rm = lrow == 0 ? 0 : lrow - 1, rp = lrow == 63 ? 63 : lrow + 1;
                const uint32_t gb = sb + R0 + h * 32768;
                const uint32_t am = gb + rm * 128 + ((((lane >> 4) ^ rm) & 7) << 4), ap = gb + rp * 128 + ((((lane >> 4) ^ rp) & 7) << 4), ac = gb + loff;
                const uint32_t dwa = sb + DWS + 512 * h + ((lane >> 3) & 1) * 16 + (lane >> 4) * 1024;
                bf16* ucp = g_uc + ((size_t)blockIdx.x * 64 + r0) * D_ + 256 * h + 8 * (lane & 3);
#pragma unroll
                for (int m = 0; m < 8; m++) {
                    uint32_t o[8], g0[2][4], g1[2][4], g2[2][4], d[2][4], d2[2][2];
#pragma unroll
                    for (int pp = 0; pp < 2; pp++) {
                        const int p = 2 * m + pp;
                        const uint32_t co = (p >> 2) * 8192, cx = (p & 3) << 5;
                        ldsm4(dwa + 32 * p, d[pp]);
                        ldsm2(dwa + 32 * p + 2048, d2[pp]);
                        ldsm4((am ^ cx) + co, g0[pp]);
                        ldsm4((ac ^ cx) + co, g1[pp]);
                        ldsm4((ap ^ cx) + co, g2[pp]);
                    }
#pragma unroll
                    for (int pp = 0; pp < 2; pp++)
#pragma unroll
                        for (int e = 0; e < 4; e++)
                            o[4 * (e & 1) + 2 * pp + (e >> 1)] =
                                bmul2(u[8 * m + 4 * pp + e], bfma2(g2[pp][e], d2[pp][e >> 1], bfma2(g1[pp][e], d[pp][2 + (e >> 1)], bmul2(g0[pp][e], d[pp][e >> 1]))));
                    stg4(ucp + 32 * m, o[0], o[1], o[2], o[3]);
                    stg4(ucp + 32 * m + 8 * D_, o[4], o[5], o[6], o[7]);
                }
                bar_sync(2, 256);
                if (tid == 128) {
                    mbar_wait(sb + B_XA, 0);
                    mbar_expect_tx(sb + B_KV, 65536);
                    tma4(sb + R0, &mp.xa, 0, 128, 0, b, sb + B_KV);
                }
            }
            PT(3 + 3 * pass);
        }
        int s = 1, ph = 0;
        fresh(acc);
#pragma unroll 1
        for (int j = 0; j < NKV; j++) {
            mbar_wait(sb + B_P + s * 8, ph);
            PL(j, 0);
            if (j > 0) {
                const float sc0 = lds_f32(sb + SCL + s * 256 + r0 * 4), sc1 = lds_f32(sb + SCL + s * 256 + r0 * 4 + 32);
                if (__any_sync(0xffffffffu, sc0 != 1.f || sc1 != 1.f)) {
#pragma unroll
                    for (int n = 0; n < 32; n++) { acc[4 * n] *= sc0; acc[4 * n + 1] *= sc0; acc[4 * n + 2] *= sc1; acc[4 * n + 3] *= sc1; }
                }
            }
            mbar_wait(sb + B_GO + s * 8, ph);
            PL(j, 1);
            const uint32_t vd = sd + s * 4096 + h * 2048, pd = sd + (s == 0 ? 2 : s - 1) * 512;
            pin(acc);
            wg_fence();
#pragma unroll
            for (int kk = 0; kk < 4; kk++) wgmma_ss_n256_tb1(acc, dsc(pd, R3 + kk * 32, 16), dsc(vd, kk * 2048, 8192), 1);
            wg_commit();
            wg_wait<0>();
            pin(acc);
            PL(j, 2);
            if (w0 && elect1()) {
                if (j == NKV - 5 && mode == 0) flag_wait(&g_sync[3], 4);
                if (atom_inc_s(sb + CNT + 4 * s) & 1) {
                    if (j + 3 < NKV) {
                        mbar_expect_tx(sb + B_KV + s * 8, 65536);
                        tma4(sb + s * 65536, &mp.xa, 0, 64 * (j + 3), 0, b, sb + B_KV + s * 8);
                    } else if (j < NKV - 1) {
                        const int n0 = j == NKV - 3 ? 0 : 8, n1 = j == NKV - 3 ? 8 : 12;
#pragma unroll 1
                        for (int n = n0; n < n1; n++) ring_ld(sb, B_R2, n * 8, &mp.wepi, 16 * (n >> 1), 4 * (n & 1));
                    }
                }
            }
            if (++s == 3) s = 0;
            if (s == 1) ph ^= 1;
        }
        {
            const float i0 = lds_f32(sb + LINV + r0 * 4), i1 = lds_f32(sb + LINV + r0 * 4 + 32);
#pragma unroll
            for (int p = 0; p < 16; p++)
                stsm4(((sb + R0 + h * 32768 + loff) ^ ((p & 3) << 5)) + (p >> 2) * 8192,
                      pack2(acc[8 * p] * i0, acc[8 * p + 1] * i0), pack2(acc[8 * p + 2] * i1, acc[8 * p + 3] * i1),
                      pack2(acc[8 * p + 4] * i0, acc[8 * p + 5] * i0), pack2(acc[8 * p + 6] * i1, acc[8 * p + 7] * i1));
        }
        fence_async();
        fence_async_g();
        bar_sync(2, 256);
        if (tid == 128) {
            mbar_expect_tx(sb + B_UC, 65536);
            tma3(sb + UCT, &mp.uc, 0, 64 * blockIdx.x, 0, sb + B_UC);
        }
        PT(7);
        fresh(acc);
        {
            uint32_t slot8 = 8 * h, par = 0, prev8 = 0;
#pragma unroll 1
            for (int kk = 0; kk < 64; kk++) {
                if (kk == 32) mbar_wait(sb + B_UC, 0);
                mbar_wait(sb + B_R2 + slot8, par);
                wg_fence();
                wgmma_ss_n256_tb1(acc, mkd(sd + (1u << 16) + (kk < 32 ? (R0 >> 4) : (UCT >> 4) - 4096) + (kk >> 2) * 512 + (kk & 3) * 2), mkd(bd2k + slot8 * 64), 1);
                wg_commit();
                wg_wait<1>();
                if (kk > 0 && w0 && elect1()) {
                    if (kk < 59) ring_ld(sb, B_R2, prev8, &mp.wepi, 16 * (kk + 5), 4 * h);
                    if (kk == 32 && (atom_inc_s(sb + CNT + 12) & 1)) {
                        mbar_expect_tx(sb + B_X, 65536);
                        tma4(sb + R0, &mp.x, 0, 62 * ti, 0, b, sb + B_X);
                    }
                }
                prev8 = slot8;
                slot8 += 16;
                if (slot8 >= 96) { slot8 -= 96; par ^= 1; }
            }
        }
        wg_wait<0>();
        pin(acc);
        PT(8);
        mbar_wait(sb + B_X, 0);
        PT(9);
        {
            const uint32_t sr = (lrow + 63) & 63;
            const uint32_t xoff = sr * 128 + ((((lane >> 4) ^ sr) & 7) << 4);
#pragma unroll
            for (int p = 0; p < 16; p++) {
                const uint32_t a = ((sb + R0 + h * 32768 + xoff) ^ ((p & 3) << 5)) + (p >> 2) * 8192;
                uint32_t xv[4];
                ldsm4(a, xv);
#pragma unroll
                for (int e = 0; e < 4; e++)
                    xv[e] = pack2(acc[8 * p + 2 * e] + __uint_as_float(xv[e] << 16), acc[8 * p + 2 * e + 1] + __uint_as_float(xv[e] & 0xffff0000u));
                stsm4(a, xv[0], xv[1], xv[2], xv[3]);
            }
        }
        fence_async();
        bar_sync(3 + h, 128);
        if (el) {
            for (int c = 0; c < 4; c++) tma4_store(&mp.out, sb + R0 + (4 * h + c) * 8192, 0, 62 * ti, 4 * h + c, b);
            asm volatile("cp.async.bulk.commit_group;" ::: "memory");
            PT(10);
            if (h == 0) cta_done(mode);
            asm volatile("cp.async.bulk.wait_group.read 0;" ::: "memory");
        }
        PT(11);
        PG(201);
        PDUMP();
    }
}

typedef CUresult (*PFN_enc)(CUtensorMap*, CUtensorMapDataType, cuuint32_t, void*, const cuuint64_t*, const cuuint64_t*,
                            const cuuint32_t*, const cuuint32_t*, CUtensorMapInterleave, CUtensorMapSwizzle,
                            CUtensorMapL2promotion, CUtensorMapFloatOOBfill);

static void enc(PFN_enc f, CUtensorMap* m, void* base, int rank, const cuuint64_t* dims, const cuuint64_t* strides, const cuuint32_t* box) {
    cuuint32_t es[5] = {1, 1, 1, 1, 1};
    f(m, CU_TENSOR_MAP_DATA_TYPE_BFLOAT16, rank, base, dims, strides, box, es, CU_TENSOR_MAP_INTERLEAVE_NONE,
      CU_TENSOR_MAP_SWIZZLE_128B, CU_TENSOR_MAP_L2_PROMOTION_L2_256B, CU_TENSOR_MAP_FLOAT_OOB_FILL_NONE);
}
static void enc_act(PFN_enc f, CUtensorMap* m, void* base, int rows, int chunks, int trows = T_, int pitch = T_) {
    cuuint64_t dims[4] = {64, (cuuint64_t)trows, 8, (cuuint64_t)NB_};
    cuuint64_t st[3] = {1024, 128, (cuuint64_t)pitch * 1024};
    cuuint32_t box[4] = {64, (cuuint32_t)rows, (cuuint32_t)chunks, 1};
    enc(f, m, base, 4, dims, st, box);
}
static void enc_w(PFN_enc f, CUtensorMap* m, void* base, int krows, int ncols, int bk, int bc) {
    cuuint64_t dims[3] = {64, (cuuint64_t)krows, (cuuint64_t)(ncols / 64)};
    cuuint64_t st[2] = {(cuuint64_t)ncols * 2, 128};
    cuuint32_t box[3] = {64, (cuuint32_t)bk, (cuuint32_t)bc};
    enc(f, m, base, 3, dims, st, box);
}

extern "C" void kernel_launch(void* const* d_in, const int* in_sizes, int n_in, void* d_out, int out_size) {
    const bf16* x = (const bf16*)d_in[0];
    static PFN_enc fenc = nullptr;
    static void *p_xa, *p_mqk, *p_wepi, *p_uc, *p_t1;
    static int fused = 0;
    if (!fenc) {
        void* fn = nullptr;
        cudaDriverEntryPointQueryResult qr;
        cudaGetDriverEntryPoint("cuTensorMapEncodeTiled", &fn, cudaEnableDefault, &qr);
        fenc = (PFN_enc)fn;
        cudaGetSymbolAddress(&p_xa, g_xa);
        cudaGetSymbolAddress(&p_mqk, g_mqk);
        cudaGetSymbolAddress(&p_wepi, g_wepi);
        cudaGetSymbolAddress(&p_uc, g_uc);
        cudaGetSymbolAddress(&p_t1, g_t1);
        cudaFuncSetAttribute(main_kernel, cudaFuncAttributeMaxDynamicSharedMemorySize, SMEM_BYTES);
        int dev = 0, sms = 0, occ = 0;
        cudaGetDevice(&dev);
        cudaDeviceGetAttribute(&sms, cudaDevAttrMultiProcessorCount, dev);
        cudaOccupancyMaxActiveBlocksPerMultiprocessor(&occ, main_kernel, 384, SMEM_BYTES);
        fused = sms * occ >= NCTA + 2;
    }
    Maps mp;
    enc_act(fenc, &mp.xa, (char*)p_xa + 1024, 64, 8, T_, T_ + 8);
    enc_act(fenc, &mp.xa2, (char*)p_xa + 1024, 64, 2, T_, T_ + 8);
    enc_act(fenc, &mp.xas, p_xa, 64, 1, T_ + 1, T_ + 8);
    enc_act(fenc, &mp.x, (void*)x, 64, 8);
    enc_act(fenc, &mp.xh, (void*)x, 32, 1);
    enc_act(fenc, &mp.out, d_out, 62, 1);
    enc_w(fenc, &mp.wup4, d_in[5], 512, 1024, 16, 4);
    enc_w(fenc, &mp.wup8, d_in[5], 512, 1024, 16, 8);
    enc_w(fenc, &mp.mqa2, p_mqk, 512, 512, 32, 2);
    enc_w(fenc, &mp.mqa4, p_mqk, 512, 512, 32, 4);
    enc_w(fenc, &mp.mqb1, p_mqk, 512, 512, 64, 1);
    enc_w(fenc, &mp.mqb2, p_mqk, 512, 512, 64, 2);
    enc_w(fenc, &mp.wepi, p_wepi, 1024, 512, 16, 4);
    enc_w(fenc, &mp.uc, p_uc, NCTA * 64, 512, 64, 8);
    enc_w(fenc, &mp.wq, d_in[1], 512, 512, 64, 8);
    enc_w(fenc, &mp.wk, d_in[2], 512, 512, 32, 8);
    enc_w(fenc, &mp.fa[0], d_in[3], 512, 512, 128, 1);
    enc_w(fenc, &mp.fa[1], d_in[7], 512, 512, 128, 1);
    enc_w(fenc, &mp.fa[2], p_t1, 512, 512, 128, 1);
    enc_w(fenc, &mp.fb[0], d_in[4], 512, 512, 64, 4);
    enc_w(fenc, &mp.fb[1], d_in[8], 1024, 512, 64, 4);
    enc_w(fenc, &mp.fc[0], p_t1, 512, 512, 64, 4);
    enc_w(fenc, &mp.fc[1], p_wepi, 1024, 512, 64, 4);
    cudaStream_t st = cudaStreamPerThread;
    if (fused) {
        main_kernel<<<NCTA + 2, 384, SMEM_BYTES, st>>>(mp, (const bf16*)d_in[6], (const bf16*)d_in[5], 0);
    } else {
        main_kernel<<<NCTA + 2, 384, SMEM_BYTES, st>>>(mp, (const bf16*)d_in[6], (const bf16*)d_in[5], 1);
        main_kernel<<<NCTA + 2, 384, SMEM_BYTES, st>>>(mp, (const bf16*)d_in[6], (const bf16*)d_in[5], 2);
    }
}
```

```cpp
#include <cuda_runtime.h>
#include <cuda_bf16.h>
#include <cuda.h>
#include <stdint.h>

typedef __nv_bfloat16 bf16;

constexpr int T_ = 4000, D_ = 512, NB_ = 2;
constexpr int TPB = 65;
constexpr int NCTA = TPB * NB_;
constexpr int NKV = 63;

__device__ __align__(1024) bf16 g_xa[NB_ * (T_ + 8) * D_];
__device__ __align__(1024) bf16 g_mqk[D_ * D_];
__device__ __align__(1024) bf16 g_t1[D_ * D_];
__device__ __align__(1024) bf16 g_wepi[2 * D_ * D_];
__device__ __align__(1024) bf16 g_uc[NCTA * 64 * D_];
__device__ unsigned g_sync[8];

#define PT(i) do { if (el) asm volatile("st.shared.u32 [%0], %1;" ::"r"(sb + MISC + 2560), "r"((unsigned)clock())); } while (0)
#define PG(i)
#define PLM 15
#define PL(j, q) do { if ((PLM >> ((q) + (wg ? 4 : 0))) & 1) PT(0); } while (0)
#define PDUMP()

#define FENCE_AT 1
#define GO_AT 25
#define LAZY 8.f
#define XS_GAP 800
#define PFW 1
constexpr uint32_t R0 = 0, R1 = 65536, R2 = 131072, R3 = 196608, QS = 221184, MISC = 229376;
constexpr uint32_t AT = 147456, DWS = R3 + 16384, UCT = 163840;
constexpr uint32_t SMEM_BYTES = 232448;
constexpr uint32_t B_A = MISC, B_R1 = MISC + 8  , B_MK = MISC + 48, B_LN = MISC + 56, B_MQ = MISC + 64, B_XA = MISC + 72, B_A2 = MISC + 80,
                   B_H1 = MISC + 88, B_H2 = MISC + 96, B_H3 = MISC + 104,
                   B_KV = MISC + 112, B_P = MISC + 136, B_GO = MISC + 160, B_R2 = MISC + 184, B_UC = MISC + 280,
                   B_X = MISC + 288, CNT = MISC + 296  , B_E2 = MISC + 320  , SCL = MISC + 512  ,
                   LINV = MISC + 1280  , STAT = MISC + 1536  ;

__device__ __forceinline__ uint32_t smem_u32(const void* p) { return (uint32_t)__cvta_generic_to_shared(p); }
__device__ __forceinline__ void wg_fence() { asm volatile("wgmma.fence.sync.aligned;" ::: "memory"); }
__device__ __forceinline__ void wg_commit() { asm volatile("wgmma.commit_group.sync.aligned;" ::: "memory"); }
template <int N> __device__ __forceinline__ void wg_wait() { asm volatile("wgmma.wait_group.sync.aligned %0;" ::"n"(N) : "memory"); }
__device__ __forceinline__ uint64_t dsc(uint32_t sd, uint32_t off, uint32_t lbo) {
    uint32_t lo = sd + (off >> 4) + ((lbo >> 4) << 16);
    uint64_t d;
    asm("mov.b64 %0, {%1, %2};" : "=l"(d) : "r"(lo), "r"((1024u >> 4) | (1u << 30)));
    return d;
}
__device__ __forceinline__ bool elect1() {
    uint32_t p;
    asm volatile("{\n.reg .pred p;\nelect.sync _|p, 0xffffffff;\nselp.u32 %0, 1, 0, p;\n}\n" : "=r"(p));
    return p != 0;
}
__device__ __forceinline__ void mbar_init(uint32_t bar, int cnt) { asm volatile("mbarrier.init.shared::cta.b64 [%0], %1;" ::"r"(bar), "r"(cnt) : "memory"); }
__device__ __forceinline__ void mbar_expect_tx(uint32_t bar, uint32_t bytes) { asm volatile("mbarrier.arrive.expect_tx.shared::cta.b64 _, [%0], %1;" ::"r"(bar), "r"(bytes) : "memory"); }
__device__ __forceinline__ void mbar_arrive(uint32_t bar) { asm volatile("mbarrier.arrive.shared::cta.b64 _, [%0];" ::"r"(bar) : "memory"); }
__device__ __forceinline__ void mbar_wait(uint32_t bar, uint32_t parity) {
    uint32_t ok;
#pragma unroll 1
    for (uint32_t it = 0;; ++it) {
        asm volatile("{\n.reg .pred p;\nmbarrier.try_wait.parity.shared::cta.b64 p, [%1], %2;\nselp.u32 %0, 1, 0, p;\n}\n" : "=r"(ok) : "r"(bar), "r"(parity) : "memory");
        if (ok) break;
        if (it > (1u << 20)) __trap();
    }
}
__device__ __forceinline__ void fence_async() { asm volatile("fence.proxy.async.shared::cta;" ::: "memory"); }
__device__ __forceinline__ void fence_async_g() { asm volatile("fence.proxy.async.global;" ::: "memory"); }
__device__ __forceinline__ void bar_sync(int id, int n) { asm volatile("bar.sync %0, %1;" ::"r"(id), "r"(n) : "memory"); }
__device__ __forceinline__ void tma3(uint32_t dst, const CUtensorMap* tm, int c0, int c1, int c2, uint32_t bar) {
    asm volatile("cp.async.bulk.tensor.3d.shared::cluster.global.mbarrier::complete_tx::bytes [%0], [%1, {%3, %4, %5}], [%2];"
                 ::"r"(dst), "l"(tm), "r"(bar), "r"(c0), "r"(c1), "r"(c2) : "memory");
}
__device__ __forceinline__ void tma4(uint32_t dst, const CUtensorMap* tm, int c0, int c1, int c2, int c3, uint32_t bar) {
    asm volatile("cp.async.bulk.tensor.4d.shared::cluster.global.mbarrier::complete_tx::bytes [%0], [%1, {%3, %4, %5, %6}], [%2];"
                 ::"r"(dst), "l"(tm), "r"(bar), "r"(c0), "r"(c1), "r"(c2), "r"(c3) : "memory");
}
__device__ __forceinline__ void tma4_store(const CUtensorMap* tm, uint32_t src, int c0, int c1, int c2, int c3) {
    asm volatile("cp.async.bulk.tensor.4d.global.shared::cta.bulk_group [%0, {%2, %3, %4, %5}], [%1];"
                 ::"l"(tm), "r"(src), "r"(c0), "r"(c1), "r"(c2), "r"(c3) : "memory");
}
__device__ __forceinline__ void tma3_store(const CUtensorMap* tm, uint32_t src, int c0, int c1, int c2) {
    asm volatile("cp.async.bulk.tensor.3d.global.shared::cta.bulk_group [%0, {%2, %3, %4}], [%1];"
                 ::"l"(tm), "r"(src), "r"(c0), "r"(c1), "r"(c2) : "memory");
}
__device__ __forceinline__ void stsm4(uint32_t addr, uint32_t a, uint32_t b, uint32_t c, uint32_t d) {
    asm volatile("stmatrix.sync.aligned.m8n8.x4.shared.b16 [%0], {%1, %2, %3, %4};" ::"r"(addr), "r"(a), "r"(b), "r"(c), "r"(d) : "memory");
}
__device__ __forceinline__ void ldsm4(uint32_t addr, uint32_t (&r)[4]) {
    asm volatile("ldmatrix.sync.aligned.m8n8.x4.shared.b16 {%0, %1, %2, %3}, [%4];" : "=r"(r[0]), "=r"(r[1]), "=r"(r[2]), "=r"(r[3]) : "r"(addr) : "memory");
}
__device__ __forceinline__ void ldsm2(uint32_t addr, uint32_t (&r)[2]) {
    asm volatile("ldmatrix.sync.aligned.m8n8.x2.shared.b16 {%0, %1}, [%2];" : "=r"(r[0]), "=r"(r[1]) : "r"(addr) : "memory");
}
__device__ __forceinline__ void stg4(void* p, uint32_t a, uint32_t b, uint32_t c, uint32_t d) {
    asm volatile("st.global.v4.u32 [%0], {%1, %2, %3, %4};" ::"l"(p), "r"(a), "r"(b), "r"(c), "r"(d) : "memory");
}
__device__ __forceinline__ uint32_t pack2(float lo, float hi) {
    uint32_t r;
    asm("cvt.rn.bf16x2.f32 %0, %1, %2;" : "=r"(r) : "f"(hi), "f"(lo));
    return r;
}
__device__ __forceinline__ uint32_t pack2v(float lo, float hi) {
    uint32_t r;
    asm volatile("cvt.rn.bf16x2.f32 %0, %1, %2;" : "=r"(r) : "f"(hi), "f"(lo));
    return r;
}
__device__ __forceinline__ uint32_t bmul2(uint32_t a, uint32_t b) { uint32_t r; asm("mul.rn.bf16x2 %0, %1, %2;" : "=r"(r) : "r"(a), "r"(b)); return r; }
__device__ __forceinline__ uint32_t bfma2(uint32_t a, uint32_t b, uint32_t c) { uint32_t r; asm("fma.rn.bf16x2 %0, %1, %2, %3;" : "=r"(r) : "r"(a), "r"(b), "r"(c)); return r; }
__device__ __forceinline__ float ex2(float x) { float r; asm("ex2.approx.ftz.f32 %0, %1;" : "=f"(r) : "f"(x)); return r; }
__device__ __forceinline__ float rcp(float x) { float r; asm("rcp.approx.ftz.f32 %0, %1;" : "=f"(r) : "f"(x)); return r; }
__device__ __forceinline__ float gelu2(float x) {
    float t = fmaf(x * x, 0.044715f * 0.7978845608028654f, 0.7978845608028654f), th;
    asm("tanh.approx.f32 %0, %1;" : "=f"(th) : "f"(x * t));
    return fmaf(x, th, x);
}
__device__ __forceinline__ uint32_t ldg_v(const uint32_t* p) { uint32_t v; asm volatile("ld.global.nc.u32 %0, [%1];" : "=r"(v) : "l"(p)); return v; }
__device__ __forceinline__ float lds_f32(uint32_t a) { float v; asm volatile("ld.shared.f32 %0, [%1];" : "=f"(v) : "r"(a) : "memory"); return v; }
__device__ __forceinline__ void sts_f32(uint32_t a, float v) { asm volatile("st.shared.f32 [%0], %1;" ::"r"(a), "f"(v) : "memory"); }
__device__ __forceinline__ uint32_t atom_inc_s(uint32_t a) { uint32_t v; asm volatile("atom.relaxed.cta.shared.add.u32 %0, [%1], 1;" : "=r"(v) : "r"(a) : "memory"); return v; }
__device__ __forceinline__ void lds4(uint32_t a, uint32_t* r) {
    asm volatile("ld.shared.v4.u32 {%0, %1, %2, %3}, [%4];" : "=r"(r[0]), "=r"(r[1]), "=r"(r[2]), "=r"(r[3]) : "r"(a) : "memory");
}
__device__ __forceinline__ void sts4(uint32_t a, uint32_t x, uint32_t y, uint32_t z, uint32_t t) {
    asm volatile("st.shared.v4.u32 [%0], {%1, %2, %3, %4};" ::"r"(a), "r"(x), "r"(y), "r"(z), "r"(t) : "memory");
}
__device__ __forceinline__ uint32_t bsub2(uint32_t a, uint32_t b) { uint32_t r; asm("sub.rn.bf16x2 %0, %1, %2;" : "=r"(r) : "r"(a), "r"(b)); return r; }
__device__ __forceinline__ float blo(uint32_t v) { return __uint_as_float(v << 16); }
__device__ __forceinline__ float bhi(uint32_t v) { return __uint_as_float(v & 0xffff0000u); }
__device__ __forceinline__ float bfr(float x) { return __bfloat162float(__float2bfloat16_rn(x)); }
__device__ __forceinline__ void l2_prefetch(const void* p, uint32_t bytes) { asm volatile("cp.async.bulk.prefetch.L2.global [%0], %1;" ::"l"(p), "r"(bytes) : "memory"); }
__device__ __forceinline__ void flag_add(unsigned* p) { asm volatile("red.release.gpu.global.add.u32 [%0], 1;" ::"l"(p) : "memory"); }
__device__ __forceinline__ void flag_wait(const unsigned* p, unsigned target) {
#pragma unroll 1
    for (uint32_t it = 0;; ++it) {
        unsigned v;
        asm volatile("ld.acquire.gpu.global.u32 %0, [%1];" : "=r"(v) : "l"(p) : "memory");
        if (v >= target) break;
        if (it > (1u << 20)) __trap();
    }
    fence_async_g();
}
template <int N> __device__ __forceinline__ void pin(float (&a)[N]) {
#pragma unroll
    for (int i = 0; i < N; i++) asm volatile("" : "+f"(a[i])::"memory");
}

template <int N> __device__ __forceinline__ void fresh(float (&a)[N]) {
#pragma unroll
    for (int i = 0; i < N; i++) a[i] = 0.f;
    pin(a);
}

__device__ __forceinline__ void wgmma_rs_n64_tb0(float (&d)[32], uint32_t a0, uint32_t a1, uint32_t a2, uint32_t a3, uint64_t db, int scale_d) {
    asm volatile("{\n.reg .pred p;\nsetp.ne.b32 p, %37, 0;\n"
        "wgmma.mma_async.sync.aligned.m64n64k16.f32.bf16.bf16 {%0, %1, %2, %3, %4, %5, %6, %7, %8, %9, %10, %11, %12, %13, %14, %15, %16, %17, %18, %19, %20, %21, %22, %23, %24, %25, %26, %27, %28, %29, %30, %31}, {%32, %33, %34, %35}, %36, p, 1, 1, 0;\n}\n"
        : "+f"(d[0]), "+f"(d[1]), "+f"(d[2]), "+f"(d[3]), "+f"(d[4]), "+f"(d[5]), "+f"(d[6]), "+f"(d[7]), "+f"(d[8]), "+f"(d[9]), "+f"(d[10]), "+f"(d[11]), "+f"(d[12]), "+f"(d[13]), "+f"(d[14]), "+f"(d[15]), "+f"(d[16]), "+f"(d[17]), "+f"(d[18]), "+f"(d[19]), "+f"(d[20]), "+f"(d[21]), "+f"(d[22]), "+f"(d[23]), "+f"(d[24]), "+f"(d[25]), "+f"(d[26]), "+f"(d[27]), "+f"(d[28]), "+f"(d[29]), "+f"(d[30]), "+f"(d[31])
        : "r"(a0), "r"(a1), "r"(a2), "r"(a3), "l"(db), "r"(scale_d));
}

__device__ __forceinline__ void wgmma_ss_n128_tb1(float (&d)[64], uint64_t da, uint64_t db, int scale_d) {
    asm volatile("{\n.reg .pred p;\nsetp.ne.b32 p, %66, 0;\n"
        "wgmma.mma_async.sync.aligned.m64n128k16.f32.bf16.bf16 {%0, %1, %2, %3, %4, %5, %6, %7, %8, %9, %10, %11, %12, %13, %14, %15, %16, %17, %18, %19, %20, %21, %22, %23, %24, %25, %26, %27, %28, %29, %30, %31, %32, %33, %34, %35, %36, %37, %38, %39, %40, %41, %42, %43, %44, %45, %46, %47, %48, %49, %50, %51, %52, %53, %54, %55, %56, %57, %58, %59, %60, %61, %62, %63}, %64, %65, p, 1, 1, 0, 1;\n}\n"
        : "+f"(d[0]), "+f"(d[1]), "+f"(d[2]), "+f"(d[3]), "+f"(d[4]), "+f"(d[5]), "+f"(d[6]), "+f"(d[7]), "+f"(d[8]), "+f"(d[9]), "+f"(d[10]), "+f"(d[11]), "+f"(d[12]), "+f"(d[13]), "+f"(d[14]), "+f"(d[15]), "+f"(d[16]), "+f"(d[17]), "+f"(d[18]), "+f"(d[19]), "+f"(d[20]), "+f"(d[21]), "+f"(d[22]), "+f"(d[23]), "+f"(d[24]), "+f"(d[25]), "+f"(d[26]), "+f"(d[27]), "+f"(d[28]), "+f"(d[29]), "+f"(d[30]), "+f"(d[31]), "+f"(d[32]), "+f"(d[33]), "+f"(d[34]), "+f"(d[35]), "+f"(d[36]), "+f"(d[37]), "+f"(d[38]), "+f"(d[39]), "+f"(d[40]), "+f"(d[41]), "+f"(d[42]), "+f"(d[43]), "+f"(d[44]), "+f"(d[45]), "+f"(d[46]), "+f"(d[47]), "+f"(d[48]), "+f"(d[49]), "+f"(d[50]), "+f"(d[51]), "+f"(d[52]), "+f"(d[53]), "+f"(d[54]), "+f"(d[55]), "+f"(d[56]), "+f"(d[57]), "+f"(d[58]), "+f"(d[59]), "+f"(d[60]), "+f"(d[61]), "+f"(d[62]), "+f"(d[63])
        : "l"(da), "l"(db), "r"(scale_d));
}

__device__ __forceinline__ void wgmma_ss_n256_tb1(float (&d)[128], uint64_t da, uint64_t db, int scale_d) {
    asm volatile("{\n.reg .pred p;\nsetp.ne.b32 p, %130, 0;\n"
        "wgmma.mma_async.sync.aligned.m64n256k16.f32.bf16.bf16 {%0, %1, %2, %3, %4, %5, %6, %7, %8, %9, %10, %11, %12, %13, %14, %15, %16, %17, %18, %19, %20, %21, %22, %23, %24, %25, %26, %27, %28, %29, %30, %31, %32, %33, %34, %35, %36, %37, %38, %39, %40, %41, %42, %43, %44, %45, %46, %47, %48, %49, %50, %51, %52, %53, %54, %55, %56, %57, %58, %59, %60, %61, %62, %63, %64, %65, %66, %67, %68, %69, %70, %71, %72, %73, %74, %75, %76, %77, %78, %79, %80, %81, %82, %83, %84, %85, %86, %87, %88, %89, %90, %91, %92, %93, %94, %95, %96, %97, %98, %99, %100, %101, %102, %103, %104, %105, %106, %107, %108, %109, %110, %111, %112, %113, %114, %115, %116, %117, %118, %119, %120, %121, %122, %123, %124, %125, %126, %127}, %128, %129, p, 1, 1, 0, 1;\n}\n"
        : "+f"(d[0]), "+f"(d[1]), "+f"(d[2]), "+f"(d[3]), "+f"(d[4]), "+f"(d[5]), "+f"(d[6]), "+f"(d[7]), "+f"(d[8]), "+f"(d[9]), "+f"(d[10]), "+f"(d[11]), "+f"(d[12]), "+f"(d[13]), "+f"(d[14]), "+f"(d[15]), "+f"(d[16]), "+f"(d[17]), "+f"(d[18]), "+f"(d[19]), "+f"(d[20]), "+f"(d[21]), "+f"(d[22]), "+f"(d[23]), "+f"(d[24]), "+f"(d[25]), "+f"(d[26]), "+f"(d[27]), "+f"(d[28]), "+f"(d[29]), "+f"(d[30]), "+f"(d[31]), "+f"(d[32]), "+f"(d[33]), "+f"(d[34]), "+f"(d[35]), "+f"(d[36]), "+f"(d[37]), "+f"(d[38]), "+f"(d[39]), "+f"(d[40]), "+f"(d[41]), "+f"(d[42]), "+f"(d[43]), "+f"(d[44]), "+f"(d[45]), "+f"(d[46]), "+f"(d[47]), "+f"(d[48]), "+f"(d[49]), "+f"(d[50]), "+f"(d[51]), "+f"(d[52]), "+f"(d[53]), "+f"(d[54]), "+f"(d[55]), "+f"(d[56]), "+f"(d[57]), "+f"(d[58]), "+f"(d[59]), "+f"(d[60]), "+f"(d[61]), "+f"(d[62]), "+f"(d[63]), "+f"(d[64]), "+f"(d[65]), "+f"(d[66]), "+f"(d[67]), "+f"(d[68]), "+f"(d[69]), "+f"(d[70]), "+f"(d[71]), "+f"(d[72]), "+f"(d[73]), "+f"(d[74]), "+f"(d[75]), "+f"(d[76]), "+f"(d[77]), "+f"(d[78]), "+f"(d[79]), "+f"(d[80]), "+f"(d[81]), "+f"(d[82]), "+f"(d[83]), "+f"(d[84]), "+f"(d[85]), "+f"(d[86]), "+f"(d[87]), "+f"(d[88]), "+f"(d[89]), "+f"(d[90]), "+f"(d[91]), "+f"(d[92]), "+f"(d[93]), "+f"(d[94]), "+f"(d[95]), "+f"(d[96]), "+f"(d[97]), "+f"(d[98]), "+f"(d[99]), "+f"(d[100]), "+f"(d[101]), "+f"(d[102]), "+f"(d[103]), "+f"(d[104]), "+f"(d[105]), "+f"(d[106]), "+f"(d[107]), "+f"(d[108]), "+f"(d[109]), "+f"(d[110]), "+f"(d[111]), "+f"(d[112]), "+f"(d[113]), "+f"(d[114]), "+f"(d[115]), "+f"(d[116]), "+f"(d[117]), "+f"(d[118]), "+f"(d[119]), "+f"(d[120]), "+f"(d[121]), "+f"(d[122]), "+f"(d[123]), "+f"(d[124]), "+f"(d[125]), "+f"(d[126]), "+f"(d[127])
        : "l"(da), "l"(db), "r"(scale_d));
}

__device__ __forceinline__ void wgmma_ss_n32_tb0(float (&d)[16], uint64_t da, uint64_t db, int scale_d) {
    asm volatile("{\n.reg .pred p;\nsetp.ne.b32 p, %18, 0;\n"
        "wgmma.mma_async.sync.aligned.m64n32k16.f32.bf16.bf16 {%0, %1, %2, %3, %4, %5, %6, %7, %8, %9, %10, %11, %12, %13, %14, %15}, %16, %17, p, 1, 1, 0, 0;\n}\n"
        : "+f"(d[0]), "+f"(d[1]), "+f"(d[2]), "+f"(d[3]), "+f"(d[4]), "+f"(d[5]), "+f"(d[6]), "+f"(d[7]), "+f"(d[8]), "+f"(d[9]), "+f"(d[10]), "+f"(d[11]), "+f"(d[12]), "+f"(d[13]), "+f"(d[14]), "+f"(d[15])
        : "l"(da), "l"(db), "r"(scale_d));
}

__device__ __forceinline__ void wgmma_ss_n64_tb0(float (&d)[32], uint64_t da, uint64_t db, int scale_d) {
    asm volatile("{\n.reg .pred p;\nsetp.ne.b32 p, %34, 0;\n"
        "wgmma.mma_async.sync.aligned.m64n64k16.f32.bf16.bf16 {%0, %1, %2, %3, %4, %5, %6, %7, %8, %9, %10, %11, %12, %13, %14, %15, %16, %17, %18, %19, %20, %21, %22, %23, %24, %25, %26, %27, %28, %29, %30, %31}, %32, %33, p, 1, 1, 0, 0;\n}\n"
        : "+f"(d[0]), "+f"(d[1]), "+f"(d[2]), "+f"(d[3]), "+f"(d[4]), "+f"(d[5]), "+f"(d[6]), "+f"(d[7]), "+f"(d[8]), "+f"(d[9]), "+f"(d[10]), "+f"(d[11]), "+f"(d[12]), "+f"(d[13]), "+f"(d[14]), "+f"(d[15]), "+f"(d[16]), "+f"(d[17]), "+f"(d[18]), "+f"(d[19]), "+f"(d[20]), "+f"(d[21]), "+f"(d[22]), "+f"(d[23]), "+f"(d[24]), "+f"(d[25]), "+f"(d[26]), "+f"(d[27]), "+f"(d[28]), "+f"(d[29]), "+f"(d[30]), "+f"(d[31])
        : "l"(da), "l"(db), "r"(scale_d));
}

struct Maps {
    CUtensorMap xa, xa2, xas, xh, wup4, wup8, mqa2, mqa4, mqb1, mqb2, wepi, uc, x, out, wq, wk, fa[3], fb[2], fc[2];
};

__device__ __forceinline__ uint64_t mkd(uint32_t lo) {
    uint64_t d;
    asm("mov.b64 %0, {%1, %2};" : "=l"(d) : "r"(lo), "r"((1024u >> 4) | (1u << 30)));
    return d;
}
__device__ __forceinline__ void ring_ld(uint32_t sb, uint32_t barbase, uint32_t slot8, const CUtensorMap* tm, int c1, int c2) {
    mbar_expect_tx(sb + barbase + slot8, 8192);
    tma3(sb + R1 + slot8 * 1024, tm, 0, c1, c2, sb + barbase + slot8);
}

__device__ __forceinline__ void ring_half(uint32_t sb, uint32_t slot8, uint32_t hoff, const CUtensorMap* tm, int c1, int c2) {
    mbar_expect_tx(sb + B_R1 + slot8, 8192);
    tma3(sb + R1 + slot8 * 2048 + hoff, tm, 0, c1, c2, sb + B_R1 + slot8);
}
__device__ __forceinline__ void ring_full(uint32_t sb, uint32_t slot8, const CUtensorMap* tm, int c1, int c2) {
    mbar_expect_tx(sb + B_R1 + slot8, 16384);
    mbar_arrive(sb + B_R1 + slot8);
    tma3(sb + R1 + slot8 * 2048, tm, 0, c1, c2, sb + B_R1 + slot8);
}
__device__ __forceinline__ void cta_done(int mode) {
    if (mode == 0 && atomicAdd(&g_sync[4], 1) == NCTA + 1) {
#pragma unroll
        for (int i = 0; i < 5; i++) g_sync[i] = 0;
    }
}

__device__ __forceinline__ void fold_cta(const Maps& mp, uint32_t sb, int mode) {
    constexpr uint32_t F_FULL = MISC, F_EMPTY = MISC + 32, F_T1 = MISC + 64, STG = 49152, FOUT = 3 * STG;
    const int tid = threadIdx.x, f = blockIdx.x - NCTA;
    if (mode == 2) return;
    if (tid == 0) {
        for (int i = 0; i < 3; i++) { mbar_init(sb + F_FULL + 8 * i, 1); mbar_init(sb + F_EMPTY + 8 * i, 2); }
        mbar_init(sb + F_T1, 2);
        asm volatile("fence.mbarrier_init.release.cluster;" ::: "memory");
        fence_async();
    }
    __syncthreads();
    const int wg = __shfl_sync(0xffffffffu, tid >> 7, 0);
    int st = 0, ph = 0;
    if (wg == 0) {
        if (tid == 0) {
#pragma unroll 1
            for (int it = 0; it < 96; it++) {
                const int p = it >> 3, kc = it & 7, job = p >> 2;
                if (it == 64) mbar_wait(sb + F_T1, 0);
                mbar_wait(sb + F_EMPTY + 8 * st, ph ^ 1);
                mbar_expect_tx(sb + F_FULL + 8 * st, STG);
                tma3(sb + st * STG, &mp.fa[job], 0, 256 * f + 128 * ((p >> 1) & 1), kc, sb + F_FULL + 8 * st);
                tma3(sb + st * STG + 16384, &mp.fb[job != 0], 0, 64 * kc + (job == 1 ? 512 : 0), 4 * (p & 1), sb + F_FULL + 8 * st);
                if (++st == 3) { st = 0; ph ^= 1; }
            }
        }
        return;
    }
    const int h = wg - 1, lane = tid & 31, w = (tid >> 5) & 3;
    const uint32_t sd = (sb & 0x3FFFF) >> 4;
    const bool el = (tid & 127) == 0;
#pragma unroll 1
    for (int p = 0; p < 12; p++) {
        float acc[128];
        fresh(acc);
#pragma unroll 1
        for (int kc = 0; kc < 8; kc++) {
            mbar_wait(sb + F_FULL + 8 * st, ph);
            wg_fence();
#pragma unroll
            for (int kk = 0; kk < 4; kk++)
                wgmma_ss_n256_tb1(acc, dsc(sd, st * STG + h * 8192 + kk * 32, 16), dsc(sd, st * STG + 16384 + kk * 2048, 8192), 1);
            wg_commit();
            wg_wait<0>();
            if (el) mbar_arrive(sb + F_EMPTY + 8 * st);
            if (++st == 3) { st = 0; ph ^= 1; }
        }
        pin(acc);
        const int job = p >> 2;
        if (el) {
            asm volatile("cp.async.bulk.wait_group 0;" ::: "memory");
            if (p == 4) { fence_async_g(); mbar_arrive(sb + F_T1); }
        }
        bar_sync(3 + h, 128);
        uint32_t r = 16 * w + (lane & 7) + ((lane >> 3) & 1) * 8;
        const float fs = job == 1 ? 0.5f : 1.f;
        if (job == 1) r = (r & ~31) | (((r >> 1) & 3) << 3) | (((r >> 3) & 3) << 1) | (r & 1);
        const uint32_t oa = sb + FOUT + h * 32768 + r * 128 + ((((lane >> 4) ^ r) & 7) << 4);
#pragma unroll
        for (int i = 0; i < 16; i++)
            stsm4((oa ^ ((i & 3) << 5)) + (i >> 2) * 8192, pack2(acc[8 * i] * fs, acc[8 * i + 1] * fs), pack2(acc[8 * i + 2] * fs, acc[8 * i + 3] * fs),
                  pack2(acc[8 * i + 4] * fs, acc[8 * i + 5] * fs), pack2(acc[8 * i + 6] * fs, acc[8 * i + 7] * fs));
        fence_async();
        bar_sync(3 + h, 128);
        if (el) {
            tma3_store(&mp.fc[job != 0], sb + FOUT + h * 32768, 0, 256 * f + 128 * ((p >> 1) & 1) + 64 * h + (job == 1 ? 512 : 0), 4 * (p & 1));
            asm volatile("cp.async.bulk.commit_group;" ::: "memory");
        }
    }
    if (el) {
        asm volatile("cp.async.bulk.wait_group 0;" ::: "memory");
        fence_async_g();
        if (mode == 0) flag_add(&g_sync[3]);
    }
    bar_sync(2, 256);
    if (tid == 128) cta_done(mode);
}

__global__ void __launch_bounds__(384, 1) main_kernel(const __grid_constant__ Maps mp, const bf16* __restrict__ dw, const bf16* wup, const int mode) {
    extern __shared__ __align__(1024) uint8_t smem[];
    const uint32_t sb = smem_u32(smem);
    const int tid = threadIdx.x;
    if (blockIdx.x >= NCTA) { fold_cta(mp, sb, mode); return; }
    const int b = blockIdx.x / TPB, ti = blockIdx.x % TPB;
    const int piece = blockIdx.x & 127;
    if (tid == 0) {
        mbar_init(sb + B_A, 1); mbar_init(sb + B_A2, 1); mbar_init(sb + B_MK, 1);
        for (int i = 0; i < 5; i++) mbar_init(sb + B_R1 + 8 * i, 2);
        asm volatile("fence.mbarrier_init.release.cluster;" ::: "memory");
        fence_async();
        mbar_expect_tx(sb + B_MK, 65536 + 32768);
        tma3(sb + R0, &mp.wq, 0, 64 * (piece >> 4), 0, sb + B_MK);
        tma3(sb + R1 + 32768, &mp.wk, 0, 32 * (piece & 15), 0, sb + B_MK);
        mbar_expect_tx(sb + B_A, 32768);
        mbar_expect_tx(sb + B_A2, 32768 + 3072);
#pragma unroll 1
        for (int i = 0; i < 16; i++) tma4(sb + AT + (i & 7) * 8192 + (i >> 3) * 4096, &mp.xh, 0, 62 * ti - 1 + 32 * (i >> 3), i & 7, b, sb + (i < 8 ? B_A : B_A2));
        asm volatile("cp.async.bulk.shared::cluster.global.mbarrier::complete_tx::bytes [%0], [%1], 3072, [%2];" ::"r"(sb + DWS), "l"(dw), "r"(sb + B_A2) : "memory");
        for (int i = 0; i < 8; i++) mbar_arrive(sb + B_R1 + 8 * (i >> 1));
        if (mode != 1) {
            ring_full(sb, 32, &mp.wup8, 0, 8);
            ring_full(sb, 0, &mp.wup8, 16, 8);
            ring_full(sb, 8, &mp.wup8, 32, 8);
        }
    } else if (tid == 32) {
        mbar_init(sb + B_LN, 1); mbar_init(sb + B_MQ, 1); mbar_init(sb + B_XA, 1);
        mbar_init(sb + B_H1, 2); mbar_init(sb + B_H2, 1); mbar_init(sb + B_H3, 2);
        for (int i = 0; i < 3; i++) { mbar_init(sb + B_KV + 8 * i, 1); mbar_init(sb + B_P + 8 * i, 4); mbar_init(sb + B_GO + 8 * i, 4); }
        for (int i = 0; i < 12; i++) { mbar_init(sb + B_R2 + 8 * i, 1); mbar_init(sb + B_E2 + 8 * i, 4); }
        mbar_init(sb + B_UC, 1); mbar_init(sb + B_X, 1);
        for (int i = 0; i < 4; i++) asm volatile("st.shared.u32 [%0], 0;" ::"r"(sb + CNT + 4 * i) : "memory");
        asm volatile("fence.mbarrier_init.release.cluster;" ::: "memory");
        fence_async();
    }
    __syncthreads();
    const int wg = __shfl_sync(0xffffffffu, tid >> 7, 0);
    const int lane = tid & 31, w = (tid >> 5) & 3;
    const bool w0 = __shfl_sync(0xffffffffu, w, 0) == 0;
    const uint32_t sd = (sb & 0x3FFFF) >> 4;
    const uint32_t adA = sd + (AT >> 4) + (1u << 16);
    const uint32_t bd0 = sd + (R1 >> 4);
    const uint32_t bd2k = bd0 + ((2048u >> 4) << 16);
    const bool el = (tid & 127) == 0;
    const uint32_t lrow = 16 * w + (lane & 7) + ((lane >> 3) & 1) * 8;
    const uint32_t loff = lrow * 128 + ((((lane >> 4) ^ lrow) & 7) << 4);
    const int r0 = 16 * w + (lane >> 2);

    if (wg == 0) {
        asm volatile("setmaxnreg.inc.sync.aligned.u32 184;");
        uint32_t q[112];
        PT(0);
        PG(200);
        {
            float mq[16];
            fresh(mq);
            mbar_wait(sb + B_MK, 0);
            PT(1);
            if (PFW && tid == 32) l2_prefetch((const char*)wup + piece * 8192, 8192);
            wg_fence();
#pragma unroll 1
            for (int c = 0; c < 8; c++)
#pragma unroll
                for (int kk = 0; kk < 4; kk++)
                    wgmma_ss_n32_tb0(mq, dsc(sd, R0 + c * 8192 + kk * 32, 16), dsc(sd, R1 + 32768 + c * 4096 + kk * 32, 16), 1);
            wg_commit();
            wg_wait<0>();
            if (mode != 1 && w0 && elect1()) { ring_full(sb, 16, &mp.wup8, 48, 8); ring_full(sb, 24, &mp.wup8, 64, 8); }
            pin(mq);
            uint32_t* c = reinterpret_cast<uint32_t*>(g_mqk + (64 * (piece >> 4) + r0) * D_ + 32 * (piece & 15) + 2 * (lane & 3));
#pragma unroll
            for (int n = 0; n < 4; n++) { c[4 * n] = pack2(mq[4 * n], mq[4 * n + 1]); c[4 * n + 4 * D_] = pack2(mq[4 * n + 2], mq[4 * n + 3]); }
            fence_async_g();
            bar_sync(1, 128);
            if (el) {
                if (mode == 0) flag_add(&g_sync[2]);
                if (mode == 0) flag_wait(&g_sync[2], NCTA);
                mbar_arrive(sb + B_MQ);
                PT(12);
                mbar_wait(sb + B_LN, 0);
#pragma unroll 1
                for (int c = 0; c < 8; c++) {
                    tma4_store(&mp.xas, sb + AT + c * 8192, 0, 62 * ti, c, b);
                    const unsigned t0 = (unsigned)clock();
                    while (c < 7 && (unsigned)clock() - t0 < XS_GAP) __nanosleep(20);
                }
                asm volatile("cp.async.bulk.commit_group;" ::: "memory");
                if (mode == 1) asm volatile("cp.async.bulk.wait_group 0;" ::: "memory");
            }
            PT(13);
            if (mode == 1) return;
        }
        mbar_wait(sb + B_H1, 0);
        PT(2);
        uint32_t slot8 = 8, par = 1, prev8 = 0;
        auto adv = [&]() { prev8 = slot8; slot8 += 8; if (slot8 == 40) { slot8 = 0; par ^= 1; } };
        {
            float acc[128];
            fresh(acc);
            auto step = [&](int i) {
                const uint32_t aa = adA + (i >> 1) * 512 + (i & 1) * 4, bb = bd0 + ((4096u >> 4) << 16) + slot8 * 128;
                wg_fence();
                wgmma_ss_n256_tb1(acc, mkd(aa), mkd(bb), 1);
                wgmma_ss_n256_tb1(acc, mkd(aa + 2), mkd(bb + 128), 1);
                wg_commit();
                wg_wait<1>();
            };
#pragma unroll 1
            for (int i = 0; i < 12; i++) {
                mbar_wait(sb + B_R1 + slot8, par);
                step(i);
                if (i > 0 && w0 && elect1()) ring_full(sb, prev8, &mp.mqa4, 32 * i + 128, 4);
                adv();
            }
#pragma unroll 1
            for (int i = 12; i < 16; i++) {
                mbar_wait(sb + B_R1 + slot8, par);
                if (i == 15 && el) mbar_arrive(sb + B_H2);
                step(i);
                if (w0 && elect1()) ring_full(sb, prev8, &mp.wup8, 16 * i - 192, 0);
                adv();
            }
            wg_wait<0>();
            if (w0 && elect1()) ring_full(sb, prev8, &mp.wup8, 64, 0);
            pin(acc);
            PT(3);
#pragma unroll
            for (int kk = 0; kk < 4; kk++)
                stsm4((sb + QS + loff) ^ (kk << 5), pack2(acc[96 + 8 * kk], acc[97 + 8 * kk]), pack2(acc[98 + 8 * kk], acc[99 + 8 * kk]),
                      pack2(acc[100 + 8 * kk], acc[101 + 8 * kk]), pack2(acc[102 + 8 * kk], acc[103 + 8 * kk]));
            fence_async();
#pragma unroll
            for (int i = 47; i >= 0; i--) q[64 + i] = pack2v(acc[2 * i], acc[2 * i + 1]);
        }
        if (el) {
            asm volatile("cp.async.bulk.wait_group 0;" ::: "memory");
            if (mode == 0) {
                fence_async_g();
                flag_add(&g_sync[b]);
                flag_wait(&g_sync[b], TPB);
            }
            mbar_arrive(sb + B_XA);
        }
        __syncwarp();
        mbar_wait(sb + B_H3, 0);
        PT(4);
        slot8 = 32; par = 0;
#pragma unroll
        for (int half = 0; half < 2; half++) {
            float acc[64];
            fresh(acc);
            auto step = [&](int m) {
                const uint32_t aa = adA + m * 512, bb = bd0 + ((8192u >> 4) << 16) + slot8 * 128;
                mbar_wait(sb + B_R1 + slot8, par);
                wg_fence();
#pragma unroll
                for (int kk = 0; kk < 4; kk++) wgmma_ss_n128_tb1(acc, mkd(aa + 2 * kk), mkd(bb + 128 * kk), 1);
                wg_commit();
                wg_wait<1>();
            };
            if (half == 0) {
#pragma unroll 1
                for (int m = 0; m < 8; m++) {
                    step(m);
                    if (m > 0 && w0 && elect1()) ring_full(sb, prev8, &mp.mqb2, (64 * m + 256) & 511, (m + 4) >> 3 << 1);
                    adv();
                }
            } else {
#pragma unroll 1
                for (int m = 0; m < 4; m++) {
                    step(m);
                    if (m > 0 && w0 && elect1()) ring_full(sb, prev8, &mp.mqb2, 64 * m + 256, 2);
                    adv();
                }
#pragma unroll 1
                for (int m = 4; m < 8; m++) {
                    step(m);
                    if (w0 && elect1()) {
                        if (m == 4) mbar_expect_tx(sb + B_KV + 8, 65536);
                        tma4(sb + R1 + prev8 * 2048, &mp.xa2, 0, 0, 2 * m - 8, b, sb + B_KV + 8);
                    }
                    adv();
                }
            }
            wg_wait<0>();
            if (w0 && elect1()) {
                if (half == 0) ring_full(sb, prev8, &mp.mqb2, 256, 2);
                else {
                    mbar_expect_tx(sb + B_KV + 16, 65536);
                    tma4(sb + R2, &mp.xa, 0, 64, 0, b, sb + B_KV + 16);
                }
            }
            pin(acc);
#pragma unroll
            for (int i = 31; i >= 0; i--) q[32 * half + i] = pack2v(acc[2 * i], acc[2 * i + 1]);
        }
        bar_sync(1, 128);
        PT(5);

        const float CS = 0.04419417382415922f * 1.4426950408889634f;
        float m0 = -INFINITY, m1 = -INFINITY, l0 = 0.f, l1 = 0.f;
        int s = 0, sn = 1, ph = 0;
        float S[32];
        const bool l0w = lane == 0, q0 = (lane & 3) == 0;
#pragma unroll 1
        for (int j = -1;; j++) {
            if (j >= 0) {
                PL(j, 1);
                if (j == NKV - 1) {
#pragma unroll
                    for (int i = (T_ - 64 * (NKV - 1)) / 2; i < 32; i++) asm volatile("mov.b32 %0, 0xff800000;" : "=f"(S[i]));
                }
                float y[8], z[8];
#pragma unroll
                for (int n = 0; n < 8; n++) { y[n] = fmaxf(S[4 * n], S[4 * n + 1]); z[n] = fmaxf(S[4 * n + 2], S[4 * n + 3]); }
#pragma unroll
                for (int n = 0; n < 4; n++) { y[n] = fmaxf(y[n], y[n + 4]); z[n] = fmaxf(z[n], z[n + 4]); }
                float x0 = fmaxf(fmaxf(y[0], y[1]), fmaxf(fmaxf(y[2], y[3]), m0)), x1 = fmaxf(fmaxf(z[0], z[1]), fmaxf(fmaxf(z[2], z[3]), m1));
                x0 = fmaxf(x0, __shfl_xor_sync(0xffffffffu, x0, 1));
                x1 = fmaxf(x1, __shfl_xor_sync(0xffffffffu, x1, 1));
                x0 = fmaxf(x0, __shfl_xor_sync(0xffffffffu, x0, 2));
                x1 = fmaxf(x1, __shfl_xor_sync(0xffffffffu, x1, 2));
                if ((x0 - m0) * CS <= LAZY) x0 = m0;
                if ((x1 - m1) * CS <= LAZY) x1 = m1;
                const float sc0 = ex2((m0 - x0) * CS), sc1 = ex2((m1 - x1) * CS);
                m0 = x0; m1 = x1;
                const float n0 = -x0 * CS, n1 = -x1 * CS;
                if (q0) { sts_f32(sb + SCL + s * 256 + r0 * 4, sc0); sts_f32(sb + SCL + s * 256 + r0 * 4 + 32, sc1); }
                __syncwarp();
                if (l0w) mbar_arrive(sb + B_P + s * 8);
                if (j < NKV - 1) mbar_wait(sb + B_KV + sn * 8, ph);
                float a0 = 0.f, a1 = 0.f;
                const uint32_t pb = sb + R3 + (s == 0 ? 2 : s - 1) * 8192;
#pragma unroll
                for (int kk = 0; kk < 4; kk++) {
                    float p[8];
#pragma unroll
                    for (int e = 0; e < 8; e++) p[e] = ex2(fmaf(S[8 * kk + e], CS, (e & 2) ? n1 : n0));
                    a0 += (p[0] + p[1]) + (p[4] + p[5]);
                    a1 += (p[2] + p[3]) + (p[6] + p[7]);
                    stsm4((pb + loff) ^ (kk << 5), pack2(p[0], p[1]), pack2(p[2], p[3]), pack2(p[4], p[5]), pack2(p[6], p[7]));
                }
                l0 = fmaf(l0, sc0, a0); l1 = fmaf(l1, sc1, a1);
                PL(j, 2);
                if (j == NKV - 1) break;
            } else {
                mbar_wait(sb + B_KV + 8, 0);
            }
            float Sn[32];
            const uint32_t kd = sd + sn * 4096;
            wg_fence();
#pragma unroll
            for (int kk = 0; kk < 28; kk++) {
                wgmma_rs_n64_tb0(Sn, q[4 * kk], q[4 * kk + 1], q[4 * kk + 2], q[4 * kk + 3], dsc(kd, (kk >> 2) * 8192 + (kk & 3) * 32, 16), kk > 0);
                if (kk == FENCE_AT) { fence_async(); __syncwarp(); }
                if (kk == GO_AT) { PL(j, 3); if (j >= 0 && l0w) mbar_arrive(sb + B_GO + s * 8); }
            }
#pragma unroll
            for (int kk = 0; kk < 4; kk++)
                wgmma_ss_n64_tb0(Sn, dsc(sd, QS + kk * 32, 16), dsc(kd, 7 * 8192 + kk * 32, 16), 1);
            wg_commit();
            PL(j, 0);
            wg_wait<0>();
            pin(Sn);
#pragma unroll
            for (int i = 0; i < 32; i++) S[i] = Sn[i];
            s = sn;
            if (++sn == 3) sn = 0;
            if (sn == 1) ph ^= 1;
        }
        l0 += __shfl_xor_sync(0xffffffffu, l0, 1); l1 += __shfl_xor_sync(0xffffffffu, l1, 1);
        l0 += __shfl_xor_sync(0xffffffffu, l0, 2); l1 += __shfl_xor_sync(0xffffffffu, l1, 2);
        if (q0) { sts_f32(sb + LINV + r0 * 4, rcp(l0)); sts_f32(sb + LINV + r0 * 4 + 32, rcp(l1)); }
        fence_async();
        __syncwarp();
        if (l0w) {
            mbar_arrive(sb + B_GO + s * 8);
            uint32_t slot8 = 8 * w, par = 0;
#pragma unroll 1
            for (int n = 12 + w; n < 128; n += 4) {
                mbar_wait(sb + B_E2 + slot8, par);
                ring_ld(sb, B_R2, slot8, &mp.wepi, 16 * (n >> 1), 4 * (n & 1));
                slot8 += 32;
                if (slot8 >= 96) { slot8 -= 96; par ^= 1; }
            }
        }
        PDUMP();
    } else {
        asm volatile("setmaxnreg.dec.sync.aligned.u32 160;");
        const int h = wg - 1;
        auto red4 = [&](float (&a)[4]) {
            const bool b4 = lane & 16, b3 = lane & 8;
            const float k0 = (b4 ? a[2] : a[0]) + __shfl_xor_sync(0xffffffffu, b4 ? a[0] : a[2], 16);
            const float k1 = (b4 ? a[3] : a[1]) + __shfl_xor_sync(0xffffffffu, b4 ? a[1] : a[3], 16);
            float k = (b3 ? k1 : k0) + __shfl_xor_sync(0xffffffffu, b3 ? k0 : k1, 8);
            k += __shfl_xor_sync(0xffffffffu, k, 4);
            k += __shfl_xor_sync(0xffffffffu, k, 2);
            k += __shfl_xor_sync(0xffffffffu, k, 1);
            return k;
        };
#pragma unroll 1
        for (int bt = 0; bt < 2; bt++) {
            mbar_wait(sb + (bt ? B_A2 : B_A), 0);
            PT(bt ? 13 : 0);
            uint32_t v[4][8];
            float a[4], f[4][16];
            const uint32_t la = sb + AT + (lane >> 3) * 8192 + (32 * bt + 16 * h + 4 * w) * 128 + (((lane & 7) ^ ((w & 1) * 4)) << 4);
#pragma unroll
            for (int r = 0; r < 4; r++) { lds4((la ^ (r << 4)) + r * 128, v[r]); lds4((la ^ (r << 4)) + r * 128 + 32768, v[r] + 4); }
#pragma unroll
            for (int r = 0; r < 4; r++) {
                float s0 = blo(v[r][0]), s1 = bhi(v[r][0]);
#pragma unroll
                for (int i = 1; i < 8; i++) { s0 += blo(v[r][i]); s1 += bhi(v[r][i]); }
                a[r] = s0 + s1;
            }
            const float mu = red4(a) * (1.f / D_);
            const uint32_t mp2 = pack2(mu, mu);
#pragma unroll
            for (int r = 0; r < 4; r++) {
                const uint32_t m2 = __shfl_sync(0xffffffffu, mp2, 8 * r);
                float s0 = 0.f, s1 = 0.f;
#pragma unroll
                for (int i = 0; i < 8; i++) {
                    const uint32_t d = bsub2(v[r][i], m2);
                    f[r][2 * i] = blo(d); f[r][2 * i + 1] = bhi(d);
                    s0 = fmaf(f[r][2 * i], f[r][2 * i], s0); s1 = fmaf(f[r][2 * i + 1], f[r][2 * i + 1], s1);
                }
                a[r] = s0 + s1;
            }
            const float dm = mu - blo(mp2);
            float sd_ = bfr(bfr(fmaxf(fmaf(red4(a), 1.f / D_, -dm * dm), 0.f)) + 1e-5f);
            asm("sqrt.approx.f32 %0, %0;" : "+f"(sd_));
            const float ri = rcp(bfr(sd_));
#pragma unroll
            for (int r = 0; r < 4; r++) {
                const float rinv = __shfl_sync(0xffffffffu, ri, 8 * r);
#pragma unroll
                for (int i = 0; i < 8; i++) v[r][i] = pack2(f[r][2 * i] * rinv, f[r][2 * i + 1] * rinv);
                sts4((la ^ (r << 4)) + r * 128, v[r][0], v[r][1], v[r][2], v[r][3]);
                sts4((la ^ (r << 4)) + r * 128 + 32768, v[r][4], v[r][5], v[r][6], v[r][7]);
            }
        }
        fence_async();
        bar_sync(2, 256);
        if (tid == 128) mbar_arrive(sb + B_LN);
        if (mode == 1) return;
        float acc[128];
#pragma unroll
        for (int pass = 0; pass < 2; pass++) {
            if (pass == 1) mbar_wait(sb + B_H2, 0);
            PT(1 + 3 * pass);
            fresh(acc);
            uint32_t slot8 = pass ? 16 : 32, par = 0, prev8 = 0;
            auto adv = [&]() { prev8 = slot8; slot8 += 8; if (slot8 == 40) { slot8 = 0; par ^= 1; } };
            auto step = [&](int kk) {
                wg_fence();
                wgmma_ss_n256_tb1(acc, mkd(adA + (kk >> 2) * 512 + (kk & 3) * 2), mkd(bd2k + h * 512 + slot8 * 128), 1);
                wg_commit();
                wg_wait<1>();
            };
#pragma unroll 1
            for (int kk = 0; kk < 28; kk++) {
                mbar_wait(sb + B_R1 + slot8, par);
                step(kk);
                if (kk > 0 && w0 && elect1()) ring_half(sb, prev8, h * 8192, &mp.wup4, 16 * kk + 64, (pass ? 0 : 8) + 4 * h);
                adv();
            }
            if (pass == 0 && w0) mbar_wait(sb + B_MQ, 0);
#pragma unroll 1
            for (int kk = 28; kk < 32; kk++) {
                mbar_wait(sb + B_R1 + slot8, par);
                if (kk == 31 && el) mbar_arrive(sb + (pass ? B_H3 : B_H1));
                step(kk);
                if (w0 && elect1()) ring_half(sb, prev8, h * 8192, pass ? &mp.mqb1 : &mp.mqa2, (pass ? 64 : 32) * (kk - 28), pass ? h : 4 + 2 * h);
                adv();
            }
            wg_wait<0>();
            if (w0 && elect1()) ring_half(sb, prev8, h * 8192, pass ? &mp.mqb1 : &mp.mqa2, pass ? 256 : 128, pass ? h : 4 + 2 * h);
            pin(acc);
            PT(2 + 3 * pass);
            if (pass == 0) {
                float s0 = 0.f, s1 = 0.f, v0 = 0.f, v1 = 0.f;
#pragma unroll
                for (int n = 0; n < 32; n++) {
#pragma unroll
                    for (int e = 0; e < 4; e++) acc[4 * n + e] = gelu2(acc[4 * n + e]);
                    s0 += acc[4 * n] + acc[4 * n + 1]; s1 += acc[4 * n + 2] + acc[4 * n + 3];
                    v0 = fmaf(acc[4 * n], acc[4 * n], v0); v0 = fmaf(acc[4 * n + 1], acc[4 * n + 1], v0);
                    v1 = fmaf(acc[4 * n + 2], acc[4 * n + 2], v1); v1 = fmaf(acc[4 * n + 3], acc[4 * n + 3], v1);
                }
#pragma unroll
                for (int o = 1; o < 4; o <<= 1) {
                    s0 += __shfl_xor_sync(0xffffffffu, s0, o); s1 += __shfl_xor_sync(0xffffffffu, s1, o);
                    v0 += __shfl_xor_sync(0xffffffffu, v0, o); v1 += __shfl_xor_sync(0xffffffffu, v1, o);
                }
                if ((lane & 3) == 0) {
                    uint32_t a = sb + STAT + h * 512 + r0 * 8;
                    sts_f32(a, s0); sts_f32(a + 4, v0); sts_f32(a + 64, s1); sts_f32(a + 68, v1);
                }
                bar_sync(2, 256);
                {
                    uint32_t a = sb + STAT + (h ^ 1) * 512 + r0 * 8;
                    s0 = (s0 + lds_f32(a)) * (1.f / 512.f); v0 = (v0 + lds_f32(a + 4)) * (1.f / 512.f);
                    s1 = (s1 + lds_f32(a + 64)) * (1.f / 512.f); v1 = (v1 + lds_f32(a + 68)) * (1.f / 512.f);
                }
                v0 = rsqrtf(fmaxf(fmaf(-s0, s0, v0), 0.f) + 4e-5f); v1 = rsqrtf(fmaxf(fmaf(-s1, s1, v1), 0.f) + 4e-5f);
                s0 = -s0 * v0; s1 = -s1 * v1;
#pragma unroll
                for (int p = 0; p < 16; p++)
                    stsm4(((sb + R0 + h * 32768 + loff) ^ ((p & 3) << 5)) + (p >> 2) * 8192,
                          pack2(fmaf(acc[8 * p], v0, s0), fmaf(acc[8 * p + 1], v0, s0)), pack2(fmaf(acc[8 * p + 2], v1, s1), fmaf(acc[8 * p + 3], v1, s1)),
                          pack2(fmaf(acc[8 * p + 4], v0, s0), fmaf(acc[8 * p + 5], v0, s0)), pack2(fmaf(acc[8 * p + 6], v1, s1), fmaf(acc[8 * p + 7], v1, s1)));
            } else {
                uint32_t u[64];
#pragma unroll
                for (int i = 63; i >= 0; i--) u[i] = pack2v(gelu2(acc[2 * i]), gelu2(acc[2 * i + 1]));
                PT(12);
                bar_sync(3 + h, 128);
                const uint32_t rm = lrow == 0 ? 0 : lrow - 1, rp = lrow == 63 ? 63 : lrow + 1;
                const uint32_t gb = sb + R0 + h * 32768;
                const uint32_t am = gb + rm * 128 + ((((lane >> 4) ^ rm) & 7) << 4), ap = gb + rp * 128 + ((((lane >> 4) ^ rp) & 7) << 4), ac = gb + loff;
                const uint32_t dwa = sb + DWS + 512 * h + ((lane >> 3) & 1) * 16 + (lane >> 4) * 1024;
                bf16* ucp = g_uc + ((size_t)blockIdx.x * 64 + r0) * D_ + 256 * h + 8 * (lane & 3);
#pragma unroll
                for (int m = 0; m < 8; m++) {
                    uint32_t o[8], g0[2][4], g1[2][4], g2[2][4], d[2][4], d2[2][2];
#pragma unroll
                    for (int pp = 0; pp < 2; pp++) {
                        const int p = 2 * m + pp;
                        const uint32_t co = (p >> 2) * 8192, cx = (p & 3) << 5;
                        ldsm4(dwa + 32 * p, d[pp]);
                        ldsm2(dwa + 32 * p + 2048, d2[pp]);
                        ldsm4((am ^ cx) + co, g0[pp]);
                        ldsm4((ac ^ cx) + co, g1[pp]);
                        ldsm4((ap ^ cx) + co, g2[pp]);
                    }
#pragma unroll
                    for (int pp = 0; pp < 2; pp++)
#pragma unroll
                        for (int e = 0; e < 4; e++)
                            o[4 * (e & 1) + 2 * pp + (e >> 1)] =
                                bmul2(u[8 * m + 4 * pp + e], bfma2(g2[pp][e], d2[pp][e >> 1], bfma2(g1[pp][e], d[pp][2 + (e >> 1)], bmul2(g0[pp][e], d[pp][e >> 1]))));
                    stg4(ucp + 32 * m, o[0], o[1], o[2], o[3]);
                    stg4(ucp + 32 * m + 8 * D_, o[4], o[5], o[6], o[7]);
                }
                bar_sync(2, 256);
                if (tid == 128) {
                    mbar_wait(sb + B_XA, 0);
                    mbar_expect_tx(sb + B_KV, 65536);
                    tma4(sb + R0, &mp.xa, 0, 128, 0, b, sb + B_KV);
                }
            }
            PT(3 + 3 * pass);
        }
        int s = 1, ph = 0;
        fresh(acc);
#pragma unroll 1
        for (int j = 0; j < NKV; j++) {
            mbar_wait(sb + B_P + s * 8, ph);
            PL(j, 0);
            if (j > 0) {
                const float sc0 = lds_f32(sb + SCL + s * 256 + r0 * 4), sc1 = lds_f32(sb + SCL + s * 256 + r0 * 4 + 32);
                if (__any_sync(0xffffffffu, sc0 != 1.f || sc1 != 1.f)) {
#pragma unroll
                    for (int n = 0; n < 32; n++) { acc[4 * n] *= sc0; acc[4 * n + 1] *= sc0; acc[4 * n + 2] *= sc1; acc[4 * n + 3] *= sc1; }
                }
            }
            mbar_wait(sb + B_GO + s * 8, ph);
            PL(j, 1);
            const uint32_t vd = sd + s * 4096 + h * 2048, pd = sd + (s == 0 ? 2 : s - 1) * 512;
            pin(acc);
            wg_fence();
#pragma unroll
            for (int kk = 0; kk < 4; kk++) wgmma_ss_n256_tb1(acc, dsc(pd, R3 + kk * 32, 16), dsc(vd, kk * 2048, 8192), 1);
            wg_commit();
            wg_wait<0>();
            pin(acc);
            PL(j, 2);
            if (w0 && elect1()) {
                if (j == NKV - 5 && mode == 0) flag_wait(&g_sync[3], 4);
                if (atom_inc_s(sb + CNT + 4 * s) & 1) {
                    if (j + 3 < NKV) {
                        mbar_expect_tx(sb + B_KV + s * 8, 65536);
                        tma4(sb + s * 65536, &mp.xa, 0, 64 * (j + 3), 0, b, sb + B_KV + s * 8);
                    } else if (j < NKV - 1) {
                        const int n0 = j == NKV - 3 ? 0 : 8, n1 = j == NKV - 3 ? 8 : 12;
#pragma unroll 1
                        for (int n = n0; n < n1; n++) ring_ld(sb, B_R2, n * 8, &mp.wepi, 16 * (n >> 1), 4 * (n & 1));
                    }
                }
            }
            if (++s == 3) s = 0;
            if (s == 1) ph ^= 1;
        }
        {
            const float i0 = lds_f32(sb + LINV + r0 * 4), i1 = lds_f32(sb + LINV + r0 * 4 + 32);
#pragma unroll
            for (int p = 0; p < 16; p++)
                stsm4(((sb + R0 + h * 32768 + loff) ^ ((p & 3) << 5)) + (p >> 2) * 8192,
                      pack2(acc[8 * p] * i0, acc[8 * p + 1] * i0), pack2(acc[8 * p + 2] * i1, acc[8 * p + 3] * i1),
                      pack2(acc[8 * p + 4] * i0, acc[8 * p + 5] * i0), pack2(acc[8 * p + 6] * i1, acc[8 * p + 7] * i1));
        }
        fence_async();
        fence_async_g();
        bar_sync(2, 256);
        if (tid == 128) {
            mbar_expect_tx(sb + B_UC, 65536);
            tma3(sb + UCT, &mp.uc, 0, 64 * blockIdx.x, 0, sb + B_UC);
        }
        PT(7);
        fresh(acc);
        {
            uint32_t slot8 = 8 * h, par = 0, prev8 = 0;
#pragma unroll 1
            for (int kk = 0; kk < 64; kk++) {
                if (kk == 32) mbar_wait(sb + B_UC, 0);
                mbar_wait(sb + B_R2 + slot8, par);
                wg_fence();
                wgmma_ss_n256_tb1(acc, mkd(sd + (1u << 16) + (kk < 32 ? (R0 >> 4) : (UCT >> 4) - 4096) + (kk >> 2) * 512 + (kk & 3) * 2), mkd(bd2k + slot8 * 64), 1);
                wg_commit();
                wg_wait<1>();
                if (kk > 0 && lane == 0) mbar_arrive(sb + B_E2 + prev8);
                if (kk == 32 && w0 && elect1() && (atom_inc_s(sb + CNT + 12) & 1)) {
                    mbar_expect_tx(sb + B_X, 65536);
                    tma4(sb + R0, &mp.x, 0, 62 * ti, 0, b, sb + B_X);
                }
                prev8 = slot8;
                slot8 += 16;
                if (slot8 >= 96) { slot8 -= 96; par ^= 1; }
            }
        }
        wg_wait<0>();
        pin(acc);
        PT(8);
        mbar_wait(sb + B_X, 0);
        PT(9);
        {
            const uint32_t sr = (lrow + 63) & 63;
            const uint32_t xoff = sr * 128 + ((((lane >> 4) ^ sr) & 7) << 4);
#pragma unroll
            for (int p = 0; p < 16; p++) {
                const uint32_t a = ((sb + R0 + h * 32768 + xoff) ^ ((p & 3) << 5)) + (p >> 2) * 8192;
                uint32_t xv[4];
                ldsm4(a, xv);
#pragma unroll
                for (int e = 0; e < 4; e++)
                    xv[e] = pack2(acc[8 * p + 2 * e] + __uint_as_float(xv[e] << 16), acc[8 * p + 2 * e + 1] + __uint_as_float(xv[e] & 0xffff0000u));
                stsm4(a, xv[0], xv[1], xv[2], xv[3]);
            }
        }
        fence_async();
        bar_sync(3 + h, 128);
        if (el) {
            for (int c = 0; c < 4; c++) tma4_store(&mp.out, sb + R0 + (4 * h + c) * 8192, 0, 62 * ti, 4 * h + c, b);
            asm volatile("cp.async.bulk.commit_group;" ::: "memory");
            PT(10);
            if (h == 0) cta_done(mode);
            asm volatile("cp.async.bulk.wait_group.read 0;" ::: "memory");
        }
        PT(11);
        PG(201);
        PDUMP();
    }
}

typedef CUresult (*PFN_enc)(CUtensorMap*, CUtensorMapDataType, cuuint32_t, void*, const cuuint64_t*, const cuuint64_t*,
                            const cuuint32_t*, const cuuint32_t*, CUtensorMapInterleave, CUtensorMapSwizzle,
                            CUtensorMapL2promotion, CUtensorMapFloatOOBfill);

static void enc(PFN_enc f, CUtensorMap* m, void* base, int rank, const cuuint64_t* dims, const cuuint64_t* strides, const cuuint32_t* box) {
    cuuint32_t es[5] = {1, 1, 1, 1, 1};
    f(m, CU_TENSOR_MAP_DATA_TYPE_BFLOAT16, rank, base, dims, strides, box, es, CU_TENSOR_MAP_INTERLEAVE_NONE,
      CU_TENSOR_MAP_SWIZZLE_128B, CU_TENSOR_MAP_L2_PROMOTION_L2_256B, CU_TENSOR_MAP_FLOAT_OOB_FILL_NONE);
}
static void enc_act(PFN_enc f, CUtensorMap* m, void* base, int rows, int chunks, int trows = T_, int pitch = T_) {
    cuuint64_t dims[4] = {64, (cuuint64_t)trows, 8, (cuuint64_t)NB_};
    cuuint64_t st[3] = {1024, 128, (cuuint64_t)pitch * 1024};
    cuuint32_t box[4] = {64, (cuuint32_t)rows, (cuuint32_t)chunks, 1};
    enc(f, m, base, 4, dims, st, box);
}
static void enc_w(PFN_enc f, CUtensorMap* m, void* base, int krows, int ncols, int bk, int bc) {
    cuuint64_t dims[3] = {64, (cuuint64_t)krows, (cuuint64_t)(ncols / 64)};
    cuuint64_t st[2] = {(cuuint64_t)ncols * 2, 128};
    cuuint32_t box[3] = {64, (cuuint32_t)bk, (cuuint32_t)bc};
    enc(f, m, base, 3, dims, st, box);
}

extern "C" void kernel_launch(void* const* d_in, const int* in_sizes, int n_in, void* d_out, int out_size) {
    const bf16* x = (const bf16*)d_in[0];
    static PFN_enc fenc = nullptr;
    static void *p_xa, *p_mqk, *p_wepi, *p_uc, *p_t1;
    static int fused = 0;
    if (!fenc) {
        void* fn = nullptr;
        cudaDriverEntryPointQueryResult qr;
        cudaGetDriverEntryPoint("cuTensorMapEncodeTiled", &fn, cudaEnableDefault, &qr);
        fenc = (PFN_enc)fn;
        cudaGetSymbolAddress(&p_xa, g_xa);
        cudaGetSymbolAddress(&p_mqk, g_mqk);
        cudaGetSymbolAddress(&p_wepi, g_wepi);
        cudaGetSymbolAddress(&p_uc, g_uc);
        cudaGetSymbolAddress(&p_t1, g_t1);
        cudaFuncSetAttribute(main_kernel, cudaFuncAttributeMaxDynamicSharedMemorySize, SMEM_BYTES);
        int dev = 0, sms = 0, occ = 0;
        cudaGetDevice(&dev);
        cudaDeviceGetAttribute(&sms, cudaDevAttrMultiProcessorCount, dev);
        cudaOccupancyMaxActiveBlocksPerMultiprocessor(&occ, main_kernel, 384, SMEM_BYTES);
        fused = sms * occ >= NCTA + 2;
    }
    Maps mp;
    enc_act(fenc, &mp.xa, (char*)p_xa + 1024, 64, 8, T_, T_ + 8);
    enc_act(fenc, &mp.xa2, (char*)p_xa + 1024, 64, 2, T_, T_ + 8);
    enc_act(fenc, &mp.xas, p_xa, 64, 1, T_ + 1, T_ + 8);
    enc_act(fenc, &mp.x, (void*)x, 64, 8);
    enc_act(fenc, &mp.xh, (void*)x, 32, 1);
    enc_act(fenc, &mp.out, d_out, 62, 1);
    enc_w(fenc, &mp.wup4, d_in[5], 512, 1024, 16, 4);
    enc_w(fenc, &mp.wup8, d_in[5], 512, 1024, 16, 8);
    enc_w(fenc, &mp.mqa2, p_mqk, 512, 512, 32, 2);
    enc_w(fenc, &mp.mqa4, p_mqk, 512, 512, 32, 4);
    enc_w(fenc, &mp.mqb1, p_mqk, 512, 512, 64, 1);
    enc_w(fenc, &mp.mqb2, p_mqk, 512, 512, 64, 2);
    enc_w(fenc, &mp.wepi, p_wepi, 1024, 512, 16, 4);
    enc_w(fenc, &mp.uc, p_uc, NCTA * 64, 512, 64, 8);
    enc_w(fenc, &mp.wq, d_in[1], 512, 512, 64, 8);
    enc_w(fenc, &mp.wk, d_in[2], 512, 512, 32, 8);
    enc_w(fenc, &mp.fa[0], d_in[3], 512, 512, 128, 1);
    enc_w(fenc, &mp.fa[1], d_in[7], 512, 512, 128, 1);
    enc_w(fenc, &mp.fa[2], p_t1, 512, 512, 128, 1);
    enc_w(fenc, &mp.fb[0], d_in[4], 512, 512, 64, 4);
    enc_w(fenc, &mp.fb[1], d_in[8], 1024, 512, 64, 4);
    enc_w(fenc, &mp.fc[0], p_t1, 512, 512, 64, 4);
    enc_w(fenc, &mp.fc[1], p_wepi, 1024, 512, 64, 4);
    cudaStream_t st = cudaStreamPerThread;
    if (fused) {
        main_kernel<<<NCTA + 2, 384, SMEM_BYTES, st>>>(mp, (const bf16*)d_in[6], (const bf16*)d_in[5], 0);
    } else {
        main_kernel<<<NCTA + 2, 384, SMEM_BYTES, st>>>(mp, (const bf16*)d_in[6], (const bf16*)d_in[5], 1);
        main_kernel<<<NCTA + 2, 384, SMEM_BYTES, st>>>(mp, (const bf16*)d_in[6], (const bf16*)d_in[5], 2);
    }
}
```

```cpp
#include <cuda_runtime.h>
#include <cuda_bf16.h>
#include <cuda.h>
#include <stdint.h>

typedef __nv_bfloat16 bf16;

constexpr int T_ = 4000, D_ = 512, NB_ = 2;
constexpr int TPB = 65;
constexpr int NCTA = TPB * NB_;
constexpr int NKV = 63;

__device__ __align__(1024) bf16 g_xa[NB_ * (T_ + 8) * D_];
__device__ __align__(1024) bf16 g_mqk[D_ * D_];
__device__ __align__(1024) bf16 g_t1[D_ * D_];
__device__ __align__(1024) bf16 g_wepi[2 * D_ * D_];
__device__ __align__(1024) bf16 g_uc[NCTA * 64 * D_];
__device__ unsigned g_sync[8];

#define PT(i) do { if (el) asm volatile("st.shared.u32 [%0], %1;" ::"r"(sb + MISC + 2560), "r"((unsigned)clock())); } while (0)
#define PG(i)
#define PLM 15
#define PL(j, q) do { if ((PLM >> ((q) + (wg ? 4 : 0))) & 1) PT(0); } while (0)
#define PDUMP()

#define FENCE_AT 1
#define GO_AT 25
#define LAZY 8.f
#define XS_GAP 800
#define PFW 1
constexpr uint32_t R0 = 0, R1 = 65536, R2 = 131072, R3 = 196608, QS = 221184, MISC = 229376;
constexpr uint32_t AT = 147456, DWS = R3 + 16384, UCT = 163840;
constexpr uint32_t SMEM_BYTES = 232448;
constexpr uint32_t B_A = MISC, B_R1 = MISC + 8  , B_MK = MISC + 48, B_LN = MISC + 56, B_MQ = MISC + 64, B_XA = MISC + 72, B_A2 = MISC + 80,
                   B_H1 = MISC + 88, B_H2 = MISC + 96, B_H3 = MISC + 104,
                   B_KV = MISC + 112, B_P = MISC + 136, B_GO = MISC + 160, B_R2 = MISC + 184, B_UC = MISC + 280,
                   B_X = MISC + 288, CNT = MISC + 296  , B_E2 = MISC + 320  , SCL = MISC + 512  ,
                   LINV = MISC + 1280  , STAT = MISC + 1536  ;

__device__ __forceinline__ uint32_t smem_u32(const void* p) { return (uint32_t)__cvta_generic_to_shared(p); }
__device__ __forceinline__ void wg_fence() { asm volatile("wgmma.fence.sync.aligned;" ::: "memory"); }
__device__ __forceinline__ void wg_commit() { asm volatile("wgmma.commit_group.sync.aligned;" ::: "memory"); }
template <int N> __device__ __forceinline__ void wg_wait() { asm volatile("wgmma.wait_group.sync.aligned %0;" ::"n"(N) : "memory"); }
__device__ __forceinline__ uint64_t dsc(uint32_t sd, uint32_t off, uint32_t lbo) {
    uint32_t lo = sd + (off >> 4) + ((lbo >> 4) << 16);
    uint64_t d;
    asm("mov.b64 %0, {%1, %2};" : "=l"(d) : "r"(lo), "r"((1024u >> 4) | (1u << 30)));
    return d;
}
__device__ __forceinline__ bool elect1() {
    uint32_t p;
    asm volatile("{\n.reg .pred p;\nelect.sync _|p, 0xffffffff;\nselp.u32 %0, 1, 0, p;\n}\n" : "=r"(p));
    return p != 0;
}
__device__ __forceinline__ void mbar_init(uint32_t bar, int cnt) { asm volatile("mbarrier.init.shared::cta.b64 [%0], %1;" ::"r"(bar), "r"(cnt) : "memory"); }
__device__ __forceinline__ void mbar_expect_tx(uint32_t bar, uint32_t bytes) { asm volatile("mbarrier.arrive.expect_tx.shared::cta.b64 _, [%0], %1;" ::"r"(bar), "r"(bytes) : "memory"); }
__device__ __forceinline__ void mbar_arrive(uint32_t bar) { asm volatile("mbarrier.arrive.shared::cta.b64 _, [%0];" ::"r"(bar) : "memory"); }
__device__ __forceinline__ void mbar_wait(uint32_t bar, uint32_t parity) {
    uint32_t ok;
#pragma unroll 1
    for (uint32_t it = 0;; ++it) {
        asm volatile("{\n.reg .pred p;\nmbarrier.try_wait.parity.shared::cta.b64 p, [%1], %2;\nselp.u32 %0, 1, 0, p;\n}\n" : "=r"(ok) : "r"(bar), "r"(parity) : "memory");
        if (ok) break;
        if (it > (1u << 20)) __trap();
    }
}
__device__ __forceinline__ void fence_async() { asm volatile("fence.proxy.async.shared::cta;" ::: "memory"); }
__device__ __forceinline__ void fence_async_g() { asm volatile("fence.proxy.async.global;" ::: "memory"); }
__device__ __forceinline__ void bar_sync(int id, int n) { asm volatile("bar.sync %0, %1;" ::"r"(id), "r"(n) : "memory"); }
__device__ __forceinline__ void tma3(uint32_t dst, const CUtensorMap* tm, int c0, int c1, int c2, uint32_t bar) {
    asm volatile("cp.async.bulk.tensor.3d.shared::cluster.global.mbarrier::complete_tx::bytes [%0], [%1, {%3, %4, %5}], [%2];"
                 ::"r"(dst), "l"(tm), "r"(bar), "r"(c0), "r"(c1), "r"(c2) : "memory");
}
__device__ __forceinline__ void tma4(uint32_t dst, const CUtensorMap* tm, int c0, int c1, int c2, int c3, uint32_t bar) {
    asm volatile("cp.async.bulk.tensor.4d.shared::cluster.global.mbarrier::complete_tx::bytes [%0], [%1, {%3, %4, %5, %6}], [%2];"
                 ::"r"(dst), "l"(tm), "r"(bar), "r"(c0), "r"(c1), "r"(c2), "r"(c3) : "memory");
}
__device__ __forceinline__ void tma4_store(const CUtensorMap* tm, uint32_t src, int c0, int c1, int c2, int c3) {
    asm volatile("cp.async.bulk.tensor.4d.global.shared::cta.bulk_group [%0, {%2, %3, %4, %5}], [%1];"
                 ::"l"(tm), "r"(src), "r"(c0), "r"(c1), "r"(c2), "r"(c3) : "memory");
}
__device__ __forceinline__ void tma3_store(const CUtensorMap* tm, uint32_t src, int c0, int c1, int c2) {
    asm volatile("cp.async.bulk.tensor.3d.global.shared::cta.bulk_group [%0, {%2, %3, %4}], [%1];"
                 ::"l"(tm), "r"(src), "r"(c0), "r"(c1), "r"(c2) : "memory");
}
__device__ __forceinline__ void stsm4(uint32_t addr, uint32_t a, uint32_t b, uint32_t c, uint32_t d) {
    asm volatile("stmatrix.sync.aligned.m8n8.x4.shared.b16 [%0], {%1, %2, %3, %4};" ::"r"(addr), "r"(a), "r"(b), "r"(c), "r"(d) : "memory");
}
__device__ __forceinline__ void ldsm4(uint32_t addr, uint32_t (&r)[4]) {
    asm volatile("ldmatrix.sync.aligned.m8n8.x4.shared.b16 {%0, %1, %2, %3}, [%4];" : "=r"(r[0]), "=r"(r[1]), "=r"(r[2]), "=r"(r[3]) : "r"(addr) : "memory");
}
__device__ __forceinline__ void ldsm2(uint32_t addr, uint32_t (&r)[2]) {
    asm volatile("ldmatrix.sync.aligned.m8n8.x2.shared.b16 {%0, %1}, [%2];" : "=r"(r[0]), "=r"(r[1]) : "r"(addr) : "memory");
}
__device__ __forceinline__ void stg4(void* p, uint32_t a, uint32_t b, uint32_t c, uint32_t d) {
    asm volatile("st.global.v4.u32 [%0], {%1, %2, %3, %4};" ::"l"(p), "r"(a), "r"(b), "r"(c), "r"(d) : "memory");
}
__device__ __forceinline__ uint32_t pack2(float lo, float hi) {
    uint32_t r;
    asm("cvt.rn.bf16x2.f32 %0, %1, %2;" : "=r"(r) : "f"(hi), "f"(lo));
    return r;
}
__device__ __forceinline__ uint32_t pack2v(float lo, float hi) {
    uint32_t r;
    asm volatile("cvt.rn.bf16x2.f32 %0, %1, %2;" : "=r"(r) : "f"(hi), "f"(lo));
    return r;
}
__device__ __forceinline__ uint32_t bmul2(uint32_t a, uint32_t b) { uint32_t r; asm("mul.rn.bf16x2 %0, %1, %2;" : "=r"(r) : "r"(a), "r"(b)); return r; }
__device__ __forceinline__ uint32_t bfma2(uint32_t a, uint32_t b, uint32_t c) { uint32_t r; asm("fma.rn.bf16x2 %0, %1, %2, %3;" : "=r"(r) : "r"(a), "r"(b), "r"(c)); return r; }
__device__ __forceinline__ float ex2(float x) { float r; asm("ex2.approx.ftz.f32 %0, %1;" : "=f"(r) : "f"(x)); return r; }
__device__ __forceinline__ float rcp(float x) { float r; asm("rcp.approx.ftz.f32 %0, %1;" : "=f"(r) : "f"(x)); return r; }
__device__ __forceinline__ float gelu2(float x) {
    float t = fmaf(x * x, 0.044715f * 0.7978845608028654f, 0.7978845608028654f), th;
    asm("tanh.approx.f32 %0, %1;" : "=f"(th) : "f"(x * t));
    return fmaf(x, th, x);
}
__device__ __forceinline__ uint32_t ldg_v(const uint32_t* p) { uint32_t v; asm volatile("ld.global.nc.u32 %0, [%1];" : "=r"(v) : "l"(p)); return v; }
__device__ __forceinline__ float lds_f32(uint32_t a) { float v; asm volatile("ld.shared.f32 %0, [%1];" : "=f"(v) : "r"(a) : "memory"); return v; }
__device__ __forceinline__ void sts_f32(uint32_t a, float v) { asm volatile("st.shared.f32 [%0], %1;" ::"r"(a), "f"(v) : "memory"); }
__device__ __forceinline__ uint32_t atom_inc_s(uint32_t a) { uint32_t v; asm volatile("atom.relaxed.cta.shared.add.u32 %0, [%1], 1;" : "=r"(v) : "r"(a) : "memory"); return v; }
__device__ __forceinline__ void lds4(uint32_t a, uint32_t* r) {
    asm volatile("ld.shared.v4.u32 {%0, %1, %2, %3}, [%4];" : "=r"(r[0]), "=r"(r[1]), "=r"(r[2]), "=r"(r[3]) : "r"(a) : "memory");
}
__device__ __forceinline__ void sts4(uint32_t a, uint32_t x, uint32_t y, uint32_t z, uint32_t t) {
    asm volatile("st.shared.v4.u32 [%0], {%1, %2, %3, %4};" ::"r"(a), "r"(x), "r"(y), "r"(z), "r"(t) : "memory");
}
__device__ __forceinline__ uint32_t bsub2(uint32_t a, uint32_t b) { uint32_t r; asm("sub.rn.bf16x2 %0, %1, %2;" : "=r"(r) : "r"(a), "r"(b)); return r; }
__device__ __forceinline__ float blo(uint32_t v) { return __uint_as_float(v << 16); }
__device__ __forceinline__ float bhi(uint32_t v) { return __uint_as_float(v & 0xffff0000u); }
__device__ __forceinline__ float bfr(float x) { return __bfloat162float(__float2bfloat16_rn(x)); }
__device__ __forceinline__ void l2_prefetch(const void* p, uint32_t bytes) { asm volatile("cp.async.bulk.prefetch.L2.global [%0], %1;" ::"l"(p), "r"(bytes) : "memory"); }
__device__ __forceinline__ void flag_add(unsigned* p) { asm volatile("red.release.gpu.global.add.u32 [%0], 1;" ::"l"(p) : "memory"); }
__device__ __forceinline__ void flag_wait(const unsigned* p, unsigned target) {
#pragma unroll 1
    for (uint32_t it = 0;; ++it) {
        unsigned v;
        asm volatile("ld.acquire.gpu.global.u32 %0, [%1];" : "=r"(v) : "l"(p) : "memory");
        if (v >= target) break;
        if (it > (1u << 20)) __trap();
    }
    fence_async_g();
}
template <int N> __device__ __forceinline__ void pin(float (&a)[N]) {
#pragma unroll
    for (int i = 0; i < N; i++) asm volatile("" : "+f"(a[i])::"memory");
}

template <int N> __device__ __forceinline__ void fresh(float (&a)[N]) {
#pragma unroll
    for (int i = 0; i < N; i++) a[i] = 0.f;
    pin(a);
}

__device__ __forceinline__ void wgmma_rs_n64_tb0(float (&d)[32], uint32_t a0, uint32_t a1, uint32_t a2, uint32_t a3, uint64_t db, int scale_d) {
    asm volatile("{\n.reg .pred p;\nsetp.ne.b32 p, %37, 0;\n"
        "wgmma.mma_async.sync.aligned.m64n64k16.f32.bf16.bf16 {%0, %1, %2, %3, %4, %5, %6, %7, %8, %9, %10, %11, %12, %13, %14, %15, %16, %17, %18, %19, %20, %21, %22, %23, %24, %25, %26, %27, %28, %29, %30, %31}, {%32, %33, %34, %35}, %36, p, 1, 1, 0;\n}\n"
        : "+f"(d[0]), "+f"(d[1]), "+f"(d[2]), "+f"(d[3]), "+f"(d[4]), "+f"(d[5]), "+f"(d[6]), "+f"(d[7]), "+f"(d[8]), "+f"(d[9]), "+f"(d[10]), "+f"(d[11]), "+f"(d[12]), "+f"(d[13]), "+f"(d[14]), "+f"(d[15]), "+f"(d[16]), "+f"(d[17]), "+f"(d[18]), "+f"(d[19]), "+f"(d[20]), "+f"(d[21]), "+f"(d[22]), "+f"(d[23]), "+f"(d[24]), "+f"(d[25]), "+f"(d[26]), "+f"(d[27]), "+f"(d[28]), "+f"(d[29]), "+f"(d[30]), "+f"(d[31])
        : "r"(a0), "r"(a1), "r"(a2), "r"(a3), "l"(db), "r"(scale_d));
}

__device__ __forceinline__ void wgmma_ss_n128_tb1(float (&d)[64], uint64_t da, uint64_t db, int scale_d) {
    asm volatile("{\n.reg .pred p;\nsetp.ne.b32 p, %66, 0;\n"
        "wgmma.mma_async.sync.aligned.m64n128k16.f32.bf16.bf16 {%0, %1, %2, %3, %4, %5, %6, %7, %8, %9, %10, %11, %12, %13, %14, %15, %16, %17, %18, %19, %20, %21, %22, %23, %24, %25, %26, %27, %28, %29, %30, %31, %32, %33, %34, %35, %36, %37, %38, %39, %40, %41, %42, %43, %44, %45, %46, %47, %48, %49, %50, %51, %52, %53, %54, %55, %56, %57, %58, %59, %60, %61, %62, %63}, %64, %65, p, 1, 1, 0, 1;\n}\n"
        : "+f"(d[0]), "+f"(d[1]), "+f"(d[2]), "+f"(d[3]), "+f"(d[4]), "+f"(d[5]), "+f"(d[6]), "+f"(d[7]), "+f"(d[8]), "+f"(d[9]), "+f"(d[10]), "+f"(d[11]), "+f"(d[12]), "+f"(d[13]), "+f"(d[14]), "+f"(d[15]), "+f"(d[16]), "+f"(d[17]), "+f"(d[18]), "+f"(d[19]), "+f"(d[20]), "+f"(d[21]), "+f"(d[22]), "+f"(d[23]), "+f"(d[24]), "+f"(d[25]), "+f"(d[26]), "+f"(d[27]), "+f"(d[28]), "+f"(d[29]), "+f"(d[30]), "+f"(d[31]), "+f"(d[32]), "+f"(d[33]), "+f"(d[34]), "+f"(d[35]), "+f"(d[36]), "+f"(d[37]), "+f"(d[38]), "+f"(d[39]), "+f"(d[40]), "+f"(d[41]), "+f"(d[42]), "+f"(d[43]), "+f"(d[44]), "+f"(d[45]), "+f"(d[46]), "+f"(d[47]), "+f"(d[48]), "+f"(d[49]), "+f"(d[50]), "+f"(d[51]), "+f"(d[52]), "+f"(d[53]), "+f"(d[54]), "+f"(d[55]), "+f"(d[56]), "+f"(d[57]), "+f"(d[58]), "+f"(d[59]), "+f"(d[60]), "+f"(d[61]), "+f"(d[62]), "+f"(d[63])
        : "l"(da), "l"(db), "r"(scale_d));
}

__device__ __forceinline__ void wgmma_ss_n256_tb1(float (&d)[128], uint64_t da, uint64_t db, int scale_d) {
    asm volatile("{\n.reg .pred p;\nsetp.ne.b32 p, %130, 0;\n"
        "wgmma.mma_async.sync.aligned.m64n256k16.f32.bf16.bf16 {%0, %1, %2, %3, %4, %5, %6, %7, %8, %9, %10, %11, %12, %13, %14, %15, %16, %17, %18, %19, %20, %21, %22, %23, %24, %25, %26, %27, %28, %29, %30, %31, %32, %33, %34, %35, %36, %37, %38, %39, %40, %41, %42, %43, %44, %45, %46, %47, %48, %49, %50, %51, %52, %53, %54, %55, %56, %57, %58, %59, %60, %61, %62, %63, %64, %65, %66, %67, %68, %69, %70, %71, %72, %73, %74, %75, %76, %77, %78, %79, %80, %81, %82, %83, %84, %85, %86, %87, %88, %89, %90, %91, %92, %93, %94, %95, %96, %97, %98, %99, %100, %101, %102, %103, %104, %105, %106, %107, %108, %109, %110, %111, %112, %113, %114, %115, %116, %117, %118, %119, %120, %121, %122, %123, %124, %125, %126, %127}, %128, %129, p, 1, 1, 0, 1;\n}\n"
        : "+f"(d[0]), "+f"(d[1]), "+f"(d[2]), "+f"(d[3]), "+f"(d[4]), "+f"(d[5]), "+f"(d[6]), "+f"(d[7]), "+f"(d[8]), "+f"(d[9]), "+f"(d[10]), "+f"(d[11]), "+f"(d[12]), "+f"(d[13]), "+f"(d[14]), "+f"(d[15]), "+f"(d[16]), "+f"(d[17]), "+f"(d[18]), "+f"(d[19]), "+f"(d[20]), "+f"(d[21]), "+f"(d[22]), "+f"(d[23]), "+f"(d[24]), "+f"(d[25]), "+f"(d[26]), "+f"(d[27]), "+f"(d[28]), "+f"(d[29]), "+f"(d[30]), "+f"(d[31]), "+f"(d[32]), "+f"(d[33]), "+f"(d[34]), "+f"(d[35]), "+f"(d[36]), "+f"(d[37]), "+f"(d[38]), "+f"(d[39]), "+f"(d[40]), "+f"(d[41]), "+f"(d[42]), "+f"(d[43]), "+f"(d[44]), "+f"(d[45]), "+f"(d[46]), "+f"(d[47]), "+f"(d[48]), "+f"(d[49]), "+f"(d[50]), "+f"(d[51]), "+f"(d[52]), "+f"(d[53]), "+f"(d[54]), "+f"(d[55]), "+f"(d[56]), "+f"(d[57]), "+f"(d[58]), "+f"(d[59]), "+f"(d[60]), "+f"(d[61]), "+f"(d[62]), "+f"(d[63]), "+f"(d[64]), "+f"(d[65]), "+f"(d[66]), "+f"(d[67]), "+f"(d[68]), "+f"(d[69]), "+f"(d[70]), "+f"(d[71]), "+f"(d[72]), "+f"(d[73]), "+f"(d[74]), "+f"(d[75]), "+f"(d[76]), "+f"(d[77]), "+f"(d[78]), "+f"(d[79]), "+f"(d[80]), "+f"(d[81]), "+f"(d[82]), "+f"(d[83]), "+f"(d[84]), "+f"(d[85]), "+f"(d[86]), "+f"(d[87]), "+f"(d[88]), "+f"(d[89]), "+f"(d[90]), "+f"(d[91]), "+f"(d[92]), "+f"(d[93]), "+f"(d[94]), "+f"(d[95]), "+f"(d[96]), "+f"(d[97]), "+f"(d[98]), "+f"(d[99]), "+f"(d[100]), "+f"(d[101]), "+f"(d[102]), "+f"(d[103]), "+f"(d[104]), "+f"(d[105]), "+f"(d[106]), "+f"(d[107]), "+f"(d[108]), "+f"(d[109]), "+f"(d[110]), "+f"(d[111]), "+f"(d[112]), "+f"(d[113]), "+f"(d[114]), "+f"(d[115]), "+f"(d[116]), "+f"(d[117]), "+f"(d[118]), "+f"(d[119]), "+f"(d[120]), "+f"(d[121]), "+f"(d[122]), "+f"(d[123]), "+f"(d[124]), "+f"(d[125]), "+f"(d[126]), "+f"(d[127])
        : "l"(da), "l"(db), "r"(scale_d));
}

__device__ __forceinline__ void wgmma_ss_n32_tb0(float (&d)[16], uint64_t da, uint64_t db, int scale_d) {
    asm volatile("{\n.reg .pred p;\nsetp.ne.b32 p, %18, 0;\n"
        "wgmma.mma_async.sync.aligned.m64n32k16.f32.bf16.bf16 {%0, %1, %2, %3, %4, %5, %6, %7, %8, %9, %10, %11, %12, %13, %14, %15}, %16, %17, p, 1, 1, 0, 0;\n}\n"
        : "+f"(d[0]), "+f"(d[1]), "+f"(d[2]), "+f"(d[3]), "+f"(d[4]), "+f"(d[5]), "+f"(d[6]), "+f"(d[7]), "+f"(d[8]), "+f"(d[9]), "+f"(d[10]), "+f"(d[11]), "+f"(d[12]), "+f"(d[13]), "+f"(d[14]), "+f"(d[15])
        : "l"(da), "l"(db), "r"(scale_d));
}

__device__ __forceinline__ void wgmma_ss_n64_tb0(float (&d)[32], uint64_t da, uint64_t db, int scale_d) {
    asm volatile("{\n.reg .pred p;\nsetp.ne.b32 p, %34, 0;\n"
        "wgmma.mma_async.sync.aligned.m64n64k16.f32.bf16.bf16 {%0, %1, %2, %3, %4, %5, %6, %7, %8, %9, %10, %11, %12, %13, %14, %15, %16, %17, %18, %19, %20, %21, %22, %23, %24, %25, %26, %27, %28, %29, %30, %31}, %32, %33, p, 1, 1, 0, 0;\n}\n"
        : "+f"(d[0]), "+f"(d[1]), "+f"(d[2]), "+f"(d[3]), "+f"(d[4]), "+f"(d[5]), "+f"(d[6]), "+f"(d[7]), "+f"(d[8]), "+f"(d[9]), "+f"(d[10]), "+f"(d[11]), "+f"(d[12]), "+f"(d[13]), "+f"(d[14]), "+f"(d[15]), "+f"(d[16]), "+f"(d[17]), "+f"(d[18]), "+f"(d[19]), "+f"(d[20]), "+f"(d[21]), "+f"(d[22]), "+f"(d[23]), "+f"(d[24]), "+f"(d[25]), "+f"(d[26]), "+f"(d[27]), "+f"(d[28]), "+f"(d[29]), "+f"(d[30]), "+f"(d[31])
        : "l"(da), "l"(db), "r"(scale_d));
}

struct Maps {
    CUtensorMap xa, xa2, xas, xh, wup4, wup8, mqa2, mqa4, mqb1, mqb2, uc, x, out, wq, wk, fa[3], fb[2], fc;
};

__device__ __forceinline__ uint64_t mkd(uint32_t lo) {
    uint64_t d;
    asm("mov.b64 %0, {%1, %2};" : "=l"(d) : "r"(lo), "r"((1024u >> 4) | (1u << 30)));
    return d;
}
__device__ __forceinline__ void bulk_ld(uint32_t dst, const void* src, uint32_t bytes, uint32_t bar) {
    asm volatile("cp.async.bulk.shared::cluster.global.mbarrier::complete_tx::bytes [%0], [%1], %2, [%3];" ::"r"(dst), "l"(src), "r"(bytes), "r"(bar) : "memory");
}
__device__ __forceinline__ void bulk_st(void* dst, uint32_t src, uint32_t bytes) {
    asm volatile("cp.async.bulk.global.shared::cta.bulk_group [%0], [%1], %2;" ::"l"(dst), "r"(src), "r"(bytes) : "memory");
}
__device__ __forceinline__ void ring_ld(uint32_t sb, uint32_t slot8, int n) {
    mbar_expect_tx(sb + B_R2 + slot8, 8192);
    bulk_ld(sb + R1 + slot8 * 1024, (const char*)g_wepi + n * 8192, 8192, sb + B_R2 + slot8);
}

__device__ __forceinline__ void ring_half(uint32_t sb, uint32_t slot8, uint32_t hoff, const CUtensorMap* tm, int c1, int c2) {
    mbar_expect_tx(sb + B_R1 + slot8, 8192);
    tma3(sb + R1 + slot8 * 2048 + hoff, tm, 0, c1, c2, sb + B_R1 + slot8);
}
__device__ __forceinline__ void ring_full(uint32_t sb, uint32_t slot8, const CUtensorMap* tm, int c1, int c2) {
    mbar_expect_tx(sb + B_R1 + slot8, 16384);
    mbar_arrive(sb + B_R1 + slot8);
    tma3(sb + R1 + slot8 * 2048, tm, 0, c1, c2, sb + B_R1 + slot8);
}
__device__ __forceinline__ void cta_done(int mode) {
    if (mode == 0 && atomicAdd(&g_sync[4], 1) == NCTA + 1) {
#pragma unroll
        for (int i = 0; i < 5; i++) g_sync[i] = 0;
    }
}

__device__ __forceinline__ void fold_cta(const Maps& mp, uint32_t sb, int mode) {
    constexpr uint32_t F_FULL = MISC, F_EMPTY = MISC + 32, F_T1 = MISC + 64, STG = 49152, FOUT = 3 * STG;
    const int tid = threadIdx.x, f = blockIdx.x - NCTA;
    if (mode == 2) return;
    if (tid == 0) {
        for (int i = 0; i < 3; i++) { mbar_init(sb + F_FULL + 8 * i, 1); mbar_init(sb + F_EMPTY + 8 * i, 2); }
        mbar_init(sb + F_T1, 2);
        asm volatile("fence.mbarrier_init.release.cluster;" ::: "memory");
        fence_async();
    }
    __syncthreads();
    const int wg = __shfl_sync(0xffffffffu, tid >> 7, 0);
    int st = 0, ph = 0;
    if (wg == 0) {
        if (tid == 0) {
#pragma unroll 1
            for (int it = 0; it < 96; it++) {
                const int p = it >> 3, kc = it & 7, job = p >> 2;
                if (it == 64) mbar_wait(sb + F_T1, 0);
                mbar_wait(sb + F_EMPTY + 8 * st, ph ^ 1);
                mbar_expect_tx(sb + F_FULL + 8 * st, STG);
                tma3(sb + st * STG, &mp.fa[job], 0, 256 * f + 128 * ((p >> 1) & 1), kc, sb + F_FULL + 8 * st);
                tma3(sb + st * STG + 16384, &mp.fb[job != 0], 0, 64 * kc + (job == 1 ? 512 : 0), 4 * (p & 1), sb + F_FULL + 8 * st);
                if (++st == 3) { st = 0; ph ^= 1; }
            }
        }
        return;
    }
    const int h = wg - 1, lane = tid & 31, w = (tid >> 5) & 3;
    const uint32_t sd = (sb & 0x3FFFF) >> 4;
    const bool el = (tid & 127) == 0;
#pragma unroll 1
    for (int p = 0; p < 12; p++) {
        float acc[128];
        fresh(acc);
#pragma unroll 1
        for (int kc = 0; kc < 8; kc++) {
            mbar_wait(sb + F_FULL + 8 * st, ph);
            wg_fence();
#pragma unroll
            for (int kk = 0; kk < 4; kk++)
                wgmma_ss_n256_tb1(acc, dsc(sd, st * STG + h * 8192 + kk * 32, 16), dsc(sd, st * STG + 16384 + kk * 2048, 8192), 1);
            wg_commit();
            wg_wait<0>();
            if (el) mbar_arrive(sb + F_EMPTY + 8 * st);
            if (++st == 3) { st = 0; ph ^= 1; }
        }
        pin(acc);
        const int job = p >> 2;
        if (el) {
            asm volatile("cp.async.bulk.wait_group 0;" ::: "memory");
            if (p == 4) { fence_async_g(); mbar_arrive(sb + F_T1); }
        }
        bar_sync(3 + h, 128);
        uint32_t r = 16 * w + (lane & 7) + ((lane >> 3) & 1) * 8;
        const float fs = job == 1 ? 0.5f : 1.f;
        if (job == 1) r = (r & ~31) | (((r >> 1) & 3) << 3) | (((r >> 3) & 3) << 1) | (r & 1);
        const uint32_t oa = sb + FOUT + h * 32768 + r * 128 + ((((lane >> 4) ^ r) & 7) << 4);
#pragma unroll
        for (int i = 0; i < 16; i++)
            stsm4((oa ^ ((i & 3) << 5)) + (i >> 2) * 8192, pack2(acc[8 * i] * fs, acc[8 * i + 1] * fs), pack2(acc[8 * i + 2] * fs, acc[8 * i + 3] * fs),
                  pack2(acc[8 * i + 4] * fs, acc[8 * i + 5] * fs), pack2(acc[8 * i + 6] * fs, acc[8 * i + 7] * fs));
        fence_async();
        bar_sync(3 + h, 128);
        if (el) {
            const int row0 = 256 * f + 128 * ((p >> 1) & 1) + 64 * h + (job == 1 ? 512 : 0);
            if (job == 0) tma3_store(&mp.fc, sb + FOUT + h * 32768, 0, row0, 4 * (p & 1));
            else {
#pragma unroll 1
                for (int i = 0; i < 16; i++)
                    bulk_st((char*)g_wepi + (row0 / 8 + 2 * (i & 3) + (p & 1)) * 8192 + (i >> 2) * 2048, sb + FOUT + h * 32768 + i * 2048, 2048);
            }
            asm volatile("cp.async.bulk.commit_group;" ::: "memory");
        }
    }
    if (el) {
        asm volatile("cp.async.bulk.wait_group 0;" ::: "memory");
        fence_async_g();
        if (mode == 0) flag_add(&g_sync[3]);
    }
    bar_sync(2, 256);
    if (tid == 128) cta_done(mode);
}

__global__ void __launch_bounds__(384, 1) main_kernel(const __grid_constant__ Maps mp, const bf16* __restrict__ dw, const bf16* wup, const int mode) {
    extern __shared__ __align__(1024) uint8_t smem[];
    const uint32_t sb = smem_u32(smem);
    const int tid = threadIdx.x;
    if (blockIdx.x >= NCTA) { fold_cta(mp, sb, mode); return; }
    const int b = blockIdx.x / TPB, ti = blockIdx.x % TPB;
    const int piece = blockIdx.x & 127;
    if (tid == 0) {
        mbar_init(sb + B_A, 1); mbar_init(sb + B_A2, 1); mbar_init(sb + B_MK, 1);
        for (int i = 0; i < 5; i++) mbar_init(sb + B_R1 + 8 * i, 2);
        asm volatile("fence.mbarrier_init.release.cluster;" ::: "memory");
        fence_async();
        mbar_expect_tx(sb + B_MK, 65536 + 32768);
        tma3(sb + R0, &mp.wq, 0, 64 * (piece >> 4), 0, sb + B_MK);
        tma3(sb + R1 + 32768, &mp.wk, 0, 32 * (piece & 15), 0, sb + B_MK);
        mbar_expect_tx(sb + B_A, 32768);
        mbar_expect_tx(sb + B_A2, 32768 + 3072);
#pragma unroll 1
        for (int i = 0; i < 16; i++) tma4(sb + AT + (i & 7) * 8192 + (i >> 3) * 4096, &mp.xh, 0, 62 * ti - 1 + 32 * (i >> 3), i & 7, b, sb + (i < 8 ? B_A : B_A2));
        bulk_ld(sb + DWS, dw, 3072, sb + B_A2);
        for (int i = 0; i < 8; i++) mbar_arrive(sb + B_R1 + 8 * (i >> 1));
        if (mode != 1) {
            ring_full(sb, 32, &mp.wup8, 0, 8);
            ring_full(sb, 0, &mp.wup8, 16, 8);
            ring_full(sb, 8, &mp.wup8, 32, 8);
        }
    } else if (tid == 32) {
        mbar_init(sb + B_LN, 1); mbar_init(sb + B_MQ, 1); mbar_init(sb + B_XA, 1);
        mbar_init(sb + B_H1, 2); mbar_init(sb + B_H2, 1); mbar_init(sb + B_H3, 2);
        for (int i = 0; i < 3; i++) { mbar_init(sb + B_KV + 8 * i, 1); mbar_init(sb + B_P + 8 * i, 4); mbar_init(sb + B_GO + 8 * i, 4); }
        for (int i = 0; i < 12; i++) { mbar_init(sb + B_R2 + 8 * i, 1); mbar_init(sb + B_E2 + 8 * i, 4); }
        mbar_init(sb + B_UC, 1); mbar_init(sb + B_X, 1);
        for (int i = 0; i < 4; i++) asm volatile("st.shared.u32 [%0], 0;" ::"r"(sb + CNT + 4 * i) : "memory");
        asm volatile("fence.mbarrier_init.release.cluster;" ::: "memory");
        fence_async();
    }
    __syncthreads();
    const int wg = __shfl_sync(0xffffffffu, tid >> 7, 0);
    const int lane = tid & 31, w = (tid >> 5) & 3;
    const bool w0 = __shfl_sync(0xffffffffu, w, 0) == 0;
    const uint32_t sd = (sb & 0x3FFFF) >> 4;
    const uint32_t adA = sd + (AT >> 4) + (1u << 16);
    const uint32_t bd0 = sd + (R1 >> 4);
    const uint32_t bd2k = bd0 + ((2048u >> 4) << 16);
    const bool el = (tid & 127) == 0;
    const uint32_t lrow = 16 * w + (lane & 7) + ((lane >> 3) & 1) * 8;
    const uint32_t loff = lrow * 128 + ((((lane >> 4) ^ lrow) & 7) << 4);
    const int r0 = 16 * w + (lane >> 2);

    if (wg == 0) {
        asm volatile("setmaxnreg.inc.sync.aligned.u32 184;");
        uint32_t q[112];
        PT(0);
        PG(200);
        {
            float mq[16];
            fresh(mq);
            mbar_wait(sb + B_MK, 0);
            PT(1);
            if (PFW && tid == 32) l2_prefetch((const char*)wup + piece * 8192, 8192);
            wg_fence();
#pragma unroll 1
            for (int c = 0; c < 8; c++)
#pragma unroll
                for (int kk = 0; kk < 4; kk++)
                    wgmma_ss_n32_tb0(mq, dsc(sd, R0 + c * 8192 + kk * 32, 16), dsc(sd, R1 + 32768 + c * 4096 + kk * 32, 16), 1);
            wg_commit();
            wg_wait<0>();
            if (mode != 1 && w0 && elect1()) { ring_full(sb, 16, &mp.wup8, 48, 8); ring_full(sb, 24, &mp.wup8, 64, 8); }
            pin(mq);
            uint32_t* c = reinterpret_cast<uint32_t*>(g_mqk + (64 * (piece >> 4) + r0) * D_ + 32 * (piece & 15) + 2 * (lane & 3));
#pragma unroll
            for (int n = 0; n < 4; n++) { c[4 * n] = pack2(mq[4 * n], mq[4 * n + 1]); c[4 * n + 4 * D_] = pack2(mq[4 * n + 2], mq[4 * n + 3]); }
            fence_async_g();
            bar_sync(1, 128);
            if (el) {
                if (mode == 0) flag_add(&g_sync[2]);
                if (mode == 0) flag_wait(&g_sync[2], NCTA);
                mbar_arrive(sb + B_MQ);
                PT(12);
                mbar_wait(sb + B_LN, 0);
#pragma unroll 1
                for (int c = 0; c < 8; c++) {
                    tma4_store(&mp.xas, sb + AT + c * 8192, 0, 62 * ti, c, b);
                    const unsigned t0 = (unsigned)clock();
                    while (c < 7 && (unsigned)clock() - t0 < XS_GAP) __nanosleep(20);
                }
                asm volatile("cp.async.bulk.commit_group;" ::: "memory");
                if (mode == 1) asm volatile("cp.async.bulk.wait_group 0;" ::: "memory");
            }
            PT(13);
            if (mode == 1) return;
        }
        mbar_wait(sb + B_H1, 0);
        PT(2);
        uint32_t slot8 = 8, par = 1, prev8 = 0;
        auto adv = [&]() { prev8 = slot8; slot8 += 8; if (slot8 == 40) { slot8 = 0; par ^= 1; } };
        {
            float acc[128];
            fresh(acc);
            auto step = [&](int i) {
                const uint32_t aa = adA + (i >> 1) * 512 + (i & 1) * 4, bb = bd0 + ((4096u >> 4) << 16) + slot8 * 128;
                wg_fence();
                wgmma_ss_n256_tb1(acc, mkd(aa), mkd(bb), 1);
                wgmma_ss_n256_tb1(acc, mkd(aa + 2), mkd(bb + 128), 1);
                wg_commit();
                wg_wait<1>();
            };
#pragma unroll 1
            for (int i = 0; i < 12; i++) {
                mbar_wait(sb + B_R1 + slot8, par);
                step(i);
                if (i > 0 && w0 && elect1()) ring_full(sb, prev8, &mp.mqa4, 32 * i + 128, 4);
                adv();
            }
#pragma unroll 1
            for (int i = 12; i < 16; i++) {
                mbar_wait(sb + B_R1 + slot8, par);
                if (i == 15 && el) mbar_arrive(sb + B_H2);
                step(i);
                if (w0 && elect1()) ring_full(sb, prev8, &mp.wup8, 16 * i - 192, 0);
                adv();
            }
            wg_wait<0>();
            if (w0 && elect1()) ring_full(sb, prev8, &mp.wup8, 64, 0);
            pin(acc);
            PT(3);
#pragma unroll
            for (int kk = 0; kk < 4; kk++)
                stsm4((sb + QS + loff) ^ (kk << 5), pack2(acc[96 + 8 * kk], acc[97 + 8 * kk]), pack2(acc[98 + 8 * kk], acc[99 + 8 * kk]),
                      pack2(acc[100 + 8 * kk], acc[101 + 8 * kk]), pack2(acc[102 + 8 * kk], acc[103 + 8 * kk]));
            fence_async();
#pragma unroll
            for (int i = 47; i >= 0; i--) q[64 + i] = pack2v(acc[2 * i], acc[2 * i + 1]);
        }
        if (el) {
            asm volatile("cp.async.bulk.wait_group 0;" ::: "memory");
            if (mode == 0) {
                fence_async_g();
                flag_add(&g_sync[b]);
                flag_wait(&g_sync[b], TPB);
            }
            mbar_arrive(sb + B_XA);
        }
        __syncwarp();
        mbar_wait(sb + B_H3, 0);
        PT(4);
        slot8 = 32; par = 0;
#pragma unroll
        for (int half = 0; half < 2; half++) {
            float acc[64];
            fresh(acc);
            auto step = [&](int m) {
                const uint32_t aa = adA + m * 512, bb = bd0 + ((8192u >> 4) << 16) + slot8 * 128;
                mbar_wait(sb + B_R1 + slot8, par);
                wg_fence();
#pragma unroll
                for (int kk = 0; kk < 4; kk++) wgmma_ss_n128_tb1(acc, mkd(aa + 2 * kk), mkd(bb + 128 * kk), 1);
                wg_commit();
                wg_wait<1>();
            };
            if (half == 0) {
#pragma unroll 1
                for (int m = 0; m < 8; m++) {
                    step(m);
                    if (m > 0 && w0 && elect1()) ring_full(sb, prev8, &mp.mqb2, (64 * m + 256) & 511, (m + 4) >> 3 << 1);
                    adv();
                }
            } else {
#pragma unroll 1
                for (int m = 0; m < 4; m++) {
                    step(m);
                    if (m > 0 && w0 && elect1()) ring_full(sb, prev8, &mp.mqb2, 64 * m + 256, 2);
                    adv();
                }
#pragma unroll 1
                for (int m = 4; m < 8; m++) {
                    step(m);
                    if (w0 && elect1()) {
                        if (m == 4) mbar_expect_tx(sb + B_KV + 8, 65536);
                        tma4(sb + R1 + prev8 * 2048, &mp.xa2, 0, 0, 2 * m - 8, b, sb + B_KV + 8);
                    }
                    adv();
                }
            }
            wg_wait<0>();
            if (w0 && elect1()) {
                if (half == 0) ring_full(sb, prev8, &mp.mqb2, 256, 2);
                else {
                    mbar_expect_tx(sb + B_KV + 16, 65536);
                    tma4(sb + R2, &mp.xa, 0, 64, 0, b, sb + B_KV + 16);
                }
            }
            pin(acc);
#pragma unroll
            for (int i = 31; i >= 0; i--) q[32 * half + i] = pack2v(acc[2 * i], acc[2 * i + 1]);
        }
        bar_sync(1, 128);
        PT(5);

        const float CS = 0.04419417382415922f * 1.4426950408889634f;
        float m0 = -INFINITY, m1 = -INFINITY, l0 = 0.f, l1 = 0.f;
        int s = 0, sn = 1, ph = 0;
        float S[32];
        const bool l0w = lane == 0, q0 = (lane & 3) == 0;
#pragma unroll 1
        for (int j = -1;; j++) {
            if (j >= 0) {
                PL(j, 1);
                if (j == NKV - 1) {
#pragma unroll
                    for (int i = (T_ - 64 * (NKV - 1)) / 2; i < 32; i++) asm volatile("mov.b32 %0, 0xff800000;" : "=f"(S[i]));
                }
                float y[8], z[8];
#pragma unroll
                for (int n = 0; n < 8; n++) { y[n] = fmaxf(S[4 * n], S[4 * n + 1]); z[n] = fmaxf(S[4 * n + 2], S[4 * n + 3]); }
#pragma unroll
                for (int n = 0; n < 4; n++) { y[n] = fmaxf(y[n], y[n + 4]); z[n] = fmaxf(z[n], z[n + 4]); }
                float x0 = fmaxf(fmaxf(y[0], y[1]), fmaxf(fmaxf(y[2], y[3]), m0)), x1 = fmaxf(fmaxf(z[0], z[1]), fmaxf(fmaxf(z[2], z[3]), m1));
                x0 = fmaxf(x0, __shfl_xor_sync(0xffffffffu, x0, 1));
                x1 = fmaxf(x1, __shfl_xor_sync(0xffffffffu, x1, 1));
                x0 = fmaxf(x0, __shfl_xor_sync(0xffffffffu, x0, 2));
                x1 = fmaxf(x1, __shfl_xor_sync(0xffffffffu, x1, 2));
                if ((x0 - m0) * CS <= LAZY) x0 = m0;
                if ((x1 - m1) * CS <= LAZY) x1 = m1;
                const float sc0 = ex2((m0 - x0) * CS), sc1 = ex2((m1 - x1) * CS);
                m0 = x0; m1 = x1;
                const float n0 = -x0 * CS, n1 = -x1 * CS;
                if (q0) { sts_f32(sb + SCL + s * 256 + r0 * 4, sc0); sts_f32(sb + SCL + s * 256 + r0 * 4 + 32, sc1); }
                __syncwarp();
                if (l0w) mbar_arrive(sb + B_P + s * 8);
                if (j < NKV - 1) mbar_wait(sb + B_KV + sn * 8, ph);
                float a0 = 0.f, a1 = 0.f;
                const uint32_t pb = sb + R3 + (s == 0 ? 2 : s - 1) * 8192;
#pragma unroll
                for (int kk = 0; kk < 4; kk++) {
                    float p[8];
#pragma unroll
                    for (int e = 0; e < 8; e++) p[e] = ex2(fmaf(S[8 * kk + e], CS, (e & 2) ? n1 : n0));
                    a0 += (p[0] + p[1]) + (p[4] + p[5]);
                    a1 += (p[2] + p[3]) + (p[6] + p[7]);
                    stsm4((pb + loff) ^ (kk << 5), pack2(p[0], p[1]), pack2(p[2], p[3]), pack2(p[4], p[5]), pack2(p[6], p[7]));
                }
                l0 = fmaf(l0, sc0, a0); l1 = fmaf(l1, sc1, a1);
                PL(j, 2);
                if (j == NKV - 1) break;
            } else {
                mbar_wait(sb + B_KV + 8, 0);
            }
            float Sn[32];
            const uint32_t kd = sd + sn * 4096;
            wg_fence();
#pragma unroll
            for (int kk = 0; kk < 28; kk++) {
                wgmma_rs_n64_tb0(Sn, q[4 * kk], q[4 * kk + 1], q[4 * kk + 2], q[4 * kk + 3], dsc(kd, (kk >> 2) * 8192 + (kk & 3) * 32, 16), kk > 0);
                if (kk == FENCE_AT) { fence_async(); __syncwarp(); }
                if (kk == GO_AT) { PL(j, 3); if (j >= 0 && l0w) mbar_arrive(sb + B_GO + s * 8); }
            }
#pragma unroll
            for (int kk = 0; kk < 4; kk++)
                wgmma_ss_n64_tb0(Sn, dsc(sd, QS + kk * 32, 16), dsc(kd, 7 * 8192 + kk * 32, 16), 1);
            wg_commit();
            PL(j, 0);
            wg_wait<0>();
            pin(Sn);
#pragma unroll
            for (int i = 0; i < 32; i++) S[i] = Sn[i];
            s = sn;
            if (++sn == 3) sn = 0;
            if (sn == 1) ph ^= 1;
        }
        l0 += __shfl_xor_sync(0xffffffffu, l0, 1); l1 += __shfl_xor_sync(0xffffffffu, l1, 1);
        l0 += __shfl_xor_sync(0xffffffffu, l0, 2); l1 += __shfl_xor_sync(0xffffffffu, l1, 2);
        if (q0) { sts_f32(sb + LINV + r0 * 4, rcp(l0)); sts_f32(sb + LINV + r0 * 4 + 32, rcp(l1)); }
        fence_async();
        __syncwarp();
        if (l0w) {
            mbar_arrive(sb + B_GO + s * 8);
            uint32_t slot8 = 8 * w, par = 0;
#pragma unroll 1
            for (int n = 12 + w; n < 128; n += 4) {
                mbar_wait(sb + B_E2 + slot8, par);
                ring_ld(sb, slot8, n);
                slot8 += 32;
                if (slot8 >= 96) { slot8 -= 96; par ^= 1; }
            }
        }
        PDUMP();
    } else {
        asm volatile("setmaxnreg.dec.sync.aligned.u32 160;");
        const int h = wg - 1;
        auto red4 = [&](float (&a)[4]) {
            const bool b4 = lane & 16, b3 = lane & 8;
            const float k0 = (b4 ? a[2] : a[0]) + __shfl_xor_sync(0xffffffffu, b4 ? a[0] : a[2], 16);
            const float k1 = (b4 ? a[3] : a[1]) + __shfl_xor_sync(0xffffffffu, b4 ? a[1] : a[3], 16);
            float k = (b3 ? k1 : k0) + __shfl_xor_sync(0xffffffffu, b3 ? k0 : k1, 8);
            k += __shfl_xor_sync(0xffffffffu, k, 4);
            k += __shfl_xor_sync(0xffffffffu, k, 2);
            k += __shfl_xor_sync(0xffffffffu, k, 1);
            return k;
        };
#pragma unroll 1
        for (int bt = 0; bt < 2; bt++) {
            mbar_wait(sb + (bt ? B_A2 : B_A), 0);
            PT(bt ? 13 : 0);
            uint32_t v[4][8];
            float a[4], f[4][16];
            const uint32_t la = sb + AT + (lane >> 3) * 8192 + (32 * bt + 16 * h + 4 * w) * 128 + (((lane & 7) ^ ((w & 1) * 4)) << 4);
#pragma unroll
            for (int r = 0; r < 4; r++) { lds4((la ^ (r << 4)) + r * 128, v[r]); lds4((la ^ (r << 4)) + r * 128 + 32768, v[r] + 4); }
#pragma unroll
            for (int r = 0; r < 4; r++) {
                float s0 = blo(v[r][0]), s1 = bhi(v[r][0]);
#pragma unroll
                for (int i = 1; i < 8; i++) { s0 += blo(v[r][i]); s1 += bhi(v[r][i]); }
                a[r] = s0 + s1;
            }
            const float mu = red4(a) * (1.f / D_);
            const uint32_t mp2 = pack2(mu, mu);
#pragma unroll
            for (int r = 0; r < 4; r++) {
                const uint32_t m2 = __shfl_sync(0xffffffffu, mp2, 8 * r);
                float s0 = 0.f, s1 = 0.f;
#pragma unroll
                for (int i = 0; i < 8; i++) {
                    const uint32_t d = bsub2(v[r][i], m2);
                    f[r][2 * i] = blo(d); f[r][2 * i + 1] = bhi(d);
                    s0 = fmaf(f[r][2 * i], f[r][2 * i], s0); s1 = fmaf(f[r][2 * i + 1], f[r][2 * i + 1], s1);
                }
                a[r] = s0 + s1;
            }
            const float dm = mu - blo(mp2);
            float sd_ = bfr(bfr(fmaxf(fmaf(red4(a), 1.f / D_, -dm * dm), 0.f)) + 1e-5f);
            asm("sqrt.approx.f32 %0, %0;" : "+f"(sd_));
            const float ri = rcp(bfr(sd_));
#pragma unroll
            for (int r = 0; r < 4; r++) {
                const float rinv = __shfl_sync(0xffffffffu, ri, 8 * r);
#pragma unroll
                for (int i = 0; i < 8; i++) v[r][i] = pack2(f[r][2 * i] * rinv, f[r][2 * i + 1] * rinv);
                sts4((la ^ (r << 4)) + r * 128, v[r][0], v[r][1], v[r][2], v[r][3]);
                sts4((la ^ (r << 4)) + r * 128 + 32768, v[r][4], v[r][5], v[r][6], v[r][7]);
            }
        }
        fence_async();
        bar_sync(2, 256);
        if (tid == 128) mbar_arrive(sb + B_LN);
        if (mode == 1) return;
        float acc[128];
#pragma unroll
        for (int pass = 0; pass < 2; pass++) {
            if (pass == 1) mbar_wait(sb + B_H2, 0);
            PT(1 + 3 * pass);
            fresh(acc);
            uint32_t slot8 = pass ? 16 : 32, par = 0, prev8 = 0;
            auto adv = [&]() { prev8 = slot8; slot8 += 8; if (slot8 == 40) { slot8 = 0; par ^= 1; } };
            auto step = [&](int kk) {
                wg_fence();
                wgmma_ss_n256_tb1(acc, mkd(adA + (kk >> 2) * 512 + (kk & 3) * 2), mkd(bd2k + h * 512 + slot8 * 128), 1);
                wg_commit();
                wg_wait<1>();
            };
#pragma unroll 1
            for (int kk = 0; kk < 28; kk++) {
                mbar_wait(sb + B_R1 + slot8, par);
                step(kk);
                if (kk > 0 && w0 && elect1()) ring_half(sb, prev8, h * 8192, &mp.wup4, 16 * kk + 64, (pass ? 0 : 8) + 4 * h);
                adv();
            }
            if (pass == 0 && w0) mbar_wait(sb + B_MQ, 0);
#pragma unroll 1
            for (int kk = 28; kk < 32; kk++) {
                mbar_wait(sb + B_R1 + slot8, par);
                if (kk == 31 && el) mbar_arrive(sb + (pass ? B_H3 : B_H1));
                step(kk);
                if (w0 && elect1()) ring_half(sb, prev8, h * 8192, pass ? &mp.mqb1 : &mp.mqa2, (pass ? 64 : 32) * (kk - 28), pass ? h : 4 + 2 * h);
                adv();
            }
            wg_wait<0>();
            if (w0 && elect1()) ring_half(sb, prev8, h * 8192, pass ? &mp.mqb1 : &mp.mqa2, pass ? 256 : 128, pass ? h : 4 + 2 * h);
            pin(acc);
            PT(2 + 3 * pass);
            if (pass == 0) {
                float s0 = 0.f, s1 = 0.f, v0 = 0.f, v1 = 0.f;
#pragma unroll
                for (int n = 0; n < 32; n++) {
#pragma unroll
                    for (int e = 0; e < 4; e++) acc[4 * n + e] = gelu2(acc[4 * n + e]);
                    s0 += acc[4 * n] + acc[4 * n + 1]; s1 += acc[4 * n + 2] + acc[4 * n + 3];
                    v0 = fmaf(acc[4 * n], acc[4 * n], v0); v0 = fmaf(acc[4 * n + 1], acc[4 * n + 1], v0);
                    v1 = fmaf(acc[4 * n + 2], acc[4 * n + 2], v1); v1 = fmaf(acc[4 * n + 3], acc[4 * n + 3], v1);
                }
#pragma unroll
                for (int o = 1; o < 4; o <<= 1) {
                    s0 += __shfl_xor_sync(0xffffffffu, s0, o); s1 += __shfl_xor_sync(0xffffffffu, s1, o);
                    v0 += __shfl_xor_sync(0xffffffffu, v0, o); v1 += __shfl_xor_sync(0xffffffffu, v1, o);
                }
                if ((lane & 3) == 0) {
                    uint32_t a = sb + STAT + h * 512 + r0 * 8;
                    sts_f32(a, s0); sts_f32(a + 4, v0); sts_f32(a + 64, s1); sts_f32(a + 68, v1);
                }
                bar_sync(2, 256);
                {
                    uint32_t a = sb + STAT + (h ^ 1) * 512 + r0 * 8;
                    s0 = (s0 + lds_f32(a)) * (1.f / 512.f); v0 = (v0 + lds_f32(a + 4)) * (1.f / 512.f);
                    s1 = (s1 + lds_f32(a + 64)) * (1.f / 512.f); v1 = (v1 + lds_f32(a + 68)) * (1.f / 512.f);
                }
                v0 = rsqrtf(fmaxf(fmaf(-s0, s0, v0), 0.f) + 4e-5f); v1 = rsqrtf(fmaxf(fmaf(-s1, s1, v1), 0.f) + 4e-5f);
                s0 = -s0 * v0; s1 = -s1 * v1;
#pragma unroll
                for (int p = 0; p < 16; p++)
                    stsm4(((sb + R0 + h * 32768 + loff) ^ ((p & 3) << 5)) + (p >> 2) * 8192,
                          pack2(fmaf(acc[8 * p], v0, s0), fmaf(acc[8 * p + 1], v0, s0)), pack2(fmaf(acc[8 * p + 2], v1, s1), fmaf(acc[8 * p + 3], v1, s1)),
                          pack2(fmaf(acc[8 * p + 4], v0, s0), fmaf(acc[8 * p + 5], v0, s0)), pack2(fmaf(acc[8 * p + 6], v1, s1), fmaf(acc[8 * p + 7], v1, s1)));
            } else {
                uint32_t u[64];
#pragma unroll
                for (int i = 63; i >= 0; i--) u[i] = pack2v(gelu2(acc[2 * i]), gelu2(acc[2 * i + 1]));
                PT(12);
                bar_sync(3 + h, 128);
                const uint32_t rm = lrow == 0 ? 0 : lrow - 1, rp = lrow == 63 ? 63 : lrow + 1;
                const uint32_t gb = sb + R0 + h * 32768;
                const uint32_t am = gb + rm * 128 + ((((lane >> 4) ^ rm) & 7) << 4), ap = gb + rp * 128 + ((((lane >> 4) ^ rp) & 7) << 4), ac = gb + loff;
                const uint32_t dwa = sb + DWS + 512 * h + ((lane >> 3) & 1) * 16 + (lane >> 4) * 1024;
                bf16* ucp = g_uc + ((size_t)blockIdx.x * 64 + r0) * D_ + 256 * h + 8 * (lane & 3);
#pragma unroll
                for (int m = 0; m < 8; m++) {
                    uint32_t o[8], g0[2][4], g1[2][4], g2[2][4], d[2][4], d2[2][2];
#pragma unroll
                    for (int pp = 0; pp < 2; pp++) {
                        const int p = 2 * m + pp;
                        const uint32_t co = (p >> 2) * 8192, cx = (p & 3) << 5;
                        ldsm4(dwa + 32 * p, d[pp]);
                        ldsm2(dwa + 32 * p + 2048, d2[pp]);
                        ldsm4((am ^ cx) + co, g0[pp]);
                        ldsm4((ac ^ cx) + co, g1[pp]);
                        ldsm4((ap ^ cx) + co, g2[pp]);
                    }
#pragma unroll
                    for (int pp = 0; pp < 2; pp++)
#pragma unroll
                        for (int e = 0; e < 4; e++)
                            o[4 * (e & 1) + 2 * pp + (e >> 1)] =
                                bmul2(u[8 * m + 4 * pp + e], bfma2(g2[pp][e], d2[pp][e >> 1], bfma2(g1[pp][e], d[pp][2 + (e >> 1)], bmul2(g0[pp][e], d[pp][e >> 1]))));
                    stg4(ucp + 32 * m, o[0], o[1], o[2], o[3]);
                    stg4(ucp + 32 * m + 8 * D_, o[4], o[5], o[6], o[7]);
                }
                bar_sync(2, 256);
                if (tid == 128) {
                    mbar_wait(sb + B_XA, 0);
                    mbar_expect_tx(sb + B_KV, 65536);
                    tma4(sb + R0, &mp.xa, 0, 128, 0, b, sb + B_KV);
                }
            }
            PT(3 + 3 * pass);
        }
        int s = 1, ph = 0;
        fresh(acc);
#pragma unroll 1
        for (int j = 0; j < NKV; j++) {
            mbar_wait(sb + B_P + s * 8, ph);
            PL(j, 0);
            if (j > 0) {
                const float sc0 = lds_f32(sb + SCL + s * 256 + r0 * 4), sc1 = lds_f32(sb + SCL + s * 256 + r0 * 4 + 32);
                if (__any_sync(0xffffffffu, sc0 != 1.f || sc1 != 1.f)) {
#pragma unroll
                    for (int n = 0; n < 32; n++) { acc[4 * n] *= sc0; acc[4 * n + 1] *= sc0; acc[4 * n + 2] *= sc1; acc[4 * n + 3] *= sc1; }
                }
            }
            mbar_wait(sb + B_GO + s * 8, ph);
            PL(j, 1);
            const uint32_t vd = sd + s * 4096 + h * 2048, pd = sd + (s == 0 ? 2 : s - 1) * 512;
            pin(acc);
            wg_fence();
#pragma unroll
            for (int kk = 0; kk < 4; kk++) wgmma_ss_n256_tb1(acc, dsc(pd, R3 + kk * 32, 16), dsc(vd, kk * 2048, 8192), 1);
            wg_commit();
            wg_wait<0>();
            pin(acc);
            PL(j, 2);
            if (w0 && elect1()) {
                if (j == NKV - 5 && mode == 0) flag_wait(&g_sync[3], 4);
                if (atom_inc_s(sb + CNT + 4 * s) & 1) {
                    if (j + 3 < NKV) {
                        mbar_expect_tx(sb + B_KV + s * 8, 65536);
                        tma4(sb + s * 65536, &mp.xa, 0, 64 * (j + 3), 0, b, sb + B_KV + s * 8);
                    } else if (j < NKV - 1) {
                        const int n0 = j == NKV - 3 ? 0 : 8, n1 = j == NKV - 3 ? 8 : 12;
#pragma unroll 1
                        for (int n = n0; n < n1; n++) ring_ld(sb, n * 8, n);
                    }
                }
            }
            if (++s == 3) s = 0;
            if (s == 1) ph ^= 1;
        }
        {
            const float i0 = lds_f32(sb + LINV + r0 * 4), i1 = lds_f32(sb + LINV + r0 * 4 + 32);
#pragma unroll
            for (int p = 0; p < 16; p++)
                stsm4(((sb + R0 + h * 32768 + loff) ^ ((p & 3) << 5)) + (p >> 2) * 8192,
                      pack2(acc[8 * p] * i0, acc[8 * p + 1] * i0), pack2(acc[8 * p + 2] * i1, acc[8 * p + 3] * i1),
                      pack2(acc[8 * p + 4] * i0, acc[8 * p + 5] * i0), pack2(acc[8 * p + 6] * i1, acc[8 * p + 7] * i1));
        }
        fence_async();
        fence_async_g();
        bar_sync(2, 256);
        if (tid == 128) {
            mbar_expect_tx(sb + B_UC, 65536);
            tma3(sb + UCT, &mp.uc, 0, 64 * blockIdx.x, 0, sb + B_UC);
        }
        PT(7);
        fresh(acc);
        {
            uint32_t slot8 = 8 * h, par = 0, prev8 = 0;
#pragma unroll 1
            for (int kk = 0; kk < 64; kk++) {
                if (kk == 32) mbar_wait(sb + B_UC, 0);
                mbar_wait(sb + B_R2 + slot8, par);
                wg_fence();
                wgmma_ss_n256_tb1(acc, mkd(sd + (1u << 16) + (kk < 32 ? (R0 >> 4) : (UCT >> 4) - 4096) + (kk >> 2) * 512 + (kk & 3) * 2), mkd(bd2k + slot8 * 64), 1);
                wg_commit();
                wg_wait<1>();
                if (kk > 0 && lane == 0) mbar_arrive(sb + B_E2 + prev8);
                if (kk == 32 && w0 && elect1() && (atom_inc_s(sb + CNT + 12) & 1)) {
                    mbar_expect_tx(sb + B_X, 65536);
                    tma4(sb + R0, &mp.x, 0, 62 * ti, 0, b, sb + B_X);
                }
                prev8 = slot8;
                slot8 += 16;
                if (slot8 >= 96) { slot8 -= 96; par ^= 1; }
            }
        }
        wg_wait<0>();
        pin(acc);
        PT(8);
        mbar_wait(sb + B_X, 0);
        PT(9);
        {
            const uint32_t sr = (lrow + 63) & 63;
            const uint32_t xoff = sr * 128 + ((((lane >> 4) ^ sr) & 7) << 4);
#pragma unroll
            for (int p = 0; p < 16; p++) {
                const uint32_t a = ((sb + R0 + h * 32768 + xoff) ^ ((p & 3) << 5)) + (p >> 2) * 8192;
                uint32_t xv[4];
                ldsm4(a, xv);
#pragma unroll
                for (int e = 0; e < 4; e++)
                    xv[e] = pack2(acc[8 * p + 2 * e] + __uint_as_float(xv[e] << 16), acc[8 * p + 2 * e + 1] + __uint_as_float(xv[e] & 0xffff0000u));
                stsm4(a, xv[0], xv[1], xv[2], xv[3]);
            }
        }
        fence_async();
        bar_sync(3 + h, 128);
        if (el) {
            for (int c = 0; c < 4; c++) tma4_store(&mp.out, sb + R0 + (4 * h + c) * 8192, 0, 62 * ti, 4 * h + c, b);
            asm volatile("cp.async.bulk.commit_group;" ::: "memory");
            PT(10);
            if (h == 0) cta_done(mode);
            asm volatile("cp.async.bulk.wait_group.read 0;" ::: "memory");
        }
        PT(11);
        PG(201);
        PDUMP();
    }
}

typedef CUresult (*PFN_enc)(CUtensorMap*, CUtensorMapDataType, cuuint32_t, void*, const cuuint64_t*, const cuuint64_t*,
                            const cuuint32_t*, const cuuint32_t*, CUtensorMapInterleave, CUtensorMapSwizzle,
                            CUtensorMapL2promotion, CUtensorMapFloatOOBfill);

static void enc(PFN_enc f, CUtensorMap* m, void* base, int rank, const cuuint64_t* dims, const cuuint64_t* strides, const cuuint32_t* box) {
    cuuint32_t es[5] = {1, 1, 1, 1, 1};
    f(m, CU_TENSOR_MAP_DATA_TYPE_BFLOAT16, rank, base, dims, strides, box, es, CU_TENSOR_MAP_INTERLEAVE_NONE,
      CU_TENSOR_MAP_SWIZZLE_128B, CU_TENSOR_MAP_L2_PROMOTION_L2_256B, CU_TENSOR_MAP_FLOAT_OOB_FILL_NONE);
}
static void enc_act(PFN_enc f, CUtensorMap* m, void* base, int rows, int chunks, int trows = T_, int pitch = T_) {
    cuuint64_t dims[4] = {64, (cuuint64_t)trows, 8, (cuuint64_t)NB_};
    cuuint64_t st[3] = {1024, 128, (cuuint64_t)pitch * 1024};
    cuuint32_t box[4] = {64, (cuuint32_t)rows, (cuuint32_t)chunks, 1};
    enc(f, m, base, 4, dims, st, box);
}
static void enc_w(PFN_enc f, CUtensorMap* m, void* base, int krows, int ncols, int bk, int bc) {
    cuuint64_t dims[3] = {64, (cuuint64_t)krows, (cuuint64_t)(ncols / 64)};
    cuuint64_t st[2] = {(cuuint64_t)ncols * 2, 128};
    cuuint32_t box[3] = {64, (cuuint32_t)bk, (cuuint32_t)bc};
    enc(f, m, base, 3, dims, st, box);
}

extern "C" void kernel_launch(void* const* d_in, const int* in_sizes, int n_in, void* d_out, int out_size) {
    const bf16* x = (const bf16*)d_in[0];
    static PFN_enc fenc = nullptr;
    static void *p_xa, *p_mqk, *p_uc, *p_t1;
    static int fused = 0;
    if (!fenc) {
        void* fn = nullptr;
        cudaDriverEntryPointQueryResult qr;
        cudaGetDriverEntryPoint("cuTensorMapEncodeTiled", &fn, cudaEnableDefault, &qr);
        fenc = (PFN_enc)fn;
        cudaGetSymbolAddress(&p_xa, g_xa);
        cudaGetSymbolAddress(&p_mqk, g_mqk);
        cudaGetSymbolAddress(&p_uc, g_uc);
        cudaGetSymbolAddress(&p_t1, g_t1);
        cudaFuncSetAttribute(main_kernel, cudaFuncAttributeMaxDynamicSharedMemorySize, SMEM_BYTES);
        int dev = 0, sms = 0, occ = 0;
        cudaGetDevice(&dev);
        cudaDeviceGetAttribute(&sms, cudaDevAttrMultiProcessorCount, dev);
        cudaOccupancyMaxActiveBlocksPerMultiprocessor(&occ, main_kernel, 384, SMEM_BYTES);
        fused = sms * occ >= NCTA + 2;
    }
    Maps mp;
    enc_act(fenc, &mp.xa, (char*)p_xa + 1024, 64, 8, T_, T_ + 8);
    enc_act(fenc, &mp.xa2, (char*)p_xa + 1024, 64, 2, T_, T_ + 8);
    enc_act(fenc, &mp.xas, p_xa, 64, 1, T_ + 1, T_ + 8);
    enc_act(fenc, &mp.x, (void*)x, 64, 8);
    enc_act(fenc, &mp.xh, (void*)x, 32, 1);
    enc_act(fenc, &mp.out, d_out, 62, 1);
    enc_w(fenc, &mp.wup4, d_in[5], 512, 1024, 16, 4);
    enc_w(fenc, &mp.wup8, d_in[5], 512, 1024, 16, 8);
    enc_w(fenc, &mp.mqa2, p_mqk, 512, 512, 32, 2);
    enc_w(fenc, &mp.mqa4, p_mqk, 512, 512, 32, 4);
    enc_w(fenc, &mp.mqb1, p_mqk, 512, 512, 64, 1);
    enc_w(fenc, &mp.mqb2, p_mqk, 512, 512, 64, 2);
    enc_w(fenc, &mp.uc, p_uc, NCTA * 64, 512, 64, 8);
    enc_w(fenc, &mp.wq, d_in[1], 512, 512, 64, 8);
    enc_w(fenc, &mp.wk, d_in[2], 512, 512, 32, 8);
    enc_w(fenc, &mp.fa[0], d_in[3], 512, 512, 128, 1);
    enc_w(fenc, &mp.fa[1], d_in[7], 512, 512, 128, 1);
    enc_w(fenc, &mp.fa[2], p_t1, 512, 512, 128, 1);
    enc_w(fenc, &mp.fb[0], d_in[4], 512, 512, 64, 4);
    enc_w(fenc, &mp.fb[1], d_in[8], 1024, 512, 64, 4);
    enc_w(fenc, &mp.fc, p_t1, 512, 512, 64, 4);
    cudaStream_t st = cudaStreamPerThread;
    if (fused) {
        main_kernel<<<NCTA + 2, 384, SMEM_BYTES, st>>>(mp, (const bf16*)d_in[6], (const bf16*)d_in[5], 0);
    } else {
        main_kernel<<<NCTA + 2, 384, SMEM_BYTES, st>>>(mp, (const bf16*)d_in[6], (const bf16*)d_in[5], 1);
        main_kernel<<<NCTA + 2, 384, SMEM_BYTES, st>>>(mp, (const bf16*)d_in[6], (const bf16*)d_in[5], 2);
    }
}
```

```cpp
#include <cuda_runtime.h>
#include <cuda_bf16.h>
#include <cuda.h>
#include <stdint.h>

typedef __nv_bfloat16 bf16;

constexpr int T_ = 4000, D_ = 512, NB_ = 2;
constexpr int TPB = 65;
constexpr int NCTA = TPB * NB_;
constexpr int NKV = 63;

__device__ __align__(1024) bf16 g_xa[NB_ * (T_ + 8) * D_];
__device__ __align__(1024) bf16 g_mqk[D_ * D_];
__device__ __align__(1024) bf16 g_t1[D_ * D_];
__device__ __align__(1024) bf16 g_wepi[2 * D_ * D_];
__device__ __align__(1024) bf16 g_uc[NCTA * 64 * D_];
__device__ unsigned g_sync[8];

#define PT(i) do { if (el) asm volatile("st.shared.u32 [%0], %1;" ::"r"(sb + MISC + 2560), "r"((unsigned)clock())); } while (0)
#define PG(i)
#define PLM 15
#define PL(j, q) do { if ((PLM >> ((q) + (wg ? 4 : 0))) & 1) PT(0); } while (0)
#define PDUMP()

#define FENCE_AT 1
#define GO_AT 25
#define LAZY 8.f
#define XS_GAP 800
#define PFW 1
constexpr uint32_t R0 = 0, R1 = 65536, R2 = 131072, R3 = 196608, QS = 221184, MISC = 229376;
constexpr uint32_t AT = 147456, DWS = R3 + 16384, UCT = 163840;
constexpr uint32_t SMEM_BYTES = 232448;
constexpr uint32_t B_A = MISC, B_R1 = MISC + 8  , B_MK = MISC + 48, B_LN = MISC + 56, B_MQ = MISC + 64, B_XA = MISC + 72, B_A2 = MISC + 80,
                   B_H1 = MISC + 88, B_H2 = MISC + 96, B_H3 = MISC + 104,
                   B_KV = MISC + 112, B_P = MISC + 136, B_GO = MISC + 160, B_R2 = MISC + 184, B_UC = MISC + 280,
                   B_X = MISC + 288, CNT = MISC + 296  , B_E2 = MISC + 320  , SCL = MISC + 512  ,
                   LINV = MISC + 1280  , STAT = MISC + 1536  ;

__device__ __forceinline__ uint32_t smem_u32(const void* p) { return (uint32_t)__cvta_generic_to_shared(p); }
__device__ __forceinline__ void wg_fence() { asm volatile("wgmma.fence.sync.aligned;" ::: "memory"); }
__device__ __forceinline__ void wg_commit() { asm volatile("wgmma.commit_group.sync.aligned;" ::: "memory"); }
template <int N> __device__ __forceinline__ void wg_wait() { asm volatile("wgmma.wait_group.sync.aligned %0;" ::"n"(N) : "memory"); }
__device__ __forceinline__ uint64_t dsc(uint32_t sd, uint32_t off, uint32_t lbo) {
    uint32_t lo = sd + (off >> 4) + ((lbo >> 4) << 16);
    uint64_t d;
    asm("mov.b64 %0, {%1, %2};" : "=l"(d) : "r"(lo), "r"((1024u >> 4) | (1u << 30)));
    return d;
}
__device__ __forceinline__ bool elect1() {
    uint32_t p;
    asm volatile("{\n.reg .pred p;\nelect.sync _|p, 0xffffffff;\nselp.u32 %0, 1, 0, p;\n}\n" : "=r"(p));
    return p != 0;
}
__device__ __forceinline__ void mbar_init(uint32_t bar, int cnt) { asm volatile("mbarrier.init.shared::cta.b64 [%0], %1;" ::"r"(bar), "r"(cnt) : "memory"); }
__device__ __forceinline__ void mbar_expect_tx(uint32_t bar, uint32_t bytes) { asm volatile("mbarrier.arrive.expect_tx.shared::cta.b64 _, [%0], %1;" ::"r"(bar), "r"(bytes) : "memory"); }
__device__ __forceinline__ void mbar_arrive(uint32_t bar) { asm volatile("mbarrier.arrive.shared::cta.b64 _, [%0];" ::"r"(bar) : "memory"); }
__device__ __forceinline__ void mbar_wait(uint32_t bar, uint32_t parity) {
    uint32_t ok;
#pragma unroll 1
    for (uint32_t it = 0;; ++it) {
        asm volatile("{\n.reg .pred p;\nmbarrier.try_wait.parity.shared::cta.b64 p, [%1], %2;\nselp.u32 %0, 1, 0, p;\n}\n" : "=r"(ok) : "r"(bar), "r"(parity) : "memory");
        if (ok) break;
        if (it > (1u << 20)) __trap();
    }
}
__device__ __forceinline__ void fence_async() { asm volatile("fence.proxy.async.shared::cta;" ::: "memory"); }
__device__ __forceinline__ void fence_async_g() { asm volatile("fence.proxy.async.global;" ::: "memory"); }
__device__ __forceinline__ void bar_sync(int id, int n) { asm volatile("bar.sync %0, %1;" ::"r"(id), "r"(n) : "memory"); }
__device__ __forceinline__ void tma3(uint32_t dst, const CUtensorMap* tm, int c0, int c1, int c2, uint32_t bar) {
    asm volatile("cp.async.bulk.tensor.3d.shared::cluster.global.mbarrier::complete_tx::bytes [%0], [%1, {%3, %4, %5}], [%2];"
                 ::"r"(dst), "l"(tm), "r"(bar), "r"(c0), "r"(c1), "r"(c2) : "memory");
}
__device__ __forceinline__ void tma4(uint32_t dst, const CUtensorMap* tm, int c0, int c1, int c2, int c3, uint32_t bar) {
    asm volatile("cp.async.bulk.tensor.4d.shared::cluster.global.mbarrier::complete_tx::bytes [%0], [%1, {%3, %4, %5, %6}], [%2];"
                 ::"r"(dst), "l"(tm), "r"(bar), "r"(c0), "r"(c1), "r"(c2), "r"(c3) : "memory");
}
__device__ __forceinline__ void tma4_store(const CUtensorMap* tm, uint32_t src, int c0, int c1, int c2, int c3) {
    asm volatile("cp.async.bulk.tensor.4d.global.shared::cta.bulk_group [%0, {%2, %3, %4, %5}], [%1];"
                 ::"l"(tm), "r"(src), "r"(c0), "r"(c1), "r"(c2), "r"(c3) : "memory");
}
__device__ __forceinline__ void tma3_store(const CUtensorMap* tm, uint32_t src, int c0, int c1, int c2) {
    asm volatile("cp.async.bulk.tensor.3d.global.shared::cta.bulk_group [%0, {%2, %3, %4}], [%1];"
                 ::"l"(tm), "r"(src), "r"(c0), "r"(c1), "r"(c2) : "memory");
}
__device__ __forceinline__ void stsm4(uint32_t addr, uint32_t a, uint32_t b, uint32_t c, uint32_t d) {
    asm volatile("stmatrix.sync.aligned.m8n8.x4.shared.b16 [%0], {%1, %2, %3, %4};" ::"r"(addr), "r"(a), "r"(b), "r"(c), "r"(d) : "memory");
}
__device__ __forceinline__ void ldsm4(uint32_t addr, uint32_t (&r)[4]) {
    asm volatile("ldmatrix.sync.aligned.m8n8.x4.shared.b16 {%0, %1, %2, %3}, [%4];" : "=r"(r[0]), "=r"(r[1]), "=r"(r[2]), "=r"(r[3]) : "r"(addr) : "memory");
}
__device__ __forceinline__ void ldsm2(uint32_t addr, uint32_t (&r)[2]) {
    asm volatile("ldmatrix.sync.aligned.m8n8.x2.shared.b16 {%0, %1}, [%2];" : "=r"(r[0]), "=r"(r[1]) : "r"(addr) : "memory");
}
__device__ __forceinline__ void stg4(void* p, uint32_t a, uint32_t b, uint32_t c, uint32_t d) {
    asm volatile("st.global.v4.u32 [%0], {%1, %2, %3, %4};" ::"l"(p), "r"(a), "r"(b), "r"(c), "r"(d) : "memory");
}
__device__ __forceinline__ uint32_t pack2(float lo, float hi) {
    uint32_t r;
    asm("cvt.rn.bf16x2.f32 %0, %1, %2;" : "=r"(r) : "f"(hi), "f"(lo));
    return r;
}
__device__ __forceinline__ uint32_t pack2v(float lo, float hi) {
    uint32_t r;
    asm volatile("cvt.rn.bf16x2.f32 %0, %1, %2;" : "=r"(r) : "f"(hi), "f"(lo));
    return r;
}
__device__ __forceinline__ uint32_t bmul2(uint32_t a, uint32_t b) { uint32_t r; asm("mul.rn.bf16x2 %0, %1, %2;" : "=r"(r) : "r"(a), "r"(b)); return r; }
__device__ __forceinline__ uint32_t bfma2(uint32_t a, uint32_t b, uint32_t c) { uint32_t r; asm("fma.rn.bf16x2 %0, %1, %2, %3;" : "=r"(r) : "r"(a), "r"(b), "r"(c)); return r; }
__device__ __forceinline__ float ex2(float x) { float r; asm("ex2.approx.ftz.f32 %0, %1;" : "=f"(r) : "f"(x)); return r; }
__device__ __forceinline__ float rcp(float x) { float r; asm("rcp.approx.ftz.f32 %0, %1;" : "=f"(r) : "f"(x)); return r; }
__device__ __forceinline__ float gelu2(float x) {
    float t = fmaf(x * x, 0.044715f * 0.7978845608028654f, 0.7978845608028654f), th;
    asm("tanh.approx.f32 %0, %1;" : "=f"(th) : "f"(x * t));
    return fmaf(x, th, x);
}
__device__ __forceinline__ uint32_t ldg_v(const uint32_t* p) { uint32_t v; asm volatile("ld.global.nc.u32 %0, [%1];" : "=r"(v) : "l"(p)); return v; }
__device__ __forceinline__ float lds_f32(uint32_t a) { float v; asm volatile("ld.shared.f32 %0, [%1];" : "=f"(v) : "r"(a) : "memory"); return v; }
__device__ __forceinline__ void sts_f32(uint32_t a, float v) { asm volatile("st.shared.f32 [%0], %1;" ::"r"(a), "f"(v) : "memory"); }
__device__ __forceinline__ uint32_t atom_inc_s(uint32_t a) { uint32_t v; asm volatile("atom.relaxed.cta.shared.add.u32 %0, [%1], 1;" : "=r"(v) : "r"(a) : "memory"); return v; }
__device__ __forceinline__ void lds4(uint32_t a, uint32_t* r) {
    asm volatile("ld.shared.v4.u32 {%0, %1, %2, %3}, [%4];" : "=r"(r[0]), "=r"(r[1]), "=r"(r[2]), "=r"(r[3]) : "r"(a) : "memory");
}
__device__ __forceinline__ void sts4(uint32_t a, uint32_t x, uint32_t y, uint32_t z, uint32_t t) {
    asm volatile("st.shared.v4.u32 [%0], {%1, %2, %3, %4};" ::"r"(a), "r"(x), "r"(y), "r"(z), "r"(t) : "memory");
}
__device__ __forceinline__ uint32_t bsub2(uint32_t a, uint32_t b) { uint32_t r; asm("sub.rn.bf16x2 %0, %1, %2;" : "=r"(r) : "r"(a), "r"(b)); return r; }
__device__ __forceinline__ float blo(uint32_t v) { return __uint_as_float(v << 16); }
__device__ __forceinline__ float bhi(uint32_t v) { return __uint_as_float(v & 0xffff0000u); }
__device__ __forceinline__ float bfr(float x) { return __bfloat162float(__float2bfloat16_rn(x)); }
__device__ __forceinline__ void l2_prefetch(const void* p, uint32_t bytes) { asm volatile("cp.async.bulk.prefetch.L2.global [%0], %1;" ::"l"(p), "r"(bytes) : "memory"); }
__device__ __forceinline__ void flag_add(unsigned* p) { asm volatile("red.release.gpu.global.add.u32 [%0], 1;" ::"l"(p) : "memory"); }
__device__ __forceinline__ void flag_wait(const unsigned* p, unsigned target) {
#pragma unroll 1
    for (uint32_t it = 0;; ++it) {
        unsigned v;
        asm volatile("ld.acquire.gpu.global.u32 %0, [%1];" : "=r"(v) : "l"(p) : "memory");
        if (v >= target) break;
        if (it > (1u << 20)) __trap();
    }
    fence_async_g();
}
template <int N> __device__ __forceinline__ void pin(float (&a)[N]) {
#pragma unroll
    for (int i = 0; i < N; i++) asm volatile("" : "+f"(a[i])::"memory");
}

template <int N> __device__ __forceinline__ void fresh(float (&a)[N]) {
#pragma unroll
    for (int i = 0; i < N; i++) a[i] = 0.f;
    pin(a);
}

__device__ __forceinline__ void wgmma_rs_n64_tb0(float (&d)[32], uint32_t a0, uint32_t a1, uint32_t a2, uint32_t a3, uint64_t db, int scale_d) {
    asm volatile("{\n.reg .pred p;\nsetp.ne.b32 p, %37, 0;\n"
        "wgmma.mma_async.sync.aligned.m64n64k16.f32.bf16.bf16 {%0, %1, %2, %3, %4, %5, %6, %7, %8, %9, %10, %11, %12, %13, %14, %15, %16, %17, %18, %19, %20, %21, %22, %23, %24, %25, %26, %27, %28, %29, %30, %31}, {%32, %33, %34, %35}, %36, p, 1, 1, 0;\n}\n"
        : "+f"(d[0]), "+f"(d[1]), "+f"(d[2]), "+f"(d[3]), "+f"(d[4]), "+f"(d[5]), "+f"(d[6]), "+f"(d[7]), "+f"(d[8]), "+f"(d[9]), "+f"(d[10]), "+f"(d[11]), "+f"(d[12]), "+f"(d[13]), "+f"(d[14]), "+f"(d[15]), "+f"(d[16]), "+f"(d[17]), "+f"(d[18]), "+f"(d[19]), "+f"(d[20]), "+f"(d[21]), "+f"(d[22]), "+f"(d[23]), "+f"(d[24]), "+f"(d[25]), "+f"(d[26]), "+f"(d[27]), "+f"(d[28]), "+f"(d[29]), "+f"(d[30]), "+f"(d[31])
        : "r"(a0), "r"(a1), "r"(a2), "r"(a3), "l"(db), "r"(scale_d));
}

__device__ __forceinline__ void wgmma_ss_n128_tb1(float (&d)[64], uint64_t da, uint64_t db, int scale_d) {
    asm volatile("{\n.reg .pred p;\nsetp.ne.b32 p, %66, 0;\n"
        "wgmma.mma_async.sync.aligned.m64n128k16.f32.bf16.bf16 {%0, %1, %2, %3, %4, %5, %6, %7, %8, %9, %10, %11, %12, %13, %14, %15, %16, %17, %18, %19, %20, %21, %22, %23, %24, %25, %26, %27, %28, %29, %30, %31, %32, %33, %34, %35, %36, %37, %38, %39, %40, %41, %42, %43, %44, %45, %46, %47, %48, %49, %50, %51, %52, %53, %54, %55, %56, %57, %58, %59, %60, %61, %62, %63}, %64, %65, p, 1, 1, 0, 1;\n}\n"
        : "+f"(d[0]), "+f"(d[1]), "+f"(d[2]), "+f"(d[3]), "+f"(d[4]), "+f"(d[5]), "+f"(d[6]), "+f"(d[7]), "+f"(d[8]), "+f"(d[9]), "+f"(d[10]), "+f"(d[11]), "+f"(d[12]), "+f"(d[13]), "+f"(d[14]), "+f"(d[15]), "+f"(d[16]), "+f"(d[17]), "+f"(d[18]), "+f"(d[19]), "+f"(d[20]), "+f"(d[21]), "+f"(d[22]), "+f"(d[23]), "+f"(d[24]), "+f"(d[25]), "+f"(d[26]), "+f"(d[27]), "+f"(d[28]), "+f"(d[29]), "+f"(d[30]), "+f"(d[31]), "+f"(d[32]), "+f"(d[33]), "+f"(d[34]), "+f"(d[35]), "+f"(d[36]), "+f"(d[37]), "+f"(d[38]), "+f"(d[39]), "+f"(d[40]), "+f"(d[41]), "+f"(d[42]), "+f"(d[43]), "+f"(d[44]), "+f"(d[45]), "+f"(d[46]), "+f"(d[47]), "+f"(d[48]), "+f"(d[49]), "+f"(d[50]), "+f"(d[51]), "+f"(d[52]), "+f"(d[53]), "+f"(d[54]), "+f"(d[55]), "+f"(d[56]), "+f"(d[57]), "+f"(d[58]), "+f"(d[59]), "+f"(d[60]), "+f"(d[61]), "+f"(d[62]), "+f"(d[63])
        : "l"(da), "l"(db), "r"(scale_d));
}

__device__ __forceinline__ void wgmma_ss_n256_tb1(float (&d)[128], uint64_t da, uint64_t db, int scale_d) {
    asm volatile("{\n.reg .pred p;\nsetp.ne.b32 p, %130, 0;\n"
        "wgmma.mma_async.sync.aligned.m64n256k16.f32.bf16.bf16 {%0, %1, %2, %3, %4, %5, %6, %7, %8, %9, %10, %11, %12, %13, %14, %15, %16, %17, %18, %19, %20, %21, %22, %23, %24, %25, %26, %27, %28, %29, %30, %31, %32, %33, %34, %35, %36, %37, %38, %39, %40, %41, %42, %43, %44, %45, %46, %47, %48, %49, %50, %51, %52, %53, %54, %55, %56, %57, %58, %59, %60, %61, %62, %63, %64, %65, %66, %67, %68, %69, %70, %71, %72, %73, %74, %75, %76, %77, %78, %79, %80, %81, %82, %83, %84, %85, %86, %87, %88, %89, %90, %91, %92, %93, %94, %95, %96, %97, %98, %99, %100, %101, %102, %103, %104, %105, %106, %107, %108, %109, %110, %111, %112, %113, %114, %115, %116, %117, %118, %119, %120, %121, %122, %123, %124, %125, %126, %127}, %128, %129, p, 1, 1, 0, 1;\n}\n"
        : "+f"(d[0]), "+f"(d[1]), "+f"(d[2]), "+f"(d[3]), "+f"(d[4]), "+f"(d[5]), "+f"(d[6]), "+f"(d[7]), "+f"(d[8]), "+f"(d[9]), "+f"(d[10]), "+f"(d[11]), "+f"(d[12]), "+f"(d[13]), "+f"(d[14]), "+f"(d[15]), "+f"(d[16]), "+f"(d[17]), "+f"(d[18]), "+f"(d[19]), "+f"(d[20]), "+f"(d[21]), "+f"(d[22]), "+f"(d[23]), "+f"(d[24]), "+f"(d[25]), "+f"(d[26]), "+f"(d[27]), "+f"(d[28]), "+f"(d[29]), "+f"(d[30]), "+f"(d[31]), "+f"(d[32]), "+f"(d[33]), "+f"(d[34]), "+f"(d[35]), "+f"(d[36]), "+f"(d[37]), "+f"(d[38]), "+f"(d[39]), "+f"(d[40]), "+f"(d[41]), "+f"(d[42]), "+f"(d[43]), "+f"(d[44]), "+f"(d[45]), "+f"(d[46]), "+f"(d[47]), "+f"(d[48]), "+f"(d[49]), "+f"(d[50]), "+f"(d[51]), "+f"(d[52]), "+f"(d[53]), "+f"(d[54]), "+f"(d[55]), "+f"(d[56]), "+f"(d[57]), "+f"(d[58]), "+f"(d[59]), "+f"(d[60]), "+f"(d[61]), "+f"(d[62]), "+f"(d[63]), "+f"(d[64]), "+f"(d[65]), "+f"(d[66]), "+f"(d[67]), "+f"(d[68]), "+f"(d[69]), "+f"(d[70]), "+f"(d[71]), "+f"(d[72]), "+f"(d[73]), "+f"(d[74]), "+f"(d[75]), "+f"(d[76]), "+f"(d[77]), "+f"(d[78]), "+f"(d[79]), "+f"(d[80]), "+f"(d[81]), "+f"(d[82]), "+f"(d[83]), "+f"(d[84]), "+f"(d[85]), "+f"(d[86]), "+f"(d[87]), "+f"(d[88]), "+f"(d[89]), "+f"(d[90]), "+f"(d[91]), "+f"(d[92]), "+f"(d[93]), "+f"(d[94]), "+f"(d[95]), "+f"(d[96]), "+f"(d[97]), "+f"(d[98]), "+f"(d[99]), "+f"(d[100]), "+f"(d[101]), "+f"(d[102]), "+f"(d[103]), "+f"(d[104]), "+f"(d[105]), "+f"(d[106]), "+f"(d[107]), "+f"(d[108]), "+f"(d[109]), "+f"(d[110]), "+f"(d[111]), "+f"(d[112]), "+f"(d[113]), "+f"(d[114]), "+f"(d[115]), "+f"(d[116]), "+f"(d[117]), "+f"(d[118]), "+f"(d[119]), "+f"(d[120]), "+f"(d[121]), "+f"(d[122]), "+f"(d[123]), "+f"(d[124]), "+f"(d[125]), "+f"(d[126]), "+f"(d[127])
        : "l"(da), "l"(db), "r"(scale_d));
}

__device__ __forceinline__ void wgmma_ss_n32_tb0(float (&d)[16], uint64_t da, uint64_t db, int scale_d) {
    asm volatile("{\n.reg .pred p;\nsetp.ne.b32 p, %18, 0;\n"
        "wgmma.mma_async.sync.aligned.m64n32k16.f32.bf16.bf16 {%0, %1, %2, %3, %4, %5, %6, %7, %8, %9, %10, %11, %12, %13, %14, %15}, %16, %17, p, 1, 1, 0, 0;\n}\n"
        : "+f"(d[0]), "+f"(d[1]), "+f"(d[2]), "+f"(d[3]), "+f"(d[4]), "+f"(d[5]), "+f"(d[6]), "+f"(d[7]), "+f"(d[8]), "+f"(d[9]), "+f"(d[10]), "+f"(d[11]), "+f"(d[12]), "+f"(d[13]), "+f"(d[14]), "+f"(d[15])
        : "l"(da), "l"(db), "r"(scale_d));
}

__device__ __forceinline__ void wgmma_ss_n64_tb0(float (&d)[32], uint64_t da, uint64_t db, int scale_d) {
    asm volatile("{\n.reg .pred p;\nsetp.ne.b32 p, %34, 0;\n"
        "wgmma.mma_async.sync.aligned.m64n64k16.f32.bf16.bf16 {%0, %1, %2, %3, %4, %5, %6, %7, %8, %9, %10, %11, %12, %13, %14, %15, %16, %17, %18, %19, %20, %21, %22, %23, %24, %25, %26, %27, %28, %29, %30, %31}, %32, %33, p, 1, 1, 0, 0;\n}\n"
        : "+f"(d[0]), "+f"(d[1]), "+f"(d[2]), "+f"(d[3]), "+f"(d[4]), "+f"(d[5]), "+f"(d[6]), "+f"(d[7]), "+f"(d[8]), "+f"(d[9]), "+f"(d[10]), "+f"(d[11]), "+f"(d[12]), "+f"(d[13]), "+f"(d[14]), "+f"(d[15]), "+f"(d[16]), "+f"(d[17]), "+f"(d[18]), "+f"(d[19]), "+f"(d[20]), "+f"(d[21]), "+f"(d[22]), "+f"(d[23]), "+f"(d[24]), "+f"(d[25]), "+f"(d[26]), "+f"(d[27]), "+f"(d[28]), "+f"(d[29]), "+f"(d[30]), "+f"(d[31])
        : "l"(da), "l"(db), "r"(scale_d));
}

struct Maps {
    CUtensorMap xa, xa2, xas, xh, wup4, wup8, mqa2, mqa4, mqb1, mqb2, uc, x, out, wq, wk, fa[3], fb[2], fc;
};

__device__ __forceinline__ uint64_t mkd(uint32_t lo) {
    uint64_t d;
    asm("mov.b64 %0, {%1, %2};" : "=l"(d) : "r"(lo), "r"((1024u >> 4) | (1u << 30)));
    return d;
}
__device__ __forceinline__ void bulk_ld(uint32_t dst, const void* src, uint32_t bytes, uint32_t bar) {
    asm volatile("cp.async.bulk.shared::cluster.global.mbarrier::complete_tx::bytes [%0], [%1], %2, [%3];" ::"r"(dst), "l"(src), "r"(bytes), "r"(bar) : "memory");
}
__device__ __forceinline__ void bulk_st(void* dst, uint32_t src, uint32_t bytes) {
    asm volatile("cp.async.bulk.global.shared::cta.bulk_group [%0], [%1], %2;" ::"l"(dst), "r"(src), "r"(bytes) : "memory");
}
__device__ __forceinline__ void ring_ld(uint32_t sb, uint32_t slot8, int n) {
    mbar_expect_tx(sb + B_R2 + slot8, 8192);
    bulk_ld(sb + R1 + slot8 * 1024, (const char*)g_wepi + n * 8192, 8192, sb + B_R2 + slot8);
}

__device__ __forceinline__ void ring_half(uint32_t sb, uint32_t slot8, uint32_t hoff, const CUtensorMap* tm, int c1, int c2) {
    mbar_expect_tx(sb + B_R1 + slot8, 8192);
    tma3(sb + R1 + slot8 * 2048 + hoff, tm, 0, c1, c2, sb + B_R1 + slot8);
}
__device__ __forceinline__ void ring_full(uint32_t sb, uint32_t slot8, const CUtensorMap* tm, int c1, int c2) {
    mbar_expect_tx(sb + B_R1 + slot8, 16384);
    mbar_arrive(sb + B_R1 + slot8);
    tma3(sb + R1 + slot8 * 2048, tm, 0, c1, c2, sb + B_R1 + slot8);
}
__device__ __forceinline__ void cta_done(int mode) {
    if (mode == 0 && atomicAdd(&g_sync[4], 1) == NCTA + 1) {
#pragma unroll
        for (int i = 0; i < 5; i++) g_sync[i] = 0;
    }
}

__device__ __forceinline__ void fold_cta(const Maps& mp, uint32_t sb, int mode) {
    constexpr uint32_t F_FULL = MISC, F_EMPTY = MISC + 32, F_T1 = MISC + 64, STG = 49152, FOUT = 3 * STG;
    const int tid = threadIdx.x, f = blockIdx.x - NCTA;
    if (mode == 2) return;
    if (tid == 0) {
        for (int i = 0; i < 3; i++) { mbar_init(sb + F_FULL + 8 * i, 1); mbar_init(sb + F_EMPTY + 8 * i, 2); }
        mbar_init(sb + F_T1, 2);
        asm volatile("fence.mbarrier_init.release.cluster;" ::: "memory");
        fence_async();
    }
    __syncthreads();
    const int wg = __shfl_sync(0xffffffffu, tid >> 7, 0);
    int st = 0, ph = 0;
    if (wg == 0) {
        if (tid == 0) {
#pragma unroll 1
            for (int it = 0; it < 96; it++) {
                const int p = it >> 3, kc = it & 7, job = p >> 2;
                if (it == 64) mbar_wait(sb + F_T1, 0);
                mbar_wait(sb + F_EMPTY + 8 * st, ph ^ 1);
                mbar_expect_tx(sb + F_FULL + 8 * st, STG);
                tma3(sb + st * STG, &mp.fa[job], 0, 256 * f + 128 * ((p >> 1) & 1), kc, sb + F_FULL + 8 * st);
                tma3(sb + st * STG + 16384, &mp.fb[job != 0], 0, 64 * kc + (job == 1 ? 512 : 0), 4 * (p & 1), sb + F_FULL + 8 * st);
                if (++st == 3) { st = 0; ph ^= 1; }
            }
        }
        return;
    }
    const int h = wg - 1, lane = tid & 31, w = (tid >> 5) & 3;
    const uint32_t sd = (sb & 0x3FFFF) >> 4;
    const bool el = (tid & 127) == 0;
#pragma unroll 1
    for (int p = 0; p < 12; p++) {
        float acc[128];
        fresh(acc);
#pragma unroll 1
        for (int kc = 0; kc < 8; kc++) {
            mbar_wait(sb + F_FULL + 8 * st, ph);
            wg_fence();
#pragma unroll
            for (int kk = 0; kk < 4; kk++)
                wgmma_ss_n256_tb1(acc, dsc(sd, st * STG + h * 8192 + kk * 32, 16), dsc(sd, st * STG + 16384 + kk * 2048, 8192), 1);
            wg_commit();
            wg_wait<0>();
            if (el) mbar_arrive(sb + F_EMPTY + 8 * st);
            if (++st == 3) { st = 0; ph ^= 1; }
        }
        pin(acc);
        const int job = p >> 2;
        if (el) {
            asm volatile("cp.async.bulk.wait_group 0;" ::: "memory");
            if (p == 4) { fence_async_g(); mbar_arrive(sb + F_T1); }
        }
        bar_sync(3 + h, 128);
        uint32_t r = 16 * w + (lane & 7) + ((lane >> 3) & 1) * 8;
        const float fs = job == 1 ? 0.5f : 1.f;
        if (job == 1) r = (r & ~31) | (((r >> 1) & 3) << 3) | (((r >> 3) & 3) << 1) | (r & 1);
        const uint32_t oa = sb + FOUT + h * 32768 + r * 128 + ((((lane >> 4) ^ r) & 7) << 4);
#pragma unroll
        for (int i = 0; i < 16; i++)
            stsm4((oa ^ ((i & 3) << 5)) + (i >> 2) * 8192, pack2(acc[8 * i] * fs, acc[8 * i + 1] * fs), pack2(acc[8 * i + 2] * fs, acc[8 * i + 3] * fs),
                  pack2(acc[8 * i + 4] * fs, acc[8 * i + 5] * fs), pack2(acc[8 * i + 6] * fs, acc[8 * i + 7] * fs));
        fence_async();
        bar_sync(3 + h, 128);
        if (el) {
            const int row0 = 256 * f + 128 * ((p >> 1) & 1) + 64 * h + (job == 1 ? 512 : 0);
            if (job == 0) tma3_store(&mp.fc, sb + FOUT + h * 32768, 0, row0, 4 * (p & 1));
            else {
#pragma unroll 1
                for (int i = 0; i < 16; i++)
                    bulk_st((char*)g_wepi + (row0 / 8 + 2 * (i & 3) + (p & 1)) * 8192 + (i >> 2) * 2048, sb + FOUT + h * 32768 + i * 2048, 2048);
            }
            asm volatile("cp.async.bulk.commit_group;" ::: "memory");
        }
    }
    if (el) {
        asm volatile("cp.async.bulk.wait_group 0;" ::: "memory");
        fence_async_g();
        if (mode == 0) flag_add(&g_sync[3]);
    }
    bar_sync(2, 256);
    if (tid == 128) cta_done(mode);
}

__global__ void __launch_bounds__(384, 1) main_kernel(const __grid_constant__ Maps mp, const bf16* __restrict__ dw, const bf16* wup, const int mode) {
    extern __shared__ __align__(1024) uint8_t smem[];
    const uint32_t sb = smem_u32(smem);
    const int tid = threadIdx.x;
    if (blockIdx.x >= NCTA) { fold_cta(mp, sb, mode); return; }
    const int b = blockIdx.x / TPB, ti = blockIdx.x % TPB;
    const int piece = blockIdx.x & 127;
    if (tid == 0) {
        mbar_init(sb + B_A, 1); mbar_init(sb + B_A2, 1); mbar_init(sb + B_MK, 1);
        for (int i = 0; i < 5; i++) mbar_init(sb + B_R1 + 8 * i, 2);
        asm volatile("fence.mbarrier_init.release.cluster;" ::: "memory");
        fence_async();
        mbar_expect_tx(sb + B_MK, 65536 + 32768);
        tma3(sb + R0, &mp.wq, 0, 64 * (piece >> 4), 0, sb + B_MK);
        tma3(sb + R1 + 32768, &mp.wk, 0, 32 * (piece & 15), 0, sb + B_MK);
        mbar_expect_tx(sb + B_A, 32768);
        mbar_expect_tx(sb + B_A2, 32768 + 3072);
#pragma unroll 1
        for (int i = 0; i < 16; i++) tma4(sb + AT + (i & 7) * 8192 + (i >> 3) * 4096, &mp.xh, 0, 62 * ti - 1 + 32 * (i >> 3), i & 7, b, sb + (i < 8 ? B_A : B_A2));
        bulk_ld(sb + DWS, dw, 3072, sb + B_A2);
        for (int i = 0; i < 8; i++) mbar_arrive(sb + B_R1 + 8 * (i >> 1));
        if (mode != 1) {
            ring_full(sb, 32, &mp.wup8, 0, 8);
            ring_full(sb, 0, &mp.wup8, 16, 8);
            ring_full(sb, 8, &mp.wup8, 32, 8);
        }
    } else if (tid == 32) {
        mbar_init(sb + B_LN, 1); mbar_init(sb + B_MQ, 1); mbar_init(sb + B_XA, 1);
        mbar_init(sb + B_H1, 2); mbar_init(sb + B_H2, 1); mbar_init(sb + B_H3, 2);
        for (int i = 0; i < 3; i++) { mbar_init(sb + B_KV + 8 * i, 1); mbar_init(sb + B_P + 8 * i, 4); mbar_init(sb + B_GO + 8 * i, 4); }
        for (int i = 0; i < 12; i++) { mbar_init(sb + B_R2 + 8 * i, 1); mbar_init(sb + B_E2 + 8 * i, 4); }
        mbar_init(sb + B_UC, 1); mbar_init(sb + B_X, 1);
        for (int i = 0; i < 4; i++) asm volatile("st.shared.u32 [%0], 0;" ::"r"(sb + CNT + 4 * i) : "memory");
        asm volatile("fence.mbarrier_init.release.cluster;" ::: "memory");
        fence_async();
    }
    __syncthreads();
    const int wg = __shfl_sync(0xffffffffu, tid >> 7, 0);
    const int lane = tid & 31, w = (tid >> 5) & 3;
    const bool w0 = __shfl_sync(0xffffffffu, w, 0) == 0;
    const uint32_t sd = (sb & 0x3FFFF) >> 4;
    const uint32_t adA = sd + (AT >> 4) + (1u << 16);
    const uint32_t bd0 = sd + (R1 >> 4);
    const uint32_t bd2k = bd0 + ((2048u >> 4) << 16);
    const bool el = (tid & 127) == 0;
    const uint32_t lrow = 16 * w + (lane & 7) + ((lane >> 3) & 1) * 8;
    const uint32_t loff = lrow * 128 + ((((lane >> 4) ^ lrow) & 7) << 4);
    const int r0 = 16 * w + (lane >> 2);

    if (wg == 0) {
        asm volatile("setmaxnreg.inc.sync.aligned.u32 184;");
        uint32_t q[112];
        PT(0);
        PG(200);
        {
            float mq[16];
            fresh(mq);
            mbar_wait(sb + B_MK, 0);
            PT(1);
            if (PFW && tid == 32) l2_prefetch((const char*)wup + piece * 8192, 8192);
            wg_fence();
#pragma unroll 1
            for (int c = 0; c < 8; c++)
#pragma unroll
                for (int kk = 0; kk < 4; kk++)
                    wgmma_ss_n32_tb0(mq, dsc(sd, R0 + c * 8192 + kk * 32, 16), dsc(sd, R1 + 32768 + c * 4096 + kk * 32, 16), 1);
            wg_commit();
            wg_wait<0>();
            if (mode != 1 && w0 && elect1()) { ring_full(sb, 16, &mp.wup8, 48, 8); ring_full(sb, 24, &mp.wup8, 64, 8); }
            pin(mq);
            uint32_t* c = reinterpret_cast<uint32_t*>(g_mqk + (64 * (piece >> 4) + r0) * D_ + 32 * (piece & 15) + 2 * (lane & 3));
#pragma unroll
            for (int n = 0; n < 4; n++) { c[4 * n] = pack2(mq[4 * n], mq[4 * n + 1]); c[4 * n + 4 * D_] = pack2(mq[4 * n + 2], mq[4 * n + 3]); }
            fence_async_g();
            bar_sync(1, 128);
            if (el) {
                if (mode == 0) flag_add(&g_sync[2]);
                if (mode == 0) flag_wait(&g_sync[2], NCTA);
                mbar_arrive(sb + B_MQ);
                PT(12);
                mbar_wait(sb + B_LN, 0);
#pragma unroll 1
                for (int c = 0; c < 8; c++) {
                    tma4_store(&mp.xas, sb + AT + c * 8192, 0, 62 * ti, c, b);
                    const unsigned t0 = (unsigned)clock();
                    while (c < 7 && (unsigned)clock() - t0 < XS_GAP) __nanosleep(20);
                }
                asm volatile("cp.async.bulk.commit_group;" ::: "memory");
                if (mode == 1) asm volatile("cp.async.bulk.wait_group 0;" ::: "memory");
            }
            PT(13);
            if (mode == 1) return;
        }
        mbar_wait(sb + B_H1, 0);
        PT(2);
        uint32_t slot8 = 8, par = 1, prev8 = 0;
        auto adv = [&]() { prev8 = slot8; slot8 += 8; if (slot8 == 40) { slot8 = 0; par ^= 1; } };
        {
            float acc[128];
            fresh(acc);
            auto step = [&](int i) {
                const uint32_t aa = adA + (i >> 1) * 512 + (i & 1) * 4, bb = bd0 + ((4096u >> 4) << 16) + slot8 * 128;
                wg_fence();
                wgmma_ss_n256_tb1(acc, mkd(aa), mkd(bb), 1);
                wgmma_ss_n256_tb1(acc, mkd(aa + 2), mkd(bb + 128), 1);
                wg_commit();
                wg_wait<1>();
            };
#pragma unroll 1
            for (int i = 0; i < 12; i++) {
                mbar_wait(sb + B_R1 + slot8, par);
                step(i);
                if (i > 0 && w0 && elect1()) ring_full(sb, prev8, &mp.mqa4, 32 * i + 128, 4);
                adv();
            }
#pragma unroll 1
            for (int i = 12; i < 16; i++) {
                mbar_wait(sb + B_R1 + slot8, par);
                if (i == 15 && el) mbar_arrive(sb + B_H2);
                step(i);
                if (w0 && elect1()) ring_full(sb, prev8, &mp.wup8, 16 * i - 192, 0);
                adv();
            }
            wg_wait<0>();
            if (w0 && elect1()) ring_full(sb, prev8, &mp.wup8, 64, 0);
            pin(acc);
            PT(3);
#pragma unroll
            for (int kk = 0; kk < 4; kk++)
                stsm4((sb + QS + loff) ^ (kk << 5), pack2(acc[96 + 8 * kk], acc[97 + 8 * kk]), pack2(acc[98 + 8 * kk], acc[99 + 8 * kk]),
                      pack2(acc[100 + 8 * kk], acc[101 + 8 * kk]), pack2(acc[102 + 8 * kk], acc[103 + 8 * kk]));
            fence_async();
#pragma unroll
            for (int i = 47; i >= 0; i--) q[64 + i] = pack2v(acc[2 * i], acc[2 * i + 1]);
        }
        if (el) {
            asm volatile("cp.async.bulk.wait_group 0;" ::: "memory");
            if (mode == 0) {
                fence_async_g();
                flag_add(&g_sync[b]);
                flag_wait(&g_sync[b], TPB);
            }
            mbar_arrive(sb + B_XA);
        }
        __syncwarp();
        mbar_wait(sb + B_H3, 0);
        PT(4);
        slot8 = 32; par = 0;
#pragma unroll
        for (int half = 0; half < 2; half++) {
            float acc[64];
            fresh(acc);
            auto step = [&](int m) {
                const uint32_t aa = adA + m * 512, bb = bd0 + ((8192u >> 4) << 16) + slot8 * 128;
                mbar_wait(sb + B_R1 + slot8, par);
                wg_fence();
#pragma unroll
                for (int kk = 0; kk < 4; kk++) wgmma_ss_n128_tb1(acc, mkd(aa + 2 * kk), mkd(bb + 128 * kk), 1);
                wg_commit();
                wg_wait<1>();
            };
            if (half == 0) {
#pragma unroll 1
                for (int m = 0; m < 8; m++) {
                    step(m);
                    if (m > 0 && w0 && elect1()) ring_full(sb, prev8, &mp.mqb2, (64 * m + 256) & 511, (m + 4) >> 3 << 1);
                    adv();
                }
            } else {
#pragma unroll 1
                for (int m = 0; m < 4; m++) {
                    step(m);
                    if (m > 0 && w0 && elect1()) ring_full(sb, prev8, &mp.mqb2, 64 * m + 256, 2);
                    adv();
                }
#pragma unroll 1
                for (int m = 4; m < 8; m++) {
                    step(m);
                    if (w0 && elect1()) {
                        if (m == 4) mbar_expect_tx(sb + B_KV + 8, 65536);
                        tma4(sb + R1 + prev8 * 2048, &mp.xa2, 0, 0, 2 * m - 8, b, sb + B_KV + 8);
                    }
                    adv();
                }
            }
            wg_wait<0>();
            if (w0 && elect1()) {
                if (half == 0) ring_full(sb, prev8, &mp.mqb2, 256, 2);
                else {
                    mbar_expect_tx(sb + B_KV + 16, 65536);
                    tma4(sb + R2, &mp.xa, 0, 64, 0, b, sb + B_KV + 16);
                }
            }
            pin(acc);
#pragma unroll
            for (int i = 31; i >= 0; i--) q[32 * half + i] = pack2v(acc[2 * i], acc[2 * i + 1]);
        }
        bar_sync(1, 128);
        PT(5);

        const float CS = 0.04419417382415922f * 1.4426950408889634f;
        float m0 = -INFINITY, m1 = -INFINITY, l0 = 0.f, l1 = 0.f;
        int s = 0, sn = 1, ph = 0;
        float S[32];
        const bool l0w = lane == 0, q0 = (lane & 3) == 0;
#pragma unroll 1
        for (int j = -1;; j++) {
            if (j >= 0) {
                PL(j, 1);
                if (j == NKV - 1) {
#pragma unroll
                    for (int i = (T_ - 64 * (NKV - 1)) / 2; i < 32; i++) asm volatile("mov.b32 %0, 0xff800000;" : "=f"(S[i]));
                }
                float y[8], z[8];
#pragma unroll
                for (int n = 0; n < 8; n++) { y[n] = fmaxf(S[4 * n], S[4 * n + 1]); z[n] = fmaxf(S[4 * n + 2], S[4 * n + 3]); }
#pragma unroll
                for (int n = 0; n < 4; n++) { y[n] = fmaxf(y[n], y[n + 4]); z[n] = fmaxf(z[n], z[n + 4]); }
                float x0 = fmaxf(fmaxf(y[0], y[1]), fmaxf(fmaxf(y[2], y[3]), m0)), x1 = fmaxf(fmaxf(z[0], z[1]), fmaxf(fmaxf(z[2], z[3]), m1));
                x0 = fmaxf(x0, __shfl_xor_sync(0xffffffffu, x0, 1));
                x1 = fmaxf(x1, __shfl_xor_sync(0xffffffffu, x1, 1));
                x0 = fmaxf(x0, __shfl_xor_sync(0xffffffffu, x0, 2));
                x1 = fmaxf(x1, __shfl_xor_sync(0xffffffffu, x1, 2));
                if ((x0 - m0) * CS <= LAZY) x0 = m0;
                if ((x1 - m1) * CS <= LAZY) x1 = m1;
                const float sc0 = ex2((m0 - x0) * CS), sc1 = ex2((m1 - x1) * CS);
                m0 = x0; m1 = x1;
                const float n0 = -x0 * CS, n1 = -x1 * CS;
                if (q0) { sts_f32(sb + SCL + s * 256 + r0 * 4, sc0); sts_f32(sb + SCL + s * 256 + r0 * 4 + 32, sc1); }
                __syncwarp();
                if (l0w) mbar_arrive(sb + B_P + s * 8);
                if (j < NKV - 1) mbar_wait(sb + B_KV + sn * 8, ph);
                float a0 = 0.f, a1 = 0.f;
                const uint32_t pb = sb + R3 + (s == 0 ? 2 : s - 1) * 8192;
#pragma unroll
                for (int kk = 0; kk < 4; kk++) {
                    float p[8];
#pragma unroll
                    for (int e = 0; e < 8; e++) p[e] = ex2(fmaf(S[8 * kk + e], CS, (e & 2) ? n1 : n0));
                    a0 += (p[0] + p[1]) + (p[4] + p[5]);
                    a1 += (p[2] + p[3]) + (p[6] + p[7]);
                    stsm4((pb + loff) ^ (kk << 5), pack2(p[0], p[1]), pack2(p[2], p[3]), pack2(p[4], p[5]), pack2(p[6], p[7]));
                }
                l0 = fmaf(l0, sc0, a0); l1 = fmaf(l1, sc1, a1);
                PL(j, 2);
                if (j == NKV - 1) break;
            } else {
                mbar_wait(sb + B_KV + 8, 0);
            }
            float Sn[32];
            const uint32_t kd = sd + sn * 4096;
            wg_fence();
#pragma unroll
            for (int kk = 0; kk < 28; kk++) {
                wgmma_rs_n64_tb0(Sn, q[4 * kk], q[4 * kk + 1], q[4 * kk + 2], q[4 * kk + 3], dsc(kd, (kk >> 2) * 8192 + (kk & 3) * 32, 16), kk > 0);
                if (kk == FENCE_AT) { fence_async(); __syncwarp(); }
                if (kk == GO_AT) { PL(j, 3); if (j >= 0 && l0w) mbar_arrive(sb + B_GO + s * 8); }
            }
#pragma unroll
            for (int kk = 0; kk < 4; kk++)
                wgmma_ss_n64_tb0(Sn, dsc(sd, QS + kk * 32, 16), dsc(kd, 7 * 8192 + kk * 32, 16), 1);
            wg_commit();
            PL(j, 0);
            wg_wait<0>();
            pin(Sn);
#pragma unroll
            for (int i = 0; i < 32; i++) S[i] = Sn[i];
            s = sn;
            if (++sn == 3) sn = 0;
            if (sn == 1) ph ^= 1;
        }
        l0 += __shfl_xor_sync(0xffffffffu, l0, 1); l1 += __shfl_xor_sync(0xffffffffu, l1, 1);
        l0 += __shfl_xor_sync(0xffffffffu, l0, 2); l1 += __shfl_xor_sync(0xffffffffu, l1, 2);
        if (q0) { sts_f32(sb + LINV + r0 * 4, rcp(l0)); sts_f32(sb + LINV + r0 * 4 + 32, rcp(l1)); }
        fence_async();
        __syncwarp();
        if (l0w) {
            mbar_arrive(sb + B_GO + s * 8);
            uint32_t slot8 = 8 * w, par = 0;
#pragma unroll 1
            for (int n = 12 + w; n < 128; n += 4) {
                mbar_wait(sb + B_E2 + slot8, par);
                ring_ld(sb, slot8, n);
                slot8 += 32;
                if (slot8 >= 96) { slot8 -= 96; par ^= 1; }
            }
        }
        PDUMP();
    } else {
        asm volatile("setmaxnreg.dec.sync.aligned.u32 160;");
        const int h = wg - 1;
        auto red4 = [&](float (&a)[4]) {
            const bool b4 = lane & 16, b3 = lane & 8;
            const float k0 = (b4 ? a[2] : a[0]) + __shfl_xor_sync(0xffffffffu, b4 ? a[0] : a[2], 16);
            const float k1 = (b4 ? a[3] : a[1]) + __shfl_xor_sync(0xffffffffu, b4 ? a[1] : a[3], 16);
            float k = (b3 ? k1 : k0) + __shfl_xor_sync(0xffffffffu, b3 ? k0 : k1, 8);
            k += __shfl_xor_sync(0xffffffffu, k, 4);
            k += __shfl_xor_sync(0xffffffffu, k, 2);
            k += __shfl_xor_sync(0xffffffffu, k, 1);
            return k;
        };
#pragma unroll 1
        for (int bt = 0; bt < 2; bt++) {
            mbar_wait(sb + (bt ? B_A2 : B_A), 0);
            PT(bt ? 13 : 0);
            uint32_t v[4][8];
            float a[4], f[4][16];
            const uint32_t la = sb + AT + (lane >> 3) * 8192 + (32 * bt + 16 * h + 4 * w) * 128 + (((lane & 7) ^ ((w & 1) * 4)) << 4);
#pragma unroll
            for (int r = 0; r < 4; r++) { lds4((la ^ (r << 4)) + r * 128, v[r]); lds4((la ^ (r << 4)) + r * 128 + 32768, v[r] + 4); }
#pragma unroll
            for (int r = 0; r < 4; r++) {
                float s0 = blo(v[r][0]), s1 = bhi(v[r][0]);
#pragma unroll
                for (int i = 1; i < 8; i++) { s0 += blo(v[r][i]); s1 += bhi(v[r][i]); }
                a[r] = s0 + s1;
            }
            const float mu = red4(a) * (1.f / D_);
            const uint32_t mp2 = pack2(mu, mu);
#pragma unroll
            for (int r = 0; r < 4; r++) {
                const uint32_t m2 = __shfl_sync(0xffffffffu, mp2, 8 * r);
                float s0 = 0.f, s1 = 0.f;
#pragma unroll
                for (int i = 0; i < 8; i++) {
                    const uint32_t d = bsub2(v[r][i], m2);
                    f[r][2 * i] = blo(d); f[r][2 * i + 1] = bhi(d);
                    s0 = fmaf(f[r][2 * i], f[r][2 * i], s0); s1 = fmaf(f[r][2 * i + 1], f[r][2 * i + 1], s1);
                }
                a[r] = s0 + s1;
            }
            const float dm = mu - blo(mp2);
            float sd_ = bfr(bfr(fmaxf(fmaf(red4(a), 1.f / D_, -dm * dm), 0.f)) + 1e-5f);
            asm("sqrt.approx.f32 %0, %0;" : "+f"(sd_));
            const float ri = rcp(bfr(sd_));
#pragma unroll
            for (int r = 0; r < 4; r++) {
                const float rinv = __shfl_sync(0xffffffffu, ri, 8 * r);
#pragma unroll
                for (int i = 0; i < 8; i++) v[r][i] = pack2(f[r][2 * i] * rinv, f[r][2 * i + 1] * rinv);
                sts4((la ^ (r << 4)) + r * 128, v[r][0], v[r][1], v[r][2], v[r][3]);
                sts4((la ^ (r << 4)) + r * 128 + 32768, v[r][4], v[r][5], v[r][6], v[r][7]);
            }
        }
        fence_async();
        bar_sync(2, 256);
        if (tid == 128) mbar_arrive(sb + B_LN);
        if (mode == 1) return;
        float acc[128];
#pragma unroll
        for (int pass = 0; pass < 2; pass++) {
            if (pass == 1) mbar_wait(sb + B_H2, 0);
            PT(1 + 3 * pass);
            fresh(acc);
            uint32_t slot8 = pass ? 16 : 32, par = 0;
            auto adv = [&]() { slot8 += 8; if (slot8 == 40) { slot8 = 0; par ^= 1; } };
            auto step = [&](int kk) {
                wg_fence();
                wgmma_ss_n256_tb1(acc, mkd(adA + (kk >> 2) * 512 + (kk & 3) * 2), mkd(bd2k + h * 512 + slot8 * 128), 1);
                wg_commit();
                wg_wait<0>();
            };
#pragma unroll 1
            for (int kk = 0; kk < 27; kk++) {
                mbar_wait(sb + B_R1 + slot8, par);
                step(kk);
                if (w0 && elect1()) ring_half(sb, slot8, h * 8192, &mp.wup4, 16 * kk + 80, (pass ? 0 : 8) + 4 * h);
                adv();
            }
            if (pass == 0 && w0) mbar_wait(sb + B_MQ, 0);
#pragma unroll 1
            for (int kk = 27; kk < 32; kk++) {
                mbar_wait(sb + B_R1 + slot8, par);
                if (kk == 31 && el) mbar_arrive(sb + (pass ? B_H3 : B_H1));
                step(kk);
                if (w0 && elect1()) ring_half(sb, slot8, h * 8192, pass ? &mp.mqb1 : &mp.mqa2, (pass ? 64 : 32) * (kk - 27), pass ? h : 4 + 2 * h);
                adv();
            }
            pin(acc);
            PT(2 + 3 * pass);
            if (pass == 0) {
                float s0 = 0.f, s1 = 0.f, v0 = 0.f, v1 = 0.f;
#pragma unroll
                for (int n = 0; n < 32; n++) {
#pragma unroll
                    for (int e = 0; e < 4; e++) acc[4 * n + e] = gelu2(acc[4 * n + e]);
                    s0 += acc[4 * n] + acc[4 * n + 1]; s1 += acc[4 * n + 2] + acc[4 * n + 3];
                    v0 = fmaf(acc[4 * n], acc[4 * n], v0); v0 = fmaf(acc[4 * n + 1], acc[4 * n + 1], v0);
                    v1 = fmaf(acc[4 * n + 2], acc[4 * n + 2], v1); v1 = fmaf(acc[4 * n + 3], acc[4 * n + 3], v1);
                }
#pragma unroll
                for (int o = 1; o < 4; o <<= 1) {
                    s0 += __shfl_xor_sync(0xffffffffu, s0, o); s1 += __shfl_xor_sync(0xffffffffu, s1, o);
                    v0 += __shfl_xor_sync(0xffffffffu, v0, o); v1 += __shfl_xor_sync(0xffffffffu, v1, o);
                }
                if ((lane & 3) == 0) {
                    uint32_t a = sb + STAT + h * 512 + r0 * 8;
                    sts_f32(a, s0); sts_f32(a + 4, v0); sts_f32(a + 64, s1); sts_f32(a + 68, v1);
                }
                bar_sync(2, 256);
                {
                    uint32_t a = sb + STAT + (h ^ 1) * 512 + r0 * 8;
                    s0 = (s0 + lds_f32(a)) * (1.f / 512.f); v0 = (v0 + lds_f32(a + 4)) * (1.f / 512.f);
                    s1 = (s1 + lds_f32(a + 64)) * (1.f / 512.f); v1 = (v1 + lds_f32(a + 68)) * (1.f / 512.f);
                }
                v0 = rsqrtf(fmaxf(fmaf(-s0, s0, v0), 0.f) + 4e-5f); v1 = rsqrtf(fmaxf(fmaf(-s1, s1, v1), 0.f) + 4e-5f);
                s0 = -s0 * v0; s1 = -s1 * v1;
#pragma unroll
                for (int p = 0; p < 16; p++)
                    stsm4(((sb + R0 + h * 32768 + loff) ^ ((p & 3) << 5)) + (p >> 2) * 8192,
                          pack2(fmaf(acc[8 * p], v0, s0), fmaf(acc[8 * p + 1], v0, s0)), pack2(fmaf(acc[8 * p + 2], v1, s1), fmaf(acc[8 * p + 3], v1, s1)),
                          pack2(fmaf(acc[8 * p + 4], v0, s0), fmaf(acc[8 * p + 5], v0, s0)), pack2(fmaf(acc[8 * p + 6], v1, s1), fmaf(acc[8 * p + 7], v1, s1)));
            } else {
                uint32_t u[64];
#pragma unroll
                for (int i = 63; i >= 0; i--) u[i] = pack2v(gelu2(acc[2 * i]), gelu2(acc[2 * i + 1]));
                PT(12);
                bar_sync(3 + h, 128);
                const uint32_t rm = lrow == 0 ? 0 : lrow - 1, rp = lrow == 63 ? 63 : lrow + 1;
                const uint32_t gb = sb + R0 + h * 32768;
                const uint32_t am = gb + rm * 128 + ((((lane >> 4) ^ rm) & 7) << 4), ap = gb + rp * 128 + ((((lane >> 4) ^ rp) & 7) << 4), ac = gb + loff;
                const uint32_t dwa = sb + DWS + 512 * h + ((lane >> 3) & 1) * 16 + (lane >> 4) * 1024;
                bf16* ucp = g_uc + ((size_t)blockIdx.x * 64 + r0) * D_ + 256 * h + 8 * (lane & 3);
#pragma unroll
                for (int m = 0; m < 8; m++) {
                    uint32_t o[8], g0[2][4], g1[2][4], g2[2][4], d[2][4], d2[2][2];
#pragma unroll
                    for (int pp = 0; pp < 2; pp++) {
                        const int p = 2 * m + pp;
                        const uint32_t co = (p >> 2) * 8192, cx = (p & 3) << 5;
                        ldsm4(dwa + 32 * p, d[pp]);
                        ldsm2(dwa + 32 * p + 2048, d2[pp]);
                        ldsm4((am ^ cx) + co, g0[pp]);
                        ldsm4((ac ^ cx) + co, g1[pp]);
                        ldsm4((ap ^ cx) + co, g2[pp]);
                    }
#pragma unroll
                    for (int pp = 0; pp < 2; pp++)
#pragma unroll
                        for (int e = 0; e < 4; e++)
                            o[4 * (e & 1) + 2 * pp + (e >> 1)] =
                                bmul2(u[8 * m + 4 * pp + e], bfma2(g2[pp][e], d2[pp][e >> 1], bfma2(g1[pp][e], d[pp][2 + (e >> 1)], bmul2(g0[pp][e], d[pp][e >> 1]))));
                    stg4(ucp + 32 * m, o[0], o[1], o[2], o[3]);
                    stg4(ucp + 32 * m + 8 * D_, o[4], o[5], o[6], o[7]);
                }
                bar_sync(2, 256);
                if (tid == 128) {
                    mbar_wait(sb + B_XA, 0);
                    mbar_expect_tx(sb + B_KV, 65536);
                    tma4(sb + R0, &mp.xa, 0, 128, 0, b, sb + B_KV);
                }
            }
            PT(3 + 3 * pass);
        }
        int s = 1, ph = 0;
        fresh(acc);
#pragma unroll 1
        for (int j = 0; j < NKV; j++) {
            mbar_wait(sb + B_P + s * 8, ph);
            PL(j, 0);
            if (j > 0) {
                const float sc0 = lds_f32(sb + SCL + s * 256 + r0 * 4), sc1 = lds_f32(sb + SCL + s * 256 + r0 * 4 + 32);
                if (__any_sync(0xffffffffu, sc0 != 1.f || sc1 != 1.f)) {
#pragma unroll
                    for (int n = 0; n < 32; n++) { acc[4 * n] *= sc0; acc[4 * n + 1] *= sc0; acc[4 * n + 2] *= sc1; acc[4 * n + 3] *= sc1; }
                }
            }
            mbar_wait(sb + B_GO + s * 8, ph);
            PL(j, 1);
            const uint32_t vd = sd + s * 4096 + h * 2048, pd = sd + (s == 0 ? 2 : s - 1) * 512;
            pin(acc);
            wg_fence();
#pragma unroll
            for (int kk = 0; kk < 4; kk++) wgmma_ss_n256_tb1(acc, dsc(pd, R3 + kk * 32, 16), dsc(vd, kk * 2048, 8192), 1);
            wg_commit();
            wg_wait<0>();
            pin(acc);
            PL(j, 2);
            if (w0 && elect1()) {
                if (j == NKV - 5 && mode == 0) flag_wait(&g_sync[3], 4);
                if (atom_inc_s(sb + CNT + 4 * s) & 1) {
                    if (j + 3 < NKV) {
                        mbar_expect_tx(sb + B_KV + s * 8, 65536);
                        tma4(sb + s * 65536, &mp.xa, 0, 64 * (j + 3), 0, b, sb + B_KV + s * 8);
                    } else if (j < NKV - 1) {
                        const int n0 = j == NKV - 3 ? 0 : 8, n1 = j == NKV - 3 ? 8 : 12;
#pragma unroll 1
                        for (int n = n0; n < n1; n++) ring_ld(sb, n * 8, n);
                    }
                }
            }
            if (++s == 3) s = 0;
            if (s == 1) ph ^= 1;
        }
        {
            const float i0 = lds_f32(sb + LINV + r0 * 4), i1 = lds_f32(sb + LINV + r0 * 4 + 32);
#pragma unroll
            for (int p = 0; p < 16; p++)
                stsm4(((sb + R0 + h * 32768 + loff) ^ ((p & 3) << 5)) + (p >> 2) * 8192,
                      pack2(acc[8 * p] * i0, acc[8 * p + 1] * i0), pack2(acc[8 * p + 2] * i1, acc[8 * p + 3] * i1),
                      pack2(acc[8 * p + 4] * i0, acc[8 * p + 5] * i0), pack2(acc[8 * p + 6] * i1, acc[8 * p + 7] * i1));
        }
        fence_async();
        fence_async_g();
        bar_sync(2, 256);
        if (tid == 128) {
            mbar_expect_tx(sb + B_UC, 65536);
            tma3(sb + UCT, &mp.uc, 0, 64 * blockIdx.x, 0, sb + B_UC);
        }
        PT(7);
        fresh(acc);
        {
            uint32_t slot8 = 8 * h, par = 0;
#pragma unroll 1
            for (int kk = 0; kk < 64; kk++) {
                if (kk == 32) mbar_wait(sb + B_UC, 0);
                mbar_wait(sb + B_R2 + slot8, par);
                wg_fence();
                wgmma_ss_n256_tb1(acc, mkd(sd + (1u << 16) + (kk < 32 ? (R0 >> 4) : (UCT >> 4) - 4096) + (kk >> 2) * 512 + (kk & 3) * 2), mkd(bd2k + slot8 * 64), 1);
                wg_commit();
                wg_wait<0>();
                if (lane == 0) mbar_arrive(sb + B_E2 + slot8);
                if (kk == 31 && w0 && elect1() && (atom_inc_s(sb + CNT + 12) & 1)) {
                    mbar_expect_tx(sb + B_X, 65536);
                    tma4(sb + R0, &mp.x, 0, 62 * ti, 0, b, sb + B_X);
                }
                slot8 += 16;
                if (slot8 >= 96) { slot8 -= 96; par ^= 1; }
            }
        }
        pin(acc);
        PT(8);
        mbar_wait(sb + B_X, 0);
        PT(9);
        {
            const uint32_t sr = (lrow + 63) & 63;
            const uint32_t xoff = sr * 128 + ((((lane >> 4) ^ sr) & 7) << 4);
#pragma unroll
            for (int p = 0; p < 16; p++) {
                const uint32_t a = ((sb + R0 + h * 32768 + xoff) ^ ((p & 3) << 5)) + (p >> 2) * 8192;
                uint32_t xv[4];
                ldsm4(a, xv);
#pragma unroll
                for (int e = 0; e < 4; e++)
                    xv[e] = pack2(acc[8 * p + 2 * e] + __uint_as_float(xv[e] << 16), acc[8 * p + 2 * e + 1] + __uint_as_float(xv[e] & 0xffff0000u));
                stsm4(a, xv[0], xv[1], xv[2], xv[3]);
            }
        }
        fence_async();
        bar_sync(3 + h, 128);
        if (el) {
            for (int c = 0; c < 4; c++) tma4_store(&mp.out, sb + R0 + (4 * h + c) * 8192, 0, 62 * ti, 4 * h + c, b);
            asm volatile("cp.async.bulk.commit_group;" ::: "memory");
            PT(10);
            if (h == 0) cta_done(mode);
            asm volatile("cp.async.bulk.wait_group.read 0;" ::: "memory");
        }
        PT(11);
        PG(201);
        PDUMP();
    }
}

typedef CUresult (*PFN_enc)(CUtensorMap*, CUtensorMapDataType, cuuint32_t, void*, const cuuint64_t*, const cuuint64_t*,
                            const cuuint32_t*, const cuuint32_t*, CUtensorMapInterleave, CUtensorMapSwizzle,
                            CUtensorMapL2promotion, CUtensorMapFloatOOBfill);

static void enc(PFN_enc f, CUtensorMap* m, void* base, int rank, const cuuint64_t* dims, const cuuint64_t* strides, const cuuint32_t* box) {
    cuuint32_t es[5] = {1, 1, 1, 1, 1};
    f(m, CU_TENSOR_MAP_DATA_TYPE_BFLOAT16, rank, base, dims, strides, box, es, CU_TENSOR_MAP_INTERLEAVE_NONE,
      CU_TENSOR_MAP_SWIZZLE_128B, CU_TENSOR_MAP_L2_PROMOTION_L2_256B, CU_TENSOR_MAP_FLOAT_OOB_FILL_NONE);
}
static void enc_act(PFN_enc f, CUtensorMap* m, void* base, int rows, int chunks, int trows = T_, int pitch = T_) {
    cuuint64_t dims[4] = {64, (cuuint64_t)trows, 8, (cuuint64_t)NB_};
    cuuint64_t st[3] = {1024, 128, (cuuint64_t)pitch * 1024};
    cuuint32_t box[4] = {64, (cuuint32_t)rows, (cuuint32_t)chunks, 1};
    enc(f, m, base, 4, dims, st, box);
}
static void enc_w(PFN_enc f, CUtensorMap* m, void* base, int krows, int ncols, int bk, int bc) {
    cuuint64_t dims[3] = {64, (cuuint64_t)krows, (cuuint64_t)(ncols / 64)};
    cuuint64_t st[2] = {(cuuint64_t)ncols * 2, 128};
    cuuint32_t box[3] = {64, (cuuint32_t)bk, (cuuint32_t)bc};
    enc(f, m, base, 3, dims, st, box);
}

extern "C" void kernel_launch(void* const* d_in, const int* in_sizes, int n_in, void* d_out, int out_size) {
    const bf16* x = (const bf16*)d_in[0];
    static PFN_enc fenc = nullptr;
    static void *p_xa, *p_mqk, *p_uc, *p_t1;
    static int fused = 0;
    if (!fenc) {
        void* fn = nullptr;
        cudaDriverEntryPointQueryResult qr;
        cudaGetDriverEntryPoint("cuTensorMapEncodeTiled", &fn, cudaEnableDefault, &qr);
        fenc = (PFN_enc)fn;
        cudaGetSymbolAddress(&p_xa, g_xa);
        cudaGetSymbolAddress(&p_mqk, g_mqk);
        cudaGetSymbolAddress(&p_uc, g_uc);
        cudaGetSymbolAddress(&p_t1, g_t1);
        cudaFuncSetAttribute(main_kernel, cudaFuncAttributeMaxDynamicSharedMemorySize, SMEM_BYTES);
        int dev = 0, sms = 0, occ = 0;
        cudaGetDevice(&dev);
        cudaDeviceGetAttribute(&sms, cudaDevAttrMultiProcessorCount, dev);
        cudaOccupancyMaxActiveBlocksPerMultiprocessor(&occ, main_kernel, 384, SMEM_BYTES);
        fused = sms * occ >= NCTA + 2;
    }
    Maps mp;
    enc_act(fenc, &mp.xa, (char*)p_xa + 1024, 64, 8, T_, T_ + 8);
    enc_act(fenc, &mp.xa2, (char*)p_xa + 1024, 64, 2, T_, T_ + 8);
    enc_act(fenc, &mp.xas, p_xa, 64, 1, T_ + 1, T_ + 8);
    enc_act(fenc, &mp.x, (void*)x, 64, 8);
    enc_act(fenc, &mp.xh, (void*)x, 32, 1);
    enc_act(fenc, &mp.out, d_out, 62, 1);
    enc_w(fenc, &mp.wup4, d_in[5], 512, 1024, 16, 4);
    enc_w(fenc, &mp.wup8, d_in[5], 512, 1024, 16, 8);
    enc_w(fenc, &mp.mqa2, p_mqk, 512, 512, 32, 2);
    enc_w(fenc, &mp.mqa4, p_mqk, 512, 512, 32, 4);
    enc_w(fenc, &mp.mqb1, p_mqk, 512, 512, 64, 1);
    enc_w(fenc, &mp.mqb2, p_mqk, 512, 512, 64, 2);
    enc_w(fenc, &mp.uc, p_uc, NCTA * 64, 512, 64, 8);
    enc_w(fenc, &mp.wq, d_in[1], 512, 512, 64, 8);
    enc_w(fenc, &mp.wk, d_in[2], 512, 512, 32, 8);
    enc_w(fenc, &mp.fa[0], d_in[3], 512, 512, 128, 1);
    enc_w(fenc, &mp.fa[1], d_in[7], 512, 512, 128, 1);
    enc_w(fenc, &mp.fa[2], p_t1, 512, 512, 128, 1);
    enc_w(fenc, &mp.fb[0], d_in[4], 512, 512, 64, 4);
    enc_w(fenc, &mp.fb[1], d_in[8], 1024, 512, 64, 4);
    enc_w(fenc, &mp.fc, p_t1, 512, 512, 64, 4);
    cudaStream_t st = cudaStreamPerThread;
    if (fused) {
        main_kernel<<<NCTA + 2, 384, SMEM_BYTES, st>>>(mp, (const bf16*)d_in[6], (const bf16*)d_in[5], 0);
    } else {
        main_kernel<<<NCTA + 2, 384, SMEM_BYTES, st>>>(mp, (const bf16*)d_in[6], (const bf16*)d_in[5], 1);
        main_kernel<<<NCTA + 2, 384, SMEM_BYTES, st>>>(mp, (const bf16*)d_in[6], (const bf16*)d_in[5], 2);
    }
}
```

```cpp
#include <cuda_runtime.h>
#include <cuda_bf16.h>
#include <cuda.h>
#include <stdint.h>

typedef __nv_bfloat16 bf16;

constexpr int T_ = 4000, D_ = 512, NB_ = 2;
constexpr int TPB = 65;
constexpr int NCTA = TPB * NB_;
constexpr int NKV = 63;

__device__ __align__(1024) bf16 g_xa[NB_ * (T_ + 8) * D_];
__device__ __align__(1024) bf16 g_mqk[D_ * D_];
__device__ __align__(1024) bf16 g_t1[D_ * D_];
__device__ __align__(1024) bf16 g_wepi[2 * D_ * D_];
__device__ __align__(1024) bf16 g_uc[NCTA * 64 * D_];
__device__ unsigned g_sync[8];

#define PT(i) do { if (el) asm volatile("st.shared.u32 [%0], %1;" ::"r"(sb + MISC + 2560), "r"((unsigned)clock())); } while (0)
#define PG(i)
#define PLM 15
#define PL(j, q) do { if ((PLM >> ((q) + (wg ? 4 : 0))) & 1) PT(0); } while (0)
#define PDUMP()

#define FENCE_AT 1
#define GO_AT 25
#define LAZY 8.f
#define XS_GAP 800
#define PFW 1
constexpr uint32_t R0 = 0, R1 = 65536, R2 = 131072, R3 = 196608, QS = 221184, MISC = 229376;
constexpr uint32_t AT = 147456, DWS = R3 + 16384;
constexpr uint32_t SMEM_BYTES = 232448;
constexpr uint32_t B_A = MISC, B_R1 = MISC + 8  , B_MK = MISC + 48, B_LN = MISC + 56, B_MQ = MISC + 64, B_XA = MISC + 72, B_A2 = MISC + 80,
                   B_H1 = MISC + 88, B_H2 = MISC + 96, B_H3 = MISC + 104,
                   B_KV = MISC + 112, B_P = MISC + 136, B_GO = MISC + 160, B_UC = MISC + 184  ,
                   B_X = MISC + 200, CNT = MISC + 208  , SCL = MISC + 512  ,
                   LINV = MISC + 1280  , STAT = MISC + 512  ,
                   B_R2 = MISC + 1536  , B_E2 = MISC + 1696  ;

__device__ __forceinline__ uint32_t smem_u32(const void* p) { return (uint32_t)__cvta_generic_to_shared(p); }
__device__ __forceinline__ void wg_fence() { asm volatile("wgmma.fence.sync.aligned;" ::: "memory"); }
__device__ __forceinline__ void wg_commit() { asm volatile("wgmma.commit_group.sync.aligned;" ::: "memory"); }
template <int N> __device__ __forceinline__ void wg_wait() { asm volatile("wgmma.wait_group.sync.aligned %0;" ::"n"(N) : "memory"); }
__device__ __forceinline__ uint64_t dsc(uint32_t sd, uint32_t off, uint32_t lbo) {
    uint32_t lo = sd + (off >> 4) + ((lbo >> 4) << 16);
    uint64_t d;
    asm("mov.b64 %0, {%1, %2};" : "=l"(d) : "r"(lo), "r"((1024u >> 4) | (1u << 30)));
    return d;
}
__device__ __forceinline__ bool elect1() {
    uint32_t p;
    asm volatile("{\n.reg .pred p;\nelect.sync _|p, 0xffffffff;\nselp.u32 %0, 1, 0, p;\n}\n" : "=r"(p));
    return p != 0;
}
__device__ __forceinline__ void mbar_init(uint32_t bar, int cnt) { asm volatile("mbarrier.init.shared::cta.b64 [%0], %1;" ::"r"(bar), "r"(cnt) : "memory"); }
__device__ __forceinline__ void mbar_expect_tx(uint32_t bar, uint32_t bytes) { asm volatile("mbarrier.arrive.expect_tx.shared::cta.b64 _, [%0], %1;" ::"r"(bar), "r"(bytes) : "memory"); }
__device__ __forceinline__ void mbar_arrive(uint32_t bar) { asm volatile("mbarrier.arrive.shared::cta.b64 _, [%0];" ::"r"(bar) : "memory"); }
__device__ __forceinline__ void mbar_wait(uint32_t bar, uint32_t parity) {
    uint32_t ok;
#pragma unroll 1
    for (uint32_t it = 0;; ++it) {
        asm volatile("{\n.reg .pred p;\nmbarrier.try_wait.parity.shared::cta.b64 p, [%1], %2;\nselp.u32 %0, 1, 0, p;\n}\n" : "=r"(ok) : "r"(bar), "r"(parity) : "memory");
        if (ok) break;
        if (it > (1u << 20)) __trap();
    }
}
__device__ __forceinline__ void fence_async() { asm volatile("fence.proxy.async.shared::cta;" ::: "memory"); }
__device__ __forceinline__ void fence_async_g() { asm volatile("fence.proxy.async.global;" ::: "memory"); }
__device__ __forceinline__ void bar_sync(int id, int n) { asm volatile("bar.sync %0, %1;" ::"r"(id), "r"(n) : "memory"); }
__device__ __forceinline__ void tma3(uint32_t dst, const CUtensorMap* tm, int c0, int c1, int c2, uint32_t bar) {
    asm volatile("cp.async.bulk.tensor.3d.shared::cluster.global.mbarrier::complete_tx::bytes [%0], [%1, {%3, %4, %5}], [%2];"
                 ::"r"(dst), "l"(tm), "r"(bar), "r"(c0), "r"(c1), "r"(c2) : "memory");
}
__device__ __forceinline__ void tma4(uint32_t dst, const CUtensorMap* tm, int c0, int c1, int c2, int c3, uint32_t bar) {
    asm volatile("cp.async.bulk.tensor.4d.shared::cluster.global.mbarrier::complete_tx::bytes [%0], [%1, {%3, %4, %5, %6}], [%2];"
                 ::"r"(dst), "l"(tm), "r"(bar), "r"(c0), "r"(c1), "r"(c2), "r"(c3) : "memory");
}
__device__ __forceinline__ void tma4_store(const CUtensorMap* tm, uint32_t src, int c0, int c1, int c2, int c3) {
    asm volatile("cp.async.bulk.tensor.4d.global.shared::cta.bulk_group [%0, {%2, %3, %4, %5}], [%1];"
                 ::"l"(tm), "r"(src), "r"(c0), "r"(c1), "r"(c2), "r"(c3) : "memory");
}
__device__ __forceinline__ void tma3_store(const CUtensorMap* tm, uint32_t src, int c0, int c1, int c2) {
    asm volatile("cp.async.bulk.tensor.3d.global.shared::cta.bulk_group [%0, {%2, %3, %4}], [%1];"
                 ::"l"(tm), "r"(src), "r"(c0), "r"(c1), "r"(c2) : "memory");
}
__device__ __forceinline__ void stsm4(uint32_t addr, uint32_t a, uint32_t b, uint32_t c, uint32_t d) {
    asm volatile("stmatrix.sync.aligned.m8n8.x4.shared.b16 [%0], {%1, %2, %3, %4};" ::"r"(addr), "r"(a), "r"(b), "r"(c), "r"(d) : "memory");
}
__device__ __forceinline__ void ldsm4(uint32_t addr, uint32_t (&r)[4]) {
    asm volatile("ldmatrix.sync.aligned.m8n8.x4.shared.b16 {%0, %1, %2, %3}, [%4];" : "=r"(r[0]), "=r"(r[1]), "=r"(r[2]), "=r"(r[3]) : "r"(addr) : "memory");
}
__device__ __forceinline__ void ldsm2(uint32_t addr, uint32_t (&r)[2]) {
    asm volatile("ldmatrix.sync.aligned.m8n8.x2.shared.b16 {%0, %1}, [%2];" : "=r"(r[0]), "=r"(r[1]) : "r"(addr) : "memory");
}
__device__ __forceinline__ void stg4(void* p, uint32_t a, uint32_t b, uint32_t c, uint32_t d) {
    asm volatile("st.global.v4.u32 [%0], {%1, %2, %3, %4};" ::"l"(p), "r"(a), "r"(b), "r"(c), "r"(d) : "memory");
}
__device__ __forceinline__ uint32_t pack2(float lo, float hi) {
    uint32_t r;
    asm("cvt.rn.bf16x2.f32 %0, %1, %2;" : "=r"(r) : "f"(hi), "f"(lo));
    return r;
}
__device__ __forceinline__ uint32_t pack2v(float lo, float hi) {
    uint32_t r;
    asm volatile("cvt.rn.bf16x2.f32 %0, %1, %2;" : "=r"(r) : "f"(hi), "f"(lo));
    return r;
}
__device__ __forceinline__ uint32_t bmul2(uint32_t a, uint32_t b) { uint32_t r; asm("mul.rn.bf16x2 %0, %1, %2;" : "=r"(r) : "r"(a), "r"(b)); return r; }
__device__ __forceinline__ uint32_t bfma2(uint32_t a, uint32_t b, uint32_t c) { uint32_t r; asm("fma.rn.bf16x2 %0, %1, %2, %3;" : "=r"(r) : "r"(a), "r"(b), "r"(c)); return r; }
__device__ __forceinline__ float ex2(float x) { float r; asm("ex2.approx.ftz.f32 %0, %1;" : "=f"(r) : "f"(x)); return r; }
__device__ __forceinline__ float rcp(float x) { float r; asm("rcp.approx.ftz.f32 %0, %1;" : "=f"(r) : "f"(x)); return r; }
__device__ __forceinline__ float gelu2(float x) {
    float t = fmaf(x * x, 0.044715f * 0.7978845608028654f, 0.7978845608028654f), th;
    asm("tanh.approx.f32 %0, %1;" : "=f"(th) : "f"(x * t));
    return fmaf(x, th, x);
}
__device__ __forceinline__ uint32_t ldg_v(const uint32_t* p) { uint32_t v; asm volatile("ld.global.nc.u32 %0, [%1];" : "=r"(v) : "l"(p)); return v; }
__device__ __forceinline__ float lds_f32(uint32_t a) { float v; asm volatile("ld.shared.f32 %0, [%1];" : "=f"(v) : "r"(a) : "memory"); return v; }
__device__ __forceinline__ void sts_f32(uint32_t a, float v) { asm volatile("st.shared.f32 [%0], %1;" ::"r"(a), "f"(v) : "memory"); }
__device__ __forceinline__ uint32_t atom_inc_s(uint32_t a) { uint32_t v; asm volatile("atom.relaxed.cta.shared.add.u32 %0, [%1], 1;" : "=r"(v) : "r"(a) : "memory"); return v; }
__device__ __forceinline__ void lds4(uint32_t a, uint32_t* r) {
    asm volatile("ld.shared.v4.u32 {%0, %1, %2, %3}, [%4];" : "=r"(r[0]), "=r"(r[1]), "=r"(r[2]), "=r"(r[3]) : "r"(a) : "memory");
}
__device__ __forceinline__ void sts4(uint32_t a, uint32_t x, uint32_t y, uint32_t z, uint32_t t) {
    asm volatile("st.shared.v4.u32 [%0], {%1, %2, %3, %4};" ::"r"(a), "r"(x), "r"(y), "r"(z), "r"(t) : "memory");
}
__device__ __forceinline__ uint32_t bsub2(uint32_t a, uint32_t b) { uint32_t r; asm("sub.rn.bf16x2 %0, %1, %2;" : "=r"(r) : "r"(a), "r"(b)); return r; }
__device__ __forceinline__ float blo(uint32_t v) { return __uint_as_float(v << 16); }
__device__ __forceinline__ float bhi(uint32_t v) { return __uint_as_float(v & 0xffff0000u); }
__device__ __forceinline__ float bfr(float x) { return __bfloat162float(__float2bfloat16_rn(x)); }
__device__ __forceinline__ void l2_prefetch(const void* p, uint32_t bytes) { asm volatile("cp.async.bulk.prefetch.L2.global [%0], %1;" ::"l"(p), "r"(bytes) : "memory"); }
__device__ __forceinline__ void flag_add(unsigned* p) { asm volatile("red.release.gpu.global.add.u32 [%0], 1;" ::"l"(p) : "memory"); }
__device__ __forceinline__ void flag_wait(const unsigned* p, unsigned target) {
#pragma unroll 1
    for (uint32_t it = 0;; ++it) {
        unsigned v;
        asm volatile("ld.acquire.gpu.global.u32 %0, [%1];" : "=r"(v) : "l"(p) : "memory");
        if (v >= target) break;
        if (it > (1u << 20)) __trap();
    }
    fence_async_g();
}
template <int N> __device__ __forceinline__ void pin(float (&a)[N]) {
#pragma unroll
    for (int i = 0; i < N; i++) asm volatile("" : "+f"(a[i])::"memory");
}

template <int N> __device__ __forceinline__ void fresh(float (&a)[N]) {
#pragma unroll
    for (int i = 0; i < N; i++) a[i] = 0.f;
    pin(a);
}

__device__ __forceinline__ void wgmma_rs_n64_tb0(float (&d)[32], uint32_t a0, uint32_t a1, uint32_t a2, uint32_t a3, uint64_t db, int scale_d) {
    asm volatile("{\n.reg .pred p;\nsetp.ne.b32 p, %37, 0;\n"
        "wgmma.mma_async.sync.aligned.m64n64k16.f32.bf16.bf16 {%0, %1, %2, %3, %4, %5, %6, %7, %8, %9, %10, %11, %12, %13, %14, %15, %16, %17, %18, %19, %20, %21, %22, %23, %24, %25, %26, %27, %28, %29, %30, %31}, {%32, %33, %34, %35}, %36, p, 1, 1, 0;\n}\n"
        : "+f"(d[0]), "+f"(d[1]), "+f"(d[2]), "+f"(d[3]), "+f"(d[4]), "+f"(d[5]), "+f"(d[6]), "+f"(d[7]), "+f"(d[8]), "+f"(d[9]), "+f"(d[10]), "+f"(d[11]), "+f"(d[12]), "+f"(d[13]), "+f"(d[14]), "+f"(d[15]), "+f"(d[16]), "+f"(d[17]), "+f"(d[18]), "+f"(d[19]), "+f"(d[20]), "+f"(d[21]), "+f"(d[22]), "+f"(d[23]), "+f"(d[24]), "+f"(d[25]), "+f"(d[26]), "+f"(d[27]), "+f"(d[28]), "+f"(d[29]), "+f"(d[30]), "+f"(d[31])
        : "r"(a0), "r"(a1), "r"(a2), "r"(a3), "l"(db), "r"(scale_d));
}

__device__ __forceinline__ void wgmma_ss_n128_tb1(float (&d)[64], uint64_t da, uint64_t db, int scale_d) {
    asm volatile("{\n.reg .pred p;\nsetp.ne.b32 p, %66, 0;\n"
        "wgmma.mma_async.sync.aligned.m64n128k16.f32.bf16.bf16 {%0, %1, %2, %3, %4, %5, %6, %7, %8, %9, %10, %11, %12, %13, %14, %15, %16, %17, %18, %19, %20, %21, %22, %23, %24, %25, %26, %27, %28, %29, %30, %31, %32, %33, %34, %35, %36, %37, %38, %39, %40, %41, %42, %43, %44, %45, %46, %47, %48, %49, %50, %51, %52, %53, %54, %55, %56, %57, %58, %59, %60, %61, %62, %63}, %64, %65, p, 1, 1, 0, 1;\n}\n"
        : "+f"(d[0]), "+f"(d[1]), "+f"(d[2]), "+f"(d[3]), "+f"(d[4]), "+f"(d[5]), "+f"(d[6]), "+f"(d[7]), "+f"(d[8]), "+f"(d[9]), "+f"(d[10]), "+f"(d[11]), "+f"(d[12]), "+f"(d[13]), "+f"(d[14]), "+f"(d[15]), "+f"(d[16]), "+f"(d[17]), "+f"(d[18]), "+f"(d[19]), "+f"(d[20]), "+f"(d[21]), "+f"(d[22]), "+f"(d[23]), "+f"(d[24]), "+f"(d[25]), "+f"(d[26]), "+f"(d[27]), "+f"(d[28]), "+f"(d[29]), "+f"(d[30]), "+f"(d[31]), "+f"(d[32]), "+f"(d[33]), "+f"(d[34]), "+f"(d[35]), "+f"(d[36]), "+f"(d[37]), "+f"(d[38]), "+f"(d[39]), "+f"(d[40]), "+f"(d[41]), "+f"(d[42]), "+f"(d[43]), "+f"(d[44]), "+f"(d[45]), "+f"(d[46]), "+f"(d[47]), "+f"(d[48]), "+f"(d[49]), "+f"(d[50]), "+f"(d[51]), "+f"(d[52]), "+f"(d[53]), "+f"(d[54]), "+f"(d[55]), "+f"(d[56]), "+f"(d[57]), "+f"(d[58]), "+f"(d[59]), "+f"(d[60]), "+f"(d[61]), "+f"(d[62]), "+f"(d[63])
        : "l"(da), "l"(db), "r"(scale_d));
}

__device__ __forceinline__ void wgmma_ss_n256_tb1(float (&d)[128], uint64_t da, uint64_t db, int scale_d) {
    asm volatile("{\n.reg .pred p;\nsetp.ne.b32 p, %130, 0;\n"
        "wgmma.mma_async.sync.aligned.m64n256k16.f32.bf16.bf16 {%0, %1, %2, %3, %4, %5, %6, %7, %8, %9, %10, %11, %12, %13, %14, %15, %16, %17, %18, %19, %20, %21, %22, %23, %24, %25, %26, %27, %28, %29, %30, %31, %32, %33, %34, %35, %36, %37, %38, %39, %40, %41, %42, %43, %44, %45, %46, %47, %48, %49, %50, %51, %52, %53, %54, %55, %56, %57, %58, %59, %60, %61, %62, %63, %64, %65, %66, %67, %68, %69, %70, %71, %72, %73, %74, %75, %76, %77, %78, %79, %80, %81, %82, %83, %84, %85, %86, %87, %88, %89, %90, %91, %92, %93, %94, %95, %96, %97, %98, %99, %100, %101, %102, %103, %104, %105, %106, %107, %108, %109, %110, %111, %112, %113, %114, %115, %116, %117, %118, %119, %120, %121, %122, %123, %124, %125, %126, %127}, %128, %129, p, 1, 1, 0, 1;\n}\n"
        : "+f"(d[0]), "+f"(d[1]), "+f"(d[2]), "+f"(d[3]), "+f"(d[4]), "+f"(d[5]), "+f"(d[6]), "+f"(d[7]), "+f"(d[8]), "+f"(d[9]), "+f"(d[10]), "+f"(d[11]), "+f"(d[12]), "+f"(d[13]), "+f"(d[14]), "+f"(d[15]), "+f"(d[16]), "+f"(d[17]), "+f"(d[18]), "+f"(d[19]), "+f"(d[20]), "+f"(d[21]), "+f"(d[22]), "+f"(d[23]), "+f"(d[24]), "+f"(d[25]), "+f"(d[26]), "+f"(d[27]), "+f"(d[28]), "+f"(d[29]), "+f"(d[30]), "+f"(d[31]), "+f"(d[32]), "+f"(d[33]), "+f"(d[34]), "+f"(d[35]), "+f"(d[36]), "+f"(d[37]), "+f"(d[38]), "+f"(d[39]), "+f"(d[40]), "+f"(d[41]), "+f"(d[42]), "+f"(d[43]), "+f"(d[44]), "+f"(d[45]), "+f"(d[46]), "+f"(d[47]), "+f"(d[48]), "+f"(d[49]), "+f"(d[50]), "+f"(d[51]), "+f"(d[52]), "+f"(d[53]), "+f"(d[54]), "+f"(d[55]), "+f"(d[56]), "+f"(d[57]), "+f"(d[58]), "+f"(d[59]), "+f"(d[60]), "+f"(d[61]), "+f"(d[62]), "+f"(d[63]), "+f"(d[64]), "+f"(d[65]), "+f"(d[66]), "+f"(d[67]), "+f"(d[68]), "+f"(d[69]), "+f"(d[70]), "+f"(d[71]), "+f"(d[72]), "+f"(d[73]), "+f"(d[74]), "+f"(d[75]), "+f"(d[76]), "+f"(d[77]), "+f"(d[78]), "+f"(d[79]), "+f"(d[80]), "+f"(d[81]), "+f"(d[82]), "+f"(d[83]), "+f"(d[84]), "+f"(d[85]), "+f"(d[86]), "+f"(d[87]), "+f"(d[88]), "+f"(d[89]), "+f"(d[90]), "+f"(d[91]), "+f"(d[92]), "+f"(d[93]), "+f"(d[94]), "+f"(d[95]), "+f"(d[96]), "+f"(d[97]), "+f"(d[98]), "+f"(d[99]), "+f"(d[100]), "+f"(d[101]), "+f"(d[102]), "+f"(d[103]), "+f"(d[104]), "+f"(d[105]), "+f"(d[106]), "+f"(d[107]), "+f"(d[108]), "+f"(d[109]), "+f"(d[110]), "+f"(d[111]), "+f"(d[112]), "+f"(d[113]), "+f"(d[114]), "+f"(d[115]), "+f"(d[116]), "+f"(d[117]), "+f"(d[118]), "+f"(d[119]), "+f"(d[120]), "+f"(d[121]), "+f"(d[122]), "+f"(d[123]), "+f"(d[124]), "+f"(d[125]), "+f"(d[126]), "+f"(d[127])
        : "l"(da), "l"(db), "r"(scale_d));
}

__device__ __forceinline__ void wgmma_ss_n32_tb0(float (&d)[16], uint64_t da, uint64_t db, int scale_d) {
    asm volatile("{\n.reg .pred p;\nsetp.ne.b32 p, %18, 0;\n"
        "wgmma.mma_async.sync.aligned.m64n32k16.f32.bf16.bf16 {%0, %1, %2, %3, %4, %5, %6, %7, %8, %9, %10, %11, %12, %13, %14, %15}, %16, %17, p, 1, 1, 0, 0;\n}\n"
        : "+f"(d[0]), "+f"(d[1]), "+f"(d[2]), "+f"(d[3]), "+f"(d[4]), "+f"(d[5]), "+f"(d[6]), "+f"(d[7]), "+f"(d[8]), "+f"(d[9]), "+f"(d[10]), "+f"(d[11]), "+f"(d[12]), "+f"(d[13]), "+f"(d[14]), "+f"(d[15])
        : "l"(da), "l"(db), "r"(scale_d));
}

__device__ __forceinline__ void wgmma_ss_n64_tb0(float (&d)[32], uint64_t da, uint64_t db, int scale_d) {
    asm volatile("{\n.reg .pred p;\nsetp.ne.b32 p, %34, 0;\n"
        "wgmma.mma_async.sync.aligned.m64n64k16.f32.bf16.bf16 {%0, %1, %2, %3, %4, %5, %6, %7, %8, %9, %10, %11, %12, %13, %14, %15, %16, %17, %18, %19, %20, %21, %22, %23, %24, %25, %26, %27, %28, %29, %30, %31}, %32, %33, p, 1, 1, 0, 0;\n}\n"
        : "+f"(d[0]), "+f"(d[1]), "+f"(d[2]), "+f"(d[3]), "+f"(d[4]), "+f"(d[5]), "+f"(d[6]), "+f"(d[7]), "+f"(d[8]), "+f"(d[9]), "+f"(d[10]), "+f"(d[11]), "+f"(d[12]), "+f"(d[13]), "+f"(d[14]), "+f"(d[15]), "+f"(d[16]), "+f"(d[17]), "+f"(d[18]), "+f"(d[19]), "+f"(d[20]), "+f"(d[21]), "+f"(d[22]), "+f"(d[23]), "+f"(d[24]), "+f"(d[25]), "+f"(d[26]), "+f"(d[27]), "+f"(d[28]), "+f"(d[29]), "+f"(d[30]), "+f"(d[31])
        : "l"(da), "l"(db), "r"(scale_d));
}

struct Maps {
    CUtensorMap xa, xa2, xas, xh, wup4, wup8, mqa2, mqa4, mqb1, mqb2, uc, x, out, wq, wk, fa[3], fb[2], fc;
};

__device__ __forceinline__ uint64_t mkd(uint32_t lo) {
    uint64_t d;
    asm("mov.b64 %0, {%1, %2};" : "=l"(d) : "r"(lo), "r"((1024u >> 4) | (1u << 30)));
    return d;
}
__device__ __forceinline__ void bulk_ld(uint32_t dst, const void* src, uint32_t bytes, uint32_t bar) {
    asm volatile("cp.async.bulk.shared::cluster.global.mbarrier::complete_tx::bytes [%0], [%1], %2, [%3];" ::"r"(dst), "l"(src), "r"(bytes), "r"(bar) : "memory");
}
__device__ __forceinline__ void bulk_st(void* dst, uint32_t src, uint32_t bytes) {
    asm volatile("cp.async.bulk.global.shared::cta.bulk_group [%0], [%1], %2;" ::"l"(dst), "r"(src), "r"(bytes) : "memory");
}
__device__ __forceinline__ void ring_ld(uint32_t sb, uint32_t slot8, int n) {
    mbar_expect_tx(sb + B_R2 + slot8, 8192);
    bulk_ld(sb + R1 + slot8 * 1024, (const char*)g_wepi + n * 8192, 8192, sb + B_R2 + slot8);
}

__device__ __forceinline__ void ring_half(uint32_t sb, uint32_t slot8, uint32_t hoff, const CUtensorMap* tm, int c1, int c2) {
    mbar_expect_tx(sb + B_R1 + slot8, 8192);
    tma3(sb + R1 + slot8 * 2048 + hoff, tm, 0, c1, c2, sb + B_R1 + slot8);
}
__device__ __forceinline__ void ring_full(uint32_t sb, uint32_t slot8, const CUtensorMap* tm, int c1, int c2) {
    mbar_expect_tx(sb + B_R1 + slot8, 16384);
    mbar_arrive(sb + B_R1 + slot8);
    tma3(sb + R1 + slot8 * 2048, tm, 0, c1, c2, sb + B_R1 + slot8);
}
__device__ __forceinline__ void cta_done(int mode) {
    if (mode == 0 && atomicAdd(&g_sync[4], 1) == NCTA + 1) {
#pragma unroll
        for (int i = 0; i < 5; i++) g_sync[i] = 0;
    }
}

__device__ __forceinline__ void fold_cta(const Maps& mp, uint32_t sb, int mode) {
    constexpr uint32_t F_FULL = MISC, F_EMPTY = MISC + 32, F_T1 = MISC + 64, STG = 49152, FOUT = 3 * STG;
    const int tid = threadIdx.x, f = blockIdx.x - NCTA;
    if (mode == 2) return;
    if (tid == 0) {
        for (int i = 0; i < 3; i++) { mbar_init(sb + F_FULL + 8 * i, 1); mbar_init(sb + F_EMPTY + 8 * i, 2); }
        mbar_init(sb + F_T1, 2);
        asm volatile("fence.mbarrier_init.release.cluster;" ::: "memory");
        fence_async();
    }
    __syncthreads();
    const int wg = __shfl_sync(0xffffffffu, tid >> 7, 0);
    int st = 0, ph = 0;
    if (wg == 0) {
        if (tid == 0) {
#pragma unroll 1
            for (int it = 0; it < 96; it++) {
                const int p = it >> 3, kc = it & 7, job = p >> 2;
                if (it == 64) mbar_wait(sb + F_T1, 0);
                mbar_wait(sb + F_EMPTY + 8 * st, ph ^ 1);
                mbar_expect_tx(sb + F_FULL + 8 * st, STG);
                tma3(sb + st * STG, &mp.fa[job], 0, 256 * f + 128 * ((p >> 1) & 1), kc, sb + F_FULL + 8 * st);
                tma3(sb + st * STG + 16384, &mp.fb[job != 0], 0, 64 * kc + (job == 1 ? 512 : 0), 4 * (p & 1), sb + F_FULL + 8 * st);
                if (++st == 3) { st = 0; ph ^= 1; }
            }
        }
        return;
    }
    const int h = wg - 1, lane = tid & 31, w = (tid >> 5) & 3;
    const uint32_t sd = (sb & 0x3FFFF) >> 4;
    const bool el = (tid & 127) == 0;
#pragma unroll 1
    for (int p = 0; p < 12; p++) {
        float acc[128];
        fresh(acc);
#pragma unroll 1
        for (int kc = 0; kc < 8; kc++) {
            mbar_wait(sb + F_FULL + 8 * st, ph);
            wg_fence();
#pragma unroll
            for (int kk = 0; kk < 4; kk++)
                wgmma_ss_n256_tb1(acc, dsc(sd, st * STG + h * 8192 + kk * 32, 16), dsc(sd, st * STG + 16384 + kk * 2048, 8192), 1);
            wg_commit();
            wg_wait<0>();
            if (el) mbar_arrive(sb + F_EMPTY + 8 * st);
            if (++st == 3) { st = 0; ph ^= 1; }
        }
        pin(acc);
        const int job = p >> 2;
        if (el) {
            asm volatile("cp.async.bulk.wait_group 0;" ::: "memory");
            if (p == 4) { fence_async_g(); mbar_arrive(sb + F_T1); }
        }
        bar_sync(3 + h, 128);
        uint32_t r = 16 * w + (lane & 7) + ((lane >> 3) & 1) * 8;
        const float fs = job == 1 ? 0.5f : 1.f;
        if (job == 1) r = (r & ~31) | (((r >> 1) & 3) << 3) | (((r >> 3) & 3) << 1) | (r & 1);
        const uint32_t oa = sb + FOUT + h * 32768 + r * 128 + ((((lane >> 4) ^ r) & 7) << 4);
#pragma unroll
        for (int i = 0; i < 16; i++)
            stsm4((oa ^ ((i & 3) << 5)) + (i >> 2) * 8192, pack2(acc[8 * i] * fs, acc[8 * i + 1] * fs), pack2(acc[8 * i + 2] * fs, acc[8 * i + 3] * fs),
                  pack2(acc[8 * i + 4] * fs, acc[8 * i + 5] * fs), pack2(acc[8 * i + 6] * fs, acc[8 * i + 7] * fs));
        fence_async();
        bar_sync(3 + h, 128);
        if (el) {
            const int row0 = 256 * f + 128 * ((p >> 1) & 1) + 64 * h + (job == 1 ? 512 : 0);
            if (job == 0) tma3_store(&mp.fc, sb + FOUT + h * 32768, 0, row0, 4 * (p & 1));
            else {
#pragma unroll 1
                for (int i = 0; i < 16; i++)
                    bulk_st((char*)g_wepi + (row0 / 8 + 2 * (i & 3) + (p & 1)) * 8192 + (i >> 2) * 2048, sb + FOUT + h * 32768 + i * 2048, 2048);
            }
            asm volatile("cp.async.bulk.commit_group;" ::: "memory");
        }
    }
    if (el) {
        asm volatile("cp.async.bulk.wait_group 0;" ::: "memory");
        fence_async_g();
        if (mode == 0) flag_add(&g_sync[3]);
    }
    bar_sync(2, 256);
    if (tid == 128) cta_done(mode);
}

__global__ void __launch_bounds__(384, 1) main_kernel(const __grid_constant__ Maps mp, const bf16* __restrict__ dw, const bf16* wup, const int mode) {
    extern __shared__ __align__(1024) uint8_t smem[];
    const uint32_t sb = smem_u32(smem);
    const int tid = threadIdx.x;
    if (blockIdx.x >= NCTA) { fold_cta(mp, sb, mode); return; }
    const int b = blockIdx.x / TPB, ti = blockIdx.x % TPB;
    const int piece = blockIdx.x & 127;
    if (tid == 0) {
        mbar_init(sb + B_A, 1); mbar_init(sb + B_A2, 1); mbar_init(sb + B_MK, 1);
        for (int i = 0; i < 5; i++) mbar_init(sb + B_R1 + 8 * i, 2);
        asm volatile("fence.mbarrier_init.release.cluster;" ::: "memory");
        fence_async();
        mbar_expect_tx(sb + B_MK, 65536 + 32768);
        tma3(sb + R0, &mp.wq, 0, 64 * (piece >> 4), 0, sb + B_MK);
        tma3(sb + R1 + 32768, &mp.wk, 0, 32 * (piece & 15), 0, sb + B_MK);
        mbar_expect_tx(sb + B_A, 32768);
        mbar_expect_tx(sb + B_A2, 32768 + 3072);
#pragma unroll 1
        for (int i = 0; i < 16; i++) tma4(sb + AT + (i & 7) * 8192 + (i >> 3) * 4096, &mp.xh, 0, 62 * ti - 1 + 32 * (i >> 3), i & 7, b, sb + (i < 8 ? B_A : B_A2));
        bulk_ld(sb + DWS, dw, 3072, sb + B_A2);
        for (int i = 0; i < 8; i++) mbar_arrive(sb + B_R1 + 8 * (i >> 1));
        if (mode != 1) {
            ring_full(sb, 32, &mp.wup8, 0, 8);
            ring_full(sb, 0, &mp.wup8, 16, 8);
            ring_full(sb, 8, &mp.wup8, 32, 8);
        }
    } else if (tid == 32) {
        mbar_init(sb + B_LN, 1); mbar_init(sb + B_MQ, 1); mbar_init(sb + B_XA, 1);
        mbar_init(sb + B_H1, 2); mbar_init(sb + B_H2, 1); mbar_init(sb + B_H3, 2);
        for (int i = 0; i < 3; i++) { mbar_init(sb + B_KV + 8 * i, 1); mbar_init(sb + B_P + 8 * i, 4); mbar_init(sb + B_GO + 8 * i, 4); }
        for (int i = 0; i < 20; i++) { mbar_init(sb + B_R2 + 8 * i, 1); mbar_init(sb + B_E2 + 8 * i, 4); }
        mbar_init(sb + B_UC, 1); mbar_init(sb + B_UC + 8, 1); mbar_init(sb + B_X, 8);
        for (int i = 0; i < 5; i++) asm volatile("st.shared.u32 [%0], 0;" ::"r"(sb + CNT + 4 * i) : "memory");
        asm volatile("fence.mbarrier_init.release.cluster;" ::: "memory");
        fence_async();
    }
    __syncthreads();
    const int wg = __shfl_sync(0xffffffffu, tid >> 7, 0);
    const int lane = tid & 31, w = (tid >> 5) & 3;
    const bool w0 = __shfl_sync(0xffffffffu, w, 0) == 0;
    const uint32_t sd = (sb & 0x3FFFF) >> 4;
    const uint32_t adA = sd + (AT >> 4) + (1u << 16);
    const uint32_t bd0 = sd + (R1 >> 4);
    const uint32_t bd2k = bd0 + ((2048u >> 4) << 16);
    const bool el = (tid & 127) == 0;
    const uint32_t lrow = 16 * w + (lane & 7) + ((lane >> 3) & 1) * 8;
    const uint32_t loff = lrow * 128 + ((((lane >> 4) ^ lrow) & 7) << 4);
    const int r0 = 16 * w + (lane >> 2);

    if (wg == 0) {
        asm volatile("setmaxnreg.inc.sync.aligned.u32 184;");
        uint32_t q[112];
        PT(0);
        PG(200);
        {
            float mq[16];
            fresh(mq);
            mbar_wait(sb + B_MK, 0);
            PT(1);
            if (PFW && tid == 32) l2_prefetch((const char*)wup + piece * 8192, 8192);
            wg_fence();
#pragma unroll 1
            for (int c = 0; c < 8; c++)
#pragma unroll
                for (int kk = 0; kk < 4; kk++)
                    wgmma_ss_n32_tb0(mq, dsc(sd, R0 + c * 8192 + kk * 32, 16), dsc(sd, R1 + 32768 + c * 4096 + kk * 32, 16), 1);
            wg_commit();
            wg_wait<0>();
            if (mode != 1 && w0 && elect1()) { ring_full(sb, 16, &mp.wup8, 48, 8); ring_full(sb, 24, &mp.wup8, 64, 8); }
            pin(mq);
            uint32_t* c = reinterpret_cast<uint32_t*>(g_mqk + (64 * (piece >> 4) + r0) * D_ + 32 * (piece & 15) + 2 * (lane & 3));
#pragma unroll
            for (int n = 0; n < 4; n++) { c[4 * n] = pack2(mq[4 * n], mq[4 * n + 1]); c[4 * n + 4 * D_] = pack2(mq[4 * n + 2], mq[4 * n + 3]); }
            fence_async_g();
            bar_sync(1, 128);
            if (el) {
                if (mode == 0) flag_add(&g_sync[2]);
                if (mode == 0) flag_wait(&g_sync[2], NCTA);
                mbar_arrive(sb + B_MQ);
                PT(12);
                mbar_wait(sb + B_LN, 0);
#pragma unroll 1
                for (int c = 0; c < 8; c++) {
                    tma4_store(&mp.xas, sb + AT + c * 8192, 0, 62 * ti, c, b);
                    const unsigned t0 = (unsigned)clock();
                    while (c < 7 && (unsigned)clock() - t0 < XS_GAP) __nanosleep(20);
                }
                asm volatile("cp.async.bulk.commit_group;" ::: "memory");
                if (mode == 1) asm volatile("cp.async.bulk.wait_group 0;" ::: "memory");
            }
            PT(13);
            if (mode == 1) return;
        }
        mbar_wait(sb + B_H1, 0);
        PT(2);
        uint32_t slot8 = 8, par = 1, prev8 = 0;
        auto adv = [&]() { prev8 = slot8; slot8 += 8; if (slot8 == 40) { slot8 = 0; par ^= 1; } };
        {
            float acc[128];
            fresh(acc);
            auto step = [&](int i) {
                const uint32_t aa = adA + (i >> 1) * 512 + (i & 1) * 4, bb = bd0 + ((4096u >> 4) << 16) + slot8 * 128;
                wg_fence();
                wgmma_ss_n256_tb1(acc, mkd(aa), mkd(bb), 1);
                wgmma_ss_n256_tb1(acc, mkd(aa + 2), mkd(bb + 128), 1);
                wg_commit();
                wg_wait<1>();
            };
#pragma unroll 1
            for (int i = 0; i < 12; i++) {
                mbar_wait(sb + B_R1 + slot8, par);
                step(i);
                if (i > 0 && w0 && elect1()) ring_full(sb, prev8, &mp.mqa4, 32 * i + 128, 4);
                adv();
            }
#pragma unroll 1
            for (int i = 12; i < 16; i++) {
                mbar_wait(sb + B_R1 + slot8, par);
                if (i == 15 && el) mbar_arrive(sb + B_H2);
                step(i);
                if (w0 && elect1()) ring_full(sb, prev8, &mp.wup8, 16 * i - 192, 0);
                adv();
            }
            wg_wait<0>();
            if (w0 && elect1()) ring_full(sb, prev8, &mp.wup8, 64, 0);
            pin(acc);
            PT(3);
#pragma unroll
            for (int kk = 0; kk < 4; kk++)
                stsm4((sb + QS + loff) ^ (kk << 5), pack2(acc[96 + 8 * kk], acc[97 + 8 * kk]), pack2(acc[98 + 8 * kk], acc[99 + 8 * kk]),
                      pack2(acc[100 + 8 * kk], acc[101 + 8 * kk]), pack2(acc[102 + 8 * kk], acc[103 + 8 * kk]));
            fence_async();
#pragma unroll
            for (int i = 47; i >= 0; i--) q[64 + i] = pack2v(acc[2 * i], acc[2 * i + 1]);
        }
        if (el) {
            asm volatile("cp.async.bulk.wait_group 0;" ::: "memory");
            if (mode == 0) {
                fence_async_g();
                flag_add(&g_sync[b]);
                flag_wait(&g_sync[b], TPB);
            }
            mbar_arrive(sb + B_XA);
        }
        __syncwarp();
        mbar_wait(sb + B_H3, 0);
        PT(4);
        slot8 = 32; par = 0;
#pragma unroll
        for (int half = 0; half < 2; half++) {
            float acc[64];
            fresh(acc);
            auto step = [&](int m) {
                const uint32_t aa = adA + m * 512, bb = bd0 + ((8192u >> 4) << 16) + slot8 * 128;
                mbar_wait(sb + B_R1 + slot8, par);
                wg_fence();
#pragma unroll
                for (int kk = 0; kk < 4; kk++) wgmma_ss_n128_tb1(acc, mkd(aa + 2 * kk), mkd(bb + 128 * kk), 1);
                wg_commit();
                wg_wait<1>();
            };
            if (half == 0) {
#pragma unroll 1
                for (int m = 0; m < 8; m++) {
                    step(m);
                    if (m > 0 && w0 && elect1()) ring_full(sb, prev8, &mp.mqb2, (64 * m + 256) & 511, (m + 4) >> 3 << 1);
                    adv();
                }
            } else {
#pragma unroll 1
                for (int m = 0; m < 4; m++) {
                    step(m);
                    if (m > 0 && w0 && elect1()) ring_full(sb, prev8, &mp.mqb2, 64 * m + 256, 2);
                    adv();
                }
#pragma unroll 1
                for (int m = 4; m < 8; m++) {
                    step(m);
                    if (w0 && elect1()) {
                        if (m == 4) mbar_expect_tx(sb + B_KV + 8, 65536);
                        tma4(sb + R1 + prev8 * 2048, &mp.xa2, 0, 0, 2 * m - 8, b, sb + B_KV + 8);
                    }
                    adv();
                }
            }
            wg_wait<0>();
            if (w0 && elect1()) {
                if (half == 0) ring_full(sb, prev8, &mp.mqb2, 256, 2);
                else {
                    mbar_expect_tx(sb + B_KV + 16, 65536);
                    tma4(sb + R2, &mp.xa, 0, 64, 0, b, sb + B_KV + 16);
                }
            }
            pin(acc);
#pragma unroll
            for (int i = 31; i >= 0; i--) q[32 * half + i] = pack2v(acc[2 * i], acc[2 * i + 1]);
        }
        bar_sync(1, 128);
        PT(5);

        const float CS = 0.04419417382415922f * 1.4426950408889634f;
        float m0 = -INFINITY, m1 = -INFINITY, l0 = 0.f, l1 = 0.f;
        int s = 0, sn = 1, ph = 0;
        float S[32];
        const bool l0w = lane == 0, q0 = (lane & 3) == 0;
#pragma unroll 1
        for (int j = -1;; j++) {
            if (j >= 0) {
                PL(j, 1);
                if (j == NKV - 1) {
#pragma unroll
                    for (int i = (T_ - 64 * (NKV - 1)) / 2; i < 32; i++) asm volatile("mov.b32 %0, 0xff800000;" : "=f"(S[i]));
                }
                float y[8], z[8];
#pragma unroll
                for (int n = 0; n < 8; n++) { y[n] = fmaxf(S[4 * n], S[4 * n + 1]); z[n] = fmaxf(S[4 * n + 2], S[4 * n + 3]); }
#pragma unroll
                for (int n = 0; n < 4; n++) { y[n] = fmaxf(y[n], y[n + 4]); z[n] = fmaxf(z[n], z[n + 4]); }
                float x0 = fmaxf(fmaxf(y[0], y[1]), fmaxf(fmaxf(y[2], y[3]), m0)), x1 = fmaxf(fmaxf(z[0], z[1]), fmaxf(fmaxf(z[2], z[3]), m1));
                x0 = fmaxf(x0, __shfl_xor_sync(0xffffffffu, x0, 1));
                x1 = fmaxf(x1, __shfl_xor_sync(0xffffffffu, x1, 1));
                x0 = fmaxf(x0, __shfl_xor_sync(0xffffffffu, x0, 2));
                x1 = fmaxf(x1, __shfl_xor_sync(0xffffffffu, x1, 2));
                if ((x0 - m0) * CS <= LAZY) x0 = m0;
                if ((x1 - m1) * CS <= LAZY) x1 = m1;
                const float sc0 = ex2((m0 - x0) * CS), sc1 = ex2((m1 - x1) * CS);
                m0 = x0; m1 = x1;
                const float n0 = -x0 * CS, n1 = -x1 * CS;
                if (q0) { sts_f32(sb + SCL + s * 256 + r0 * 4, sc0); sts_f32(sb + SCL + s * 256 + r0 * 4 + 32, sc1); }
                __syncwarp();
                if (l0w) mbar_arrive(sb + B_P + s * 8);
                if (j < NKV - 1) mbar_wait(sb + B_KV + sn * 8, ph);
                float a0 = 0.f, a1 = 0.f;
                const uint32_t pb = sb + R3 + (s == 0 ? 2 : s - 1) * 8192;
#pragma unroll
                for (int kk = 0; kk < 4; kk++) {
                    float p[8];
#pragma unroll
                    for (int e = 0; e < 8; e++) p[e] = ex2(fmaf(S[8 * kk + e], CS, (e & 2) ? n1 : n0));
                    a0 += (p[0] + p[1]) + (p[4] + p[5]);
                    a1 += (p[2] + p[3]) + (p[6] + p[7]);
                    stsm4((pb + loff) ^ (kk << 5), pack2(p[0], p[1]), pack2(p[2], p[3]), pack2(p[4], p[5]), pack2(p[6], p[7]));
                }
                l0 = fmaf(l0, sc0, a0); l1 = fmaf(l1, sc1, a1);
                PL(j, 2);
                if (j == NKV - 1) break;
            } else {
                mbar_wait(sb + B_KV + 8, 0);
            }
            float Sn[32];
            const uint32_t kd = sd + sn * 4096;
            wg_fence();
#pragma unroll
            for (int kk = 0; kk < 28; kk++) {
                wgmma_rs_n64_tb0(Sn, q[4 * kk], q[4 * kk + 1], q[4 * kk + 2], q[4 * kk + 3], dsc(kd, (kk >> 2) * 8192 + (kk & 3) * 32, 16), kk > 0);
                if (kk == FENCE_AT) { fence_async(); __syncwarp(); }
                if (kk == GO_AT) { PL(j, 3); if (j >= 0 && l0w) mbar_arrive(sb + B_GO + s * 8); }
            }
#pragma unroll
            for (int kk = 0; kk < 4; kk++)
                wgmma_ss_n64_tb0(Sn, dsc(sd, QS + kk * 32, 16), dsc(kd, 7 * 8192 + kk * 32, 16), 1);
            wg_commit();
            PL(j, 0);
            wg_wait<0>();
            pin(Sn);
#pragma unroll
            for (int i = 0; i < 32; i++) S[i] = Sn[i];
            s = sn;
            if (++sn == 3) sn = 0;
            if (sn == 1) ph ^= 1;
        }
        l0 += __shfl_xor_sync(0xffffffffu, l0, 1); l1 += __shfl_xor_sync(0xffffffffu, l1, 1);
        l0 += __shfl_xor_sync(0xffffffffu, l0, 2); l1 += __shfl_xor_sync(0xffffffffu, l1, 2);
        if (q0) { sts_f32(sb + LINV + r0 * 4, rcp(l0)); sts_f32(sb + LINV + r0 * 4 + 32, rcp(l1)); }
        fence_async();
        __syncwarp();
        if (l0w) {
            mbar_arrive(sb + B_GO + s * 8);
            uint32_t slot8 = 8 * w, par = 0;
#pragma unroll 1
            for (int n = 20 + w; n < 136; n += 4) {
                mbar_wait(sb + B_E2 + slot8, par);
                if (n < 128) ring_ld(sb, slot8, n);
                else {
                    mbar_expect_tx(sb + B_X, 8192);
                    tma4(sb + R1 + slot8 * 1024, &mp.x, 0, 62 * ti, n - 128, b, sb + B_X);
                }
                slot8 += 32;
                if (slot8 >= 160) { slot8 -= 160; par ^= 1; }
            }
        }
        PDUMP();
    } else {
        asm volatile("setmaxnreg.dec.sync.aligned.u32 160;");
        const int h = wg - 1;
        auto red4 = [&](float (&a)[4]) {
            const bool b4 = lane & 16, b3 = lane & 8;
            const float k0 = (b4 ? a[2] : a[0]) + __shfl_xor_sync(0xffffffffu, b4 ? a[0] : a[2], 16);
            const float k1 = (b4 ? a[3] : a[1]) + __shfl_xor_sync(0xffffffffu, b4 ? a[1] : a[3], 16);
            float k = (b3 ? k1 : k0) + __shfl_xor_sync(0xffffffffu, b3 ? k0 : k1, 8);
            k += __shfl_xor_sync(0xffffffffu, k, 4);
            k += __shfl_xor_sync(0xffffffffu, k, 2);
            k += __shfl_xor_sync(0xffffffffu, k, 1);
            return k;
        };
#pragma unroll 1
        for (int bt = 0; bt < 2; bt++) {
            mbar_wait(sb + (bt ? B_A2 : B_A), 0);
            PT(bt ? 13 : 0);
            uint32_t v[4][8];
            float a[4], f[4][16];
            const uint32_t la = sb + AT + (lane >> 3) * 8192 + (32 * bt + 16 * h + 4 * w) * 128 + (((lane & 7) ^ ((w & 1) * 4)) << 4);
#pragma unroll
            for (int r = 0; r < 4; r++) { lds4((la ^ (r << 4)) + r * 128, v[r]); lds4((la ^ (r << 4)) + r * 128 + 32768, v[r] + 4); }
#pragma unroll
            for (int r = 0; r < 4; r++) {
                float s0 = blo(v[r][0]), s1 = bhi(v[r][0]);
#pragma unroll
                for (int i = 1; i < 8; i++) { s0 += blo(v[r][i]); s1 += bhi(v[r][i]); }
                a[r] = s0 + s1;
            }
            const float mu = red4(a) * (1.f / D_);
            const uint32_t mp2 = pack2(mu, mu);
#pragma unroll
            for (int r = 0; r < 4; r++) {
                const uint32_t m2 = __shfl_sync(0xffffffffu, mp2, 8 * r);
                float s0 = 0.f, s1 = 0.f;
#pragma unroll
                for (int i = 0; i < 8; i++) {
                    const uint32_t d = bsub2(v[r][i], m2);
                    f[r][2 * i] = blo(d); f[r][2 * i + 1] = bhi(d);
                    s0 = fmaf(f[r][2 * i], f[r][2 * i], s0); s1 = fmaf(f[r][2 * i + 1], f[r][2 * i + 1], s1);
                }
                a[r] = s0 + s1;
            }
            const float dm = mu - blo(mp2);
            float sd_ = bfr(bfr(fmaxf(fmaf(red4(a), 1.f / D_, -dm * dm), 0.f)) + 1e-5f);
            asm("sqrt.approx.f32 %0, %0;" : "+f"(sd_));
            const float ri = rcp(bfr(sd_));
#pragma unroll
            for (int r = 0; r < 4; r++) {
                const float rinv = __shfl_sync(0xffffffffu, ri, 8 * r);
#pragma unroll
                for (int i = 0; i < 8; i++) v[r][i] = pack2(f[r][2 * i] * rinv, f[r][2 * i + 1] * rinv);
                sts4((la ^ (r << 4)) + r * 128, v[r][0], v[r][1], v[r][2], v[r][3]);
                sts4((la ^ (r << 4)) + r * 128 + 32768, v[r][4], v[r][5], v[r][6], v[r][7]);
            }
        }
        fence_async();
        bar_sync(2, 256);
        if (tid == 128) mbar_arrive(sb + B_LN);
        if (mode == 1) return;
        float acc[128];
#pragma unroll
        for (int pass = 0; pass < 2; pass++) {
            if (pass == 1) mbar_wait(sb + B_H2, 0);
            PT(1 + 3 * pass);
            fresh(acc);
            uint32_t slot8 = pass ? 16 : 32, par = 0, prev8 = 0;
            auto adv = [&]() { prev8 = slot8; slot8 += 8; if (slot8 == 40) { slot8 = 0; par ^= 1; } };
            auto step = [&](int kk) {
                wg_fence();
                wgmma_ss_n256_tb1(acc, mkd(adA + (kk >> 2) * 512 + (kk & 3) * 2), mkd(bd2k + h * 512 + slot8 * 128), 1);
                wg_commit();
                wg_wait<1>();
            };
#pragma unroll 1
            for (int kk = 0; kk < 28; kk++) {
                mbar_wait(sb + B_R1 + slot8, par);
                step(kk);
                if (kk > 0 && w0 && elect1()) ring_half(sb, prev8, h * 8192, &mp.wup4, 16 * kk + 64, (pass ? 0 : 8) + 4 * h);
                adv();
            }
            if (pass == 0 && w0) mbar_wait(sb + B_MQ, 0);
#pragma unroll 1
            for (int kk = 28; kk < 32; kk++) {
                mbar_wait(sb + B_R1 + slot8, par);
                if (kk == 31 && el) mbar_arrive(sb + (pass ? B_H3 : B_H1));
                step(kk);
                if (w0 && elect1()) ring_half(sb, prev8, h * 8192, pass ? &mp.mqb1 : &mp.mqa2, (pass ? 64 : 32) * (kk - 28), pass ? h : 4 + 2 * h);
                adv();
            }
            wg_wait<0>();
            if (w0 && elect1()) ring_half(sb, prev8, h * 8192, pass ? &mp.mqb1 : &mp.mqa2, pass ? 256 : 128, pass ? h : 4 + 2 * h);
            pin(acc);
            PT(2 + 3 * pass);
            if (pass == 0) {
                float s0 = 0.f, s1 = 0.f, v0 = 0.f, v1 = 0.f;
#pragma unroll
                for (int n = 0; n < 32; n++) {
#pragma unroll
                    for (int e = 0; e < 4; e++) acc[4 * n + e] = gelu2(acc[4 * n + e]);
                    s0 += acc[4 * n] + acc[4 * n + 1]; s1 += acc[4 * n + 2] + acc[4 * n + 3];
                    v0 = fmaf(acc[4 * n], acc[4 * n], v0); v0 = fmaf(acc[4 * n + 1], acc[4 * n + 1], v0);
                    v1 = fmaf(acc[4 * n + 2], acc[4 * n + 2], v1); v1 = fmaf(acc[4 * n + 3], acc[4 * n + 3], v1);
                }
#pragma unroll
                for (int o = 1; o < 4; o <<= 1) {
                    s0 += __shfl_xor_sync(0xffffffffu, s0, o); s1 += __shfl_xor_sync(0xffffffffu, s1, o);
                    v0 += __shfl_xor_sync(0xffffffffu, v0, o); v1 += __shfl_xor_sync(0xffffffffu, v1, o);
                }
                if ((lane & 3) == 0) {
                    uint32_t a = sb + STAT + h * 512 + r0 * 8;
                    sts_f32(a, s0); sts_f32(a + 4, v0); sts_f32(a + 64, s1); sts_f32(a + 68, v1);
                }
                bar_sync(2, 256);
                {
                    uint32_t a = sb + STAT + (h ^ 1) * 512 + r0 * 8;
                    s0 = (s0 + lds_f32(a)) * (1.f / 512.f); v0 = (v0 + lds_f32(a + 4)) * (1.f / 512.f);
                    s1 = (s1 + lds_f32(a + 64)) * (1.f / 512.f); v1 = (v1 + lds_f32(a + 68)) * (1.f / 512.f);
                }
                v0 = rsqrtf(fmaxf(fmaf(-s0, s0, v0), 0.f) + 4e-5f); v1 = rsqrtf(fmaxf(fmaf(-s1, s1, v1), 0.f) + 4e-5f);
                s0 = -s0 * v0; s1 = -s1 * v1;
#pragma unroll
                for (int p = 0; p < 16; p++)
                    stsm4(((sb + R0 + h * 32768 + loff) ^ ((p & 3) << 5)) + (p >> 2) * 8192,
                          pack2(fmaf(acc[8 * p], v0, s0), fmaf(acc[8 * p + 1], v0, s0)), pack2(fmaf(acc[8 * p + 2], v1, s1), fmaf(acc[8 * p + 3], v1, s1)),
                          pack2(fmaf(acc[8 * p + 4], v0, s0), fmaf(acc[8 * p + 5], v0, s0)), pack2(fmaf(acc[8 * p + 6], v1, s1), fmaf(acc[8 * p + 7], v1, s1)));
            } else {
                uint32_t u[64];
#pragma unroll
                for (int i = 63; i >= 0; i--) u[i] = pack2v(gelu2(acc[2 * i]), gelu2(acc[2 * i + 1]));
                PT(12);
                bar_sync(3 + h, 128);
                const uint32_t rm = lrow == 0 ? 0 : lrow - 1, rp = lrow == 63 ? 63 : lrow + 1;
                const uint32_t gb = sb + R0 + h * 32768;
                const uint32_t am = gb + rm * 128 + ((((lane >> 4) ^ rm) & 7) << 4), ap = gb + rp * 128 + ((((lane >> 4) ^ rp) & 7) << 4), ac = gb + loff;
                const uint32_t dwa = sb + DWS + 512 * h + ((lane >> 3) & 1) * 16 + (lane >> 4) * 1024;
                bf16* ucp = g_uc + ((size_t)blockIdx.x * 64 + r0) * D_ + 256 * h + 8 * (lane & 3);
#pragma unroll
                for (int m = 0; m < 8; m++) {
                    uint32_t o[8], g0[2][4], g1[2][4], g2[2][4], d[2][4], d2[2][2];
#pragma unroll
                    for (int pp = 0; pp < 2; pp++) {
                        const int p = 2 * m + pp;
                        const uint32_t co = (p >> 2) * 8192, cx = (p & 3) << 5;
                        ldsm4(dwa + 32 * p, d[pp]);
                        ldsm2(dwa + 32 * p + 2048, d2[pp]);
                        ldsm4((am ^ cx) + co, g0[pp]);
                        ldsm4((ac ^ cx) + co, g1[pp]);
                        ldsm4((ap ^ cx) + co, g2[pp]);
                    }
#pragma unroll
                    for (int pp = 0; pp < 2; pp++)
#pragma unroll
                        for (int e = 0; e < 4; e++)
                            o[4 * (e & 1) + 2 * pp + (e >> 1)] =
                                bmul2(u[8 * m + 4 * pp + e], bfma2(g2[pp][e], d2[pp][e >> 1], bfma2(g1[pp][e], d[pp][2 + (e >> 1)], bmul2(g0[pp][e], d[pp][e >> 1]))));
                    stg4(ucp + 32 * m, o[0], o[1], o[2], o[3]);
                    stg4(ucp + 32 * m + 8 * D_, o[4], o[5], o[6], o[7]);
                }
                bar_sync(2, 256);
                if (tid == 128) {
                    mbar_wait(sb + B_XA, 0);
                    mbar_expect_tx(sb + B_KV, 65536);
                    tma4(sb + R0, &mp.xa, 0, 128, 0, b, sb + B_KV);
                }
            }
            PT(3 + 3 * pass);
        }
        int s = 1, ph = 0;
        fresh(acc);
#pragma unroll 1
        for (int j = 0; j < NKV; j++) {
            mbar_wait(sb + B_P + s * 8, ph);
            PL(j, 0);
            if (j > 0) {
                const float sc0 = lds_f32(sb + SCL + s * 256 + r0 * 4), sc1 = lds_f32(sb + SCL + s * 256 + r0 * 4 + 32);
                if (__any_sync(0xffffffffu, sc0 != 1.f || sc1 != 1.f)) {
#pragma unroll
                    for (int n = 0; n < 32; n++) { acc[4 * n] *= sc0; acc[4 * n + 1] *= sc0; acc[4 * n + 2] *= sc1; acc[4 * n + 3] *= sc1; }
                }
            }
            mbar_wait(sb + B_GO + s * 8, ph);
            PL(j, 1);
            const uint32_t vd = sd + s * 4096 + h * 2048, pd = sd + (s == 0 ? 2 : s - 1) * 512;
            pin(acc);
            wg_fence();
#pragma unroll
            for (int kk = 0; kk < 4; kk++) wgmma_ss_n256_tb1(acc, dsc(pd, R3 + kk * 32, 16), dsc(vd, kk * 2048, 8192), 1);
            wg_commit();
            wg_wait<0>();
            pin(acc);
            PL(j, 2);
            if (w0 && elect1()) {
                if (j == NKV - 5 && mode == 0) flag_wait(&g_sync[3], 4);
                if (atom_inc_s(sb + CNT + 4 * s) & 1) {
                    if (j + 3 < NKV) {
                        mbar_expect_tx(sb + B_KV + s * 8, 65536);
                        tma4(sb + s * 65536, &mp.xa, 0, 64 * (j + 3), 0, b, sb + B_KV + s * 8);
                    } else if (j < NKV - 1) {
                        const int n0 = j == NKV - 3 ? 0 : 8, n1 = n0 + 8;
#pragma unroll 1
                        for (int n = n0; n < n1; n++) ring_ld(sb, n * 8, n);
                    }
                }
            }
            if (++s == 3) s = 0;
            if (s == 1) ph ^= 1;
        }
        {
            const float i0 = lds_f32(sb + LINV + r0 * 4), i1 = lds_f32(sb + LINV + r0 * 4 + 32);
#pragma unroll
            for (int p = 0; p < 16; p++)
                stsm4(((sb + R0 + h * 32768 + loff) ^ ((p & 3) << 5)) + (p >> 2) * 8192,
                      pack2(acc[8 * p] * i0, acc[8 * p + 1] * i0), pack2(acc[8 * p + 2] * i1, acc[8 * p + 3] * i1),
                      pack2(acc[8 * p + 4] * i0, acc[8 * p + 5] * i0), pack2(acc[8 * p + 6] * i1, acc[8 * p + 7] * i1));
        }
        fence_async();
        fence_async_g();
        bar_sync(2, 256);
        if (lane == 0 && w < 2) ring_ld(sb, 128 + 16 * w + 8 * h, 16 + 2 * w + h);
        PT(7);
        fresh(acc);
        {
            uint32_t slot8 = 8 * h, par = 0, prev8 = 0;
#pragma unroll 1
            for (int kk = 0; kk < 64; kk++) {
                if (kk == 32 || kk == 48) mbar_wait(sb + B_UC + (kk >> 1 & 8), 0);
                mbar_wait(sb + B_R2 + slot8, par);
                wg_fence();
                wgmma_ss_n256_tb1(acc, mkd(sd + (1u << 16) + (R0 >> 4) + (kk >> 2 & 7) * 512 + (kk & 3) * 2), mkd(bd2k + slot8 * 64), 1);
                wg_commit();
                wg_wait<1>();
                if (kk > 0 && lane == 0) mbar_arrive(sb + B_E2 + prev8);
                if ((kk == 16 || kk == 32) && w0 && elect1() && (atom_inc_s(sb + CNT + 12 + (kk >> 3 & 4)) & 1)) {
                    mbar_expect_tx(sb + B_UC + (kk >> 2 & 8), 32768);
                    tma3(sb + R0 + (kk & 32) * 1024, &mp.uc, 0, 64 * blockIdx.x, kk >> 3 & 4, sb + B_UC + (kk >> 2 & 8));
                }
                prev8 = slot8;
                slot8 += 16;
                if (slot8 >= 160) { slot8 -= 160; par ^= 1; }
            }
        }
        wg_wait<0>();
        pin(acc);
        PT(8);
        mbar_wait(sb + B_X, 0);
        PT(9);
        {
            const uint32_t sr = (lrow + 63) & 63;
            const uint32_t xoff = sr * 128 + ((((lane >> 4) ^ sr) & 7) << 4);
#pragma unroll
            for (int p = 0; p < 16; p++) {
                const uint32_t a = ((sb + R2 + h * 32768 + xoff) ^ ((p & 3) << 5)) + (p >> 2) * 8192;
                uint32_t xv[4];
                ldsm4(a, xv);
#pragma unroll
                for (int e = 0; e < 4; e++)
                    xv[e] = pack2(acc[8 * p + 2 * e] + __uint_as_float(xv[e] << 16), acc[8 * p + 2 * e + 1] + __uint_as_float(xv[e] & 0xffff0000u));
                stsm4(a, xv[0], xv[1], xv[2], xv[3]);
            }
        }
        fence_async();
        bar_sync(3 + h, 128);
        if (el) {
            for (int c = 0; c < 4; c++) tma4_store(&mp.out, sb + R2 + (4 * h + c) * 8192, 0, 62 * ti, 4 * h + c, b);
            asm volatile("cp.async.bulk.commit_group;" ::: "memory");
            PT(10);
            if (h == 0) cta_done(mode);
            asm volatile("cp.async.bulk.wait_group.read 0;" ::: "memory");
        }
        PT(11);
        PG(201);
        PDUMP();
    }
}

typedef CUresult (*PFN_enc)(CUtensorMap*, CUtensorMapDataType, cuuint32_t, void*, const cuuint64_t*, const cuuint64_t*,
                            const cuuint32_t*, const cuuint32_t*, CUtensorMapInterleave, CUtensorMapSwizzle,
                            CUtensorMapL2promotion, CUtensorMapFloatOOBfill);

static void enc(PFN_enc f, CUtensorMap* m, void* base, int rank, const cuuint64_t* dims, const cuuint64_t* strides, const cuuint32_t* box) {
    cuuint32_t es[5] = {1, 1, 1, 1, 1};
    f(m, CU_TENSOR_MAP_DATA_TYPE_BFLOAT16, rank, base, dims, strides, box, es, CU_TENSOR_MAP_INTERLEAVE_NONE,
      CU_TENSOR_MAP_SWIZZLE_128B, CU_TENSOR_MAP_L2_PROMOTION_L2_256B, CU_TENSOR_MAP_FLOAT_OOB_FILL_NONE);
}
static void enc_act(PFN_enc f, CUtensorMap* m, void* base, int rows, int chunks, int trows = T_, int pitch = T_) {
    cuuint64_t dims[4] = {64, (cuuint64_t)trows, 8, (cuuint64_t)NB_};
    cuuint64_t st[3] = {1024, 128, (cuuint64_t)pitch * 1024};
    cuuint32_t box[4] = {64, (cuuint32_t)rows, (cuuint32_t)chunks, 1};
    enc(f, m, base, 4, dims, st, box);
}
static void enc_w(PFN_enc f, CUtensorMap* m, void* base, int krows, int ncols, int bk, int bc) {
    cuuint64_t dims[3] = {64, (cuuint64_t)krows, (cuuint64_t)(ncols / 64)};
    cuuint64_t st[2] = {(cuuint64_t)ncols * 2, 128};
    cuuint32_t box[3] = {64, (cuuint32_t)bk, (cuuint32_t)bc};
    enc(f, m, base, 3, dims, st, box);
}

extern "C" void kernel_launch(void* const* d_in, const int* in_sizes, int n_in, void* d_out, int out_size) {
    const bf16* x = (const bf16*)d_in[0];
    static PFN_enc fenc = nullptr;
    static void *p_xa, *p_mqk, *p_uc, *p_t1;
    static int fused = 0;
    if (!fenc) {
        void* fn = nullptr;
        cudaDriverEntryPointQueryResult qr;
        cudaGetDriverEntryPoint("cuTensorMapEncodeTiled", &fn, cudaEnableDefault, &qr);
        fenc = (PFN_enc)fn;
        cudaGetSymbolAddress(&p_xa, g_xa);
        cudaGetSymbolAddress(&p_mqk, g_mqk);
        cudaGetSymbolAddress(&p_uc, g_uc);
        cudaGetSymbolAddress(&p_t1, g_t1);
        cudaFuncSetAttribute(main_kernel, cudaFuncAttributeMaxDynamicSharedMemorySize, SMEM_BYTES);
        int dev = 0, sms = 0, occ = 0;
        cudaGetDevice(&dev);
        cudaDeviceGetAttribute(&sms, cudaDevAttrMultiProcessorCount, dev);
        cudaOccupancyMaxActiveBlocksPerMultiprocessor(&occ, main_kernel, 384, SMEM_BYTES);
        fused = sms * occ >= NCTA + 2;
    }
    Maps mp;
    enc_act(fenc, &mp.xa, (char*)p_xa + 1024, 64, 8, T_, T_ + 8);
    enc_act(fenc, &mp.xa2, (char*)p_xa + 1024, 64, 2, T_, T_ + 8);
    enc_act(fenc, &mp.xas, p_xa, 64, 1, T_ + 1, T_ + 8);
    enc_act(fenc, &mp.x, (void*)x, 64, 1);
    enc_act(fenc, &mp.xh, (void*)x, 32, 1);
    enc_act(fenc, &mp.out, d_out, 62, 1);
    enc_w(fenc, &mp.wup4, d_in[5], 512, 1024, 16, 4);
    enc_w(fenc, &mp.wup8, d_in[5], 512, 1024, 16, 8);
    enc_w(fenc, &mp.mqa2, p_mqk, 512, 512, 32, 2);
    enc_w(fenc, &mp.mqa4, p_mqk, 512, 512, 32, 4);
    enc_w(fenc, &mp.mqb1, p_mqk, 512, 512, 64, 1);
    enc_w(fenc, &mp.mqb2, p_mqk, 512, 512, 64, 2);
    enc_w(fenc, &mp.uc, p_uc, NCTA * 64, 512, 64, 4);
    enc_w(fenc, &mp.wq, d_in[1], 512, 512, 64, 8);
    enc_w(fenc, &mp.wk, d_in[2], 512, 512, 32, 8);
    enc_w(fenc, &mp.fa[0], d_in[3], 512, 512, 128, 1);
    enc_w(fenc, &mp.fa[1], d_in[7], 512, 512, 128, 1);
    enc_w(fenc, &mp.fa[2], p_t1, 512, 512, 128, 1);
    enc_w(fenc, &mp.fb[0], d_in[4], 512, 512, 64, 4);
    enc_w(fenc, &mp.fb[1], d_in[8], 1024, 512, 64, 4);
    enc_w(fenc, &mp.fc, p_t1, 512, 512, 64, 4);
    cudaStream_t st = cudaStreamPerThread;
    if (fused) {
        main_kernel<<<NCTA + 2, 384, SMEM_BYTES, st>>>(mp, (const bf16*)d_in[6], (const bf16*)d_in[5], 0);
    } else {
        main_kernel<<<NCTA + 2, 384, SMEM_BYTES, st>>>(mp, (const bf16*)d_in[6], (const bf16*)d_in[5], 1);
        main_kernel<<<NCTA + 2, 384, SMEM_BYTES, st>>>(mp, (const bf16*)d_in[6], (const bf16*)d_in[5], 2);
    }
}
```

```cpp
#include <cuda_runtime.h>
#include <cuda_bf16.h>
#include <cuda.h>
#include <stdint.h>

typedef __nv_bfloat16 bf16;

constexpr int T_ = 4000, D_ = 512, NB_ = 2;
constexpr int TPB = 65;
constexpr int NCTA = TPB * NB_;
constexpr int NKV = 63;

__device__ __align__(1024) bf16 g_xa[NB_ * (T_ + 8) * D_];
__device__ __align__(1024) bf16 g_mqk[D_ * D_];
__device__ __align__(1024) bf16 g_t1[D_ * D_];
__device__ __align__(1024) bf16 g_wepi[2 * D_ * D_];
__device__ __align__(1024) bf16 g_uc[NCTA * 64 * D_];
__device__ unsigned g_sync[8];

#define PT(i) do { if (el) asm volatile("st.shared.u32 [%0], %1;" ::"r"(sb + MISC + 2560), "r"((unsigned)clock())); } while (0)
#define PG(i)
#define PLM 15
#define PL(j, q) do { if ((PLM >> ((q) + (wg ? 4 : 0))) & 1) PT(0); } while (0)
#define PDUMP()

#define FENCE_AT 1
#define GO_AT 25
#define LAZY 8.f
#define XS_GAP 800
#define PFW 1
constexpr uint32_t R0 = 0, R1 = 65536, R2 = 131072, R3 = 196608, QS = 221184, MISC = 229376;
constexpr uint32_t AT = 147456, DWS = R3 + 16384;
constexpr uint32_t SMEM_BYTES = 232448;
constexpr uint32_t B_R1 = MISC + 8  , B_MK = MISC + 48, B_LN = MISC + 56, B_MQ = MISC + 64, B_XA = MISC + 72,
                   B_H1 = MISC + 88, B_H2 = MISC + 96, B_H3 = MISC + 104,
                   B_KV = MISC + 112, B_P = MISC + 136, B_GO = MISC + 160, B_UC = MISC + 184  ,
                   B_X = MISC + 200, CNT = MISC + 208  , SCL = MISC + 512  ,
                   LINV = MISC + 1280  , STAT = MISC + 512  ,
                   B_R2 = MISC + 1536  , B_E2 = MISC + 1696  ;

__device__ __forceinline__ uint32_t smem_u32(const void* p) { return (uint32_t)__cvta_generic_to_shared(p); }
__device__ __forceinline__ void wg_fence() { asm volatile("wgmma.fence.sync.aligned;" ::: "memory"); }
__device__ __forceinline__ void wg_commit() { asm volatile("wgmma.commit_group.sync.aligned;" ::: "memory"); }
template <int N> __device__ __forceinline__ void wg_wait() { asm volatile("wgmma.wait_group.sync.aligned %0;" ::"n"(N) : "memory"); }
__device__ __forceinline__ uint64_t dsc(uint32_t sd, uint32_t off, uint32_t lbo) {
    uint32_t lo = sd + (off >> 4) + ((lbo >> 4) << 16);
    uint64_t d;
    asm("mov.b64 %0, {%1, %2};" : "=l"(d) : "r"(lo), "r"((1024u >> 4) | (1u << 30)));
    return d;
}
__device__ __forceinline__ bool elect1() {
    uint32_t p;
    asm volatile("{\n.reg .pred p;\nelect.sync _|p, 0xffffffff;\nselp.u32 %0, 1, 0, p;\n}\n" : "=r"(p));
    return p != 0;
}
__device__ __forceinline__ void mbar_init(uint32_t bar, int cnt) { asm volatile("mbarrier.init.shared::cta.b64 [%0], %1;" ::"r"(bar), "r"(cnt) : "memory"); }
__device__ __forceinline__ void mbar_expect_tx(uint32_t bar, uint32_t bytes) { asm volatile("mbarrier.arrive.expect_tx.shared::cta.b64 _, [%0], %1;" ::"r"(bar), "r"(bytes) : "memory"); }
__device__ __forceinline__ void mbar_arrive(uint32_t bar) { asm volatile("mbarrier.arrive.shared::cta.b64 _, [%0];" ::"r"(bar) : "memory"); }
__device__ __forceinline__ void mbar_wait(uint32_t bar, uint32_t parity) {
    uint32_t ok;
#pragma unroll 1
    for (uint32_t it = 0;; ++it) {
        asm volatile("{\n.reg .pred p;\nmbarrier.try_wait.parity.shared::cta.b64 p, [%1], %2;\nselp.u32 %0, 1, 0, p;\n}\n" : "=r"(ok) : "r"(bar), "r"(parity) : "memory");
        if (ok) break;
        if (it > (1u << 20)) __trap();
    }
}
__device__ __forceinline__ void fence_async() { asm volatile("fence.proxy.async.shared::cta;" ::: "memory"); }
__device__ __forceinline__ void fence_async_g() { asm volatile("fence.proxy.async.global;" ::: "memory"); }
__device__ __forceinline__ void bar_sync(int id, int n) { asm volatile("bar.sync %0, %1;" ::"r"(id), "r"(n) : "memory"); }
__device__ __forceinline__ void tma3(uint32_t dst, const CUtensorMap* tm, int c0, int c1, int c2, uint32_t bar) {
    asm volatile("cp.async.bulk.tensor.3d.shared::cluster.global.mbarrier::complete_tx::bytes [%0], [%1, {%3, %4, %5}], [%2];"
                 ::"r"(dst), "l"(tm), "r"(bar), "r"(c0), "r"(c1), "r"(c2) : "memory");
}
__device__ __forceinline__ void tma4(uint32_t dst, const CUtensorMap* tm, int c0, int c1, int c2, int c3, uint32_t bar) {
    asm volatile("cp.async.bulk.tensor.4d.shared::cluster.global.mbarrier::complete_tx::bytes [%0], [%1, {%3, %4, %5, %6}], [%2];"
                 ::"r"(dst), "l"(tm), "r"(bar), "r"(c0), "r"(c1), "r"(c2), "r"(c3) : "memory");
}
__device__ __forceinline__ void tma4_store(const CUtensorMap* tm, uint32_t src, int c0, int c1, int c2, int c3) {
    asm volatile("cp.async.bulk.tensor.4d.global.shared::cta.bulk_group [%0, {%2, %3, %4, %5}], [%1];"
                 ::"l"(tm), "r"(src), "r"(c0), "r"(c1), "r"(c2), "r"(c3) : "memory");
}
__device__ __forceinline__ void tma3_store(const CUtensorMap* tm, uint32_t src, int c0, int c1, int c2) {
    asm volatile("cp.async.bulk.tensor.3d.global.shared::cta.bulk_group [%0, {%2, %3, %4}], [%1];"
                 ::"l"(tm), "r"(src), "r"(c0), "r"(c1), "r"(c2) : "memory");
}
__device__ __forceinline__ void stsm4(uint32_t addr, uint32_t a, uint32_t b, uint32_t c, uint32_t d) {
    asm volatile("stmatrix.sync.aligned.m8n8.x4.shared.b16 [%0], {%1, %2, %3, %4};" ::"r"(addr), "r"(a), "r"(b), "r"(c), "r"(d) : "memory");
}
__device__ __forceinline__ void ldsm4(uint32_t addr, uint32_t (&r)[4]) {
    asm volatile("ldmatrix.sync.aligned.m8n8.x4.shared.b16 {%0, %1, %2, %3}, [%4];" : "=r"(r[0]), "=r"(r[1]), "=r"(r[2]), "=r"(r[3]) : "r"(addr) : "memory");
}
__device__ __forceinline__ void ldsm2(uint32_t addr, uint32_t (&r)[2]) {
    asm volatile("ldmatrix.sync.aligned.m8n8.x2.shared.b16 {%0, %1}, [%2];" : "=r"(r[0]), "=r"(r[1]) : "r"(addr) : "memory");
}
__device__ __forceinline__ void stg4(void* p, uint32_t a, uint32_t b, uint32_t c, uint32_t d) {
    asm volatile("st.global.v4.u32 [%0], {%1, %2, %3, %4};" ::"l"(p), "r"(a), "r"(b), "r"(c), "r"(d) : "memory");
}
__device__ __forceinline__ uint32_t pack2(float lo, float hi) {
    uint32_t r;
    asm("cvt.rn.bf16x2.f32 %0, %1, %2;" : "=r"(r) : "f"(hi), "f"(lo));
    return r;
}
__device__ __forceinline__ uint32_t pack2v(float lo, float hi) {
    uint32_t r;
    asm volatile("cvt.rn.bf16x2.f32 %0, %1, %2;" : "=r"(r) : "f"(hi), "f"(lo));
    return r;
}
__device__ __forceinline__ uint32_t bmul2(uint32_t a, uint32_t b) { uint32_t r; asm("mul.rn.bf16x2 %0, %1, %2;" : "=r"(r) : "r"(a), "r"(b)); return r; }
__device__ __forceinline__ uint32_t bfma2(uint32_t a, uint32_t b, uint32_t c) { uint32_t r; asm("fma.rn.bf16x2 %0, %1, %2, %3;" : "=r"(r) : "r"(a), "r"(b), "r"(c)); return r; }
__device__ __forceinline__ float ex2(float x) { float r; asm("ex2.approx.ftz.f32 %0, %1;" : "=f"(r) : "f"(x)); return r; }
__device__ __forceinline__ float rcp(float x) { float r; asm("rcp.approx.ftz.f32 %0, %1;" : "=f"(r) : "f"(x)); return r; }
__device__ __forceinline__ float gelu2(float x) {
    float t = fmaf(x * x, 0.044715f * 0.7978845608028654f, 0.7978845608028654f), th;
    asm("tanh.approx.f32 %0, %1;" : "=f"(th) : "f"(x * t));
    return fmaf(x, th, x);
}
__device__ __forceinline__ uint32_t ldg_v(const uint32_t* p) { uint32_t v; asm volatile("ld.global.nc.u32 %0, [%1];" : "=r"(v) : "l"(p)); return v; }
__device__ __forceinline__ float lds_f32(uint32_t a) { float v; asm volatile("ld.shared.f32 %0, [%1];" : "=f"(v) : "r"(a) : "memory"); return v; }
__device__ __forceinline__ void sts_f32(uint32_t a, float v) { asm volatile("st.shared.f32 [%0], %1;" ::"r"(a), "f"(v) : "memory"); }
__device__ __forceinline__ uint32_t atom_inc_s(uint32_t a) { uint32_t v; asm volatile("atom.relaxed.cta.shared.add.u32 %0, [%1], 1;" : "=r"(v) : "r"(a) : "memory"); return v; }
__device__ __forceinline__ void lds4(uint32_t a, uint32_t* r) {
    asm volatile("ld.shared.v4.u32 {%0, %1, %2, %3}, [%4];" : "=r"(r[0]), "=r"(r[1]), "=r"(r[2]), "=r"(r[3]) : "r"(a) : "memory");
}
__device__ __forceinline__ void sts4(uint32_t a, uint32_t x, uint32_t y, uint32_t z, uint32_t t) {
    asm volatile("st.shared.v4.u32 [%0], {%1, %2, %3, %4};" ::"r"(a), "r"(x), "r"(y), "r"(z), "r"(t) : "memory");
}
__device__ __forceinline__ uint32_t bsub2(uint32_t a, uint32_t b) { uint32_t r; asm("sub.rn.bf16x2 %0, %1, %2;" : "=r"(r) : "r"(a), "r"(b)); return r; }
__device__ __forceinline__ float blo(uint32_t v) { return __uint_as_float(v << 16); }
__device__ __forceinline__ float bhi(uint32_t v) { return __uint_as_float(v & 0xffff0000u); }
__device__ __forceinline__ float bfr(float x) { return __bfloat162float(__float2bfloat16_rn(x)); }
__device__ __forceinline__ void l2_prefetch(const void* p, uint32_t bytes) { asm volatile("cp.async.bulk.prefetch.L2.global [%0], %1;" ::"l"(p), "r"(bytes) : "memory"); }
__device__ __forceinline__ void flag_add(unsigned* p) { asm volatile("red.release.gpu.global.add.u32 [%0], 1;" ::"l"(p) : "memory"); }
__device__ __forceinline__ void flag_wait(const unsigned* p, unsigned target) {
#pragma unroll 1
    for (uint32_t it = 0;; ++it) {
        unsigned v;
        asm volatile("ld.acquire.gpu.global.u32 %0, [%1];" : "=r"(v) : "l"(p) : "memory");
        if (v >= target) break;
        if (it > (1u << 20)) __trap();
    }
    fence_async_g();
}
template <int N> __device__ __forceinline__ void pin(float (&a)[N]) {
#pragma unroll
    for (int i = 0; i < N; i++) asm volatile("" : "+f"(a[i])::"memory");
}

template <int N> __device__ __forceinline__ void fresh(float (&a)[N]) {
#pragma unroll
    for (int i = 0; i < N; i++) a[i] = 0.f;
    pin(a);
}

__device__ __forceinline__ void wgmma_rs_n64_tb0(float (&d)[32], uint32_t a0, uint32_t a1, uint32_t a2, uint32_t a3, uint64_t db, int scale_d) {
    asm volatile("{\n.reg .pred p;\nsetp.ne.b32 p, %37, 0;\n"
        "wgmma.mma_async.sync.aligned.m64n64k16.f32.bf16.bf16 {%0, %1, %2, %3, %4, %5, %6, %7, %8, %9, %10, %11, %12, %13, %14, %15, %16, %17, %18, %19, %20, %21, %22, %23, %24, %25, %26, %27, %28, %29, %30, %31}, {%32, %33, %34, %35}, %36, p, 1, 1, 0;\n}\n"
        : "+f"(d[0]), "+f"(d[1]), "+f"(d[2]), "+f"(d[3]), "+f"(d[4]), "+f"(d[5]), "+f"(d[6]), "+f"(d[7]), "+f"(d[8]), "+f"(d[9]), "+f"(d[10]), "+f"(d[11]), "+f"(d[12]), "+f"(d[13]), "+f"(d[14]), "+f"(d[15]), "+f"(d[16]), "+f"(d[17]), "+f"(d[18]), "+f"(d[19]), "+f"(d[20]), "+f"(d[21]), "+f"(d[22]), "+f"(d[23]), "+f"(d[24]), "+f"(d[25]), "+f"(d[26]), "+f"(d[27]), "+f"(d[28]), "+f"(d[29]), "+f"(d[30]), "+f"(d[31])
        : "r"(a0), "r"(a1), "r"(a2), "r"(a3), "l"(db), "r"(scale_d));
}

__device__ __forceinline__ void wgmma_ss_n128_tb1(float (&d)[64], uint64_t da, uint64_t db, int scale_d) {
    asm volatile("{\n.reg .pred p;\nsetp.ne.b32 p, %66, 0;\n"
        "wgmma.mma_async.sync.aligned.m64n128k16.f32.bf16.bf16 {%0, %1, %2, %3, %4, %5, %6, %7, %8, %9, %10, %11, %12, %13, %14, %15, %16, %17, %18, %19, %20, %21, %22, %23, %24, %25, %26, %27, %28, %29, %30, %31, %32, %33, %34, %35, %36, %37, %38, %39, %40, %41, %42, %43, %44, %45, %46, %47, %48, %49, %50, %51, %52, %53, %54, %55, %56, %57, %58, %59, %60, %61, %62, %63}, %64, %65, p, 1, 1, 0, 1;\n}\n"
        : "+f"(d[0]), "+f"(d[1]), "+f"(d[2]), "+f"(d[3]), "+f"(d[4]), "+f"(d[5]), "+f"(d[6]), "+f"(d[7]), "+f"(d[8]), "+f"(d[9]), "+f"(d[10]), "+f"(d[11]), "+f"(d[12]), "+f"(d[13]), "+f"(d[14]), "+f"(d[15]), "+f"(d[16]), "+f"(d[17]), "+f"(d[18]), "+f"(d[19]), "+f"(d[20]), "+f"(d[21]), "+f"(d[22]), "+f"(d[23]), "+f"(d[24]), "+f"(d[25]), "+f"(d[26]), "+f"(d[27]), "+f"(d[28]), "+f"(d[29]), "+f"(d[30]), "+f"(d[31]), "+f"(d[32]), "+f"(d[33]), "+f"(d[34]), "+f"(d[35]), "+f"(d[36]), "+f"(d[37]), "+f"(d[38]), "+f"(d[39]), "+f"(d[40]), "+f"(d[41]), "+f"(d[42]), "+f"(d[43]), "+f"(d[44]), "+f"(d[45]), "+f"(d[46]), "+f"(d[47]), "+f"(d[48]), "+f"(d[49]), "+f"(d[50]), "+f"(d[51]), "+f"(d[52]), "+f"(d[53]), "+f"(d[54]), "+f"(d[55]), "+f"(d[56]), "+f"(d[57]), "+f"(d[58]), "+f"(d[59]), "+f"(d[60]), "+f"(d[61]), "+f"(d[62]), "+f"(d[63])
        : "l"(da), "l"(db), "r"(scale_d));
}

__device__ __forceinline__ void wgmma_ss_n256_tb1(float (&d)[128], uint64_t da, uint64_t db, int scale_d) {
    asm volatile("{\n.reg .pred p;\nsetp.ne.b32 p, %130, 0;\n"
        "wgmma.mma_async.sync.aligned.m64n256k16.f32.bf16.bf16 {%0, %1, %2, %3, %4, %5, %6, %7, %8, %9, %10, %11, %12, %13, %14, %15, %16, %17, %18, %19, %20, %21, %22, %23, %24, %25, %26, %27, %28, %29, %30, %31, %32, %33, %34, %35, %36, %37, %38, %39, %40, %41, %42, %43, %44, %45, %46, %47, %48, %49, %50, %51, %52, %53, %54, %55, %56, %57, %58, %59, %60, %61, %62, %63, %64, %65, %66, %67, %68, %69, %70, %71, %72, %73, %74, %75, %76, %77, %78, %79, %80, %81, %82, %83, %84, %85, %86, %87, %88, %89, %90, %91, %92, %93, %94, %95, %96, %97, %98, %99, %100, %101, %102, %103, %104, %105, %106, %107, %108, %109, %110, %111, %112, %113, %114, %115, %116, %117, %118, %119, %120, %121, %122, %123, %124, %125, %126, %127}, %128, %129, p, 1, 1, 0, 1;\n}\n"
        : "+f"(d[0]), "+f"(d[1]), "+f"(d[2]), "+f"(d[3]), "+f"(d[4]), "+f"(d[5]), "+f"(d[6]), "+f"(d[7]), "+f"(d[8]), "+f"(d[9]), "+f"(d[10]), "+f"(d[11]), "+f"(d[12]), "+f"(d[13]), "+f"(d[14]), "+f"(d[15]), "+f"(d[16]), "+f"(d[17]), "+f"(d[18]), "+f"(d[19]), "+f"(d[20]), "+f"(d[21]), "+f"(d[22]), "+f"(d[23]), "+f"(d[24]), "+f"(d[25]), "+f"(d[26]), "+f"(d[27]), "+f"(d[28]), "+f"(d[29]), "+f"(d[30]), "+f"(d[31]), "+f"(d[32]), "+f"(d[33]), "+f"(d[34]), "+f"(d[35]), "+f"(d[36]), "+f"(d[37]), "+f"(d[38]), "+f"(d[39]), "+f"(d[40]), "+f"(d[41]), "+f"(d[42]), "+f"(d[43]), "+f"(d[44]), "+f"(d[45]), "+f"(d[46]), "+f"(d[47]), "+f"(d[48]), "+f"(d[49]), "+f"(d[50]), "+f"(d[51]), "+f"(d[52]), "+f"(d[53]), "+f"(d[54]), "+f"(d[55]), "+f"(d[56]), "+f"(d[57]), "+f"(d[58]), "+f"(d[59]), "+f"(d[60]), "+f"(d[61]), "+f"(d[62]), "+f"(d[63]), "+f"(d[64]), "+f"(d[65]), "+f"(d[66]), "+f"(d[67]), "+f"(d[68]), "+f"(d[69]), "+f"(d[70]), "+f"(d[71]), "+f"(d[72]), "+f"(d[73]), "+f"(d[74]), "+f"(d[75]), "+f"(d[76]), "+f"(d[77]), "+f"(d[78]), "+f"(d[79]), "+f"(d[80]), "+f"(d[81]), "+f"(d[82]), "+f"(d[83]), "+f"(d[84]), "+f"(d[85]), "+f"(d[86]), "+f"(d[87]), "+f"(d[88]), "+f"(d[89]), "+f"(d[90]), "+f"(d[91]), "+f"(d[92]), "+f"(d[93]), "+f"(d[94]), "+f"(d[95]), "+f"(d[96]), "+f"(d[97]), "+f"(d[98]), "+f"(d[99]), "+f"(d[100]), "+f"(d[101]), "+f"(d[102]), "+f"(d[103]), "+f"(d[104]), "+f"(d[105]), "+f"(d[106]), "+f"(d[107]), "+f"(d[108]), "+f"(d[109]), "+f"(d[110]), "+f"(d[111]), "+f"(d[112]), "+f"(d[113]), "+f"(d[114]), "+f"(d[115]), "+f"(d[116]), "+f"(d[117]), "+f"(d[118]), "+f"(d[119]), "+f"(d[120]), "+f"(d[121]), "+f"(d[122]), "+f"(d[123]), "+f"(d[124]), "+f"(d[125]), "+f"(d[126]), "+f"(d[127])
        : "l"(da), "l"(db), "r"(scale_d));
}

__device__ __forceinline__ void wgmma_ss_n32_tb0(float (&d)[16], uint64_t da, uint64_t db, int scale_d) {
    asm volatile("{\n.reg .pred p;\nsetp.ne.b32 p, %18, 0;\n"
        "wgmma.mma_async.sync.aligned.m64n32k16.f32.bf16.bf16 {%0, %1, %2, %3, %4, %5, %6, %7, %8, %9, %10, %11, %12, %13, %14, %15}, %16, %17, p, 1, 1, 0, 0;\n}\n"
        : "+f"(d[0]), "+f"(d[1]), "+f"(d[2]), "+f"(d[3]), "+f"(d[4]), "+f"(d[5]), "+f"(d[6]), "+f"(d[7]), "+f"(d[8]), "+f"(d[9]), "+f"(d[10]), "+f"(d[11]), "+f"(d[12]), "+f"(d[13]), "+f"(d[14]), "+f"(d[15])
        : "l"(da), "l"(db), "r"(scale_d));
}

__device__ __forceinline__ void wgmma_ss_n64_tb0(float (&d)[32], uint64_t da, uint64_t db, int scale_d) {
    asm volatile("{\n.reg .pred p;\nsetp.ne.b32 p, %34, 0;\n"
        "wgmma.mma_async.sync.aligned.m64n64k16.f32.bf16.bf16 {%0, %1, %2, %3, %4, %5, %6, %7, %8, %9, %10, %11, %12, %13, %14, %15, %16, %17, %18, %19, %20, %21, %22, %23, %24, %25, %26, %27, %28, %29, %30, %31}, %32, %33, p, 1, 1, 0, 0;\n}\n"
        : "+f"(d[0]), "+f"(d[1]), "+f"(d[2]), "+f"(d[3]), "+f"(d[4]), "+f"(d[5]), "+f"(d[6]), "+f"(d[7]), "+f"(d[8]), "+f"(d[9]), "+f"(d[10]), "+f"(d[11]), "+f"(d[12]), "+f"(d[13]), "+f"(d[14]), "+f"(d[15]), "+f"(d[16]), "+f"(d[17]), "+f"(d[18]), "+f"(d[19]), "+f"(d[20]), "+f"(d[21]), "+f"(d[22]), "+f"(d[23]), "+f"(d[24]), "+f"(d[25]), "+f"(d[26]), "+f"(d[27]), "+f"(d[28]), "+f"(d[29]), "+f"(d[30]), "+f"(d[31])
        : "l"(da), "l"(db), "r"(scale_d));
}

struct Maps {
    CUtensorMap xa, xa2, xas, wup4, wup8, mqa2, mqa4, mqb1, mqb2, uc, x, out, wq, wk, fa[3], fb[2], fc;
};

__device__ __forceinline__ uint64_t mkd(uint32_t lo) {
    uint64_t d;
    asm("mov.b64 %0, {%1, %2};" : "=l"(d) : "r"(lo), "r"((1024u >> 4) | (1u << 30)));
    return d;
}
__device__ __forceinline__ void bulk_ld(uint32_t dst, const void* src, uint32_t bytes, uint32_t bar) {
    asm volatile("cp.async.bulk.shared::cluster.global.mbarrier::complete_tx::bytes [%0], [%1], %2, [%3];" ::"r"(dst), "l"(src), "r"(bytes), "r"(bar) : "memory");
}
__device__ __forceinline__ void bulk_st(void* dst, uint32_t src, uint32_t bytes) {
    asm volatile("cp.async.bulk.global.shared::cta.bulk_group [%0], [%1], %2;" ::"l"(dst), "r"(src), "r"(bytes) : "memory");
}
__device__ __forceinline__ void ring_ld(uint32_t sb, uint32_t slot8, int n) {
    mbar_expect_tx(sb + B_R2 + slot8, 8192);
    bulk_ld(sb + R1 + slot8 * 1024, (const char*)g_wepi + n * 8192, 8192, sb + B_R2 + slot8);
}

__device__ __forceinline__ void ring_half(uint32_t sb, uint32_t slot8, uint32_t hoff, const CUtensorMap* tm, int c1, int c2) {
    mbar_expect_tx(sb + B_R1 + slot8, 8192);
    tma3(sb + R1 + slot8 * 2048 + hoff, tm, 0, c1, c2, sb + B_R1 + slot8);
}
__device__ __forceinline__ void ring_full(uint32_t sb, uint32_t slot8, const CUtensorMap* tm, int c1, int c2) {
    mbar_expect_tx(sb + B_R1 + slot8, 16384);
    mbar_arrive(sb + B_R1 + slot8);
    tma3(sb + R1 + slot8 * 2048, tm, 0, c1, c2, sb + B_R1 + slot8);
}
__device__ __forceinline__ void cta_done(int mode) {
    if (mode == 0 && atomicAdd(&g_sync[4], 1) == NCTA + 1) {
#pragma unroll
        for (int i = 0; i < 5; i++) g_sync[i] = 0;
    }
}

__device__ __forceinline__ void fold_cta(const Maps& mp, uint32_t sb, int mode) {
    constexpr uint32_t F_FULL = MISC, F_EMPTY = MISC + 32, F_T1 = MISC + 64, STG = 49152, FOUT = 3 * STG;
    const int tid = threadIdx.x, f = blockIdx.x - NCTA;
    if (mode == 2) return;
    if (tid == 0) {
        for (int i = 0; i < 3; i++) { mbar_init(sb + F_FULL + 8 * i, 1); mbar_init(sb + F_EMPTY + 8 * i, 2); }
        mbar_init(sb + F_T1, 2);
        asm volatile("fence.mbarrier_init.release.cluster;" ::: "memory");
        fence_async();
    }
    __syncthreads();
    const int wg = __shfl_sync(0xffffffffu, tid >> 7, 0);
    int st = 0, ph = 0;
    if (wg == 0) {
        if (tid == 0) {
#pragma unroll 1
            for (int it = 0; it < 96; it++) {
                const int p = it >> 3, kc = it & 7, job = p >> 2;
                if (it == 64) mbar_wait(sb + F_T1, 0);
                mbar_wait(sb + F_EMPTY + 8 * st, ph ^ 1);
                mbar_expect_tx(sb + F_FULL + 8 * st, STG);
                tma3(sb + st * STG, &mp.fa[job], 0, 256 * f + 128 * ((p >> 1) & 1), kc, sb + F_FULL + 8 * st);
                tma3(sb + st * STG + 16384, &mp.fb[job != 0], 0, 64 * kc + (job == 1 ? 512 : 0), 4 * (p & 1), sb + F_FULL + 8 * st);
                if (++st == 3) { st = 0; ph ^= 1; }
            }
        }
        return;
    }
    const int h = wg - 1, lane = tid & 31, w = (tid >> 5) & 3;
    const uint32_t sd = (sb & 0x3FFFF) >> 4;
    const bool el = (tid & 127) == 0;
#pragma unroll 1
    for (int p = 0; p < 12; p++) {
        float acc[128];
        fresh(acc);
#pragma unroll 1
        for (int kc = 0; kc < 8; kc++) {
            mbar_wait(sb + F_FULL + 8 * st, ph);
            wg_fence();
#pragma unroll
            for (int kk = 0; kk < 4; kk++)
                wgmma_ss_n256_tb1(acc, dsc(sd, st * STG + h * 8192 + kk * 32, 16), dsc(sd, st * STG + 16384 + kk * 2048, 8192), 1);
            wg_commit();
            wg_wait<0>();
            if (el) mbar_arrive(sb + F_EMPTY + 8 * st);
            if (++st == 3) { st = 0; ph ^= 1; }
        }
        pin(acc);
        const int job = p >> 2;
        if (el) {
            asm volatile("cp.async.bulk.wait_group 0;" ::: "memory");
            if (p == 4) { fence_async_g(); mbar_arrive(sb + F_T1); }
        }
        bar_sync(3 + h, 128);
        uint32_t r = 16 * w + (lane & 7) + ((lane >> 3) & 1) * 8;
        const float fs = job == 1 ? 0.5f : 1.f;
        if (job == 1) r = (r & ~31) | (((r >> 1) & 3) << 3) | (((r >> 3) & 3) << 1) | (r & 1);
        const uint32_t oa = sb + FOUT + h * 32768 + r * 128 + ((((lane >> 4) ^ r) & 7) << 4);
#pragma unroll
        for (int i = 0; i < 16; i++)
            stsm4((oa ^ ((i & 3) << 5)) + (i >> 2) * 8192, pack2(acc[8 * i] * fs, acc[8 * i + 1] * fs), pack2(acc[8 * i + 2] * fs, acc[8 * i + 3] * fs),
                  pack2(acc[8 * i + 4] * fs, acc[8 * i + 5] * fs), pack2(acc[8 * i + 6] * fs, acc[8 * i + 7] * fs));
        fence_async();
        bar_sync(3 + h, 128);
        if (el) {
            const int row0 = 256 * f + 128 * ((p >> 1) & 1) + 64 * h + (job == 1 ? 512 : 0);
            if (job == 0) tma3_store(&mp.fc, sb + FOUT + h * 32768, 0, row0, 4 * (p & 1));
            else {
#pragma unroll 1
                for (int i = 0; i < 16; i++)
                    bulk_st((char*)g_wepi + (row0 / 8 + 2 * (i & 3) + (p & 1)) * 8192 + (i >> 2) * 2048, sb + FOUT + h * 32768 + i * 2048, 2048);
            }
            asm volatile("cp.async.bulk.commit_group;" ::: "memory");
        }
    }
    if (el) {
        asm volatile("cp.async.bulk.wait_group 0;" ::: "memory");
        fence_async_g();
        if (mode == 0) flag_add(&g_sync[3]);
    }
    bar_sync(2, 256);
    if (tid == 128) cta_done(mode);
}

__global__ void __launch_bounds__(384, 1) main_kernel(const __grid_constant__ Maps mp, const bf16* __restrict__ x, const bf16* __restrict__ dw, const bf16* wup, const int mode) {
    extern __shared__ __align__(1024) uint8_t smem[];
    const uint32_t sb = smem_u32(smem);
    const int tid = threadIdx.x;
    if (blockIdx.x >= NCTA) { fold_cta(mp, sb, mode); return; }
    const int b = blockIdx.x / TPB, ti = blockIdx.x % TPB;
    const int piece = blockIdx.x & 127;
    uint32_t xv[2][4][8];
    if (tid >= 128) {
#pragma unroll
        for (int i = 0; i < 8; i++) {
            const int t = 62 * ti - 1 + 32 * (i >> 2) + ((tid - 128) >> 5) * 4 + (i & 3);
            const uint4* p = reinterpret_cast<const uint4*>(x + ((size_t)b * T_ + t) * D_) + (tid & 31);
#pragma unroll
            for (int c = 0; c < 2; c++)
                asm volatile("{\n.reg .pred p;\nsetp.lt.u32 p, %5, %6;\nmov.b32 %0, 0;\nmov.b32 %1, 0;\nmov.b32 %2, 0;\nmov.b32 %3, 0;\n"
                             "@p ld.global.nc.L1::no_allocate.v4.u32 {%0, %1, %2, %3}, [%4];\n}\n"
                             : "=r"(xv[i >> 2][i & 3][4 * c]), "=r"(xv[i >> 2][i & 3][4 * c + 1]), "=r"(xv[i >> 2][i & 3][4 * c + 2]), "=r"(xv[i >> 2][i & 3][4 * c + 3])
                             : "l"(p + 32 * c), "r"(t), "n"(T_));
        }
    }
    if (tid == 0) {
        mbar_init(sb + B_MK, 1);
        for (int i = 0; i < 5; i++) mbar_init(sb + B_R1 + 8 * i, 2);
        asm volatile("fence.mbarrier_init.release.cluster;" ::: "memory");
        fence_async();
        mbar_expect_tx(sb + B_MK, 65536 + 32768 + 3072);
        tma3(sb + R0, &mp.wq, 0, 64 * (piece >> 4), 0, sb + B_MK);
        tma3(sb + R1 + 32768, &mp.wk, 0, 32 * (piece & 15), 0, sb + B_MK);
        bulk_ld(sb + DWS, dw, 3072, sb + B_MK);
        for (int i = 0; i < 8; i++) mbar_arrive(sb + B_R1 + 8 * (i >> 1));
        if (mode != 1) {
            ring_full(sb, 32, &mp.wup8, 0, 8);
            ring_full(sb, 0, &mp.wup8, 16, 8);
            ring_full(sb, 8, &mp.wup8, 32, 8);
        }
    } else if (tid == 32) {
        mbar_init(sb + B_LN, 1); mbar_init(sb + B_MQ, 1); mbar_init(sb + B_XA, 1);
        mbar_init(sb + B_H1, 2); mbar_init(sb + B_H2, 1); mbar_init(sb + B_H3, 2);
        for (int i = 0; i < 3; i++) { mbar_init(sb + B_KV + 8 * i, 1); mbar_init(sb + B_P + 8 * i, 4); mbar_init(sb + B_GO + 8 * i, 4); }
        for (int i = 0; i < 20; i++) { mbar_init(sb + B_R2 + 8 * i, 1); mbar_init(sb + B_E2 + 8 * i, 4); }
        mbar_init(sb + B_UC, 1); mbar_init(sb + B_UC + 8, 1); mbar_init(sb + B_X, 8);
        for (int i = 0; i < 5; i++) asm volatile("st.shared.u32 [%0], 0;" ::"r"(sb + CNT + 4 * i) : "memory");
        asm volatile("fence.mbarrier_init.release.cluster;" ::: "memory");
        fence_async();
    }
    __syncthreads();
    const int wg = __shfl_sync(0xffffffffu, tid >> 7, 0);
    const int lane = tid & 31, w = (tid >> 5) & 3;
    const bool w0 = __shfl_sync(0xffffffffu, w, 0) == 0;
    const uint32_t sd = (sb & 0x3FFFF) >> 4;
    const uint32_t adA = sd + (AT >> 4) + (1u << 16);
    const uint32_t bd0 = sd + (R1 >> 4);
    const uint32_t bd2k = bd0 + ((2048u >> 4) << 16);
    const bool el = (tid & 127) == 0;
    const uint32_t lrow = 16 * w + (lane & 7) + ((lane >> 3) & 1) * 8;
    const uint32_t loff = lrow * 128 + ((((lane >> 4) ^ lrow) & 7) << 4);
    const int r0 = 16 * w + (lane >> 2);

    if (wg == 0) {
        asm volatile("setmaxnreg.inc.sync.aligned.u32 184;");
        uint32_t q[112];
        PT(0);
        PG(200);
        {
            float mq[16];
            fresh(mq);
            mbar_wait(sb + B_MK, 0);
            PT(1);
            if (PFW && tid == 32) l2_prefetch((const char*)wup + piece * 8192, 8192);
            wg_fence();
#pragma unroll 1
            for (int c = 0; c < 8; c++)
#pragma unroll
                for (int kk = 0; kk < 4; kk++)
                    wgmma_ss_n32_tb0(mq, dsc(sd, R0 + c * 8192 + kk * 32, 16), dsc(sd, R1 + 32768 + c * 4096 + kk * 32, 16), 1);
            wg_commit();
            wg_wait<0>();
            if (mode != 1 && w0 && elect1()) { ring_full(sb, 16, &mp.wup8, 48, 8); ring_full(sb, 24, &mp.wup8, 64, 8); }
            pin(mq);
            uint32_t* c = reinterpret_cast<uint32_t*>(g_mqk + (64 * (piece >> 4) + r0) * D_ + 32 * (piece & 15) + 2 * (lane & 3));
#pragma unroll
            for (int n = 0; n < 4; n++) { c[4 * n] = pack2(mq[4 * n], mq[4 * n + 1]); c[4 * n + 4 * D_] = pack2(mq[4 * n + 2], mq[4 * n + 3]); }
            fence_async_g();
            bar_sync(1, 128);
            if (el) {
                if (mode == 0) flag_add(&g_sync[2]);
                if (mode == 0) flag_wait(&g_sync[2], NCTA);
                mbar_arrive(sb + B_MQ);
                PT(12);
                mbar_wait(sb + B_LN, 0);
#pragma unroll 1
                for (int c = 0; c < 8; c++) {
                    tma4_store(&mp.xas, sb + AT + c * 8192, 0, 62 * ti, c, b);
                    const unsigned t0 = (unsigned)clock();
                    while (c < 7 && (unsigned)clock() - t0 < XS_GAP) __nanosleep(20);
                }
                asm volatile("cp.async.bulk.commit_group;" ::: "memory");
                if (mode == 1) asm volatile("cp.async.bulk.wait_group 0;" ::: "memory");
            }
            PT(13);
            if (mode == 1) return;
        }
        mbar_wait(sb + B_H1, 0);
        PT(2);
        uint32_t slot8 = 8, par = 1, prev8 = 0;
        auto adv = [&]() { prev8 = slot8; slot8 += 8; if (slot8 == 40) { slot8 = 0; par ^= 1; } };
        {
            float acc[128];
            fresh(acc);
            auto step = [&](int i) {
                const uint32_t aa = adA + (i >> 1) * 512 + (i & 1) * 4, bb = bd0 + ((4096u >> 4) << 16) + slot8 * 128;
                wg_fence();
                wgmma_ss_n256_tb1(acc, mkd(aa), mkd(bb), 1);
                wgmma_ss_n256_tb1(acc, mkd(aa + 2), mkd(bb + 128), 1);
                wg_commit();
                wg_wait<1>();
            };
#pragma unroll 1
            for (int i = 0; i < 12; i++) {
                mbar_wait(sb + B_R1 + slot8, par);
                step(i);
                if (i > 0 && w0 && elect1()) ring_full(sb, prev8, &mp.mqa4, 32 * i + 128, 4);
                adv();
            }
#pragma unroll 1
            for (int i = 12; i < 16; i++) {
                mbar_wait(sb + B_R1 + slot8, par);
                if (i == 15 && el) mbar_arrive(sb + B_H2);
                step(i);
                if (w0 && elect1()) ring_full(sb, prev8, &mp.wup8, 16 * i - 192, 0);
                adv();
            }
            wg_wait<0>();
            if (w0 && elect1()) ring_full(sb, prev8, &mp.wup8, 64, 0);
            pin(acc);
            PT(3);
#pragma unroll
            for (int kk = 0; kk < 4; kk++)
                stsm4((sb + QS + loff) ^ (kk << 5), pack2(acc[96 + 8 * kk], acc[97 + 8 * kk]), pack2(acc[98 + 8 * kk], acc[99 + 8 * kk]),
                      pack2(acc[100 + 8 * kk], acc[101 + 8 * kk]), pack2(acc[102 + 8 * kk], acc[103 + 8 * kk]));
            fence_async();
#pragma unroll
            for (int i = 47; i >= 0; i--) q[64 + i] = pack2v(acc[2 * i], acc[2 * i + 1]);
        }
        if (el) {
            asm volatile("cp.async.bulk.wait_group 0;" ::: "memory");
            if (mode == 0) {
                fence_async_g();
                flag_add(&g_sync[b]);
                flag_wait(&g_sync[b], TPB);
            }
            mbar_arrive(sb + B_XA);
        }
        __syncwarp();
        mbar_wait(sb + B_H3, 0);
        PT(4);
        slot8 = 32; par = 0;
#pragma unroll
        for (int half = 0; half < 2; half++) {
            float acc[64];
            fresh(acc);
            auto step = [&](int m) {
                const uint32_t aa = adA + m * 512, bb = bd0 + ((8192u >> 4) << 16) + slot8 * 128;
                mbar_wait(sb + B_R1 + slot8, par);
                wg_fence();
#pragma unroll
                for (int kk = 0; kk < 4; kk++) wgmma_ss_n128_tb1(acc, mkd(aa + 2 * kk), mkd(bb + 128 * kk), 1);
                wg_commit();
                wg_wait<1>();
            };
            if (half == 0) {
#pragma unroll 1
                for (int m = 0; m < 8; m++) {
                    step(m);
                    if (m > 0 && w0 && elect1()) ring_full(sb, prev8, &mp.mqb2, (64 * m + 256) & 511, (m + 4) >> 3 << 1);
                    adv();
                }
            } else {
#pragma unroll 1
                for (int m = 0; m < 4; m++) {
                    step(m);
                    if (m > 0 && w0 && elect1()) ring_full(sb, prev8, &mp.mqb2, 64 * m + 256, 2);
                    adv();
                }
#pragma unroll 1
                for (int m = 4; m < 8; m++) {
                    step(m);
                    if (w0 && elect1()) {
                        if (m == 4) mbar_expect_tx(sb + B_KV + 8, 65536);
                        tma4(sb + R1 + prev8 * 2048, &mp.xa2, 0, 0, 2 * m - 8, b, sb + B_KV + 8);
                    }
                    adv();
                }
            }
            wg_wait<0>();
            if (w0 && elect1()) {
                if (half == 0) ring_full(sb, prev8, &mp.mqb2, 256, 2);
                else {
                    mbar_expect_tx(sb + B_KV + 16, 65536);
                    tma4(sb + R2, &mp.xa, 0, 64, 0, b, sb + B_KV + 16);
                }
            }
            pin(acc);
#pragma unroll
            for (int i = 31; i >= 0; i--) q[32 * half + i] = pack2v(acc[2 * i], acc[2 * i + 1]);
        }
        bar_sync(1, 128);
        PT(5);

        const float CS = 0.04419417382415922f * 1.4426950408889634f;
        float m0 = -INFINITY, m1 = -INFINITY, l0 = 0.f, l1 = 0.f;
        int s = 0, sn = 1, ph = 0;
        float S[32];
        const bool l0w = lane == 0, q0 = (lane & 3) == 0;
#pragma unroll 1
        for (int j = -1;; j++) {
            if (j >= 0) {
                PL(j, 1);
                if (j == NKV - 1) {
#pragma unroll
                    for (int i = (T_ - 64 * (NKV - 1)) / 2; i < 32; i++) asm volatile("mov.b32 %0, 0xff800000;" : "=f"(S[i]));
                }
                float y[8], z[8];
#pragma unroll
                for (int n = 0; n < 8; n++) { y[n] = fmaxf(S[4 * n], S[4 * n + 1]); z[n] = fmaxf(S[4 * n + 2], S[4 * n + 3]); }
#pragma unroll
                for (int n = 0; n < 4; n++) { y[n] = fmaxf(y[n], y[n + 4]); z[n] = fmaxf(z[n], z[n + 4]); }
                float x0 = fmaxf(fmaxf(y[0], y[1]), fmaxf(fmaxf(y[2], y[3]), m0)), x1 = fmaxf(fmaxf(z[0], z[1]), fmaxf(fmaxf(z[2], z[3]), m1));
                x0 = fmaxf(x0, __shfl_xor_sync(0xffffffffu, x0, 1));
                x1 = fmaxf(x1, __shfl_xor_sync(0xffffffffu, x1, 1));
                x0 = fmaxf(x0, __shfl_xor_sync(0xffffffffu, x0, 2));
                x1 = fmaxf(x1, __shfl_xor_sync(0xffffffffu, x1, 2));
                if ((x0 - m0) * CS <= LAZY) x0 = m0;
                if ((x1 - m1) * CS <= LAZY) x1 = m1;
                const float sc0 = ex2((m0 - x0) * CS), sc1 = ex2((m1 - x1) * CS);
                m0 = x0; m1 = x1;
                const float n0 = -x0 * CS, n1 = -x1 * CS;
                if (q0) { sts_f32(sb + SCL + s * 256 + r0 * 4, sc0); sts_f32(sb + SCL + s * 256 + r0 * 4 + 32, sc1); }
                __syncwarp();
                if (l0w) mbar_arrive(sb + B_P + s * 8);
                if (j < NKV - 1) mbar_wait(sb + B_KV + sn * 8, ph);
                float a0 = 0.f, a1 = 0.f;
                const uint32_t pb = sb + R3 + (s == 0 ? 2 : s - 1) * 8192;
#pragma unroll
                for (int kk = 0; kk < 4; kk++) {
                    float p[8];
#pragma unroll
                    for (int e = 0; e < 8; e++) p[e] = ex2(fmaf(S[8 * kk + e], CS, (e & 2) ? n1 : n0));
                    a0 += (p[0] + p[1]) + (p[4] + p[5]);
                    a1 += (p[2] + p[3]) + (p[6] + p[7]);
                    stsm4((pb + loff) ^ (kk << 5), pack2(p[0], p[1]), pack2(p[2], p[3]), pack2(p[4], p[5]), pack2(p[6], p[7]));
                }
                l0 = fmaf(l0, sc0, a0); l1 = fmaf(l1, sc1, a1);
                PL(j, 2);
                if (j == NKV - 1) break;
            } else {
                mbar_wait(sb + B_KV + 8, 0);
            }
            float Sn[32];
            const uint32_t kd = sd + sn * 4096;
            wg_fence();
#pragma unroll
            for (int kk = 0; kk < 28; kk++) {
                wgmma_rs_n64_tb0(Sn, q[4 * kk], q[4 * kk + 1], q[4 * kk + 2], q[4 * kk + 3], dsc(kd, (kk >> 2) * 8192 + (kk & 3) * 32, 16), kk > 0);
                if (kk == FENCE_AT) { fence_async(); __syncwarp(); }
                if (kk == GO_AT) { PL(j, 3); if (j >= 0 && l0w) mbar_arrive(sb + B_GO + s * 8); }
            }
#pragma unroll
            for (int kk = 0; kk < 4; kk++)
                wgmma_ss_n64_tb0(Sn, dsc(sd, QS + kk * 32, 16), dsc(kd, 7 * 8192 + kk * 32, 16), 1);
            wg_commit();
            PL(j, 0);
            wg_wait<0>();
            pin(Sn);
#pragma unroll
            for (int i = 0; i < 32; i++) S[i] = Sn[i];
            s = sn;
            if (++sn == 3) sn = 0;
            if (sn == 1) ph ^= 1;
        }
        l0 += __shfl_xor_sync(0xffffffffu, l0, 1); l1 += __shfl_xor_sync(0xffffffffu, l1, 1);
        l0 += __shfl_xor_sync(0xffffffffu, l0, 2); l1 += __shfl_xor_sync(0xffffffffu, l1, 2);
        if (q0) { sts_f32(sb + LINV + r0 * 4, rcp(l0)); sts_f32(sb + LINV + r0 * 4 + 32, rcp(l1)); }
        fence_async();
        __syncwarp();
        if (l0w) {
            mbar_arrive(sb + B_GO + s * 8);
            uint32_t slot8 = 8 * w, par = 0;
#pragma unroll 1
            for (int n = 20 + w; n < 136; n += 4) {
                mbar_wait(sb + B_E2 + slot8, par);
                if (n < 128) ring_ld(sb, slot8, n);
                else {
                    mbar_expect_tx(sb + B_X, 8192);
                    tma4(sb + R1 + slot8 * 1024, &mp.x, 0, 62 * ti, n - 128, b, sb + B_X);
                }
                slot8 += 32;
                if (slot8 >= 160) { slot8 -= 160; par ^= 1; }
            }
        }
        PDUMP();
    } else {
        asm volatile("setmaxnreg.dec.sync.aligned.u32 160;");
        const int h = wg - 1;
        auto red4 = [&](float (&a)[4]) {
            const bool b4 = lane & 16, b3 = lane & 8;
            const float k0 = (b4 ? a[2] : a[0]) + __shfl_xor_sync(0xffffffffu, b4 ? a[0] : a[2], 16);
            const float k1 = (b4 ? a[3] : a[1]) + __shfl_xor_sync(0xffffffffu, b4 ? a[1] : a[3], 16);
            float k = (b3 ? k1 : k0) + __shfl_xor_sync(0xffffffffu, b3 ? k0 : k1, 8);
            k += __shfl_xor_sync(0xffffffffu, k, 4);
            k += __shfl_xor_sync(0xffffffffu, k, 2);
            k += __shfl_xor_sync(0xffffffffu, k, 1);
            return k;
        };
#pragma unroll 1
        for (int bt = 0; bt < 2; bt++) {
            PT(bt ? 13 : 0);
            uint32_t (&v)[4][8] = xv[0];
            float a[4], f[4][16];
            const uint32_t la = sb + AT + (lane >> 3) * 8192 + (32 * bt + 16 * h + 4 * w) * 128 + (((lane & 7) ^ ((w & 1) * 4)) << 4);
#pragma unroll
            for (int r = 0; r < 4; r++) {
                float s0 = blo(v[r][0]), s1 = bhi(v[r][0]);
#pragma unroll
                for (int i = 1; i < 8; i++) { s0 += blo(v[r][i]); s1 += bhi(v[r][i]); }
                a[r] = s0 + s1;
            }
            const float mu = red4(a) * (1.f / D_);
            const uint32_t mp2 = pack2(mu, mu);
#pragma unroll
            for (int r = 0; r < 4; r++) {
                const uint32_t m2 = __shfl_sync(0xffffffffu, mp2, 8 * r);
                float s0 = 0.f, s1 = 0.f;
#pragma unroll
                for (int i = 0; i < 8; i++) {
                    const uint32_t d = bsub2(v[r][i], m2);
                    f[r][2 * i] = blo(d); f[r][2 * i + 1] = bhi(d);
                    s0 = fmaf(f[r][2 * i], f[r][2 * i], s0); s1 = fmaf(f[r][2 * i + 1], f[r][2 * i + 1], s1);
                }
                a[r] = s0 + s1;
            }
            const float dm = mu - blo(mp2);
            float sd_ = bfr(bfr(fmaxf(fmaf(red4(a), 1.f / D_, -dm * dm), 0.f)) + 1e-5f);
            asm("sqrt.approx.f32 %0, %0;" : "+f"(sd_));
            const float ri = rcp(bfr(sd_));
#pragma unroll
            for (int r = 0; r < 4; r++) {
                const float rinv = __shfl_sync(0xffffffffu, ri, 8 * r);
#pragma unroll
                for (int i = 0; i < 8; i++) v[r][i] = pack2(f[r][2 * i] * rinv, f[r][2 * i + 1] * rinv);
                sts4((la ^ (r << 4)) + r * 128, v[r][0], v[r][1], v[r][2], v[r][3]);
                sts4((la ^ (r << 4)) + r * 128 + 32768, v[r][4], v[r][5], v[r][6], v[r][7]);
#pragma unroll
                for (int i = 0; i < 8; i++) v[r][i] = xv[1][r][i];
            }
        }
        fence_async();
        bar_sync(2, 256);
        if (tid == 128) mbar_arrive(sb + B_LN);
        if (mode == 1) return;
        float acc[128];
#pragma unroll
        for (int pass = 0; pass < 2; pass++) {
            if (pass == 1) mbar_wait(sb + B_H2, 0);
            PT(1 + 3 * pass);
            fresh(acc);
            uint32_t slot8 = pass ? 16 : 32, par = 0, prev8 = 0;
            auto adv = [&]() { prev8 = slot8; slot8 += 8; if (slot8 == 40) { slot8 = 0; par ^= 1; } };
            auto step = [&](int kk) {
                wg_fence();
                wgmma_ss_n256_tb1(acc, mkd(adA + (kk >> 2) * 512 + (kk & 3) * 2), mkd(bd2k + h * 512 + slot8 * 128), 1);
                wg_commit();
                wg_wait<1>();
            };
#pragma unroll 1
            for (int kk = 0; kk < 28; kk++) {
                mbar_wait(sb + B_R1 + slot8, par);
                step(kk);
                if (kk > 0 && w0 && elect1()) ring_half(sb, prev8, h * 8192, &mp.wup4, 16 * kk + 64, (pass ? 0 : 8) + 4 * h);
                adv();
            }
            if (pass == 0 && w0) mbar_wait(sb + B_MQ, 0);
#pragma unroll 1
            for (int kk = 28; kk < 32; kk++) {
                mbar_wait(sb + B_R1 + slot8, par);
                if (kk == 31 && el) mbar_arrive(sb + (pass ? B_H3 : B_H1));
                step(kk);
                if (w0 && elect1()) ring_half(sb, prev8, h * 8192, pass ? &mp.mqb1 : &mp.mqa2, (pass ? 64 : 32) * (kk - 28), pass ? h : 4 + 2 * h);
                adv();
            }
            wg_wait<0>();
            if (w0 && elect1()) ring_half(sb, prev8, h * 8192, pass ? &mp.mqb1 : &mp.mqa2, pass ? 256 : 128, pass ? h : 4 + 2 * h);
            pin(acc);
            PT(2 + 3 * pass);
            if (pass == 0) {
                float s0 = 0.f, s1 = 0.f, v0 = 0.f, v1 = 0.f;
#pragma unroll
                for (int n = 0; n < 32; n++) {
#pragma unroll
                    for (int e = 0; e < 4; e++) acc[4 * n + e] = gelu2(acc[4 * n + e]);
                    s0 += acc[4 * n] + acc[4 * n + 1]; s1 += acc[4 * n + 2] + acc[4 * n + 3];
                    v0 = fmaf(acc[4 * n], acc[4 * n], v0); v0 = fmaf(acc[4 * n + 1], acc[4 * n + 1], v0);
                    v1 = fmaf(acc[4 * n + 2], acc[4 * n + 2], v1); v1 = fmaf(acc[4 * n + 3], acc[4 * n + 3], v1);
                }
#pragma unroll
                for (int o = 1; o < 4; o <<= 1) {
                    s0 += __shfl_xor_sync(0xffffffffu, s0, o); s1 += __shfl_xor_sync(0xffffffffu, s1, o);
                    v0 += __shfl_xor_sync(0xffffffffu, v0, o); v1 += __shfl_xor_sync(0xffffffffu, v1, o);
                }
                if ((lane & 3) == 0) {
                    uint32_t a = sb + STAT + h * 512 + r0 * 8;
                    sts_f32(a, s0); sts_f32(a + 4, v0); sts_f32(a + 64, s1); sts_f32(a + 68, v1);
                }
                bar_sync(2, 256);
                {
                    uint32_t a = sb + STAT + (h ^ 1) * 512 + r0 * 8;
                    s0 = (s0 + lds_f32(a)) * (1.f / 512.f); v0 = (v0 + lds_f32(a + 4)) * (1.f / 512.f);
                    s1 = (s1 + lds_f32(a + 64)) * (1.f / 512.f); v1 = (v1 + lds_f32(a + 68)) * (1.f / 512.f);
                }
                v0 = rsqrtf(fmaxf(fmaf(-s0, s0, v0), 0.f) + 4e-5f); v1 = rsqrtf(fmaxf(fmaf(-s1, s1, v1), 0.f) + 4e-5f);
                s0 = -s0 * v0; s1 = -s1 * v1;
#pragma unroll
                for (int p = 0; p < 16; p++)
                    stsm4(((sb + R0 + h * 32768 + loff) ^ ((p & 3) << 5)) + (p >> 2) * 8192,
                          pack2(fmaf(acc[8 * p], v0, s0), fmaf(acc[8 * p + 1], v0, s0)), pack2(fmaf(acc[8 * p + 2], v1, s1), fmaf(acc[8 * p + 3], v1, s1)),
                          pack2(fmaf(acc[8 * p + 4], v0, s0), fmaf(acc[8 * p + 5], v0, s0)), pack2(fmaf(acc[8 * p + 6], v1, s1), fmaf(acc[8 * p + 7], v1, s1)));
            } else {
                uint32_t u[64];
#pragma unroll
                for (int i = 63; i >= 0; i--) u[i] = pack2v(gelu2(acc[2 * i]), gelu2(acc[2 * i + 1]));
                PT(12);
                bar_sync(3 + h, 128);
                const uint32_t rm = lrow == 0 ? 0 : lrow - 1, rp = lrow == 63 ? 63 : lrow + 1;
                const uint32_t gb = sb + R0 + h * 32768;
                const uint32_t am = gb + rm * 128 + ((((lane >> 4) ^ rm) & 7) << 4), ap = gb + rp * 128 + ((((lane >> 4) ^ rp) & 7) << 4), ac = gb + loff;
                const uint32_t dwa = sb + DWS + 512 * h + ((lane >> 3) & 1) * 16 + (lane >> 4) * 1024;
                bf16* ucp = g_uc + ((size_t)blockIdx.x * 64 + r0) * D_ + 256 * h + 8 * (lane & 3);
#pragma unroll
                for (int m = 0; m < 8; m++) {
                    uint32_t o[8], g0[2][4], g1[2][4], g2[2][4], d[2][4], d2[2][2];
#pragma unroll
                    for (int pp = 0; pp < 2; pp++) {
                        const int p = 2 * m + pp;
                        const uint32_t co = (p >> 2) * 8192, cx = (p & 3) << 5;
                        ldsm4(dwa + 32 * p, d[pp]);
                        ldsm2(dwa + 32 * p + 2048, d2[pp]);
                        ldsm4((am ^ cx) + co, g0[pp]);
                        ldsm4((ac ^ cx) + co, g1[pp]);
                        ldsm4((ap ^ cx) + co, g2[pp]);
                    }
#pragma unroll
                    for (int pp = 0; pp < 2; pp++)
#pragma unroll
                        for (int e = 0; e < 4; e++)
                            o[4 * (e & 1) + 2 * pp + (e >> 1)] =
                                bmul2(u[8 * m + 4 * pp + e], bfma2(g2[pp][e], d2[pp][e >> 1], bfma2(g1[pp][e], d[pp][2 + (e >> 1)], bmul2(g0[pp][e], d[pp][e >> 1]))));
                    stg4(ucp + 32 * m, o[0], o[1], o[2], o[3]);
                    stg4(ucp + 32 * m + 8 * D_, o[4], o[5], o[6], o[7]);
                }
                bar_sync(2, 256);
                if (tid == 128) {
                    mbar_wait(sb + B_XA, 0);
                    mbar_expect_tx(sb + B_KV, 65536);
                    tma4(sb + R0, &mp.xa, 0, 128, 0, b, sb + B_KV);
                }
            }
            PT(3 + 3 * pass);
        }
        int s = 1, ph = 0;
        fresh(acc);
#pragma unroll 1
        for (int j = 0; j < NKV; j++) {
            mbar_wait(sb + B_P + s * 8, ph);
            PL(j, 0);
            if (j > 0) {
                const float sc0 = lds_f32(sb + SCL + s * 256 + r0 * 4), sc1 = lds_f32(sb + SCL + s * 256 + r0 * 4 + 32);
                if (__any_sync(0xffffffffu, sc0 != 1.f || sc1 != 1.f)) {
#pragma unroll
                    for (int n = 0; n < 32; n++) { acc[4 * n] *= sc0; acc[4 * n + 1] *= sc0; acc[4 * n + 2] *= sc1; acc[4 * n + 3] *= sc1; }
                }
            }
            mbar_wait(sb + B_GO + s * 8, ph);
            PL(j, 1);
            const uint32_t vd = sd + s * 4096 + h * 2048, pd = sd + (s == 0 ? 2 : s - 1) * 512;
            pin(acc);
            wg_fence();
#pragma unroll
            for (int kk = 0; kk < 4; kk++) wgmma_ss_n256_tb1(acc, dsc(pd, R3 + kk * 32, 16), dsc(vd, kk * 2048, 8192), 1);
            wg_commit();
            wg_wait<0>();
            pin(acc);
            PL(j, 2);
            if (w0 && elect1()) {
                if (j == NKV - 5 && mode == 0) flag_wait(&g_sync[3], 4);
                if (atom_inc_s(sb + CNT + 4 * s) & 1) {
                    if (j + 3 < NKV) {
                        mbar_expect_tx(sb + B_KV + s * 8, 65536);
                        tma4(sb + s * 65536, &mp.xa, 0, 64 * (j + 3), 0, b, sb + B_KV + s * 8);
                    } else if (j < NKV - 1) {
                        const int n0 = j == NKV - 3 ? 0 : 8, n1 = n0 + 8;
#pragma unroll 1
                        for (int n = n0; n < n1; n++) ring_ld(sb, n * 8, n);
                    }
                }
            }
            if (++s == 3) s = 0;
            if (s == 1) ph ^= 1;
        }
        {
            const float i0 = lds_f32(sb + LINV + r0 * 4), i1 = lds_f32(sb + LINV + r0 * 4 + 32);
#pragma unroll
            for (int p = 0; p < 16; p++)
                stsm4(((sb + R0 + h * 32768 + loff) ^ ((p & 3) << 5)) + (p >> 2) * 8192,
                      pack2(acc[8 * p] * i0, acc[8 * p + 1] * i0), pack2(acc[8 * p + 2] * i1, acc[8 * p + 3] * i1),
                      pack2(acc[8 * p + 4] * i0, acc[8 * p + 5] * i0), pack2(acc[8 * p + 6] * i1, acc[8 * p + 7] * i1));
        }
        fence_async();
        fence_async_g();
        bar_sync(2, 256);
        if (lane == 0 && w < 2) ring_ld(sb, 128 + 16 * w + 8 * h, 16 + 2 * w + h);
        PT(7);
        fresh(acc);
        {
            uint32_t slot8 = 8 * h, par = 0, prev8 = 0;
#pragma unroll 1
            for (int kk = 0; kk < 64; kk++) {
                if (kk == 32 || kk == 48) mbar_wait(sb + B_UC + (kk >> 1 & 8), 0);
                mbar_wait(sb + B_R2 + slot8, par);
                wg_fence();
                wgmma_ss_n256_tb1(acc, mkd(sd + (1u << 16) + (R0 >> 4) + (kk >> 2 & 7) * 512 + (kk & 3) * 2), mkd(bd2k + slot8 * 64), 1);
                wg_commit();
                wg_wait<1>();
                if (kk > 0 && lane == 0) mbar_arrive(sb + B_E2 + prev8);
                if ((kk == 16 || kk == 32) && w0 && elect1() && (atom_inc_s(sb + CNT + 12 + (kk >> 3 & 4)) & 1)) {
                    mbar_expect_tx(sb + B_UC + (kk >> 2 & 8), 32768);
                    tma3(sb + R0 + (kk & 32) * 1024, &mp.uc, 0, 64 * blockIdx.x, kk >> 3 & 4, sb + B_UC + (kk >> 2 & 8));
                }
                prev8 = slot8;
                slot8 += 16;
                if (slot8 >= 160) { slot8 -= 160; par ^= 1; }
            }
        }
        wg_wait<0>();
        pin(acc);
        PT(8);
        mbar_wait(sb + B_X, 0);
        PT(9);
        {
            const uint32_t sr = (lrow + 63) & 63;
            const uint32_t xoff = sr * 128 + ((((lane >> 4) ^ sr) & 7) << 4);
#pragma unroll
            for (int p = 0; p < 16; p++) {
                const uint32_t a = ((sb + R2 + h * 32768 + xoff) ^ ((p & 3) << 5)) + (p >> 2) * 8192;
                uint32_t xv[4];
                ldsm4(a, xv);
#pragma unroll
                for (int e = 0; e < 4; e++)
                    xv[e] = pack2(acc[8 * p + 2 * e] + __uint_as_float(xv[e] << 16), acc[8 * p + 2 * e + 1] + __uint_as_float(xv[e] & 0xffff0000u));
                stsm4(a, xv[0], xv[1], xv[2], xv[3]);
            }
        }
        fence_async();
        bar_sync(3 + h, 128);
        if (el) {
            for (int c = 0; c < 4; c++) tma4_store(&mp.out, sb + R2 + (4 * h + c) * 8192, 0, 62 * ti, 4 * h + c, b);
            asm volatile("cp.async.bulk.commit_group;" ::: "memory");
            PT(10);
            if (h == 0) cta_done(mode);
            asm volatile("cp.async.bulk.wait_group.read 0;" ::: "memory");
        }
        PT(11);
        PG(201);
        PDUMP();
    }
}

typedef CUresult (*PFN_enc)(CUtensorMap*, CUtensorMapDataType, cuuint32_t, void*, const cuuint64_t*, const cuuint64_t*,
                            const cuuint32_t*, const cuuint32_t*, CUtensorMapInterleave, CUtensorMapSwizzle,
                            CUtensorMapL2promotion, CUtensorMapFloatOOBfill);

static void enc(PFN_enc f, CUtensorMap* m, void* base, int rank, const cuuint64_t* dims, const cuuint64_t* strides, const cuuint32_t* box) {
    cuuint32_t es[5] = {1, 1, 1, 1, 1};
    f(m, CU_TENSOR_MAP_DATA_TYPE_BFLOAT16, rank, base, dims, strides, box, es, CU_TENSOR_MAP_INTERLEAVE_NONE,
      CU_TENSOR_MAP_SWIZZLE_128B, CU_TENSOR_MAP_L2_PROMOTION_L2_256B, CU_TENSOR_MAP_FLOAT_OOB_FILL_NONE);
}
static void enc_act(PFN_enc f, CUtensorMap* m, void* base, int rows, int chunks, int trows = T_, int pitch = T_) {
    cuuint64_t dims[4] = {64, (cuuint64_t)trows, 8, (cuuint64_t)NB_};
    cuuint64_t st[3] = {1024, 128, (cuuint64_t)pitch * 1024};
    cuuint32_t box[4] = {64, (cuuint32_t)rows, (cuuint32_t)chunks, 1};
    enc(f, m, base, 4, dims, st, box);
}
static void enc_w(PFN_enc f, CUtensorMap* m, void* base, int krows, int ncols, int bk, int bc) {
    cuuint64_t dims[3] = {64, (cuuint64_t)krows, (cuuint64_t)(ncols / 64)};
    cuuint64_t st[2] = {(cuuint64_t)ncols * 2, 128};
    cuuint32_t box[3] = {64, (cuuint32_t)bk, (cuuint32_t)bc};
    enc(f, m, base, 3, dims, st, box);
}

extern "C" void kernel_launch(void* const* d_in, const int* in_sizes, int n_in, void* d_out, int out_size) {
    const bf16* x = (const bf16*)d_in[0];
    static PFN_enc fenc = nullptr;
    static void *p_xa, *p_mqk, *p_uc, *p_t1;
    static int fused = 0;
    if (!fenc) {
        void* fn = nullptr;
        cudaDriverEntryPointQueryResult qr;
        cudaGetDriverEntryPoint("cuTensorMapEncodeTiled", &fn, cudaEnableDefault, &qr);
        fenc = (PFN_enc)fn;
        cudaGetSymbolAddress(&p_xa, g_xa);
        cudaGetSymbolAddress(&p_mqk, g_mqk);
        cudaGetSymbolAddress(&p_uc, g_uc);
        cudaGetSymbolAddress(&p_t1, g_t1);
        cudaFuncSetAttribute(main_kernel, cudaFuncAttributeMaxDynamicSharedMemorySize, SMEM_BYTES);
        int dev = 0, sms = 0, occ = 0;
        cudaGetDevice(&dev);
        cudaDeviceGetAttribute(&sms, cudaDevAttrMultiProcessorCount, dev);
        cudaOccupancyMaxActiveBlocksPerMultiprocessor(&occ, main_kernel, 384, SMEM_BYTES);
        fused = sms * occ >= NCTA + 2;
    }
    Maps mp;
    enc_act(fenc, &mp.xa, (char*)p_xa + 1024, 64, 8, T_, T_ + 8);
    enc_act(fenc, &mp.xa2, (char*)p_xa + 1024, 64, 2, T_, T_ + 8);
    enc_act(fenc, &mp.xas, p_xa, 64, 1, T_ + 1, T_ + 8);
    enc_act(fenc, &mp.x, (void*)x, 64, 1);
    enc_act(fenc, &mp.out, d_out, 62, 1);
    enc_w(fenc, &mp.wup4, d_in[5], 512, 1024, 16, 4);
    enc_w(fenc, &mp.wup8, d_in[5], 512, 1024, 16, 8);
    enc_w(fenc, &mp.mqa2, p_mqk, 512, 512, 32, 2);
    enc_w(fenc, &mp.mqa4, p_mqk, 512, 512, 32, 4);
    enc_w(fenc, &mp.mqb1, p_mqk, 512, 512, 64, 1);
    enc_w(fenc, &mp.mqb2, p_mqk, 512, 512, 64, 2);
    enc_w(fenc, &mp.uc, p_uc, NCTA * 64, 512, 64, 4);
    enc_w(fenc, &mp.wq, d_in[1], 512, 512, 64, 8);
    enc_w(fenc, &mp.wk, d_in[2], 512, 512, 32, 8);
    enc_w(fenc, &mp.fa[0], d_in[3], 512, 512, 128, 1);
    enc_w(fenc, &mp.fa[1], d_in[7], 512, 512, 128, 1);
    enc_w(fenc, &mp.fa[2], p_t1, 512, 512, 128, 1);
    enc_w(fenc, &mp.fb[0], d_in[4], 512, 512, 64, 4);
    enc_w(fenc, &mp.fb[1], d_in[8], 1024, 512, 64, 4);
    enc_w(fenc, &mp.fc, p_t1, 512, 512, 64, 4);
    cudaStream_t st = cudaStreamPerThread;
    if (fused) {
        main_kernel<<<NCTA + 2, 384, SMEM_BYTES, st>>>(mp, x, (const bf16*)d_in[6], (const bf16*)d_in[5], 0);
    } else {
        main_kernel<<<NCTA + 2, 384, SMEM_BYTES, st>>>(mp, x, (const bf16*)d_in[6], (const bf16*)d_in[5], 1);
        main_kernel<<<NCTA + 2, 384, SMEM_BYTES, st>>>(mp, x, (const bf16*)d_in[6], (const bf16*)d_in[5], 2);
    }
}
```

```cpp
#include <cuda_runtime.h>
#include <cuda_bf16.h>
#include <cuda.h>
#include <stdint.h>

typedef __nv_bfloat16 bf16;

constexpr int T_ = 4000, D_ = 512, NB_ = 2;
constexpr int TPB = 65;
constexpr int NCTA = TPB * NB_;
constexpr int NKV = 63;

__device__ __align__(1024) bf16 g_xa[NB_ * (T_ + 8) * D_];
__device__ __align__(1024) bf16 g_mqk[D_ * D_];
__device__ __align__(1024) bf16 g_t1[D_ * D_];
__device__ __align__(1024) bf16 g_wepi[2 * D_ * D_];
__device__ __align__(1024) bf16 g_uc[NCTA * 64 * D_];
__device__ unsigned g_sync[8];

#define PT(i) do { if (el) asm volatile("st.shared.u32 [%0], %1;" ::"r"(sb + MISC + 2560), "r"((unsigned)clock())); } while (0)
#define PG(i)
#define PE()
#define PLM 15
#define PL(j, q) do { if ((PLM >> ((q) + (wg ? 4 : 0))) & 1) PT(0); } while (0)
#define PDUMP()

#define FENCE_AT 1
#define GO_AT 25
#define LAZY 8.f
#define XS_GAP 800
#define PFW 1
constexpr uint32_t R0 = 0, R1 = 65536, R2 = 131072, R3 = 196608, QS = 221184, MISC = 229376;
constexpr uint32_t AT = 147456, DWS = R3 + 16384;
constexpr uint32_t SMEM_BYTES = 232448;
constexpr uint32_t B_R1 = MISC + 8  , B_MK = MISC + 48, B_LN = MISC + 56, B_MQ = MISC + 64, B_XA = MISC + 72,
                   B_H1 = MISC + 88, B_H2 = MISC + 96, B_H3 = MISC + 104,
                   B_KV = MISC + 112, B_P = MISC + 136, B_GO = MISC + 160, B_UC = MISC + 184  ,
                   B_X = MISC + 200, CNT = MISC + 208  , SCL = MISC + 512  ,
                   LINV = MISC + 1280  , STAT = MISC + 512  ,
                   B_R2 = MISC + 1536  , B_E2 = MISC + 1696  ;

__device__ __forceinline__ uint32_t smem_u32(const void* p) { return (uint32_t)__cvta_generic_to_shared(p); }
__device__ __forceinline__ void wg_fence() { asm volatile("wgmma.fence.sync.aligned;" ::: "memory"); }
__device__ __forceinline__ void wg_commit() { asm volatile("wgmma.commit_group.sync.aligned;" ::: "memory"); }
template <int N> __device__ __forceinline__ void wg_wait() { asm volatile("wgmma.wait_group.sync.aligned %0;" ::"n"(N) : "memory"); }
__device__ __forceinline__ uint64_t dsc(uint32_t sd, uint32_t off, uint32_t lbo) {
    uint32_t lo = sd + (off >> 4) + ((lbo >> 4) << 16);
    uint64_t d;
    asm("mov.b64 %0, {%1, %2};" : "=l"(d) : "r"(lo), "r"((1024u >> 4) | (1u << 30)));
    return d;
}
__device__ __forceinline__ bool elect1() {
    uint32_t p;
    asm volatile("{\n.reg .pred p;\nelect.sync _|p, 0xffffffff;\nselp.u32 %0, 1, 0, p;\n}\n" : "=r"(p));
    return p != 0;
}
__device__ __forceinline__ void mbar_init(uint32_t bar, int cnt) { asm volatile("mbarrier.init.shared::cta.b64 [%0], %1;" ::"r"(bar), "r"(cnt) : "memory"); }
__device__ __forceinline__ void mbar_expect_tx(uint32_t bar, uint32_t bytes) { asm volatile("mbarrier.arrive.expect_tx.shared::cta.b64 _, [%0], %1;" ::"r"(bar), "r"(bytes) : "memory"); }
__device__ __forceinline__ void mbar_arrive(uint32_t bar) { asm volatile("mbarrier.arrive.shared::cta.b64 _, [%0];" ::"r"(bar) : "memory"); }
__device__ __forceinline__ void mbar_wait(uint32_t bar, uint32_t parity) {
    uint32_t ok;
#pragma unroll 1
    for (uint32_t it = 0;; ++it) {
        asm volatile("{\n.reg .pred p;\nmbarrier.try_wait.parity.shared::cta.b64 p, [%1], %2;\nselp.u32 %0, 1, 0, p;\n}\n" : "=r"(ok) : "r"(bar), "r"(parity) : "memory");
        if (ok) break;
        if (it > (1u << 20)) __trap();
    }
}
__device__ __forceinline__ void fence_async() { asm volatile("fence.proxy.async.shared::cta;" ::: "memory"); }
__device__ __forceinline__ void fence_async_g() { asm volatile("fence.proxy.async.global;" ::: "memory"); }
__device__ __forceinline__ void bar_sync(int id, int n) { asm volatile("bar.sync %0, %1;" ::"r"(id), "r"(n) : "memory"); }
__device__ __forceinline__ void tma3(uint32_t dst, const CUtensorMap* tm, int c0, int c1, int c2, uint32_t bar) {
    asm volatile("cp.async.bulk.tensor.3d.shared::cluster.global.mbarrier::complete_tx::bytes [%0], [%1, {%3, %4, %5}], [%2];"
                 ::"r"(dst), "l"(tm), "r"(bar), "r"(c0), "r"(c1), "r"(c2) : "memory");
}
__device__ __forceinline__ void tma4(uint32_t dst, const CUtensorMap* tm, int c0, int c1, int c2, int c3, uint32_t bar) {
    asm volatile("cp.async.bulk.tensor.4d.shared::cluster.global.mbarrier::complete_tx::bytes [%0], [%1, {%3, %4, %5, %6}], [%2];"
                 ::"r"(dst), "l"(tm), "r"(bar), "r"(c0), "r"(c1), "r"(c2), "r"(c3) : "memory");
}
__device__ __forceinline__ void tma4_store(const CUtensorMap* tm, uint32_t src, int c0, int c1, int c2, int c3) {
    asm volatile("cp.async.bulk.tensor.4d.global.shared::cta.bulk_group [%0, {%2, %3, %4, %5}], [%1];"
                 ::"l"(tm), "r"(src), "r"(c0), "r"(c1), "r"(c2), "r"(c3) : "memory");
}
__device__ __forceinline__ void tma3_store(const CUtensorMap* tm, uint32_t src, int c0, int c1, int c2) {
    asm volatile("cp.async.bulk.tensor.3d.global.shared::cta.bulk_group [%0, {%2, %3, %4}], [%1];"
                 ::"l"(tm), "r"(src), "r"(c0), "r"(c1), "r"(c2) : "memory");
}
__device__ __forceinline__ void stsm4(uint32_t addr, uint32_t a, uint32_t b, uint32_t c, uint32_t d) {
    asm volatile("stmatrix.sync.aligned.m8n8.x4.shared.b16 [%0], {%1, %2, %3, %4};" ::"r"(addr), "r"(a), "r"(b), "r"(c), "r"(d) : "memory");
}
__device__ __forceinline__ void ldsm4(uint32_t addr, uint32_t (&r)[4]) {
    asm volatile("ldmatrix.sync.aligned.m8n8.x4.shared.b16 {%0, %1, %2, %3}, [%4];" : "=r"(r[0]), "=r"(r[1]), "=r"(r[2]), "=r"(r[3]) : "r"(addr) : "memory");
}
__device__ __forceinline__ void ldsm2(uint32_t addr, uint32_t (&r)[2]) {
    asm volatile("ldmatrix.sync.aligned.m8n8.x2.shared.b16 {%0, %1}, [%2];" : "=r"(r[0]), "=r"(r[1]) : "r"(addr) : "memory");
}
__device__ __forceinline__ void stg4(void* p, uint32_t a, uint32_t b, uint32_t c, uint32_t d) {
    asm volatile("st.global.v4.u32 [%0], {%1, %2, %3, %4};" ::"l"(p), "r"(a), "r"(b), "r"(c), "r"(d) : "memory");
}
__device__ __forceinline__ void hmma(float (&c)[4], uint32_t a0, uint32_t a1, uint32_t a2, uint32_t a3, uint32_t b0, uint32_t b1) {
    asm("mma.sync.aligned.m16n8k16.row.col.f32.bf16.bf16.f32 {%0, %1, %2, %3}, {%4, %5, %6, %7}, {%8, %9}, {%0, %1, %2, %3};"
        : "+f"(c[0]), "+f"(c[1]), "+f"(c[2]), "+f"(c[3]) : "r"(a0), "r"(a1), "r"(a2), "r"(a3), "r"(b0), "r"(b1));
}
__device__ __forceinline__ uint32_t pack2(float lo, float hi) {
    uint32_t r;
    asm("cvt.rn.bf16x2.f32 %0, %1, %2;" : "=r"(r) : "f"(hi), "f"(lo));
    return r;
}
__device__ __forceinline__ uint32_t pack2v(float lo, float hi) {
    uint32_t r;
    asm volatile("cvt.rn.bf16x2.f32 %0, %1, %2;" : "=r"(r) : "f"(hi), "f"(lo));
    return r;
}
__device__ __forceinline__ uint32_t bmul2(uint32_t a, uint32_t b) { uint32_t r; asm("mul.rn.bf16x2 %0, %1, %2;" : "=r"(r) : "r"(a), "r"(b)); return r; }
__device__ __forceinline__ uint32_t bfma2(uint32_t a, uint32_t b, uint32_t c) { uint32_t r; asm("fma.rn.bf16x2 %0, %1, %2, %3;" : "=r"(r) : "r"(a), "r"(b), "r"(c)); return r; }
__device__ __forceinline__ float ex2(float x) { float r; asm("ex2.approx.ftz.f32 %0, %1;" : "=f"(r) : "f"(x)); return r; }
__device__ __forceinline__ float rcp(float x) { float r; asm("rcp.approx.ftz.f32 %0, %1;" : "=f"(r) : "f"(x)); return r; }
__device__ __forceinline__ float gelu2(float x) {
    float t = fmaf(x * x, 0.044715f * 0.7978845608028654f, 0.7978845608028654f), th;
    asm("tanh.approx.f32 %0, %1;" : "=f"(th) : "f"(x * t));
    return fmaf(x, th, x);
}
__device__ __forceinline__ uint32_t ldg_v(const uint32_t* p) { uint32_t v; asm volatile("ld.global.nc.u32 %0, [%1];" : "=r"(v) : "l"(p)); return v; }
__device__ __forceinline__ float lds_f32(uint32_t a) { float v; asm volatile("ld.shared.f32 %0, [%1];" : "=f"(v) : "r"(a) : "memory"); return v; }
__device__ __forceinline__ void sts_f32(uint32_t a, float v) { asm volatile("st.shared.f32 [%0], %1;" ::"r"(a), "f"(v) : "memory"); }
__device__ __forceinline__ uint32_t atom_inc_s(uint32_t a) { uint32_t v; asm volatile("atom.relaxed.cta.shared.add.u32 %0, [%1], 1;" : "=r"(v) : "r"(a) : "memory"); return v; }
__device__ __forceinline__ void lds4(uint32_t a, uint32_t* r) {
    asm volatile("ld.shared.v4.u32 {%0, %1, %2, %3}, [%4];" : "=r"(r[0]), "=r"(r[1]), "=r"(r[2]), "=r"(r[3]) : "r"(a) : "memory");
}
__device__ __forceinline__ void sts4(uint32_t a, uint32_t x, uint32_t y, uint32_t z, uint32_t t) {
    asm volatile("st.shared.v4.u32 [%0], {%1, %2, %3, %4};" ::"r"(a), "r"(x), "r"(y), "r"(z), "r"(t) : "memory");
}
__device__ __forceinline__ uint32_t bsub2(uint32_t a, uint32_t b) { uint32_t r; asm("sub.rn.bf16x2 %0, %1, %2;" : "=r"(r) : "r"(a), "r"(b)); return r; }
__device__ __forceinline__ float blo(uint32_t v) { return __uint_as_float(v << 16); }
__device__ __forceinline__ float bhi(uint32_t v) { return __uint_as_float(v & 0xffff0000u); }
__device__ __forceinline__ float bfr(float x) { return __bfloat162float(__float2bfloat16_rn(x)); }
__device__ __forceinline__ void l2_prefetch(const void* p, uint32_t bytes) { asm volatile("cp.async.bulk.prefetch.L2.global [%0], %1;" ::"l"(p), "r"(bytes) : "memory"); }
__device__ __forceinline__ void flag_add(unsigned* p) { asm volatile("red.release.gpu.global.add.u32 [%0], 1;" ::"l"(p) : "memory"); }
__device__ __forceinline__ void flag_wait(const unsigned* p, unsigned target) {
#pragma unroll 1
    for (uint32_t it = 0;; ++it) {
        unsigned v;
        asm volatile("ld.acquire.gpu.global.u32 %0, [%1];" : "=r"(v) : "l"(p) : "memory");
        if (v >= target) break;
        if (it > (1u << 20)) __trap();
    }
    fence_async_g();
}
template <int N> __device__ __forceinline__ void pin(float (&a)[N]) {
#pragma unroll
    for (int i = 0; i < N; i++) asm volatile("" : "+f"(a[i])::"memory");
}

template <int N> __device__ __forceinline__ void fresh(float (&a)[N]) {
#pragma unroll
    for (int i = 0; i < N; i++) a[i] = 0.f;
    pin(a);
}

__device__ __forceinline__ void wgmma_rs_n64_tb0(float (&d)[32], uint32_t a0, uint32_t a1, uint32_t a2, uint32_t a3, uint64_t db, int scale_d) {
    asm volatile("{\n.reg .pred p;\nsetp.ne.b32 p, %37, 0;\n"
        "wgmma.mma_async.sync.aligned.m64n64k16.f32.bf16.bf16 {%0, %1, %2, %3, %4, %5, %6, %7, %8, %9, %10, %11, %12, %13, %14, %15, %16, %17, %18, %19, %20, %21, %22, %23, %24, %25, %26, %27, %28, %29, %30, %31}, {%32, %33, %34, %35}, %36, p, 1, 1, 0;\n}\n"
        : "+f"(d[0]), "+f"(d[1]), "+f"(d[2]), "+f"(d[3]), "+f"(d[4]), "+f"(d[5]), "+f"(d[6]), "+f"(d[7]), "+f"(d[8]), "+f"(d[9]), "+f"(d[10]), "+f"(d[11]), "+f"(d[12]), "+f"(d[13]), "+f"(d[14]), "+f"(d[15]), "+f"(d[16]), "+f"(d[17]), "+f"(d[18]), "+f"(d[19]), "+f"(d[20]), "+f"(d[21]), "+f"(d[22]), "+f"(d[23]), "+f"(d[24]), "+f"(d[25]), "+f"(d[26]), "+f"(d[27]), "+f"(d[28]), "+f"(d[29]), "+f"(d[30]), "+f"(d[31])
        : "r"(a0), "r"(a1), "r"(a2), "r"(a3), "l"(db), "r"(scale_d));
}

__device__ __forceinline__ void wgmma_ss_n128_tb1(float (&d)[64], uint64_t da, uint64_t db, int scale_d) {
    asm volatile("{\n.reg .pred p;\nsetp.ne.b32 p, %66, 0;\n"
        "wgmma.mma_async.sync.aligned.m64n128k16.f32.bf16.bf16 {%0, %1, %2, %3, %4, %5, %6, %7, %8, %9, %10, %11, %12, %13, %14, %15, %16, %17, %18, %19, %20, %21, %22, %23, %24, %25, %26, %27, %28, %29, %30, %31, %32, %33, %34, %35, %36, %37, %38, %39, %40, %41, %42, %43, %44, %45, %46, %47, %48, %49, %50, %51, %52, %53, %54, %55, %56, %57, %58, %59, %60, %61, %62, %63}, %64, %65, p, 1, 1, 0, 1;\n}\n"
        : "+f"(d[0]), "+f"(d[1]), "+f"(d[2]), "+f"(d[3]), "+f"(d[4]), "+f"(d[5]), "+f"(d[6]), "+f"(d[7]), "+f"(d[8]), "+f"(d[9]), "+f"(d[10]), "+f"(d[11]), "+f"(d[12]), "+f"(d[13]), "+f"(d[14]), "+f"(d[15]), "+f"(d[16]), "+f"(d[17]), "+f"(d[18]), "+f"(d[19]), "+f"(d[20]), "+f"(d[21]), "+f"(d[22]), "+f"(d[23]), "+f"(d[24]), "+f"(d[25]), "+f"(d[26]), "+f"(d[27]), "+f"(d[28]), "+f"(d[29]), "+f"(d[30]), "+f"(d[31]), "+f"(d[32]), "+f"(d[33]), "+f"(d[34]), "+f"(d[35]), "+f"(d[36]), "+f"(d[37]), "+f"(d[38]), "+f"(d[39]), "+f"(d[40]), "+f"(d[41]), "+f"(d[42]), "+f"(d[43]), "+f"(d[44]), "+f"(d[45]), "+f"(d[46]), "+f"(d[47]), "+f"(d[48]), "+f"(d[49]), "+f"(d[50]), "+f"(d[51]), "+f"(d[52]), "+f"(d[53]), "+f"(d[54]), "+f"(d[55]), "+f"(d[56]), "+f"(d[57]), "+f"(d[58]), "+f"(d[59]), "+f"(d[60]), "+f"(d[61]), "+f"(d[62]), "+f"(d[63])
        : "l"(da), "l"(db), "r"(scale_d));
}

__device__ __forceinline__ void wgmma_ss_n256_tb1(float (&d)[128], uint64_t da, uint64_t db, int scale_d) {
    asm volatile("{\n.reg .pred p;\nsetp.ne.b32 p, %130, 0;\n"
        "wgmma.mma_async.sync.aligned.m64n256k16.f32.bf16.bf16 {%0, %1, %2, %3, %4, %5, %6, %7, %8, %9, %10, %11, %12, %13, %14, %15, %16, %17, %18, %19, %20, %21, %22, %23, %24, %25, %26, %27, %28, %29, %30, %31, %32, %33, %34, %35, %36, %37, %38, %39, %40, %41, %42, %43, %44, %45, %46, %47, %48, %49, %50, %51, %52, %53, %54, %55, %56, %57, %58, %59, %60, %61, %62, %63, %64, %65, %66, %67, %68, %69, %70, %71, %72, %73, %74, %75, %76, %77, %78, %79, %80, %81, %82, %83, %84, %85, %86, %87, %88, %89, %90, %91, %92, %93, %94, %95, %96, %97, %98, %99, %100, %101, %102, %103, %104, %105, %106, %107, %108, %109, %110, %111, %112, %113, %114, %115, %116, %117, %118, %119, %120, %121, %122, %123, %124, %125, %126, %127}, %128, %129, p, 1, 1, 0, 1;\n}\n"
        : "+f"(d[0]), "+f"(d[1]), "+f"(d[2]), "+f"(d[3]), "+f"(d[4]), "+f"(d[5]), "+f"(d[6]), "+f"(d[7]), "+f"(d[8]), "+f"(d[9]), "+f"(d[10]), "+f"(d[11]), "+f"(d[12]), "+f"(d[13]), "+f"(d[14]), "+f"(d[15]), "+f"(d[16]), "+f"(d[17]), "+f"(d[18]), "+f"(d[19]), "+f"(d[20]), "+f"(d[21]), "+f"(d[22]), "+f"(d[23]), "+f"(d[24]), "+f"(d[25]), "+f"(d[26]), "+f"(d[27]), "+f"(d[28]), "+f"(d[29]), "+f"(d[30]), "+f"(d[31]), "+f"(d[32]), "+f"(d[33]), "+f"(d[34]), "+f"(d[35]), "+f"(d[36]), "+f"(d[37]), "+f"(d[38]), "+f"(d[39]), "+f"(d[40]), "+f"(d[41]), "+f"(d[42]), "+f"(d[43]), "+f"(d[44]), "+f"(d[45]), "+f"(d[46]), "+f"(d[47]), "+f"(d[48]), "+f"(d[49]), "+f"(d[50]), "+f"(d[51]), "+f"(d[52]), "+f"(d[53]), "+f"(d[54]), "+f"(d[55]), "+f"(d[56]), "+f"(d[57]), "+f"(d[58]), "+f"(d[59]), "+f"(d[60]), "+f"(d[61]), "+f"(d[62]), "+f"(d[63]), "+f"(d[64]), "+f"(d[65]), "+f"(d[66]), "+f"(d[67]), "+f"(d[68]), "+f"(d[69]), "+f"(d[70]), "+f"(d[71]), "+f"(d[72]), "+f"(d[73]), "+f"(d[74]), "+f"(d[75]), "+f"(d[76]), "+f"(d[77]), "+f"(d[78]), "+f"(d[79]), "+f"(d[80]), "+f"(d[81]), "+f"(d[82]), "+f"(d[83]), "+f"(d[84]), "+f"(d[85]), "+f"(d[86]), "+f"(d[87]), "+f"(d[88]), "+f"(d[89]), "+f"(d[90]), "+f"(d[91]), "+f"(d[92]), "+f"(d[93]), "+f"(d[94]), "+f"(d[95]), "+f"(d[96]), "+f"(d[97]), "+f"(d[98]), "+f"(d[99]), "+f"(d[100]), "+f"(d[101]), "+f"(d[102]), "+f"(d[103]), "+f"(d[104]), "+f"(d[105]), "+f"(d[106]), "+f"(d[107]), "+f"(d[108]), "+f"(d[109]), "+f"(d[110]), "+f"(d[111]), "+f"(d[112]), "+f"(d[113]), "+f"(d[114]), "+f"(d[115]), "+f"(d[116]), "+f"(d[117]), "+f"(d[118]), "+f"(d[119]), "+f"(d[120]), "+f"(d[121]), "+f"(d[122]), "+f"(d[123]), "+f"(d[124]), "+f"(d[125]), "+f"(d[126]), "+f"(d[127])
        : "l"(da), "l"(db), "r"(scale_d));
}

__device__ __forceinline__ void wgmma_ss_n32_tb0(float (&d)[16], uint64_t da, uint64_t db, int scale_d) {
    asm volatile("{\n.reg .pred p;\nsetp.ne.b32 p, %18, 0;\n"
        "wgmma.mma_async.sync.aligned.m64n32k16.f32.bf16.bf16 {%0, %1, %2, %3, %4, %5, %6, %7, %8, %9, %10, %11, %12, %13, %14, %15}, %16, %17, p, 1, 1, 0, 0;\n}\n"
        : "+f"(d[0]), "+f"(d[1]), "+f"(d[2]), "+f"(d[3]), "+f"(d[4]), "+f"(d[5]), "+f"(d[6]), "+f"(d[7]), "+f"(d[8]), "+f"(d[9]), "+f"(d[10]), "+f"(d[11]), "+f"(d[12]), "+f"(d[13]), "+f"(d[14]), "+f"(d[15])
        : "l"(da), "l"(db), "r"(scale_d));
}

__device__ __forceinline__ void wgmma_ss_n64_tb0(float (&d)[32], uint64_t da, uint64_t db, int scale_d) {
    asm volatile("{\n.reg .pred p;\nsetp.ne.b32 p, %34, 0;\n"
        "wgmma.mma_async.sync.aligned.m64n64k16.f32.bf16.bf16 {%0, %1, %2, %3, %4, %5, %6, %7, %8, %9, %10, %11, %12, %13, %14, %15, %16, %17, %18, %19, %20, %21, %22, %23, %24, %25, %26, %27, %28, %29, %30, %31}, %32, %33, p, 1, 1, 0, 0;\n}\n"
        : "+f"(d[0]), "+f"(d[1]), "+f"(d[2]), "+f"(d[3]), "+f"(d[4]), "+f"(d[5]), "+f"(d[6]), "+f"(d[7]), "+f"(d[8]), "+f"(d[9]), "+f"(d[10]), "+f"(d[11]), "+f"(d[12]), "+f"(d[13]), "+f"(d[14]), "+f"(d[15]), "+f"(d[16]), "+f"(d[17]), "+f"(d[18]), "+f"(d[19]), "+f"(d[20]), "+f"(d[21]), "+f"(d[22]), "+f"(d[23]), "+f"(d[24]), "+f"(d[25]), "+f"(d[26]), "+f"(d[27]), "+f"(d[28]), "+f"(d[29]), "+f"(d[30]), "+f"(d[31])
        : "l"(da), "l"(db), "r"(scale_d));
}

struct Maps {
    CUtensorMap xa, xa2, xas, wup4, wup8, mqa2, mqa4, mqb1, mqb2, uc, x, out, wq, wk, fa[3], fb[2], fc;
};

__device__ __forceinline__ uint64_t mkd(uint32_t lo) {
    uint64_t d;
    asm("mov.b64 %0, {%1, %2};" : "=l"(d) : "r"(lo), "r"((1024u >> 4) | (1u << 30)));
    return d;
}
__device__ __forceinline__ void bulk_ld(uint32_t dst, const void* src, uint32_t bytes, uint32_t bar) {
    asm volatile("cp.async.bulk.shared::cluster.global.mbarrier::complete_tx::bytes [%0], [%1], %2, [%3];" ::"r"(dst), "l"(src), "r"(bytes), "r"(bar) : "memory");
}
__device__ __forceinline__ void bulk_st(void* dst, uint32_t src, uint32_t bytes) {
    asm volatile("cp.async.bulk.global.shared::cta.bulk_group [%0], [%1], %2;" ::"l"(dst), "r"(src), "r"(bytes) : "memory");
}
__device__ __forceinline__ void ring_ld(uint32_t sb, uint32_t slot8, int n) {
    mbar_expect_tx(sb + B_R2 + slot8, 8192);
    bulk_ld(sb + R1 + slot8 * 1024, (const char*)g_wepi + n * 8192, 8192, sb + B_R2 + slot8);
}

__device__ __forceinline__ void ring_half(uint32_t sb, uint32_t slot8, uint32_t hoff, const CUtensorMap* tm, int c1, int c2) {
    mbar_expect_tx(sb + B_R1 + slot8, 8192);
    tma3(sb + R1 + slot8 * 2048 + hoff, tm, 0, c1, c2, sb + B_R1 + slot8);
}
__device__ __forceinline__ void ring_full(uint32_t sb, uint32_t slot8, const CUtensorMap* tm, int c1, int c2) {
    mbar_expect_tx(sb + B_R1 + slot8, 16384);
    mbar_arrive(sb + B_R1 + slot8);
    tma3(sb + R1 + slot8 * 2048, tm, 0, c1, c2, sb + B_R1 + slot8);
}
__device__ __forceinline__ void cta_done(int mode) {
    if (mode == 0 && atomicAdd(&g_sync[4], 1) == NCTA + 1) {
#pragma unroll
        for (int i = 0; i < 5; i++) g_sync[i] = 0;
    }
}

__device__ __forceinline__ void fold_cta(const Maps& mp, uint32_t sb, int mode) {
    constexpr uint32_t F_FULL = MISC, F_EMPTY = MISC + 32, F_T1 = MISC + 64, STG = 49152, FOUT = 3 * STG;
    const int tid = threadIdx.x, f = blockIdx.x - NCTA;
    if (mode == 2) return;
    if (tid == 0) {
        for (int i = 0; i < 3; i++) { mbar_init(sb + F_FULL + 8 * i, 1); mbar_init(sb + F_EMPTY + 8 * i, 2); }
        mbar_init(sb + F_T1, 2);
        asm volatile("fence.mbarrier_init.release.cluster;" ::: "memory");
        fence_async();
    }
    __syncthreads();
    const int wg = __shfl_sync(0xffffffffu, tid >> 7, 0);
    int st = 0, ph = 0;
    if (wg == 0) {
        if (tid == 0) {
#pragma unroll 1
            for (int it = 0; it < 96; it++) {
                const int p = it >> 3, kc = it & 7, job = p >> 2;
                if (it == 64) mbar_wait(sb + F_T1, 0);
                mbar_wait(sb + F_EMPTY + 8 * st, ph ^ 1);
                mbar_expect_tx(sb + F_FULL + 8 * st, STG);
                tma3(sb + st * STG, &mp.fa[job], 0, 256 * f + 128 * ((p >> 1) & 1), kc, sb + F_FULL + 8 * st);
                tma3(sb + st * STG + 16384, &mp.fb[job != 0], 0, 64 * kc + (job == 1 ? 512 : 0), 4 * (p & 1), sb + F_FULL + 8 * st);
                if (++st == 3) { st = 0; ph ^= 1; }
            }
        }
        return;
    }
    const int h = wg - 1, lane = tid & 31, w = (tid >> 5) & 3;
    const uint32_t sd = (sb & 0x3FFFF) >> 4;
    const bool el = (tid & 127) == 0;
#pragma unroll 1
    for (int p = 0; p < 12; p++) {
        float acc[128];
        fresh(acc);
#pragma unroll 1
        for (int kc = 0; kc < 8; kc++) {
            mbar_wait(sb + F_FULL + 8 * st, ph);
            wg_fence();
#pragma unroll
            for (int kk = 0; kk < 4; kk++)
                wgmma_ss_n256_tb1(acc, dsc(sd, st * STG + h * 8192 + kk * 32, 16), dsc(sd, st * STG + 16384 + kk * 2048, 8192), 1);
            wg_commit();
            wg_wait<0>();
            if (el) mbar_arrive(sb + F_EMPTY + 8 * st);
            if (++st == 3) { st = 0; ph ^= 1; }
        }
        pin(acc);
        const int job = p >> 2;
        if (el) {
            asm volatile("cp.async.bulk.wait_group 0;" ::: "memory");
            if (p == 4) { fence_async_g(); mbar_arrive(sb + F_T1); }
        }
        bar_sync(3 + h, 128);
        uint32_t r = 16 * w + (lane & 7) + ((lane >> 3) & 1) * 8;
        const float fs = job == 1 ? 0.5f : 1.f;
        if (job == 1) r = (r & ~31) | (((r >> 1) & 3) << 3) | (((r >> 3) & 3) << 1) | (r & 1);
        const uint32_t oa = sb + FOUT + h * 32768 + r * 128 + ((((lane >> 4) ^ r) & 7) << 4);
#pragma unroll
        for (int i = 0; i < 16; i++)
            stsm4((oa ^ ((i & 3) << 5)) + (i >> 2) * 8192, pack2(acc[8 * i] * fs, acc[8 * i + 1] * fs), pack2(acc[8 * i + 2] * fs, acc[8 * i + 3] * fs),
                  pack2(acc[8 * i + 4] * fs, acc[8 * i + 5] * fs), pack2(acc[8 * i + 6] * fs, acc[8 * i + 7] * fs));
        fence_async();
        bar_sync(3 + h, 128);
        if (el) {
            const int row0 = 256 * f + 128 * ((p >> 1) & 1) + 64 * h + (job == 1 ? 512 : 0);
            if (job == 0) tma3_store(&mp.fc, sb + FOUT + h * 32768, 0, row0, 4 * (p & 1));
            else {
#pragma unroll 1
                for (int i = 0; i < 16; i++)
                    bulk_st((char*)g_wepi + (row0 / 8 + 2 * (i & 3) + (p & 1)) * 8192 + (i >> 2) * 2048, sb + FOUT + h * 32768 + i * 2048, 2048);
            }
            asm volatile("cp.async.bulk.commit_group;" ::: "memory");
        }
    }
    if (el) {
        asm volatile("cp.async.bulk.wait_group 0;" ::: "memory");
        fence_async_g();
        if (mode == 0) flag_add(&g_sync[3]);
    }
    bar_sync(2, 256);
    if (tid == 128) cta_done(mode);
}

__global__ void __launch_bounds__(384, 1) main_kernel(const __grid_constant__ Maps mp, const bf16* __restrict__ x, const bf16* __restrict__ dw, const bf16* wup, const int mode) {
    extern __shared__ __align__(1024) uint8_t smem[];
    const uint32_t sb = smem_u32(smem);
    const int tid = threadIdx.x;
    PE();
    if (blockIdx.x >= NCTA) { fold_cta(mp, sb, mode); return; }
    const int b = blockIdx.x / TPB, ti = blockIdx.x % TPB;
    const int piece = blockIdx.x & 127;
    const int wg = __shfl_sync(0xffffffffu, tid >> 7, 0);
    const int lane = tid & 31, w = (tid >> 5) & 3;
    const bool w0 = __shfl_sync(0xffffffffu, w, 0) == 0;
    const uint32_t sd = (sb & 0x3FFFF) >> 4;
    const uint32_t adA = sd + (AT >> 4) + (1u << 16);
    const uint32_t bd0 = sd + (R1 >> 4);
    const uint32_t bd2k = bd0 + ((2048u >> 4) << 16);
    const bool el = (tid & 127) == 0;
    const uint32_t lrow = 16 * w + (lane & 7) + ((lane >> 3) & 1) * 8;
    const uint32_t loff = lrow * 128 + ((((lane >> 4) ^ lrow) & 7) << 4);
    const int r0 = 16 * w + (lane >> 2);

    if (wg == 0) {
        asm volatile("setmaxnreg.inc.sync.aligned.u32 184;");
        uint32_t q[112];
        if (tid < 26) {
            mbar_init(sb + MISC + 8 * tid, (int)((tid < 16 ? 0x1121221111222221ull : 0x0000008114444441ull) >> (4 * (tid & 15))) & 15);
        } else if (tid >= 32 && tid < 72) {
            mbar_init(sb + B_R2 + 8 * (tid - 32), tid < 52 ? 1 : 4);
        } else if (tid >= 96 && tid < 101) {
            asm volatile("st.shared.u32 [%0], 0;" ::"r"(sb + CNT + 4 * (tid - 96)) : "memory");
        }
        asm volatile("fence.mbarrier_init.release.cluster;" ::: "memory");
        fence_async();
        bar_sync(1, 128);
        asm volatile("bar.arrive 5, 384;" ::: "memory");
        if (tid == 0) {
            mbar_expect_tx(sb + B_MK, 65536 + 32768 + 3072);
            tma3(sb + R0, &mp.wq, 0, 64 * (piece >> 4), 0, sb + B_MK);
            tma3(sb + R1 + 32768, &mp.wk, 0, 32 * (piece & 15), 0, sb + B_MK);
            bulk_ld(sb + DWS, dw, 3072, sb + B_MK);
        } else if (tid == 32) {
            for (int i = 0; i < 8; i++) mbar_arrive(sb + B_R1 + 8 * (i >> 1));
            if (mode != 1) {
                ring_full(sb, 32, &mp.wup8, 0, 8);
                ring_full(sb, 0, &mp.wup8, 16, 8);
                ring_full(sb, 8, &mp.wup8, 32, 8);
            }
        }
        __syncwarp();
        PT(0);
        PG(200);
        {
            float mq[16];
            fresh(mq);
            mbar_wait(sb + B_MK, 0);
            PT(1);
            if (PFW && tid == 32) l2_prefetch((const char*)wup + piece * 8192, 8192);
            wg_fence();
#pragma unroll 1
            for (int c = 0; c < 8; c++)
#pragma unroll
                for (int kk = 0; kk < 4; kk++)
                    wgmma_ss_n32_tb0(mq, dsc(sd, R0 + c * 8192 + kk * 32, 16), dsc(sd, R1 + 32768 + c * 4096 + kk * 32, 16), 1);
            wg_commit();
            wg_wait<0>();
            if (mode != 1 && w0 && elect1()) { ring_full(sb, 16, &mp.wup8, 48, 8); ring_full(sb, 24, &mp.wup8, 64, 8); }
            pin(mq);
            uint32_t* c = reinterpret_cast<uint32_t*>(g_mqk + (64 * (piece >> 4) + r0) * D_ + 32 * (piece & 15) + 2 * (lane & 3));
#pragma unroll
            for (int n = 0; n < 4; n++) { c[4 * n] = pack2(mq[4 * n], mq[4 * n + 1]); c[4 * n + 4 * D_] = pack2(mq[4 * n + 2], mq[4 * n + 3]); }
            fence_async_g();
            bar_sync(1, 128);
            if (el) {
                if (mode == 0) flag_add(&g_sync[2]);
                if (mode == 0) flag_wait(&g_sync[2], NCTA);
                mbar_arrive(sb + B_MQ);
                PG(203);
                PT(12);
                mbar_wait(sb + B_LN, 0);
#pragma unroll 1
                for (int c = 0; c < 8; c++) {
                    tma4_store(&mp.xas, sb + AT + c * 8192, 0, 62 * ti, c, b);
                    const unsigned t0 = (unsigned)clock();
                    while (c < 7 && (unsigned)clock() - t0 < XS_GAP) __nanosleep(20);
                }
                asm volatile("cp.async.bulk.commit_group;" ::: "memory");
                if (mode == 1) asm volatile("cp.async.bulk.wait_group 0;" ::: "memory");
            }
            PT(13);
            if (mode == 1) return;
        }
        mbar_wait(sb + B_H1, 0);
        PT(2);
        uint32_t slot8 = 8, par = 1, prev8 = 0;
        auto adv = [&]() { prev8 = slot8; slot8 += 8; if (slot8 == 40) { slot8 = 0; par ^= 1; } };
        {
            float acc[128];
            fresh(acc);
            auto step = [&](int i) {
                const uint32_t aa = adA + (i >> 1) * 512 + (i & 1) * 4, bb = bd0 + ((4096u >> 4) << 16) + slot8 * 128;
                wg_fence();
                wgmma_ss_n256_tb1(acc, mkd(aa), mkd(bb), 1);
                wgmma_ss_n256_tb1(acc, mkd(aa + 2), mkd(bb + 128), 1);
                wg_commit();
                wg_wait<1>();
            };
#pragma unroll 1
            for (int i = 0; i < 12; i++) {
                mbar_wait(sb + B_R1 + slot8, par);
                step(i);
                if (i > 0 && w0 && elect1()) ring_full(sb, prev8, &mp.mqa4, 32 * i + 128, 4);
                adv();
            }
#pragma unroll 1
            for (int i = 12; i < 16; i++) {
                mbar_wait(sb + B_R1 + slot8, par);
                if (i == 15 && el) mbar_arrive(sb + B_H2);
                step(i);
                if (w0 && elect1()) ring_full(sb, prev8, &mp.wup8, 16 * i - 192, 0);
                adv();
            }
            wg_wait<0>();
            if (w0 && elect1()) ring_full(sb, prev8, &mp.wup8, 64, 0);
            pin(acc);
            PT(3);
#pragma unroll
            for (int kk = 0; kk < 4; kk++)
                stsm4((sb + QS + loff) ^ (kk << 5), pack2(acc[96 + 8 * kk], acc[97 + 8 * kk]), pack2(acc[98 + 8 * kk], acc[99 + 8 * kk]),
                      pack2(acc[100 + 8 * kk], acc[101 + 8 * kk]), pack2(acc[102 + 8 * kk], acc[103 + 8 * kk]));
            fence_async();
#pragma unroll
            for (int i = 47; i >= 0; i--) q[64 + i] = pack2v(acc[2 * i], acc[2 * i + 1]);
        }
        if (el) {
            asm volatile("cp.async.bulk.wait_group 0;" ::: "memory");
            if (mode == 0) {
                fence_async_g();
                flag_add(&g_sync[b]);
                flag_wait(&g_sync[b], TPB);
            }
            mbar_arrive(sb + B_XA);
        }
        __syncwarp();
        mbar_wait(sb + B_H3, 0);
        PT(4);
        slot8 = 32; par = 0;
#pragma unroll
        for (int half = 0; half < 2; half++) {
            float acc[64];
            fresh(acc);
            auto step = [&](int m) {
                const uint32_t aa = adA + m * 512, bb = bd0 + ((8192u >> 4) << 16) + slot8 * 128;
                mbar_wait(sb + B_R1 + slot8, par);
                wg_fence();
#pragma unroll
                for (int kk = 0; kk < 4; kk++) wgmma_ss_n128_tb1(acc, mkd(aa + 2 * kk), mkd(bb + 128 * kk), 1);
                wg_commit();
                wg_wait<1>();
            };
            if (half == 0) {
#pragma unroll 1
                for (int m = 0; m < 8; m++) {
                    step(m);
                    if (m > 0 && w0 && elect1()) ring_full(sb, prev8, &mp.mqb2, (64 * m + 256) & 511, (m + 4) >> 3 << 1);
                    adv();
                }
            } else {
#pragma unroll 1
                for (int m = 0; m < 4; m++) {
                    step(m);
                    if (m > 0 && w0 && elect1()) ring_full(sb, prev8, &mp.mqb2, 64 * m + 256, 2);
                    adv();
                }
#pragma unroll 1
                for (int m = 4; m < 8; m++) {
                    step(m);
                    if (w0 && elect1()) {
                        if (m == 4) mbar_expect_tx(sb + B_KV + 8, 65536);
                        tma4(sb + R1 + prev8 * 2048, &mp.xa2, 0, 0, 2 * m - 8, b, sb + B_KV + 8);
                    }
                    adv();
                }
            }
            wg_wait<0>();
            if (w0 && elect1()) {
                if (half == 0) ring_full(sb, prev8, &mp.mqb2, 256, 2);
                else {
                    mbar_expect_tx(sb + B_KV + 16, 65536);
                    tma4(sb + R2, &mp.xa, 0, 64, 0, b, sb + B_KV + 16);
                }
            }
            pin(acc);
#pragma unroll
            for (int i = 31; i >= 0; i--) q[32 * half + i] = pack2v(acc[2 * i], acc[2 * i + 1]);
        }
        bar_sync(1, 128);
        PT(5);

        const float CS = 0.04419417382415922f * 1.4426950408889634f;
        float m0 = -INFINITY, m1 = -INFINITY, l0 = 0.f, l1 = 0.f;
        int s = 0, sn = 1, ph = 0;
        float S[32];
        const bool l0w = lane == 0, q0 = (lane & 3) == 0;
#pragma unroll 1
        for (int j = -1;; j++) {
            if (j >= 0) {
                PL(j, 1);
                if (j == NKV - 1) {
#pragma unroll
                    for (int i = (T_ - 64 * (NKV - 1)) / 2; i < 32; i++) asm volatile("mov.b32 %0, 0xff800000;" : "=f"(S[i]));
                }
                float y[8], z[8];
#pragma unroll
                for (int n = 0; n < 8; n++) { y[n] = fmaxf(S[4 * n], S[4 * n + 1]); z[n] = fmaxf(S[4 * n + 2], S[4 * n + 3]); }
#pragma unroll
                for (int n = 0; n < 4; n++) { y[n] = fmaxf(y[n], y[n + 4]); z[n] = fmaxf(z[n], z[n + 4]); }
                float x0 = fmaxf(fmaxf(y[0], y[1]), fmaxf(fmaxf(y[2], y[3]), m0)), x1 = fmaxf(fmaxf(z[0], z[1]), fmaxf(fmaxf(z[2], z[3]), m1));
                x0 = fmaxf(x0, __shfl_xor_sync(0xffffffffu, x0, 1));
                x1 = fmaxf(x1, __shfl_xor_sync(0xffffffffu, x1, 1));
                x0 = fmaxf(x0, __shfl_xor_sync(0xffffffffu, x0, 2));
                x1 = fmaxf(x1, __shfl_xor_sync(0xffffffffu, x1, 2));
                if ((x0 - m0) * CS <= LAZY) x0 = m0;
                if ((x1 - m1) * CS <= LAZY) x1 = m1;
                const float sc0 = ex2((m0 - x0) * CS), sc1 = ex2((m1 - x1) * CS);
                m0 = x0; m1 = x1;
                const float n0 = -x0 * CS, n1 = -x1 * CS;
                if (q0) { sts_f32(sb + SCL + s * 256 + r0 * 4, sc0); sts_f32(sb + SCL + s * 256 + r0 * 4 + 32, sc1); }
                __syncwarp();
                if (l0w) mbar_arrive(sb + B_P + s * 8);
                if (j < NKV - 1) mbar_wait(sb + B_KV + sn * 8, ph);
                float a0 = 0.f, a1 = 0.f;
                const uint32_t pb = sb + R3 + (s == 0 ? 2 : s - 1) * 8192;
#pragma unroll
                for (int kk = 0; kk < 4; kk++) {
                    float p[8];
#pragma unroll
                    for (int e = 0; e < 8; e++) p[e] = ex2(fmaf(S[8 * kk + e], CS, (e & 2) ? n1 : n0));
                    a0 += (p[0] + p[1]) + (p[4] + p[5]);
                    a1 += (p[2] + p[3]) + (p[6] + p[7]);
                    stsm4((pb + loff) ^ (kk << 5), pack2(p[0], p[1]), pack2(p[2], p[3]), pack2(p[4], p[5]), pack2(p[6], p[7]));
                }
                l0 = fmaf(l0, sc0, a0); l1 = fmaf(l1, sc1, a1);
                PL(j, 2);
                if (j == NKV - 1) break;
            } else {
                mbar_wait(sb + B_KV + 8, 0);
            }
            float Sn[32];
            const uint32_t kd = sd + sn * 4096;
            wg_fence();
#pragma unroll
            for (int kk = 0; kk < 28; kk++) {
                wgmma_rs_n64_tb0(Sn, q[4 * kk], q[4 * kk + 1], q[4 * kk + 2], q[4 * kk + 3], dsc(kd, (kk >> 2) * 8192 + (kk & 3) * 32, 16), kk > 0);
                if (kk == FENCE_AT) { fence_async(); __syncwarp(); }
                if (kk == GO_AT) { PL(j, 3); if (j >= 0 && l0w) mbar_arrive(sb + B_GO + s * 8); }
            }
#pragma unroll
            for (int kk = 0; kk < 4; kk++)
                wgmma_ss_n64_tb0(Sn, dsc(sd, QS + kk * 32, 16), dsc(kd, 7 * 8192 + kk * 32, 16), 1);
            wg_commit();
            PL(j, 0);
            wg_wait<0>();
            pin(Sn);
#pragma unroll
            for (int i = 0; i < 32; i++) S[i] = Sn[i];
            s = sn;
            if (++sn == 3) sn = 0;
            if (sn == 1) ph ^= 1;
        }
        l0 += __shfl_xor_sync(0xffffffffu, l0, 1); l1 += __shfl_xor_sync(0xffffffffu, l1, 1);
        l0 += __shfl_xor_sync(0xffffffffu, l0, 2); l1 += __shfl_xor_sync(0xffffffffu, l1, 2);
        if (q0) { sts_f32(sb + LINV + r0 * 4, rcp(l0)); sts_f32(sb + LINV + r0 * 4 + 32, rcp(l1)); }
        fence_async();
        __syncwarp();
        if (l0w) {
            mbar_arrive(sb + B_GO + s * 8);
            uint32_t slot8 = 8 * w, par = 0;
#pragma unroll 1
            for (int n = 20 + w; n < 136; n += 4) {
                mbar_wait(sb + B_E2 + slot8, par);
                if (n < 128) ring_ld(sb, slot8, n);
                else {
                    mbar_expect_tx(sb + B_X, 8192);
                    tma4(sb + R1 + slot8 * 1024, &mp.x, 0, 62 * ti, n - 128, b, sb + B_X);
                }
                slot8 += 32;
                if (slot8 >= 160) { slot8 -= 160; par ^= 1; }
            }
        }
        PDUMP();
    } else {
        asm volatile("setmaxnreg.dec.sync.aligned.u32 160;");
        const int h = wg - 1;
        uint32_t v[4][8], v2[4][8];
#pragma unroll
        for (int i = 0; i < 8; i++) {
            const int t = 62 * ti - 1 + 32 * (i >> 2) + 16 * h + 4 * w + (i & 3);
            const uint4* p = reinterpret_cast<const uint4*>(x + ((size_t)b * T_ + t) * D_) + lane;
            uint32_t* d = i < 4 ? v[i & 3] : v2[i & 3];
#pragma unroll
            for (int c = 0; c < 2; c++)
                asm volatile("{\n.reg .pred p;\nsetp.lt.u32 p, %5, %6;\nmov.b32 %0, 0;\nmov.b32 %1, 0;\nmov.b32 %2, 0;\nmov.b32 %3, 0;\n"
                             "@p ld.global.nc.v4.u32 {%0, %1, %2, %3}, [%4];\n}\n"
                             : "=r"(d[4 * c]), "=r"(d[4 * c + 1]), "=r"(d[4 * c + 2]), "=r"(d[4 * c + 3]) : "l"(p + 32 * c), "r"(t), "n"(T_));
        }
#pragma unroll 1
        for (int bt = 0; bt < 2; bt++) {
            PT(bt ? 13 : 0);
            float a[8];
            const uint32_t la = sb + AT + (lane >> 3) * 8192 + (32 * bt + 16 * h + 4 * w) * 128 + (((lane & 7) ^ ((w & 1) * 4)) << 4);
            const bool b4 = lane & 16, b3 = lane & 8, b2 = lane & 4;
#pragma unroll
            for (int r = 0; r < 4; r++) {
                float c[4] = {0.f, 0.f, 0.f, 0.f};
#pragma unroll
                for (int i = 0; i < 8; i += 2) hmma(c, v[r][i], v[r][i], v[r][i + 1], v[r][i + 1], v[r][i], v[r][i + 1]);
                a[4 + r] = (lane & 3) == (lane >> 3) ? (b2 ? c[1] : c[0]) : 0.f;
                if (r & 1) {
                    float e[4] = {0.f, 0.f, 0.f, 0.f};
#pragma unroll
                    for (int i = 0; i < 8; i += 2) hmma(e, v[r - 1][i], v[r][i], v[r - 1][i + 1], v[r][i + 1], 0x3f803f80u, 0x3f803f80u);
                    a[r - 1] = e[0]; a[r] = e[2];
                }
            }
            float k[4];
#pragma unroll
            for (int i = 0; i < 4; i++) {
                const int lo = (i & 1) + 4 * (i >> 1);
                k[i] = (b4 ? a[lo + 2] : a[lo]) + __shfl_xor_sync(0xffffffffu, b4 ? a[lo] : a[lo + 2], 16);
            }
            const float k0 = (b3 ? k[1] : k[0]) + __shfl_xor_sync(0xffffffffu, b3 ? k[0] : k[1], 8);
            const float k1 = (b3 ? k[3] : k[2]) + __shfl_xor_sync(0xffffffffu, b3 ? k[2] : k[3], 8);
            float z = (b2 ? k1 : k0) + __shfl_xor_sync(0xffffffffu, b2 ? k0 : k1, 4);
            z += __shfl_xor_sync(0xffffffffu, z, 2);
            z += __shfl_xor_sync(0xffffffffu, z, 1);
            const float zo = __shfl_xor_sync(0xffffffffu, z, 4);
            PG(204 + bt);
            const float mu = (b2 ? zo : z) * (0.25f / D_);
            float sd_ = bfr(bfr(fmaxf(fmaf(b2 ? z : zo, 1.f / D_, -mu * mu), 0.f)) + 1e-5f);
            asm("sqrt.approx.f32 %0, %0;" : "+f"(sd_));
            const float ri = rcp(bfr(sd_));
            const uint32_t w1 = pack2(mu, ri), w2 = pack2(ri - bhi(w1), ri - bhi(w1));
#pragma unroll
            for (int r = 0; r < 4; r++) {
                const uint32_t s1 = __shfl_sync(0xffffffffu, w1, 8 * r), rl = __shfl_sync(0xffffffffu, w2, 8 * r);
                const uint32_t m2 = __byte_perm(s1, 0, 0x1010), rh = __byte_perm(s1, 0, 0x3232);
#pragma unroll
                for (int i = 0; i < 8; i++) { const uint32_t d = bsub2(v[r][i], m2); v[r][i] = bfma2(d, rh, bmul2(d, rl)); }
                sts4((la ^ (r << 4)) + r * 128, v[r][0], v[r][1], v[r][2], v[r][3]);
                sts4((la ^ (r << 4)) + r * 128 + 32768, v[r][4], v[r][5], v[r][6], v[r][7]);
#pragma unroll
                for (int i = 0; i < 8; i++) v[r][i] = v2[r][i];
            }
        }
        fence_async();
        bar_sync(5, 384);
        if (tid == 128) mbar_arrive(sb + B_LN);
        PG(202);
        if (mode == 1) return;
        float acc[128];
#pragma unroll
        for (int pass = 0; pass < 2; pass++) {
            if (pass == 1) mbar_wait(sb + B_H2, 0);
            PT(1 + 3 * pass);
            fresh(acc);
            uint32_t slot8 = pass ? 16 : 32, par = 0, prev8 = 0;
            auto adv = [&]() { prev8 = slot8; slot8 += 8; if (slot8 == 40) { slot8 = 0; par ^= 1; } };
            auto step = [&](int kk) {
                wg_fence();
                wgmma_ss_n256_tb1(acc, mkd(adA + (kk >> 2) * 512 + (kk & 3) * 2), mkd(bd2k + h * 512 + slot8 * 128), 1);
                wg_commit();
                wg_wait<1>();
            };
#pragma unroll 1
            for (int kk = 0; kk < 28; kk++) {
                mbar_wait(sb + B_R1 + slot8, par);
                step(kk);
                if (kk > 0 && w0 && elect1()) ring_half(sb, prev8, h * 8192, &mp.wup4, 16 * kk + 64, (pass ? 0 : 8) + 4 * h);
                adv();
            }
            if (pass == 0 && w0) mbar_wait(sb + B_MQ, 0);
#pragma unroll 1
            for (int kk = 28; kk < 32; kk++) {
                mbar_wait(sb + B_R1 + slot8, par);
                if (kk == 31 && el) mbar_arrive(sb + (pass ? B_H3 : B_H1));
                step(kk);
                if (w0 && elect1()) ring_half(sb, prev8, h * 8192, pass ? &mp.mqb1 : &mp.mqa2, (pass ? 64 : 32) * (kk - 28), pass ? h : 4 + 2 * h);
                adv();
            }
            wg_wait<0>();
            if (w0 && elect1()) ring_half(sb, prev8, h * 8192, pass ? &mp.mqb1 : &mp.mqa2, pass ? 256 : 128, pass ? h : 4 + 2 * h);
            pin(acc);
            PT(2 + 3 * pass);
            if (pass == 0) {
                float s0 = 0.f, s1 = 0.f, v0 = 0.f, v1 = 0.f;
#pragma unroll
                for (int n = 0; n < 32; n++) {
#pragma unroll
                    for (int e = 0; e < 4; e++) acc[4 * n + e] = gelu2(acc[4 * n + e]);
                    s0 += acc[4 * n] + acc[4 * n + 1]; s1 += acc[4 * n + 2] + acc[4 * n + 3];
                    v0 = fmaf(acc[4 * n], acc[4 * n], v0); v0 = fmaf(acc[4 * n + 1], acc[4 * n + 1], v0);
                    v1 = fmaf(acc[4 * n + 2], acc[4 * n + 2], v1); v1 = fmaf(acc[4 * n + 3], acc[4 * n + 3], v1);
                }
#pragma unroll
                for (int o = 1; o < 4; o <<= 1) {
                    s0 += __shfl_xor_sync(0xffffffffu, s0, o); s1 += __shfl_xor_sync(0xffffffffu, s1, o);
                    v0 += __shfl_xor_sync(0xffffffffu, v0, o); v1 += __shfl_xor_sync(0xffffffffu, v1, o);
                }
                if ((lane & 3) == 0) {
                    uint32_t a = sb + STAT + h * 512 + r0 * 8;
                    sts_f32(a, s0); sts_f32(a + 4, v0); sts_f32(a + 64, s1); sts_f32(a + 68, v1);
                }
                bar_sync(2, 256);
                {
                    uint32_t a = sb + STAT + (h ^ 1) * 512 + r0 * 8;
                    s0 = (s0 + lds_f32(a)) * (1.f / 512.f); v0 = (v0 + lds_f32(a + 4)) * (1.f / 512.f);
                    s1 = (s1 + lds_f32(a + 64)) * (1.f / 512.f); v1 = (v1 + lds_f32(a + 68)) * (1.f / 512.f);
                }
                v0 = rsqrtf(fmaxf(fmaf(-s0, s0, v0), 0.f) + 4e-5f); v1 = rsqrtf(fmaxf(fmaf(-s1, s1, v1), 0.f) + 4e-5f);
                s0 = -s0 * v0; s1 = -s1 * v1;
#pragma unroll
                for (int p = 0; p < 16; p++)
                    stsm4(((sb + R0 + h * 32768 + loff) ^ ((p & 3) << 5)) + (p >> 2) * 8192,
                          pack2(fmaf(acc[8 * p], v0, s0), fmaf(acc[8 * p + 1], v0, s0)), pack2(fmaf(acc[8 * p + 2], v1, s1), fmaf(acc[8 * p + 3], v1, s1)),
                          pack2(fmaf(acc[8 * p + 4], v0, s0), fmaf(acc[8 * p + 5], v0, s0)), pack2(fmaf(acc[8 * p + 6], v1, s1), fmaf(acc[8 * p + 7], v1, s1)));
            } else {
                uint32_t u[64];
#pragma unroll
                for (int i = 63; i >= 0; i--) u[i] = pack2v(gelu2(acc[2 * i]), gelu2(acc[2 * i + 1]));
                PT(12);
                bar_sync(3 + h, 128);
                const uint32_t rm = lrow == 0 ? 0 : lrow - 1, rp = lrow == 63 ? 63 : lrow + 1;
                const uint32_t gb = sb + R0 + h * 32768;
                const uint32_t am = gb + rm * 128 + ((((lane >> 4) ^ rm) & 7) << 4), ap = gb + rp * 128 + ((((lane >> 4) ^ rp) & 7) << 4), ac = gb + loff;
                const uint32_t dwa = sb + DWS + 512 * h + ((lane >> 3) & 1) * 16 + (lane >> 4) * 1024;
                bf16* ucp = g_uc + ((size_t)blockIdx.x * 64 + r0) * D_ + 256 * h + 8 * (lane & 3);
#pragma unroll
                for (int m = 0; m < 8; m++) {
                    uint32_t o[8], g0[2][4], g1[2][4], g2[2][4], d[2][4], d2[2][2];
#pragma unroll
                    for (int pp = 0; pp < 2; pp++) {
                        const int p = 2 * m + pp;
                        const uint32_t co = (p >> 2) * 8192, cx = (p & 3) << 5;
                        ldsm4(dwa + 32 * p, d[pp]);
                        ldsm2(dwa + 32 * p + 2048, d2[pp]);
                        ldsm4((am ^ cx) + co, g0[pp]);
                        ldsm4((ac ^ cx) + co, g1[pp]);
                        ldsm4((ap ^ cx) + co, g2[pp]);
                    }
#pragma unroll
                    for (int pp = 0; pp < 2; pp++)
#pragma unroll
                        for (int e = 0; e < 4; e++)
                            o[4 * (e & 1) + 2 * pp + (e >> 1)] =
                                bmul2(u[8 * m + 4 * pp + e], bfma2(g2[pp][e], d2[pp][e >> 1], bfma2(g1[pp][e], d[pp][2 + (e >> 1)], bmul2(g0[pp][e], d[pp][e >> 1]))));
                    stg4(ucp + 32 * m, o[0], o[1], o[2], o[3]);
                    stg4(ucp + 32 * m + 8 * D_, o[4], o[5], o[6], o[7]);
                }
                bar_sync(2, 256);
                if (tid == 128) {
                    mbar_wait(sb + B_XA, 0);
                    mbar_expect_tx(sb + B_KV, 65536);
                    tma4(sb + R0, &mp.xa, 0, 128, 0, b, sb + B_KV);
                }
            }
            PT(3 + 3 * pass);
        }
        int s = 1, ph = 0;
        fresh(acc);
#pragma unroll 1
        for (int j = 0; j < NKV; j++) {
            mbar_wait(sb + B_P + s * 8, ph);
            PL(j, 0);
            if (j > 0) {
                const float sc0 = lds_f32(sb + SCL + s * 256 + r0 * 4), sc1 = lds_f32(sb + SCL + s * 256 + r0 * 4 + 32);
                if (__any_sync(0xffffffffu, sc0 != 1.f || sc1 != 1.f)) {
#pragma unroll
                    for (int n = 0; n < 32; n++) { acc[4 * n] *= sc0; acc[4 * n + 1] *= sc0; acc[4 * n + 2] *= sc1; acc[4 * n + 3] *= sc1; }
                }
            }
            mbar_wait(sb + B_GO + s * 8, ph);
            PL(j, 1);
            const uint32_t vd = sd + s * 4096 + h * 2048, pd = sd + (s == 0 ? 2 : s - 1) * 512;
            pin(acc);
            wg_fence();
#pragma unroll
            for (int kk = 0; kk < 4; kk++) wgmma_ss_n256_tb1(acc, dsc(pd, R3 + kk * 32, 16), dsc(vd, kk * 2048, 8192), 1);
            wg_commit();
            wg_wait<0>();
            pin(acc);
            PL(j, 2);
            if (w0 && elect1()) {
                if (j == NKV - 5 && mode == 0) flag_wait(&g_sync[3], 4);
                if (atom_inc_s(sb + CNT + 4 * s) & 1) {
                    if (j + 3 < NKV) {
                        mbar_expect_tx(sb + B_KV + s * 8, 65536);
                        tma4(sb + s * 65536, &mp.xa, 0, 64 * (j + 3), 0, b, sb + B_KV + s * 8);
                    } else if (j < NKV - 1) {
                        const int n0 = j == NKV - 3 ? 0 : 8, n1 = n0 + 8;
#pragma unroll 1
                        for (int n = n0; n < n1; n++) ring_ld(sb, n * 8, n);
                    }
                }
            }
            if (++s == 3) s = 0;
            if (s == 1) ph ^= 1;
        }
        {
            const float i0 = lds_f32(sb + LINV + r0 * 4), i1 = lds_f32(sb + LINV + r0 * 4 + 32);
#pragma unroll
            for (int p = 0; p < 16; p++)
                stsm4(((sb + R0 + h * 32768 + loff) ^ ((p & 3) << 5)) + (p >> 2) * 8192,
                      pack2(acc[8 * p] * i0, acc[8 * p + 1] * i0), pack2(acc[8 * p + 2] * i1, acc[8 * p + 3] * i1),
                      pack2(acc[8 * p + 4] * i0, acc[8 * p + 5] * i0), pack2(acc[8 * p + 6] * i1, acc[8 * p + 7] * i1));
        }
        fence_async();
        fence_async_g();
        bar_sync(2, 256);
        if (lane == 0 && w < 2) ring_ld(sb, 128 + 16 * w + 8 * h, 16 + 2 * w + h);
        PT(7);
        fresh(acc);
        {
            uint32_t slot8 = 8 * h, par = 0, prev8 = 0;
#pragma unroll 1
            for (int kk = 0; kk < 64; kk++) {
                if (kk == 32 || kk == 48) mbar_wait(sb + B_UC + (kk >> 1 & 8), 0);
                mbar_wait(sb + B_R2 + slot8, par);
                wg_fence();
                wgmma_ss_n256_tb1(acc, mkd(sd + (1u << 16) + (R0 >> 4) + (kk >> 2 & 7) * 512 + (kk & 3) * 2), mkd(bd2k + slot8 * 64), 1);
                wg_commit();
                wg_wait<1>();
                if (kk > 0 && lane == 0) mbar_arrive(sb + B_E2 + prev8);
                if ((kk == 16 || kk == 32) && w0 && elect1() && (atom_inc_s(sb + CNT + 12 + (kk >> 3 & 4)) & 1)) {
                    mbar_expect_tx(sb + B_UC + (kk >> 2 & 8), 32768);
                    tma3(sb + R0 + (kk & 32) * 1024, &mp.uc, 0, 64 * blockIdx.x, kk >> 3 & 4, sb + B_UC + (kk >> 2 & 8));
                }
                prev8 = slot8;
                slot8 += 16;
                if (slot8 >= 160) { slot8 -= 160; par ^= 1; }
            }
        }
        wg_wait<0>();
        pin(acc);
        PT(8);
        mbar_wait(sb + B_X, 0);
        PT(9);
        {
            const uint32_t sr = (lrow + 63) & 63;
            const uint32_t xoff = sr * 128 + ((((lane >> 4) ^ sr) & 7) << 4);
#pragma unroll
            for (int p = 0; p < 16; p++) {
                const uint32_t a = ((sb + R2 + h * 32768 + xoff) ^ ((p & 3) << 5)) + (p >> 2) * 8192;
                uint32_t xv[4];
                ldsm4(a, xv);
#pragma unroll
                for (int e = 0; e < 4; e++)
                    xv[e] = pack2(acc[8 * p + 2 * e] + __uint_as_float(xv[e] << 16), acc[8 * p + 2 * e + 1] + __uint_as_float(xv[e] & 0xffff0000u));
                stsm4(a, xv[0], xv[1], xv[2], xv[3]);
            }
        }
        fence_async();
        bar_sync(3 + h, 128);
        if (el) {
            for (int c = 0; c < 4; c++) tma4_store(&mp.out, sb + R2 + (4 * h + c) * 8192, 0, 62 * ti, 4 * h + c, b);
            asm volatile("cp.async.bulk.commit_group;" ::: "memory");
            PT(10);
            if (h == 0) cta_done(mode);
            asm volatile("cp.async.bulk.wait_group.read 0;" ::: "memory");
        }
        PT(11);
        PG(201);
        PDUMP();
    }
}

typedef CUresult (*PFN_enc)(CUtensorMap*, CUtensorMapDataType, cuuint32_t, void*, const cuuint64_t*, const cuuint64_t*,
                            const cuuint32_t*, const cuuint32_t*, CUtensorMapInterleave, CUtensorMapSwizzle,
                            CUtensorMapL2promotion, CUtensorMapFloatOOBfill);

static void enc(PFN_enc f, CUtensorMap* m, void* base, int rank, const cuuint64_t* dims, const cuuint64_t* strides, const cuuint32_t* box) {
    cuuint32_t es[5] = {1, 1, 1, 1, 1};
    f(m, CU_TENSOR_MAP_DATA_TYPE_BFLOAT16, rank, base, dims, strides, box, es, CU_TENSOR_MAP_INTERLEAVE_NONE,
      CU_TENSOR_MAP_SWIZZLE_128B, CU_TENSOR_MAP_L2_PROMOTION_L2_256B, CU_TENSOR_MAP_FLOAT_OOB_FILL_NONE);
}
static void enc_act(PFN_enc f, CUtensorMap* m, void* base, int rows, int chunks, int trows = T_, int pitch = T_) {
    cuuint64_t dims[4] = {64, (cuuint64_t)trows, 8, (cuuint64_t)NB_};
    cuuint64_t st[3] = {1024, 128, (cuuint64_t)pitch * 1024};
    cuuint32_t box[4] = {64, (cuuint32_t)rows, (cuuint32_t)chunks, 1};
    enc(f, m, base, 4, dims, st, box);
}
static void enc_w(PFN_enc f, CUtensorMap* m, void* base, int krows, int ncols, int bk, int bc) {
    cuuint64_t dims[3] = {64, (cuuint64_t)krows, (cuuint64_t)(ncols / 64)};
    cuuint64_t st[2] = {(cuuint64_t)ncols * 2, 128};
    cuuint32_t box[3] = {64, (cuuint32_t)bk, (cuuint32_t)bc};
    enc(f, m, base, 3, dims, st, box);
}

extern "C" void kernel_launch(void* const* d_in, const int* in_sizes, int n_in, void* d_out, int out_size) {
    const bf16* x = (const bf16*)d_in[0];
    static PFN_enc fenc = nullptr;
    static void *p_xa, *p_mqk, *p_uc, *p_t1;
    static int fused = 0;
    if (!fenc) {
        void* fn = nullptr;
        cudaDriverEntryPointQueryResult qr;
        cudaGetDriverEntryPoint("cuTensorMapEncodeTiled", &fn, cudaEnableDefault, &qr);
        fenc = (PFN_enc)fn;
        cudaGetSymbolAddress(&p_xa, g_xa);
        cudaGetSymbolAddress(&p_mqk, g_mqk);
        cudaGetSymbolAddress(&p_uc, g_uc);
        cudaGetSymbolAddress(&p_t1, g_t1);
        cudaFuncSetAttribute(main_kernel, cudaFuncAttributeMaxDynamicSharedMemorySize, SMEM_BYTES);
        int dev = 0, sms = 0, occ = 0;
        cudaGetDevice(&dev);
        cudaDeviceGetAttribute(&sms, cudaDevAttrMultiProcessorCount, dev);
        cudaOccupancyMaxActiveBlocksPerMultiprocessor(&occ, main_kernel, 384, SMEM_BYTES);
        fused = sms * occ >= NCTA + 2;
    }
    Maps mp;
    enc_act(fenc, &mp.xa, (char*)p_xa + 1024, 64, 8, T_, T_ + 8);
    enc_act(fenc, &mp.xa2, (char*)p_xa + 1024, 64, 2, T_, T_ + 8);
    enc_act(fenc, &mp.xas, p_xa, 64, 1, T_ + 1, T_ + 8);
    enc_act(fenc, &mp.x, (void*)x, 64, 1);
    enc_act(fenc, &mp.out, d_out, 62, 1);
    enc_w(fenc, &mp.wup4, d_in[5], 512, 1024, 16, 4);
    enc_w(fenc, &mp.wup8, d_in[5], 512, 1024, 16, 8);
    enc_w(fenc, &mp.mqa2, p_mqk, 512, 512, 32, 2);
    enc_w(fenc, &mp.mqa4, p_mqk, 512, 512, 32, 4);
    enc_w(fenc, &mp.mqb1, p_mqk, 512, 512, 64, 1);
    enc_w(fenc, &mp.mqb2, p_mqk, 512, 512, 64, 2);
    enc_w(fenc, &mp.uc, p_uc, NCTA * 64, 512, 64, 4);
    enc_w(fenc, &mp.wq, d_in[1], 512, 512, 64, 8);
    enc_w(fenc, &mp.wk, d_in[2], 512, 512, 32, 8);
    enc_w(fenc, &mp.fa[0], d_in[3], 512, 512, 128, 1);
    enc_w(fenc, &mp.fa[1], d_in[7], 512, 512, 128, 1);
    enc_w(fenc, &mp.fa[2], p_t1, 512, 512, 128, 1);
    enc_w(fenc, &mp.fb[0], d_in[4], 512, 512, 64, 4);
    enc_w(fenc, &mp.fb[1], d_in[8], 1024, 512, 64, 4);
    enc_w(fenc, &mp.fc, p_t1, 512, 512, 64, 4);
    cudaStream_t st = cudaStreamPerThread;
    if (fused) {
        main_kernel<<<NCTA + 2, 384, SMEM_BYTES, st>>>(mp, x, (const bf16*)d_in[6], (const bf16*)d_in[5], 0);
    } else {
        main_kernel<<<NCTA + 2, 384, SMEM_BYTES, st>>>(mp, x, (const bf16*)d_in[6], (const bf16*)d_in[5], 1);
        main_kernel<<<NCTA + 2, 384, SMEM_BYTES, st>>>(mp, x, (const bf16*)d_in[6], (const bf16*)d_in[5], 2);
    }
}
```

```cpp
#include <cuda_runtime.h>
#include <cuda_bf16.h>
#include <cuda.h>
#include <stdint.h>

typedef __nv_bfloat16 bf16;

constexpr int T_ = 4000, D_ = 512, NB_ = 2;
constexpr int TPB = 65;
constexpr int NCTA = TPB * NB_;
constexpr int NKV = 63;

__device__ __align__(1024) bf16 g_xa[NB_ * (T_ + 8) * D_];
__device__ __align__(1024) bf16 g_mqk[D_ * D_];
__device__ __align__(1024) bf16 g_t1[D_ * D_];
__device__ __align__(1024) bf16 g_wepi[2 * D_ * D_];
__device__ __align__(1024) bf16 g_uc[NCTA * 128 * D_];
__device__ unsigned g_sync[8];

#define PT(i) do { if (el) asm volatile("st.shared.u32 [%0], %1;" ::"r"(sb + MISC + 2560), "r"((unsigned)clock())); } while (0)
#define PG(i)
#define PE()
#define PLM 15
#define PL(j, q) do { if ((PLM >> ((q) + (wg ? 4 : 0))) & 1) PT(0); } while (0)
#define PDUMP()

#define FENCE_AT 1
#define GO_AT 25
#define LAZY 8.f
#define SU 2
#define XS_GAP 800
#define PFW 1
constexpr uint32_t R0 = 0, R1 = 65536, R2 = 131072, R3 = 196608, QS = 221184, MISC = 229376;
constexpr uint32_t AT = 147456;
constexpr uint32_t SMEM_BYTES = 232448;
constexpr uint32_t B_R1 = MISC + 1856  , B_MK = MISC + 48, B_LN = MISC + 56, B_MQ = MISC + 64,
                   B_H1 = MISC + 88, B_H2 = MISC + 96, B_H3 = MISC + 104,
                   B_KV = MISC + 112, B_P = MISC + 136, B_GO = MISC + 160, B_UC = MISC + 184  ,
                   B_X = MISC + 200, CNT = MISC + 208  , SCL = MISC + 512  ,
                   LINV = MISC + 1280  , STAT = MISC + 512  ,
                   B_R2 = MISC + 1536  , B_E2 = MISC + 1696  ;

__device__ __forceinline__ uint32_t smem_u32(const void* p) { return (uint32_t)__cvta_generic_to_shared(p); }
__device__ __forceinline__ void wg_fence() { asm volatile("wgmma.fence.sync.aligned;" ::: "memory"); }
__device__ __forceinline__ void wg_commit() { asm volatile("wgmma.commit_group.sync.aligned;" ::: "memory"); }
template <int N> __device__ __forceinline__ void wg_wait() { asm volatile("wgmma.wait_group.sync.aligned %0;" ::"n"(N) : "memory"); }
__device__ __forceinline__ uint64_t dsc(uint32_t sd, uint32_t off, uint32_t lbo) {
    uint32_t lo = sd + (off >> 4) + ((lbo >> 4) << 16);
    uint64_t d;
    asm("mov.b64 %0, {%1, %2};" : "=l"(d) : "r"(lo), "r"((1024u >> 4) | (1u << 30)));
    return d;
}
__device__ __forceinline__ bool elect1() {
    uint32_t p;
    asm volatile("{\n.reg .pred p;\nelect.sync _|p, 0xffffffff;\nselp.u32 %0, 1, 0, p;\n}\n" : "=r"(p));
    return p != 0;
}
__device__ __forceinline__ void mbar_init(uint32_t bar, int cnt) { asm volatile("mbarrier.init.shared::cta.b64 [%0], %1;" ::"r"(bar), "r"(cnt) : "memory"); }
__device__ __forceinline__ void mbar_expect_tx(uint32_t bar, uint32_t bytes) { asm volatile("mbarrier.arrive.expect_tx.shared::cta.b64 _, [%0], %1;" ::"r"(bar), "r"(bytes) : "memory"); }
__device__ __forceinline__ void mbar_arrive(uint32_t bar) { asm volatile("mbarrier.arrive.shared::cta.b64 _, [%0];" ::"r"(bar) : "memory"); }
__device__ __forceinline__ void mbar_wait(uint32_t bar, uint32_t parity) {
    uint32_t ok;
#pragma unroll 1
    for (uint32_t it = 0;; ++it) {
        asm volatile("{\n.reg .pred p;\nmbarrier.try_wait.parity.shared::cta.b64 p, [%1], %2;\nselp.u32 %0, 1, 0, p;\n}\n" : "=r"(ok) : "r"(bar), "r"(parity) : "memory");
        if (ok) break;
        if (it > (1u << 20)) __trap();
    }
}
__device__ __forceinline__ void fence_async() { asm volatile("fence.proxy.async.shared::cta;" ::: "memory"); }
__device__ __forceinline__ void fence_async_g() { asm volatile("fence.proxy.async.global;" ::: "memory"); }
__device__ __forceinline__ void bar_sync(int id, int n) { asm volatile("bar.sync %0, %1;" ::"r"(id), "r"(n) : "memory"); }
__device__ __forceinline__ void tma3(uint32_t dst, const CUtensorMap* tm, int c0, int c1, int c2, uint32_t bar) {
    asm volatile("cp.async.bulk.tensor.3d.shared::cluster.global.mbarrier::complete_tx::bytes [%0], [%1, {%3, %4, %5}], [%2];"
                 ::"r"(dst), "l"(tm), "r"(bar), "r"(c0), "r"(c1), "r"(c2) : "memory");
}
__device__ __forceinline__ void tma4(uint32_t dst, const CUtensorMap* tm, int c0, int c1, int c2, int c3, uint32_t bar) {
    asm volatile("cp.async.bulk.tensor.4d.shared::cluster.global.mbarrier::complete_tx::bytes [%0], [%1, {%3, %4, %5, %6}], [%2];"
                 ::"r"(dst), "l"(tm), "r"(bar), "r"(c0), "r"(c1), "r"(c2), "r"(c3) : "memory");
}
__device__ __forceinline__ void tma4_store(const CUtensorMap* tm, uint32_t src, int c0, int c1, int c2, int c3) {
    asm volatile("cp.async.bulk.tensor.4d.global.shared::cta.bulk_group [%0, {%2, %3, %4, %5}], [%1];"
                 ::"l"(tm), "r"(src), "r"(c0), "r"(c1), "r"(c2), "r"(c3) : "memory");
}
__device__ __forceinline__ void tma3_store(const CUtensorMap* tm, uint32_t src, int c0, int c1, int c2) {
    asm volatile("cp.async.bulk.tensor.3d.global.shared::cta.bulk_group [%0, {%2, %3, %4}], [%1];"
                 ::"l"(tm), "r"(src), "r"(c0), "r"(c1), "r"(c2) : "memory");
}
__device__ __forceinline__ void stsm4(uint32_t addr, uint32_t a, uint32_t b, uint32_t c, uint32_t d) {
    asm volatile("stmatrix.sync.aligned.m8n8.x4.shared.b16 [%0], {%1, %2, %3, %4};" ::"r"(addr), "r"(a), "r"(b), "r"(c), "r"(d) : "memory");
}
__device__ __forceinline__ void ldsm4(uint32_t addr, uint32_t (&r)[4]) {
    asm volatile("ldmatrix.sync.aligned.m8n8.x4.shared.b16 {%0, %1, %2, %3}, [%4];" : "=r"(r[0]), "=r"(r[1]), "=r"(r[2]), "=r"(r[3]) : "r"(addr) : "memory");
}
__device__ __forceinline__ void ldsm2(uint32_t addr, uint32_t (&r)[2]) {
    asm volatile("ldmatrix.sync.aligned.m8n8.x2.shared.b16 {%0, %1}, [%2];" : "=r"(r[0]), "=r"(r[1]) : "r"(addr) : "memory");
}
__device__ __forceinline__ void stg4(void* p, uint32_t a, uint32_t b, uint32_t c, uint32_t d) {
    asm volatile("st.global.v4.u32 [%0], {%1, %2, %3, %4};" ::"l"(p), "r"(a), "r"(b), "r"(c), "r"(d) : "memory");
}
__device__ __forceinline__ void hmma(float (&c)[4], uint32_t a0, uint32_t a1, uint32_t a2, uint32_t a3, uint32_t b0, uint32_t b1) {
    asm("mma.sync.aligned.m16n8k16.row.col.f32.bf16.bf16.f32 {%0, %1, %2, %3}, {%4, %5, %6, %7}, {%8, %9}, {%0, %1, %2, %3};"
        : "+f"(c[0]), "+f"(c[1]), "+f"(c[2]), "+f"(c[3]) : "r"(a0), "r"(a1), "r"(a2), "r"(a3), "r"(b0), "r"(b1));
}
__device__ __forceinline__ uint32_t pack2(float lo, float hi) {
    uint32_t r;
    asm("cvt.rn.bf16x2.f32 %0, %1, %2;" : "=r"(r) : "f"(hi), "f"(lo));
    return r;
}
__device__ __forceinline__ uint32_t pack2v(float lo, float hi) {
    uint32_t r;
    asm volatile("cvt.rn.bf16x2.f32 %0, %1, %2;" : "=r"(r) : "f"(hi), "f"(lo));
    return r;
}
__device__ __forceinline__ uint32_t bmul2(uint32_t a, uint32_t b) { uint32_t r; asm("mul.rn.bf16x2 %0, %1, %2;" : "=r"(r) : "r"(a), "r"(b)); return r; }
__device__ __forceinline__ uint32_t bfma2(uint32_t a, uint32_t b, uint32_t c) { uint32_t r; asm("fma.rn.bf16x2 %0, %1, %2, %3;" : "=r"(r) : "r"(a), "r"(b), "r"(c)); return r; }
__device__ __forceinline__ float ex2(float x) { float r; asm("ex2.approx.ftz.f32 %0, %1;" : "=f"(r) : "f"(x)); return r; }
__device__ __forceinline__ float rcp(float x) { float r; asm("rcp.approx.ftz.f32 %0, %1;" : "=f"(r) : "f"(x)); return r; }
__device__ __forceinline__ float gelu2(float x) {
    float t = fmaf(x * x, 0.044715f * 0.7978845608028654f, 0.7978845608028654f), th;
    asm("tanh.approx.f32 %0, %1;" : "=f"(th) : "f"(x * t));
    return fmaf(x, th, x);
}
__device__ __forceinline__ uint32_t ldg_v(const uint32_t* p) { uint32_t v; asm volatile("ld.global.nc.u32 %0, [%1];" : "=r"(v) : "l"(p)); return v; }
__device__ __forceinline__ uint32_t ldg_cg(const uint32_t* p) { uint32_t v; asm volatile("ld.global.cg.u32 %0, [%1];" : "=r"(v) : "l"(p) : "memory"); return v; }
__device__ __forceinline__ float lds_f32(uint32_t a) { float v; asm volatile("ld.shared.f32 %0, [%1];" : "=f"(v) : "r"(a) : "memory"); return v; }
__device__ __forceinline__ void sts_f32(uint32_t a, float v) { asm volatile("st.shared.f32 [%0], %1;" ::"r"(a), "f"(v) : "memory"); }
__device__ __forceinline__ uint32_t atom_inc_s(uint32_t a) { uint32_t v; asm volatile("atom.relaxed.cta.shared.add.u32 %0, [%1], 1;" : "=r"(v) : "r"(a) : "memory"); return v; }
__device__ __forceinline__ void lds4(uint32_t a, uint32_t* r) {
    asm volatile("ld.shared.v4.u32 {%0, %1, %2, %3}, [%4];" : "=r"(r[0]), "=r"(r[1]), "=r"(r[2]), "=r"(r[3]) : "r"(a) : "memory");
}
__device__ __forceinline__ void sts4(uint32_t a, uint32_t x, uint32_t y, uint32_t z, uint32_t t) {
    asm volatile("st.shared.v4.u32 [%0], {%1, %2, %3, %4};" ::"r"(a), "r"(x), "r"(y), "r"(z), "r"(t) : "memory");
}
__device__ __forceinline__ uint32_t bsub2(uint32_t a, uint32_t b) { uint32_t r; asm("sub.rn.bf16x2 %0, %1, %2;" : "=r"(r) : "r"(a), "r"(b)); return r; }
__device__ __forceinline__ float blo(uint32_t v) { return __uint_as_float(v << 16); }
__device__ __forceinline__ float bhi(uint32_t v) { return __uint_as_float(v & 0xffff0000u); }
__device__ __forceinline__ float bfr(float x) { return __bfloat162float(__float2bfloat16_rn(x)); }
__device__ __forceinline__ void l2_prefetch(const void* p, uint32_t bytes) { asm volatile("cp.async.bulk.prefetch.L2.global [%0], %1;" ::"l"(p), "r"(bytes) : "memory"); }
__device__ __forceinline__ void flag_add(unsigned* p) { asm volatile("red.release.gpu.global.add.u32 [%0], 1;" ::"l"(p) : "memory"); }
__device__ __forceinline__ void flag_wait(const unsigned* p, unsigned target) {
#pragma unroll 1
    for (uint32_t it = 0;; ++it) {
        unsigned v;
        asm volatile("ld.acquire.gpu.global.u32 %0, [%1];" : "=r"(v) : "l"(p) : "memory");
        if (v >= target) break;
        if (it > (1u << 20)) __trap();
    }
    fence_async_g();
}
template <int N> __device__ __forceinline__ void pin(float (&a)[N]) {
#pragma unroll
    for (int i = 0; i < N; i++) asm volatile("" : "+f"(a[i])::"memory");
}

template <int N> __device__ __forceinline__ void fresh(float (&a)[N]) {
#pragma unroll
    for (int i = 0; i < N; i++) a[i] = 0.f;
    pin(a);
}

__device__ __forceinline__ void wgmma_rs_n64_tb0(float (&d)[32], uint32_t a0, uint32_t a1, uint32_t a2, uint32_t a3, uint64_t db, int scale_d) {
    asm volatile("{\n.reg .pred p;\nsetp.ne.b32 p, %37, 0;\n"
        "wgmma.mma_async.sync.aligned.m64n64k16.f32.bf16.bf16 {%0, %1, %2, %3, %4, %5, %6, %7, %8, %9, %10, %11, %12, %13, %14, %15, %16, %17, %18, %19, %20, %21, %22, %23, %24, %25, %26, %27, %28, %29, %30, %31}, {%32, %33, %34, %35}, %36, p, 1, 1, 0;\n}\n"
        : "+f"(d[0]), "+f"(d[1]), "+f"(d[2]), "+f"(d[3]), "+f"(d[4]), "+f"(d[5]), "+f"(d[6]), "+f"(d[7]), "+f"(d[8]), "+f"(d[9]), "+f"(d[10]), "+f"(d[11]), "+f"(d[12]), "+f"(d[13]), "+f"(d[14]), "+f"(d[15]), "+f"(d[16]), "+f"(d[17]), "+f"(d[18]), "+f"(d[19]), "+f"(d[20]), "+f"(d[21]), "+f"(d[22]), "+f"(d[23]), "+f"(d[24]), "+f"(d[25]), "+f"(d[26]), "+f"(d[27]), "+f"(d[28]), "+f"(d[29]), "+f"(d[30]), "+f"(d[31])
        : "r"(a0), "r"(a1), "r"(a2), "r"(a3), "l"(db), "r"(scale_d));
}

__device__ __forceinline__ void wgmma_ss_n128_tb1(float (&d)[64], uint64_t da, uint64_t db, int scale_d) {
    asm volatile("{\n.reg .pred p;\nsetp.ne.b32 p, %66, 0;\n"
        "wgmma.mma_async.sync.aligned.m64n128k16.f32.bf16.bf16 {%0, %1, %2, %3, %4, %5, %6, %7, %8, %9, %10, %11, %12, %13, %14, %15, %16, %17, %18, %19, %20, %21, %22, %23, %24, %25, %26, %27, %28, %29, %30, %31, %32, %33, %34, %35, %36, %37, %38, %39, %40, %41, %42, %43, %44, %45, %46, %47, %48, %49, %50, %51, %52, %53, %54, %55, %56, %57, %58, %59, %60, %61, %62, %63}, %64, %65, p, 1, 1, 0, 1;\n}\n"
        : "+f"(d[0]), "+f"(d[1]), "+f"(d[2]), "+f"(d[3]), "+f"(d[4]), "+f"(d[5]), "+f"(d[6]), "+f"(d[7]), "+f"(d[8]), "+f"(d[9]), "+f"(d[10]), "+f"(d[11]), "+f"(d[12]), "+f"(d[13]), "+f"(d[14]), "+f"(d[15]), "+f"(d[16]), "+f"(d[17]), "+f"(d[18]), "+f"(d[19]), "+f"(d[20]), "+f"(d[21]), "+f"(d[22]), "+f"(d[23]), "+f"(d[24]), "+f"(d[25]), "+f"(d[26]), "+f"(d[27]), "+f"(d[28]), "+f"(d[29]), "+f"(d[30]), "+f"(d[31]), "+f"(d[32]), "+f"(d[33]), "+f"(d[34]), "+f"(d[35]), "+f"(d[36]), "+f"(d[37]), "+f"(d[38]), "+f"(d[39]), "+f"(d[40]), "+f"(d[41]), "+f"(d[42]), "+f"(d[43]), "+f"(d[44]), "+f"(d[45]), "+f"(d[46]), "+f"(d[47]), "+f"(d[48]), "+f"(d[49]), "+f"(d[50]), "+f"(d[51]), "+f"(d[52]), "+f"(d[53]), "+f"(d[54]), "+f"(d[55]), "+f"(d[56]), "+f"(d[57]), "+f"(d[58]), "+f"(d[59]), "+f"(d[60]), "+f"(d[61]), "+f"(d[62]), "+f"(d[63])
        : "l"(da), "l"(db), "r"(scale_d));
}

__device__ __forceinline__ void wgmma_ss_n256_tb1(float (&d)[128], uint64_t da, uint64_t db, int scale_d) {
    asm volatile("{\n.reg .pred p;\nsetp.ne.b32 p, %130, 0;\n"
        "wgmma.mma_async.sync.aligned.m64n256k16.f32.bf16.bf16 {%0, %1, %2, %3, %4, %5, %6, %7, %8, %9, %10, %11, %12, %13, %14, %15, %16, %17, %18, %19, %20, %21, %22, %23, %24, %25, %26, %27, %28, %29, %30, %31, %32, %33, %34, %35, %36, %37, %38, %39, %40, %41, %42, %43, %44, %45, %46, %47, %48, %49, %50, %51, %52, %53, %54, %55, %56, %57, %58, %59, %60, %61, %62, %63, %64, %65, %66, %67, %68, %69, %70, %71, %72, %73, %74, %75, %76, %77, %78, %79, %80, %81, %82, %83, %84, %85, %86, %87, %88, %89, %90, %91, %92, %93, %94, %95, %96, %97, %98, %99, %100, %101, %102, %103, %104, %105, %106, %107, %108, %109, %110, %111, %112, %113, %114, %115, %116, %117, %118, %119, %120, %121, %122, %123, %124, %125, %126, %127}, %128, %129, p, 1, 1, 0, 1;\n}\n"
        : "+f"(d[0]), "+f"(d[1]), "+f"(d[2]), "+f"(d[3]), "+f"(d[4]), "+f"(d[5]), "+f"(d[6]), "+f"(d[7]), "+f"(d[8]), "+f"(d[9]), "+f"(d[10]), "+f"(d[11]), "+f"(d[12]), "+f"(d[13]), "+f"(d[14]), "+f"(d[15]), "+f"(d[16]), "+f"(d[17]), "+f"(d[18]), "+f"(d[19]), "+f"(d[20]), "+f"(d[21]), "+f"(d[22]), "+f"(d[23]), "+f"(d[24]), "+f"(d[25]), "+f"(d[26]), "+f"(d[27]), "+f"(d[28]), "+f"(d[29]), "+f"(d[30]), "+f"(d[31]), "+f"(d[32]), "+f"(d[33]), "+f"(d[34]), "+f"(d[35]), "+f"(d[36]), "+f"(d[37]), "+f"(d[38]), "+f"(d[39]), "+f"(d[40]), "+f"(d[41]), "+f"(d[42]), "+f"(d[43]), "+f"(d[44]), "+f"(d[45]), "+f"(d[46]), "+f"(d[47]), "+f"(d[48]), "+f"(d[49]), "+f"(d[50]), "+f"(d[51]), "+f"(d[52]), "+f"(d[53]), "+f"(d[54]), "+f"(d[55]), "+f"(d[56]), "+f"(d[57]), "+f"(d[58]), "+f"(d[59]), "+f"(d[60]), "+f"(d[61]), "+f"(d[62]), "+f"(d[63]), "+f"(d[64]), "+f"(d[65]), "+f"(d[66]), "+f"(d[67]), "+f"(d[68]), "+f"(d[69]), "+f"(d[70]), "+f"(d[71]), "+f"(d[72]), "+f"(d[73]), "+f"(d[74]), "+f"(d[75]), "+f"(d[76]), "+f"(d[77]), "+f"(d[78]), "+f"(d[79]), "+f"(d[80]), "+f"(d[81]), "+f"(d[82]), "+f"(d[83]), "+f"(d[84]), "+f"(d[85]), "+f"(d[86]), "+f"(d[87]), "+f"(d[88]), "+f"(d[89]), "+f"(d[90]), "+f"(d[91]), "+f"(d[92]), "+f"(d[93]), "+f"(d[94]), "+f"(d[95]), "+f"(d[96]), "+f"(d[97]), "+f"(d[98]), "+f"(d[99]), "+f"(d[100]), "+f"(d[101]), "+f"(d[102]), "+f"(d[103]), "+f"(d[104]), "+f"(d[105]), "+f"(d[106]), "+f"(d[107]), "+f"(d[108]), "+f"(d[109]), "+f"(d[110]), "+f"(d[111]), "+f"(d[112]), "+f"(d[113]), "+f"(d[114]), "+f"(d[115]), "+f"(d[116]), "+f"(d[117]), "+f"(d[118]), "+f"(d[119]), "+f"(d[120]), "+f"(d[121]), "+f"(d[122]), "+f"(d[123]), "+f"(d[124]), "+f"(d[125]), "+f"(d[126]), "+f"(d[127])
        : "l"(da), "l"(db), "r"(scale_d));
}

__device__ __forceinline__ void wgmma_ss_n32_tb0(float (&d)[16], uint64_t da, uint64_t db, int scale_d) {
    asm volatile("{\n.reg .pred p;\nsetp.ne.b32 p, %18, 0;\n"
        "wgmma.mma_async.sync.aligned.m64n32k16.f32.bf16.bf16 {%0, %1, %2, %3, %4, %5, %6, %7, %8, %9, %10, %11, %12, %13, %14, %15}, %16, %17, p, 1, 1, 0, 0;\n}\n"
        : "+f"(d[0]), "+f"(d[1]), "+f"(d[2]), "+f"(d[3]), "+f"(d[4]), "+f"(d[5]), "+f"(d[6]), "+f"(d[7]), "+f"(d[8]), "+f"(d[9]), "+f"(d[10]), "+f"(d[11]), "+f"(d[12]), "+f"(d[13]), "+f"(d[14]), "+f"(d[15])
        : "l"(da), "l"(db), "r"(scale_d));
}

__device__ __forceinline__ void wgmma_ss_n64_tb0(float (&d)[32], uint64_t da, uint64_t db, int scale_d) {
    asm volatile("{\n.reg .pred p;\nsetp.ne.b32 p, %34, 0;\n"
        "wgmma.mma_async.sync.aligned.m64n64k16.f32.bf16.bf16 {%0, %1, %2, %3, %4, %5, %6, %7, %8, %9, %10, %11, %12, %13, %14, %15, %16, %17, %18, %19, %20, %21, %22, %23, %24, %25, %26, %27, %28, %29, %30, %31}, %32, %33, p, 1, 1, 0, 0;\n}\n"
        : "+f"(d[0]), "+f"(d[1]), "+f"(d[2]), "+f"(d[3]), "+f"(d[4]), "+f"(d[5]), "+f"(d[6]), "+f"(d[7]), "+f"(d[8]), "+f"(d[9]), "+f"(d[10]), "+f"(d[11]), "+f"(d[12]), "+f"(d[13]), "+f"(d[14]), "+f"(d[15]), "+f"(d[16]), "+f"(d[17]), "+f"(d[18]), "+f"(d[19]), "+f"(d[20]), "+f"(d[21]), "+f"(d[22]), "+f"(d[23]), "+f"(d[24]), "+f"(d[25]), "+f"(d[26]), "+f"(d[27]), "+f"(d[28]), "+f"(d[29]), "+f"(d[30]), "+f"(d[31])
        : "l"(da), "l"(db), "r"(scale_d));
}

struct Maps {
    CUtensorMap xa, xa2, xas, wup4, wup8, mqa2, mqa4, mqb1, mqb2, uc, x, out, wq, wk, fa[3], fb[2], fc;
};

__device__ __forceinline__ uint64_t mkd(uint32_t lo) {
    uint64_t d;
    asm("mov.b64 %0, {%1, %2};" : "=l"(d) : "r"(lo), "r"((1024u >> 4) | (1u << 30)));
    return d;
}
__device__ __forceinline__ void bulk_ld(uint32_t dst, const void* src, uint32_t bytes, uint32_t bar) {
    asm volatile("cp.async.bulk.shared::cluster.global.mbarrier::complete_tx::bytes [%0], [%1], %2, [%3];" ::"r"(dst), "l"(src), "r"(bytes), "r"(bar) : "memory");
}
__device__ __forceinline__ void bulk_st(void* dst, uint32_t src, uint32_t bytes) {
    asm volatile("cp.async.bulk.global.shared::cta.bulk_group [%0], [%1], %2;" ::"l"(dst), "r"(src), "r"(bytes) : "memory");
}
__device__ __forceinline__ void ring_ld(uint32_t sb, uint32_t slot8, int n) {
    mbar_expect_tx(sb + B_R2 + slot8, 8192);
    bulk_ld(sb + R1 + slot8 * 1024, (const char*)g_wepi + n * 8192, 8192, sb + B_R2 + slot8);
}

__device__ __forceinline__ void ring_half(uint32_t sb, uint32_t slot8, uint32_t hoff, const CUtensorMap* tm, int c1, int c2) {
    mbar_expect_tx(sb + B_R1 + slot8, 8192);
    tma3(sb + slot8 * 2048 + hoff, tm, 0, c1, c2, sb + B_R1 + slot8);
}
__device__ __forceinline__ void ring_full(uint32_t sb, uint32_t slot8, const CUtensorMap* tm, int c1, int c2) {
    mbar_expect_tx(sb + B_R1 + slot8, 16384);
    mbar_arrive(sb + B_R1 + slot8);
    tma3(sb + slot8 * 2048, tm, 0, c1, c2, sb + B_R1 + slot8);
}
__device__ __forceinline__ void cta_done(int mode) {
    if (mode == 0 && atomicAdd(&g_sync[4], 1) == NCTA + 1) {
#pragma unroll
        for (int i = 0; i < 5; i++) g_sync[i] = 0;
    }
}

__device__ __forceinline__ void fold_cta(const Maps& mp, uint32_t sb, int mode) {
    constexpr uint32_t F_FULL = MISC, F_EMPTY = MISC + 32, F_T1 = MISC + 64, STG = 49152, FOUT = 3 * STG;
    const int tid = threadIdx.x, f = blockIdx.x - NCTA;
    if (mode == 2) return;
    if (tid == 0) {
        for (int i = 0; i < 3; i++) { mbar_init(sb + F_FULL + 8 * i, 1); mbar_init(sb + F_EMPTY + 8 * i, 2); }
        mbar_init(sb + F_T1, 2);
        asm volatile("fence.mbarrier_init.release.cluster;" ::: "memory");
        fence_async();
    }
    __syncthreads();
    const int wg = __shfl_sync(0xffffffffu, tid >> 7, 0);
    int st = 0, ph = 0;
    if (wg == 0) {
        if (tid == 0) {
#pragma unroll 1
            for (int it = 0; it < 96; it++) {
                const int p = it >> 3, kc = it & 7, job = p >> 2;
                if (it == 64) mbar_wait(sb + F_T1, 0);
                mbar_wait(sb + F_EMPTY + 8 * st, ph ^ 1);
                mbar_expect_tx(sb + F_FULL + 8 * st, STG);
                tma3(sb + st * STG, &mp.fa[job], 0, 256 * f + 128 * ((p >> 1) & 1), kc, sb + F_FULL + 8 * st);
                tma3(sb + st * STG + 16384, &mp.fb[job != 0], 0, 64 * kc + (job == 1 ? 512 : 0), 4 * (p & 1), sb + F_FULL + 8 * st);
                if (++st == 3) { st = 0; ph ^= 1; }
            }
        }
        return;
    }
    const int h = wg - 1, lane = tid & 31, w = (tid >> 5) & 3;
    const uint32_t sd = (sb & 0x3FFFF) >> 4;
    const bool el = (tid & 127) == 0;
#pragma unroll 1
    for (int p = 0; p < 12; p++) {
        float acc[128];
        fresh(acc);
#pragma unroll 1
        for (int kc = 0; kc < 8; kc++) {
            mbar_wait(sb + F_FULL + 8 * st, ph);
            wg_fence();
#pragma unroll
            for (int kk = 0; kk < 4; kk++)
                wgmma_ss_n256_tb1(acc, dsc(sd, st * STG + h * 8192 + kk * 32, 16), dsc(sd, st * STG + 16384 + kk * 2048, 8192), 1);
            wg_commit();
            wg_wait<0>();
            if (el) mbar_arrive(sb + F_EMPTY + 8 * st);
            if (++st == 3) { st = 0; ph ^= 1; }
        }
        pin(acc);
        const int job = p >> 2;
        if (el) {
            asm volatile("cp.async.bulk.wait_group 0;" ::: "memory");
            if (p == 4) { fence_async_g(); mbar_arrive(sb + F_T1); }
        }
        bar_sync(3 + h, 128);
        uint32_t r = 16 * w + (lane & 7) + ((lane >> 3) & 1) * 8;
        const float fs = job == 1 ? 0.5f : 1.f;
        if (job == 1) r = (r & ~31) | (((r >> 1) & 3) << 3) | (((r >> 3) & 3) << 1) | (r & 1);
        const uint32_t oa = sb + FOUT + h * 32768 + r * 128 + ((((lane >> 4) ^ r) & 7) << 4);
#pragma unroll
        for (int i = 0; i < 16; i++)
            stsm4((oa ^ ((i & 3) << 5)) + (i >> 2) * 8192, pack2(acc[8 * i] * fs, acc[8 * i + 1] * fs), pack2(acc[8 * i + 2] * fs, acc[8 * i + 3] * fs),
                  pack2(acc[8 * i + 4] * fs, acc[8 * i + 5] * fs), pack2(acc[8 * i + 6] * fs, acc[8 * i + 7] * fs));
        fence_async();
        bar_sync(3 + h, 128);
        if (el) {
            const int row0 = 256 * f + 128 * ((p >> 1) & 1) + 64 * h + (job == 1 ? 512 : 0);
            if (job == 0) tma3_store(&mp.fc, sb + FOUT + h * 32768, 0, row0, 4 * (p & 1));
            else {
#pragma unroll 1
                for (int i = 0; i < 16; i++)
                    bulk_st((char*)g_wepi + (row0 / 8 + 2 * (i & 3) + (p & 1)) * 8192 + (i >> 2) * 2048, sb + FOUT + h * 32768 + i * 2048, 2048);
            }
            asm volatile("cp.async.bulk.commit_group;" ::: "memory");
        }
    }
    if (el) {
        asm volatile("cp.async.bulk.wait_group 0;" ::: "memory");
        fence_async_g();
        if (mode == 0) flag_add(&g_sync[3]);
    }
    bar_sync(2, 256);
    if (tid == 128) cta_done(mode);
}

__global__ void __launch_bounds__(384, 1) main_kernel(const __grid_constant__ Maps mp, const bf16* __restrict__ x, const bf16* __restrict__ dw, const bf16* wup, const int mode) {
    extern __shared__ __align__(1024) uint8_t smem[];
    const uint32_t sb = smem_u32(smem);
    const int tid = threadIdx.x;
    PE();
    if (blockIdx.x >= NCTA) { fold_cta(mp, sb, mode); return; }
    const int b = blockIdx.x / TPB, ti = blockIdx.x % TPB;
    const int piece = blockIdx.x & 127;
    const int wg = __shfl_sync(0xffffffffu, tid >> 7, 0);
    const int lane = tid & 31, w = (tid >> 5) & 3;
    const bool w0 = __shfl_sync(0xffffffffu, w, 0) == 0;
    const uint32_t sd = (sb & 0x3FFFF) >> 4;
    const uint32_t adA = sd + (AT >> 4) + (1u << 16);
    const uint32_t bd0 = sd;
    const uint32_t bd2k = bd0 + ((2048u >> 4) << 16);
    const bool el = (tid & 127) == 0;
    const uint32_t lrow = 16 * w + (lane & 7) + ((lane >> 3) & 1) * 8;
    const uint32_t loff = lrow * 128 + ((((lane >> 4) ^ lrow) & 7) << 4);
    const int r0 = 16 * w + (lane >> 2);

    if (wg == 0) {
        asm volatile("setmaxnreg.inc.sync.aligned.u32 184;");
        uint32_t q[112];
        PG(206);
        if (tid == 0) {
            mbar_init(sb + B_MK, 1);
            for (int i = 0; i < 9; i++) mbar_init(sb + B_R1 + 8 * i, 2);
            for (int i = 0; i < 5; i++) asm volatile("st.shared.u32 [%0], 0;" ::"r"(sb + CNT + 4 * i) : "memory");
        } else if (tid == 32) {
            mbar_init(sb + B_LN, 1); mbar_init(sb + B_MQ, 1);
            mbar_init(sb + B_H1, 2); mbar_init(sb + B_H2, 1); mbar_init(sb + B_H3, 2);
            for (int i = 0; i < 3; i++) { mbar_init(sb + B_KV + 8 * i, 1); mbar_init(sb + B_P + 8 * i, 4); mbar_init(sb + B_GO + 8 * i, 4); }
            mbar_init(sb + B_UC, 1); mbar_init(sb + B_UC + 8, 1); mbar_init(sb + B_X, 8);
        } else if (tid == 64) {
            for (int i = 0; i < 20; i++) mbar_init(sb + B_R2 + 8 * i, 1);
        } else if (tid == 96) {
            for (int i = 0; i < 20; i++) mbar_init(sb + B_E2 + 8 * i, 4);
        }
        if (lane == 0) {
            asm volatile("fence.mbarrier_init.release.cluster;" ::: "memory");
            fence_async();
        }
        PG(207);
        __syncwarp();
        if (SU != 2) asm volatile("bar.arrive 5, 384;" ::: "memory");
        if (tid == 0) {
            mbar_expect_tx(sb + B_MK, 65536 + 32768);
            tma3(sb + 16384, &mp.wq, 0, 64 * (piece >> 4), 0, sb + B_MK);
            tma3(sb + 81920, &mp.wk, 0, 32 * (piece & 15), 0, sb + B_MK);
            for (int i = 0; i < 14; i++) mbar_arrive(sb + B_R1 + 8 * (i >> 1));
            if (mode != 1) {
                ring_full(sb, 56, &mp.wup8, 0, 8);
                ring_full(sb, 64, &mp.wup8, 16, 8);
                ring_full(sb, 0, &mp.wup8, 32, 8);
            }
        }
        PG(208);
        bar_sync(1, 128);
        if (SU == 2) asm volatile("bar.arrive 5, 384;" ::: "memory");
        PT(0);
        PG(200);
        {
            float mq[16];
            fresh(mq);
            mbar_wait(sb + B_MK, 0);
            PT(1);
            if (tid == 32) l2_prefetch((const char*)wup + piece * 8192, 8192);
            wg_fence();
#pragma unroll 1
            for (int c = 0; c < 8; c++)
#pragma unroll
                for (int kk = 0; kk < 4; kk++)
                    wgmma_ss_n32_tb0(mq, dsc(sd, 16384 + c * 8192 + kk * 32, 16), dsc(sd, 81920 + c * 4096 + kk * 32, 16), 1);
            wg_commit();
            wg_wait<0>();
            if (mode != 1 && w0 && elect1()) {
#pragma unroll 1
                for (int i = 1; i < 7; i++) ring_full(sb, 8 * i, &mp.wup8, 32 + 16 * i, 8);
            }
            pin(mq);
            uint32_t* c = reinterpret_cast<uint32_t*>(g_mqk + (64 * (piece >> 4) + r0) * D_ + 32 * (piece & 15) + 2 * (lane & 3));
#pragma unroll
            for (int n = 0; n < 4; n++) { c[4 * n] = pack2(mq[4 * n], mq[4 * n + 1]); c[4 * n + 4 * D_] = pack2(mq[4 * n + 2], mq[4 * n + 3]); }
            fence_async_g();
            bar_sync(1, 128);
            if (el) {
                if (mode == 0) flag_add(&g_sync[2]);
                if (mode == 0) flag_wait(&g_sync[2], NCTA);
                mbar_arrive(sb + B_MQ);
                PG(203);
                PT(12);
                mbar_wait(sb + B_LN, 0);
#pragma unroll 1
                for (int c = 0; c < 8; c++) {
                    tma4_store(&mp.xas, sb + AT + c * 8192, 0, 62 * ti, c, b);
                    const unsigned t0 = (unsigned)clock();
                    while (c < 7 && (unsigned)clock() - t0 < XS_GAP) __nanosleep(20);
                }
                asm volatile("cp.async.bulk.commit_group;" ::: "memory");
                if (mode == 1) asm volatile("cp.async.bulk.wait_group 0;" ::: "memory");
            }
            PT(13);
            if (mode == 1) return;
        }
        mbar_wait(sb + B_H1, 0);
        PT(2);
        uint32_t slot8 = 24, par = 0, prev8 = 0;
        auto adv = [&]() { prev8 = slot8; slot8 += 8; if (slot8 == 72) { slot8 = 0; par ^= 1; } };
        {
            float acc[128];
            fresh(acc);
            auto step = [&](int i) {
                const uint32_t aa = adA + (i >> 1) * 512 + (i & 1) * 4, bb = bd0 + ((4096u >> 4) << 16) + slot8 * 128;
                wg_fence();
                wgmma_ss_n256_tb1(acc, mkd(aa), mkd(bb), 1);
                wgmma_ss_n256_tb1(acc, mkd(aa + 2), mkd(bb + 128), 1);
                wg_commit();
                wg_wait<1>();
            };
#pragma unroll 1
            for (int i = 0; i < 8; i++) {
                mbar_wait(sb + B_R1 + slot8, par);
                step(i);
                if (i > 0 && w0 && elect1()) ring_full(sb, prev8, &mp.mqa4, 32 * i + 256, 4);
                adv();
            }
#pragma unroll 1
            for (int i = 8; i < 16; i++) {
                mbar_wait(sb + B_R1 + slot8, par);
                if (i == 15 && el) mbar_arrive(sb + B_H2);
                step(i);
                if (w0 && elect1()) ring_full(sb, prev8, &mp.wup8, 16 * i - 128, 0);
                adv();
            }
            wg_wait<0>();
            if (w0 && elect1()) ring_full(sb, prev8, &mp.wup8, 128, 0);
            pin(acc);
            PT(3);
#pragma unroll
            for (int kk = 0; kk < 4; kk++)
                stsm4((sb + QS + loff) ^ (kk << 5), pack2(acc[96 + 8 * kk], acc[97 + 8 * kk]), pack2(acc[98 + 8 * kk], acc[99 + 8 * kk]),
                      pack2(acc[100 + 8 * kk], acc[101 + 8 * kk]), pack2(acc[102 + 8 * kk], acc[103 + 8 * kk]));
            fence_async();
#pragma unroll
            for (int i = 47; i >= 0; i--) q[64 + i] = pack2v(acc[2 * i], acc[2 * i + 1]);
        }
        if (el) {
            asm volatile("cp.async.bulk.wait_group 0;" ::: "memory");
            if (mode == 0) {
                fence_async_g();
                flag_add(&g_sync[b]);
                flag_wait(&g_sync[b], TPB);
            }
        }
        __syncwarp();
        mbar_wait(sb + B_H3, 0);
        PT(4);
        slot8 = 48; par = 1;
#pragma unroll
        for (int half = 0; half < 2; half++) {
            float acc[64];
            fresh(acc);
            auto step = [&](int m) {
                const uint32_t aa = adA + m * 512, bb = bd0 + ((8192u >> 4) << 16) + slot8 * 128;
                mbar_wait(sb + B_R1 + slot8, par);
                wg_fence();
#pragma unroll
                for (int kk = 0; kk < 4; kk++) wgmma_ss_n128_tb1(acc, mkd(aa + 2 * kk), mkd(bb + 128 * kk), 1);
                wg_commit();
                wg_wait<1>();
            };
#pragma unroll 1
            for (int m = 0; m < 8; m++) {
                step(m);
                if (m > 0 && w0 && elect1()) {
                    if (half == 0) ring_full(sb, prev8, &mp.mqb2, 64 * m, 2);
                    else if (m < 4) tma4(sb + prev8 * 2048, &mp.xa2, 0, 0, 2 * m, b, sb + B_KV + 8);
                }
                adv();
            }
            wg_wait<0>();
            if (w0 && elect1()) {
                if (half == 0) {
                    mbar_expect_tx(sb + B_KV + 8, 65536);
                    tma4(sb + prev8 * 2048, &mp.xa2, 0, 0, 0, b, sb + B_KV + 8);
                } else {
                    mbar_expect_tx(sb + B_KV + 16, 65536);
                    tma4(sb + R2, &mp.xa, 0, 64, 0, b, sb + B_KV + 16);
                    mbar_expect_tx(sb + B_KV, 65536);
                    tma4(sb + R0, &mp.xa, 0, 128, 0, b, sb + B_KV);
                }
            }
            pin(acc);
#pragma unroll
            for (int i = 31; i >= 0; i--) q[32 * half + i] = pack2v(acc[2 * i], acc[2 * i + 1]);
        }
        bar_sync(1, 128);
        PT(5);

        const float CS = 0.04419417382415922f * 1.4426950408889634f;
        float m0 = -INFINITY, m1 = -INFINITY, l0 = 0.f, l1 = 0.f;
        int s = 0, sn = 1, ph = 0;
        float S[32];
        const bool l0w = lane == 0, q0 = (lane & 3) == 0;
#pragma unroll 1
        for (int j = -1;; j++) {
            if (j >= 0) {
                PL(j, 1);
                if (j == NKV - 1) {
#pragma unroll
                    for (int i = (T_ - 64 * (NKV - 1)) / 2; i < 32; i++) asm volatile("mov.b32 %0, 0xff800000;" : "=f"(S[i]));
                }
                float y[8], z[8];
#pragma unroll
                for (int n = 0; n < 8; n++) { y[n] = fmaxf(S[4 * n], S[4 * n + 1]); z[n] = fmaxf(S[4 * n + 2], S[4 * n + 3]); }
#pragma unroll
                for (int n = 0; n < 4; n++) { y[n] = fmaxf(y[n], y[n + 4]); z[n] = fmaxf(z[n], z[n + 4]); }
                float x0 = fmaxf(fmaxf(y[0], y[1]), fmaxf(fmaxf(y[2], y[3]), m0)), x1 = fmaxf(fmaxf(z[0], z[1]), fmaxf(fmaxf(z[2], z[3]), m1));
                x0 = fmaxf(x0, __shfl_xor_sync(0xffffffffu, x0, 1));
                x1 = fmaxf(x1, __shfl_xor_sync(0xffffffffu, x1, 1));
                x0 = fmaxf(x0, __shfl_xor_sync(0xffffffffu, x0, 2));
                x1 = fmaxf(x1, __shfl_xor_sync(0xffffffffu, x1, 2));
                if ((x0 - m0) * CS <= LAZY) x0 = m0;
                if ((x1 - m1) * CS <= LAZY) x1 = m1;
                const float sc0 = ex2((m0 - x0) * CS), sc1 = ex2((m1 - x1) * CS);
                m0 = x0; m1 = x1;
                const float n0 = -x0 * CS, n1 = -x1 * CS;
                if (q0) { sts_f32(sb + SCL + s * 256 + r0 * 4, sc0); sts_f32(sb + SCL + s * 256 + r0 * 4 + 32, sc1); }
                __syncwarp();
                if (l0w) mbar_arrive(sb + B_P + s * 8);
                if (j < NKV - 1) mbar_wait(sb + B_KV + sn * 8, ph);
                float a0 = 0.f, a1 = 0.f;
                const uint32_t pb = sb + R3 + (s == 0 ? 2 : s - 1) * 8192;
#pragma unroll
                for (int kk = 0; kk < 4; kk++) {
                    float p[8];
#pragma unroll
                    for (int e = 0; e < 8; e++) p[e] = ex2(fmaf(S[8 * kk + e], CS, (e & 2) ? n1 : n0));
                    a0 += (p[0] + p[1]) + (p[4] + p[5]);
                    a1 += (p[2] + p[3]) + (p[6] + p[7]);
                    stsm4((pb + loff) ^ (kk << 5), pack2(p[0], p[1]), pack2(p[2], p[3]), pack2(p[4], p[5]), pack2(p[6], p[7]));
                }
                l0 = fmaf(l0, sc0, a0); l1 = fmaf(l1, sc1, a1);
                PL(j, 2);
                if (j == NKV - 1) break;
            } else {
                mbar_wait(sb + B_KV + 8, 0);
            }
            float Sn[32];
            const uint32_t kd = sd + sn * 4096;
            wg_fence();
#pragma unroll
            for (int kk = 0; kk < 28; kk++) {
                wgmma_rs_n64_tb0(Sn, q[4 * kk], q[4 * kk + 1], q[4 * kk + 2], q[4 * kk + 3], dsc(kd, (kk >> 2) * 8192 + (kk & 3) * 32, 16), kk > 0);
                if (kk == FENCE_AT) { fence_async(); __syncwarp(); }
                if (kk == GO_AT) { PL(j, 3); if (j >= 0 && l0w) mbar_arrive(sb + B_GO + s * 8); }
            }
#pragma unroll
            for (int kk = 0; kk < 4; kk++)
                wgmma_ss_n64_tb0(Sn, dsc(sd, QS + kk * 32, 16), dsc(kd, 7 * 8192 + kk * 32, 16), 1);
            wg_commit();
            PL(j, 0);
            wg_wait<0>();
            pin(Sn);
#pragma unroll
            for (int i = 0; i < 32; i++) S[i] = Sn[i];
            s = sn;
            if (++sn == 3) sn = 0;
            if (sn == 1) ph ^= 1;
        }
        l0 += __shfl_xor_sync(0xffffffffu, l0, 1); l1 += __shfl_xor_sync(0xffffffffu, l1, 1);
        l0 += __shfl_xor_sync(0xffffffffu, l0, 2); l1 += __shfl_xor_sync(0xffffffffu, l1, 2);
        if (q0) { sts_f32(sb + LINV + r0 * 4, rcp(l0)); sts_f32(sb + LINV + r0 * 4 + 32, rcp(l1)); }
        fence_async();
        __syncwarp();
        if (l0w) {
            mbar_arrive(sb + B_GO + s * 8);
            uint32_t slot8 = 8 * w, par = 0;
#pragma unroll 1
            for (int n = 20 + w; n < 136; n += 4) {
                mbar_wait(sb + B_E2 + slot8, par);
                if (n < 128) ring_ld(sb, slot8, n);
                else {
                    mbar_expect_tx(sb + B_X, 8192);
                    tma4(sb + R1 + slot8 * 1024, &mp.x, 0, 62 * ti, n - 128, b, sb + B_X);
                }
                slot8 += 32;
                if (slot8 >= 160) { slot8 -= 160; par ^= 1; }
            }
        }
        PDUMP();
    } else {
        asm volatile("setmaxnreg.dec.sync.aligned.u32 160;");
        const int h = wg - 1;
        uint32_t v[4][8], v2[4][8];
        if (SU != 0) bar_sync(5, 384);
        PG(206);
#pragma unroll
        for (int i = 0; i < 8; i++) {
            const int t = 62 * ti - 1 + 32 * (i >> 2) + 16 * h + 4 * w + (i & 3);
            const uint4* p = reinterpret_cast<const uint4*>(x + ((size_t)b * T_ + t) * D_) + lane;
            uint32_t* d = i < 4 ? v[i & 3] : v2[i & 3];
#pragma unroll
            for (int c = 0; c < 2; c++)
                asm volatile("{\n.reg .pred p;\nsetp.lt.u32 p, %5, %6;\nmov.b32 %0, 0;\nmov.b32 %1, 0;\nmov.b32 %2, 0;\nmov.b32 %3, 0;\n"
                             "@p ld.global.nc.v4.u32 {%0, %1, %2, %3}, [%4];\n}\n"
                             : "=r"(d[4 * c]), "=r"(d[4 * c + 1]), "=r"(d[4 * c + 2]), "=r"(d[4 * c + 3]) : "l"(p + 32 * c), "r"(t), "n"(T_));
        }
#pragma unroll 1
        for (int bt = 0; bt < 2; bt++) {
            PT(bt ? 13 : 0);
            float a[8];
            const uint32_t la = sb + AT + (lane >> 3) * 8192 + (32 * bt + 16 * h + 4 * w) * 128 + (((lane & 7) ^ ((w & 1) * 4)) << 4);
            const bool b4 = lane & 16, b3 = lane & 8, b2 = lane & 4;
#pragma unroll
            for (int r = 0; r < 4; r++) {
                float c[4] = {0.f, 0.f, 0.f, 0.f};
#pragma unroll
                for (int i = 0; i < 8; i += 2) hmma(c, v[r][i], v[r][i], v[r][i + 1], v[r][i + 1], v[r][i], v[r][i + 1]);
                a[4 + r] = (lane & 3) == (lane >> 3) ? (b2 ? c[1] : c[0]) : 0.f;
                if (r & 1) {
                    float e[4] = {0.f, 0.f, 0.f, 0.f};
#pragma unroll
                    for (int i = 0; i < 8; i += 2) hmma(e, v[r - 1][i], v[r][i], v[r - 1][i + 1], v[r][i + 1], 0x3f803f80u, 0x3f803f80u);
                    a[r - 1] = e[0]; a[r] = e[2];
                }
            }
            float k[4];
#pragma unroll
            for (int i = 0; i < 4; i++) {
                const int lo = (i & 1) + 4 * (i >> 1);
                k[i] = (b4 ? a[lo + 2] : a[lo]) + __shfl_xor_sync(0xffffffffu, b4 ? a[lo] : a[lo + 2], 16);
            }
            const float k0 = (b3 ? k[1] : k[0]) + __shfl_xor_sync(0xffffffffu, b3 ? k[0] : k[1], 8);
            const float k1 = (b3 ? k[3] : k[2]) + __shfl_xor_sync(0xffffffffu, b3 ? k[2] : k[3], 8);
            float z = (b2 ? k1 : k0) + __shfl_xor_sync(0xffffffffu, b2 ? k0 : k1, 4);
            z += __shfl_xor_sync(0xffffffffu, z, 2);
            z += __shfl_xor_sync(0xffffffffu, z, 1);
            const float zo = __shfl_xor_sync(0xffffffffu, z, 4);
            PG(204 + bt);
            const float mu = (b2 ? zo : z) * (0.25f / D_);
            float sd_ = bfr(bfr(fmaxf(fmaf(b2 ? z : zo, 1.f / D_, -mu * mu), 0.f)) + 1e-5f);
            asm("sqrt.approx.f32 %0, %0;" : "+f"(sd_));
            const float ri = rcp(bfr(sd_));
            const uint32_t w1 = pack2(mu, ri), w2 = pack2(ri - bhi(w1), ri - bhi(w1));
#pragma unroll
            for (int r = 0; r < 4; r++) {
                const uint32_t s1 = __shfl_sync(0xffffffffu, w1, 8 * r), rl = __shfl_sync(0xffffffffu, w2, 8 * r);
                const uint32_t m2 = __byte_perm(s1, 0, 0x1010), rh = __byte_perm(s1, 0, 0x3232);
#pragma unroll
                for (int i = 0; i < 8; i++) { const uint32_t d = bsub2(v[r][i], m2); v[r][i] = bfma2(d, rh, bmul2(d, rl)); }
                sts4((la ^ (r << 4)) + r * 128, v[r][0], v[r][1], v[r][2], v[r][3]);
                sts4((la ^ (r << 4)) + r * 128 + 32768, v[r][4], v[r][5], v[r][6], v[r][7]);
#pragma unroll
                for (int i = 0; i < 8; i++) v[r][i] = v2[r][i];
            }
        }
        fence_async();
        if (SU == 0) bar_sync(5, 384); else bar_sync(2, 256);
        if (tid == 128) mbar_arrive(sb + B_LN);
        PG(202);
        if (mode == 1) return;
        float acc[128];
#pragma unroll
        for (int pass = 0; pass < 2; pass++) {
            if (pass == 1) mbar_wait(sb + B_H2, 0);
            PT(1 + 3 * pass);
            fresh(acc);
            uint32_t slot8 = pass ? 8 : 56, par = 0, prev8 = 0;
            auto adv = [&]() { prev8 = slot8; slot8 += 8; if (slot8 == 72) { slot8 = 0; par ^= 1; } };
            auto step = [&](int kk) {
                wg_fence();
                wgmma_ss_n256_tb1(acc, mkd(adA + (kk >> 2) * 512 + (kk & 3) * 2), mkd(bd2k + h * 512 + slot8 * 128), 1);
                wg_commit();
                wg_wait<1>();
            };
#pragma unroll 1
            for (int kk = 0; kk < 24; kk++) {
                mbar_wait(sb + B_R1 + slot8, par);
                step(kk);
                if (kk > 0 && w0 && elect1()) ring_half(sb, prev8, h * 8192, &mp.wup4, 16 * kk + 128, (pass ? 0 : 8) + 4 * h);
                adv();
            }
            if (pass == 0 && w0) mbar_wait(sb + B_MQ, 0);
#pragma unroll 1
            for (int kk = 24; kk < 32; kk++) {
                mbar_wait(sb + B_R1 + slot8, par);
                if (kk == 31 && el) mbar_arrive(sb + (pass ? B_H3 : B_H1));
                step(kk);
                if (w0 && elect1()) ring_half(sb, prev8, h * 8192, pass ? &mp.mqb1 : &mp.mqa2, (pass ? 64 : 32) * (kk - 24), pass ? h : 4 + 2 * h);
                adv();
            }
            wg_wait<0>();
            if (w0 && elect1()) ring_half(sb, prev8, h * 8192, pass ? &mp.mqb1 : &mp.mqa2, pass ? 0 : 256, pass ? 2 + h : 4 + 2 * h);
            pin(acc);
            PT(2 + 3 * pass);
            bf16* ucp = g_uc + ((size_t)blockIdx.x * 128 + r0) * D_ + 256 * h + 8 * (lane & 3);
            if (pass == 0) {
                float s0 = 0.f, s1 = 0.f, v0 = 0.f, v1 = 0.f;
#pragma unroll
                for (int n = 0; n < 32; n++) {
#pragma unroll
                    for (int e = 0; e < 4; e++) acc[4 * n + e] = gelu2(acc[4 * n + e]);
                    s0 += acc[4 * n] + acc[4 * n + 1]; s1 += acc[4 * n + 2] + acc[4 * n + 3];
                    v0 = fmaf(acc[4 * n], acc[4 * n], v0); v0 = fmaf(acc[4 * n + 1], acc[4 * n + 1], v0);
                    v1 = fmaf(acc[4 * n + 2], acc[4 * n + 2], v1); v1 = fmaf(acc[4 * n + 3], acc[4 * n + 3], v1);
                }
#pragma unroll
                for (int o = 1; o < 4; o <<= 1) {
                    s0 += __shfl_xor_sync(0xffffffffu, s0, o); s1 += __shfl_xor_sync(0xffffffffu, s1, o);
                    v0 += __shfl_xor_sync(0xffffffffu, v0, o); v1 += __shfl_xor_sync(0xffffffffu, v1, o);
                }
                if ((lane & 3) == 0) {
                    uint32_t a = sb + STAT + h * 512 + r0 * 8;
                    sts_f32(a, s0); sts_f32(a + 4, v0); sts_f32(a + 64, s1); sts_f32(a + 68, v1);
                }
                bar_sync(2, 256);
                {
                    uint32_t a = sb + STAT + (h ^ 1) * 512 + r0 * 8;
                    s0 = (s0 + lds_f32(a)) * (1.f / 512.f); v0 = (v0 + lds_f32(a + 4)) * (1.f / 512.f);
                    s1 = (s1 + lds_f32(a + 64)) * (1.f / 512.f); v1 = (v1 + lds_f32(a + 68)) * (1.f / 512.f);
                }
                v0 = rsqrtf(fmaxf(fmaf(-s0, s0, v0), 0.f) + 4e-5f); v1 = rsqrtf(fmaxf(fmaf(-s1, s1, v1), 0.f) + 4e-5f);
                s0 = -s0 * v0; s1 = -s1 * v1;
#pragma unroll
                for (int m = 0; m < 8; m++) {
                    const float* a_ = acc + 16 * m;
                    stg4(ucp + 64 * D_ + 32 * m, pack2(fmaf(a_[0], v0, s0), fmaf(a_[1], v0, s0)), pack2(fmaf(a_[4], v0, s0), fmaf(a_[5], v0, s0)),
                         pack2(fmaf(a_[8], v0, s0), fmaf(a_[9], v0, s0)), pack2(fmaf(a_[12], v0, s0), fmaf(a_[13], v0, s0)));
                    stg4(ucp + 72 * D_ + 32 * m, pack2(fmaf(a_[2], v1, s1), fmaf(a_[3], v1, s1)), pack2(fmaf(a_[6], v1, s1), fmaf(a_[7], v1, s1)),
                         pack2(fmaf(a_[10], v1, s1), fmaf(a_[11], v1, s1)), pack2(fmaf(a_[14], v1, s1), fmaf(a_[15], v1, s1)));
                }
            } else {
#pragma unroll
                for (int m = 0; m < 8; m++) {
                    const float* a_ = acc + 16 * m;
                    stg4(ucp + 32 * m, pack2(gelu2(a_[0]), gelu2(a_[1])), pack2(gelu2(a_[4]), gelu2(a_[5])),
                         pack2(gelu2(a_[8]), gelu2(a_[9])), pack2(gelu2(a_[12]), gelu2(a_[13])));
                    stg4(ucp + 8 * D_ + 32 * m, pack2(gelu2(a_[2]), gelu2(a_[3])), pack2(gelu2(a_[6]), gelu2(a_[7])),
                         pack2(gelu2(a_[10]), gelu2(a_[11])), pack2(gelu2(a_[14]), gelu2(a_[15])));
                    if (m & 1) PT(12);
                }
                bar_sync(3 + h, 128);
            }
            PT(3 + 3 * pass);
        }
        int s = 1, ph = 0;
        uint32_t* cp = reinterpret_cast<uint32_t*>(g_uc + (size_t)blockIdx.x * 128 * D_) + (tid - 128);
        const uint32_t* dp = reinterpret_cast<const uint32_t*>(dw) + (((tid - 128) & ~15) | ((lane & 3) << 2) | ((lane >> 2) & 3));
        const uint32_t d0 = ldg_v(dp), d1 = ldg_v(dp + D_ / 2), d2 = ldg_v(dp + D_);
        uint32_t ga = ldg_cg(cp + 64 * (D_ / 2)), gb = ldg_cg(cp + 65 * (D_ / 2));
        fresh(acc);
#pragma unroll 1
        for (int j = 0; j < NKV; j++) {
            cp += D_ / 2;
            uint32_t gc = 0, uu = 0;
            if (j < NKV - 1) { gc = ldg_cg(cp + 65 * (D_ / 2)); uu = ldg_cg(cp); }
            mbar_wait(sb + B_P + s * 8, ph);
            PL(j, 0);
            if (j > 0) {
                const float sc0 = lds_f32(sb + SCL + s * 256 + r0 * 4), sc1 = lds_f32(sb + SCL + s * 256 + r0 * 4 + 32);
                if (__any_sync(0xffffffffu, sc0 != 1.f || sc1 != 1.f)) {
#pragma unroll
                    for (int n = 0; n < 32; n++) { acc[4 * n] *= sc0; acc[4 * n + 1] *= sc0; acc[4 * n + 2] *= sc1; acc[4 * n + 3] *= sc1; }
                }
            }
            mbar_wait(sb + B_GO + s * 8, ph);
            PL(j, 1);
            const uint32_t vd = sd + s * 4096 + h * 2048, pd = sd + (s == 0 ? 2 : s - 1) * 512;
            pin(acc);
            wg_fence();
#pragma unroll
            for (int kk = 0; kk < 4; kk++) wgmma_ss_n256_tb1(acc, dsc(pd, R3 + kk * 32, 16), dsc(vd, kk * 2048, 8192), 1);
            wg_commit();
            wg_wait<0>();
            pin(acc);
            PL(j, 2);
            if (w0 && elect1()) {
                if (j == NKV - 5 && mode == 0) flag_wait(&g_sync[3], 4);
                if (atom_inc_s(sb + CNT + 4 * s) & 1) {
                    if (j + 3 < NKV) {
                        mbar_expect_tx(sb + B_KV + s * 8, 65536);
                        tma4(sb + s * 65536, &mp.xa, 0, 64 * (j + 3), 0, b, sb + B_KV + s * 8);
                    } else if (j < NKV - 1) {
                        const int n0 = j == NKV - 3 ? 0 : 8, n1 = n0 + 8;
#pragma unroll 1
                        for (int n = n0; n < n1; n++) ring_ld(sb, n * 8, n);
                    }
                }
            }
            if (j < NKV - 1) asm volatile("st.global.u32 [%0], %1;" ::"l"(cp), "r"(bmul2(uu, bfma2(gc, d2, bfma2(gb, d1, bmul2(ga, d0))))) : "memory");
            ga = gb; gb = gc;
            if (++s == 3) s = 0;
            if (s == 1) ph ^= 1;
        }
        {
            const float i0 = lds_f32(sb + LINV + r0 * 4), i1 = lds_f32(sb + LINV + r0 * 4 + 32);
#pragma unroll
            for (int p = 0; p < 16; p++)
                stsm4(((sb + R0 + h * 32768 + loff) ^ ((p & 3) << 5)) + (p >> 2) * 8192,
                      pack2(acc[8 * p] * i0, acc[8 * p + 1] * i0), pack2(acc[8 * p + 2] * i1, acc[8 * p + 3] * i1),
                      pack2(acc[8 * p + 4] * i0, acc[8 * p + 5] * i0), pack2(acc[8 * p + 6] * i1, acc[8 * p + 7] * i1));
        }
        fence_async();
        fence_async_g();
        bar_sync(2, 256);
        if (lane == 0 && w < 2) ring_ld(sb, 128 + 16 * w + 8 * h, 16 + 2 * w + h);
        PT(7);
        fresh(acc);
        {
            uint32_t slot8 = 8 * h, par = 0, prev8 = 0;
#pragma unroll 1
            for (int kk = 0; kk < 64; kk++) {
                if (kk == 32 || kk == 48) mbar_wait(sb + B_UC + (kk >> 1 & 8), 0);
                mbar_wait(sb + B_R2 + slot8, par);
                wg_fence();
                wgmma_ss_n256_tb1(acc, mkd(sd + (1u << 16) + (R0 >> 4) + (kk >> 2 & 7) * 512 + (kk & 3) * 2), mkd(bd2k + (R1 >> 4) + slot8 * 64), 1);
                wg_commit();
                wg_wait<1>();
                if (kk > 0 && lane == 0) mbar_arrive(sb + B_E2 + prev8);
                if ((kk == 16 || kk == 32) && w0 && elect1() && (atom_inc_s(sb + CNT + 12 + (kk >> 3 & 4)) & 1)) {
                    mbar_expect_tx(sb + B_UC + (kk >> 2 & 8), 32768);
                    tma3(sb + R0 + (kk & 32) * 1024, &mp.uc, 0, 128 * blockIdx.x, kk >> 3 & 4, sb + B_UC + (kk >> 2 & 8));
                }
                prev8 = slot8;
                slot8 += 16;
                if (slot8 >= 160) { slot8 -= 160; par ^= 1; }
            }
        }
        wg_wait<0>();
        pin(acc);
        PT(8);
        mbar_wait(sb + B_X, 0);
        PT(9);
        {
            const uint32_t sr = (lrow + 63) & 63;
            const uint32_t xoff = sr * 128 + ((((lane >> 4) ^ sr) & 7) << 4);
#pragma unroll
            for (int p = 0; p < 16; p++) {
                const uint32_t a = ((sb + R2 + h * 32768 + xoff) ^ ((p & 3) << 5)) + (p >> 2) * 8192;
                uint32_t xv[4];
                ldsm4(a, xv);
#pragma unroll
                for (int e = 0; e < 4; e++)
                    xv[e] = pack2(acc[8 * p + 2 * e] + __uint_as_float(xv[e] << 16), acc[8 * p + 2 * e + 1] + __uint_as_float(xv[e] & 0xffff0000u));
                stsm4(a, xv[0], xv[1], xv[2], xv[3]);
            }
        }
        fence_async();
        bar_sync(3 + h, 128);
        if (el) {
            for (int c = 0; c < 4; c++) tma4_store(&mp.out, sb + R2 + (4 * h + c) * 8192, 0, 62 * ti, 4 * h + c, b);
            asm volatile("cp.async.bulk.commit_group;" ::: "memory");
            PT(10);
            if (h == 0) cta_done(mode);
            asm volatile("cp.async.bulk.wait_group.read 0;" ::: "memory");
        }
        PT(11);
        PG(201);
        PDUMP();
    }
}

typedef CUresult (*PFN_enc)(CUtensorMap*, CUtensorMapDataType, cuuint32_t, void*, const cuuint64_t*, const cuuint64_t*,
                            const cuuint32_t*, const cuuint32_t*, CUtensorMapInterleave, CUtensorMapSwizzle,
                            CUtensorMapL2promotion, CUtensorMapFloatOOBfill);

static void enc(PFN_enc f, CUtensorMap* m, void* base, int rank, const cuuint64_t* dims, const cuuint64_t* strides, const cuuint32_t* box) {
    cuuint32_t es[5] = {1, 1, 1, 1, 1};
    f(m, CU_TENSOR_MAP_DATA_TYPE_BFLOAT16, rank, base, dims, strides, box, es, CU_TENSOR_MAP_INTERLEAVE_NONE,
      CU_TENSOR_MAP_SWIZZLE_128B, CU_TENSOR_MAP_L2_PROMOTION_L2_256B, CU_TENSOR_MAP_FLOAT_OOB_FILL_NONE);
}
static void enc_act(PFN_enc f, CUtensorMap* m, void* base, int rows, int chunks, int trows = T_, int pitch = T_) {
    cuuint64_t dims[4] = {64, (cuuint64_t)trows, 8, (cuuint64_t)NB_};
    cuuint64_t st[3] = {1024, 128, (cuuint64_t)pitch * 1024};
    cuuint32_t box[4] = {64, (cuuint32_t)rows, (cuuint32_t)chunks, 1};
    enc(f, m, base, 4, dims, st, box);
}
static void enc_w(PFN_enc f, CUtensorMap* m, void* base, int krows, int ncols, int bk, int bc) {
    cuuint64_t dims[3] = {64, (cuuint64_t)krows, (cuuint64_t)(ncols / 64)};
    cuuint64_t st[2] = {(cuuint64_t)ncols * 2, 128};
    cuuint32_t box[3] = {64, (cuuint32_t)bk, (cuuint32_t)bc};
    enc(f, m, base, 3, dims, st, box);
}

extern "C" void kernel_launch(void* const* d_in, const int* in_sizes, int n_in, void* d_out, int out_size) {
    const bf16* x = (const bf16*)d_in[0];
    static PFN_enc fenc = nullptr;
    static void *p_xa, *p_mqk, *p_uc, *p_t1;
    static int fused = 0;
    if (!fenc) {
        void* fn = nullptr;
        cudaDriverEntryPointQueryResult qr;
        cudaGetDriverEntryPoint("cuTensorMapEncodeTiled", &fn, cudaEnableDefault, &qr);
        fenc = (PFN_enc)fn;
        cudaGetSymbolAddress(&p_xa, g_xa);
        cudaGetSymbolAddress(&p_mqk, g_mqk);
        cudaGetSymbolAddress(&p_uc, g_uc);
        cudaGetSymbolAddress(&p_t1, g_t1);
        cudaFuncSetAttribute(main_kernel, cudaFuncAttributeMaxDynamicSharedMemorySize, SMEM_BYTES);
        int dev = 0, sms = 0, occ = 0;
        cudaGetDevice(&dev);
        cudaDeviceGetAttribute(&sms, cudaDevAttrMultiProcessorCount, dev);
        cudaOccupancyMaxActiveBlocksPerMultiprocessor(&occ, main_kernel, 384, SMEM_BYTES);
        fused = sms * occ >= NCTA + 2;
    }
    Maps mp;
    enc_act(fenc, &mp.xa, (char*)p_xa + 1024, 64, 8, T_, T_ + 8);
    enc_act(fenc, &mp.xa2, (char*)p_xa + 1024, 64, 2, T_, T_ + 8);
    enc_act(fenc, &mp.xas, p_xa, 64, 1, T_ + 1, T_ + 8);
    enc_act(fenc, &mp.x, (void*)x, 64, 1);
    enc_act(fenc, &mp.out, d_out, 62, 1);
    enc_w(fenc, &mp.wup4, d_in[5], 512, 1024, 16, 4);
    enc_w(fenc, &mp.wup8, d_in[5], 512, 1024, 16, 8);
    enc_w(fenc, &mp.mqa2, p_mqk, 512, 512, 32, 2);
    enc_w(fenc, &mp.mqa4, p_mqk, 512, 512, 32, 4);
    enc_w(fenc, &mp.mqb1, p_mqk, 512, 512, 64, 1);
    enc_w(fenc, &mp.mqb2, p_mqk, 512, 512, 64, 2);
    enc_w(fenc, &mp.uc, p_uc, NCTA * 128, 512, 64, 4);
    enc_w(fenc, &mp.wq, d_in[1], 512, 512, 64, 8);
    enc_w(fenc, &mp.wk, d_in[2], 512, 512, 32, 8);
    enc_w(fenc, &mp.fa[0], d_in[3], 512, 512, 128, 1);
    enc_w(fenc, &mp.fa[1], d_in[7], 512, 512, 128, 1);
    enc_w(fenc, &mp.fa[2], p_t1, 512, 512, 128, 1);
    enc_w(fenc, &mp.fb[0], d_in[4], 512, 512, 64, 4);
    enc_w(fenc, &mp.fb[1], d_in[8], 1024, 512, 64, 4);
    enc_w(fenc, &mp.fc, p_t1, 512, 512, 64, 4);
    cudaStream_t st = cudaStreamPerThread;
    if (fused) {
        main_kernel<<<NCTA + 2, 384, SMEM_BYTES, st>>>(mp, x, (const bf16*)d_in[6], (const bf16*)d_in[5], 0);
    } else {
        main_kernel<<<NCTA + 2, 384, SMEM_BYTES, st>>>(mp, x, (const bf16*)d_in[6], (const bf16*)d_in[5], 1);
        main_kernel<<<NCTA + 2, 384, SMEM_BYTES, st>>>(mp, x, (const bf16*)d_in[6], (const bf16*)d_in[5], 2);
    }
}
```

```cpp
#include <cuda_runtime.h>
#include <cuda_bf16.h>
#include <cuda.h>
#include <stdint.h>

typedef __nv_bfloat16 bf16;

constexpr int T_ = 4000, D_ = 512, NB_ = 2;
constexpr int TPB = 65;
constexpr int NCTA = TPB * NB_;
constexpr int NKV = 63;

__device__ __align__(1024) bf16 g_xa[NB_ * (T_ + 8) * D_];
__device__ __align__(1024) bf16 g_mqk[D_ * D_];
__device__ __align__(1024) bf16 g_t1[D_ * D_];
__device__ __align__(1024) bf16 g_wepi[2 * D_ * D_];
__device__ __align__(1024) bf16 g_uc[NCTA * 128 * D_];
__device__ unsigned g_sync[8];

#define PT(i) do { if (el) asm volatile("st.shared.u32 [%0], %1;" ::"r"(sb + MISC + 2560), "r"((unsigned)clock())); } while (0)
#define PG(i)
#define PE()
#define PLM 15
#define PL(j, q) do { if ((PLM >> ((q) + (wg ? 4 : 0))) & 1) PT(0); } while (0)
#define PDUMP()

#define FENCE_AT 1
#define GO_AT 25
#define LAZY 256.f
#define SU 2
#define XS_GAP 800
#define XPF 54
#define URAW 0
#define PFW 1
constexpr uint32_t R0 = 0, R1 = 65536, R2 = 131072, R3 = 196608, QS = 221184, MISC = 229376;
constexpr uint32_t AT = 147456;
constexpr uint32_t SMEM_BYTES = 232448;
constexpr uint32_t B_R1 = MISC + 1856  , B_MK = MISC + 48, B_LN = MISC + 56, B_MQ = MISC + 64,
                   B_H1 = MISC + 88, B_H2 = MISC + 96, B_H3 = MISC + 104,
                   B_KV = MISC + 112, B_P = MISC + 136, B_GO = MISC + 160, B_UC = MISC + 184  ,
                   B_X = MISC + 200, CNT = MISC + 208  , SCL = MISC + 512  ,
                   LINV = MISC + 1280  , STAT = MISC + 512  ,
                   B_R2 = MISC + 1536  , B_E2 = MISC + 1696  ;

__device__ __forceinline__ uint32_t smem_u32(const void* p) { return (uint32_t)__cvta_generic_to_shared(p); }
__device__ __forceinline__ void wg_fence() { asm volatile("wgmma.fence.sync.aligned;" ::: "memory"); }
__device__ __forceinline__ void wg_commit() { asm volatile("wgmma.commit_group.sync.aligned;" ::: "memory"); }
template <int N> __device__ __forceinline__ void wg_wait() { asm volatile("wgmma.wait_group.sync.aligned %0;" ::"n"(N) : "memory"); }
__device__ __forceinline__ uint64_t dsc(uint32_t sd, uint32_t off, uint32_t lbo) {
    uint32_t lo = sd + (off >> 4) + ((lbo >> 4) << 16);
    uint64_t d;
    asm("mov.b64 %0, {%1, %2};" : "=l"(d) : "r"(lo), "r"((1024u >> 4) | (1u << 30)));
    return d;
}
__device__ __forceinline__ bool elect1() {
    uint32_t p;
    asm volatile("{\n.reg .pred p;\nelect.sync _|p, 0xffffffff;\nselp.u32 %0, 1, 0, p;\n}\n" : "=r"(p));
    return p != 0;
}
__device__ __forceinline__ void mbar_init(uint32_t bar, int cnt) { asm volatile("mbarrier.init.shared::cta.b64 [%0], %1;" ::"r"(bar), "r"(cnt) : "memory"); }
__device__ __forceinline__ void mbar_expect_tx(uint32_t bar, uint32_t bytes) { asm volatile("mbarrier.arrive.expect_tx.shared::cta.b64 _, [%0], %1;" ::"r"(bar), "r"(bytes) : "memory"); }
__device__ __forceinline__ void mbar_arrive(uint32_t bar) { asm volatile("mbarrier.arrive.shared::cta.b64 _, [%0];" ::"r"(bar) : "memory"); }
__device__ __forceinline__ void mbar_wait(uint32_t bar, uint32_t parity) {
    uint32_t ok;
#pragma unroll 1
    for (uint32_t it = 0;; ++it) {
        asm volatile("{\n.reg .pred p;\nmbarrier.try_wait.parity.shared::cta.b64 p, [%1], %2;\nselp.u32 %0, 1, 0, p;\n}\n" : "=r"(ok) : "r"(bar), "r"(parity) : "memory");
        if (ok) break;
        if (it > (1u << 20)) __trap();
    }
}
__device__ __forceinline__ bool mbar_test(uint32_t bar, uint32_t parity) {
    uint32_t ok;
    asm volatile("{\n.reg .pred p;\nmbarrier.test_wait.parity.shared::cta.b64 p, [%1], %2;\nselp.u32 %0, 1, 0, p;\n}\n" : "=r"(ok) : "r"(bar), "r"(parity) : "memory");
    return ok != 0;
}
__device__ __forceinline__ void fence_async() { asm volatile("fence.proxy.async.shared::cta;" ::: "memory"); }
__device__ __forceinline__ void fence_async_g() { asm volatile("fence.proxy.async.global;" ::: "memory"); }
__device__ __forceinline__ void bar_sync(int id, int n) { asm volatile("bar.sync %0, %1;" ::"r"(id), "r"(n) : "memory"); }
__device__ __forceinline__ void tma3(uint32_t dst, const CUtensorMap* tm, int c0, int c1, int c2, uint32_t bar) {
    asm volatile("cp.async.bulk.tensor.3d.shared::cluster.global.mbarrier::complete_tx::bytes [%0], [%1, {%3, %4, %5}], [%2];"
                 ::"r"(dst), "l"(tm), "r"(bar), "r"(c0), "r"(c1), "r"(c2) : "memory");
}
__device__ __forceinline__ void tma4(uint32_t dst, const CUtensorMap* tm, int c0, int c1, int c2, int c3, uint32_t bar) {
    asm volatile("cp.async.bulk.tensor.4d.shared::cluster.global.mbarrier::complete_tx::bytes [%0], [%1, {%3, %4, %5, %6}], [%2];"
                 ::"r"(dst), "l"(tm), "r"(bar), "r"(c0), "r"(c1), "r"(c2), "r"(c3) : "memory");
}
__device__ __forceinline__ void tma4_store(const CUtensorMap* tm, uint32_t src, int c0, int c1, int c2, int c3) {
    asm volatile("cp.async.bulk.tensor.4d.global.shared::cta.bulk_group [%0, {%2, %3, %4, %5}], [%1];"
                 ::"l"(tm), "r"(src), "r"(c0), "r"(c1), "r"(c2), "r"(c3) : "memory");
}
__device__ __forceinline__ void tma3_store(const CUtensorMap* tm, uint32_t src, int c0, int c1, int c2) {
    asm volatile("cp.async.bulk.tensor.3d.global.shared::cta.bulk_group [%0, {%2, %3, %4}], [%1];"
                 ::"l"(tm), "r"(src), "r"(c0), "r"(c1), "r"(c2) : "memory");
}
__device__ __forceinline__ void stsm4(uint32_t addr, uint32_t a, uint32_t b, uint32_t c, uint32_t d) {
    asm volatile("stmatrix.sync.aligned.m8n8.x4.shared.b16 [%0], {%1, %2, %3, %4};" ::"r"(addr), "r"(a), "r"(b), "r"(c), "r"(d) : "memory");
}
__device__ __forceinline__ void ldsm4(uint32_t addr, uint32_t (&r)[4]) {
    asm volatile("ldmatrix.sync.aligned.m8n8.x4.shared.b16 {%0, %1, %2, %3}, [%4];" : "=r"(r[0]), "=r"(r[1]), "=r"(r[2]), "=r"(r[3]) : "r"(addr) : "memory");
}
__device__ __forceinline__ void ldsm2(uint32_t addr, uint32_t (&r)[2]) {
    asm volatile("ldmatrix.sync.aligned.m8n8.x2.shared.b16 {%0, %1}, [%2];" : "=r"(r[0]), "=r"(r[1]) : "r"(addr) : "memory");
}
__device__ __forceinline__ void stg4(void* p, uint32_t a, uint32_t b, uint32_t c, uint32_t d) {
    asm volatile("st.global.v4.u32 [%0], {%1, %2, %3, %4};" ::"l"(p), "r"(a), "r"(b), "r"(c), "r"(d) : "memory");
}
__device__ __forceinline__ void hmma(float (&c)[4], uint32_t a0, uint32_t a1, uint32_t a2, uint32_t a3, uint32_t b0, uint32_t b1) {
    asm("mma.sync.aligned.m16n8k16.row.col.f32.bf16.bf16.f32 {%0, %1, %2, %3}, {%4, %5, %6, %7}, {%8, %9}, {%0, %1, %2, %3};"
        : "+f"(c[0]), "+f"(c[1]), "+f"(c[2]), "+f"(c[3]) : "r"(a0), "r"(a1), "r"(a2), "r"(a3), "r"(b0), "r"(b1));
}
__device__ __forceinline__ uint32_t pack2(float lo, float hi) {
    uint32_t r;
    asm("cvt.rn.bf16x2.f32 %0, %1, %2;" : "=r"(r) : "f"(hi), "f"(lo));
    return r;
}
__device__ __forceinline__ uint32_t pack2v(float lo, float hi) {
    uint32_t r;
    asm volatile("cvt.rn.bf16x2.f32 %0, %1, %2;" : "=r"(r) : "f"(hi), "f"(lo));
    return r;
}
__device__ __forceinline__ uint32_t bmul2(uint32_t a, uint32_t b) { uint32_t r; asm("mul.rn.bf16x2 %0, %1, %2;" : "=r"(r) : "r"(a), "r"(b)); return r; }
__device__ __forceinline__ uint32_t bfma2(uint32_t a, uint32_t b, uint32_t c) { uint32_t r; asm("fma.rn.bf16x2 %0, %1, %2, %3;" : "=r"(r) : "r"(a), "r"(b), "r"(c)); return r; }
__device__ __forceinline__ float ex2(float x) { float r; asm("ex2.approx.ftz.f32 %0, %1;" : "=f"(r) : "f"(x)); return r; }
__device__ __forceinline__ float rcp(float x) { float r; asm("rcp.approx.ftz.f32 %0, %1;" : "=f"(r) : "f"(x)); return r; }
__device__ __forceinline__ float gelu2(float x) {
    float t = fmaf(x * x, 0.044715f * 0.7978845608028654f, 0.7978845608028654f), th;
    asm("tanh.approx.f32 %0, %1;" : "=f"(th) : "f"(x * t));
    return fmaf(x, th, x);
}
__device__ __forceinline__ uint32_t ldg_v(const uint32_t* p) { uint32_t v; asm volatile("ld.global.nc.u32 %0, [%1];" : "=r"(v) : "l"(p)); return v; }
__device__ __forceinline__ uint32_t ldg_cg(const uint32_t* p) { uint32_t v; asm volatile("ld.global.cg.u32 %0, [%1];" : "=r"(v) : "l"(p) : "memory"); return v; }
__device__ __forceinline__ float lds_f32(uint32_t a) { float v; asm volatile("ld.shared.f32 %0, [%1];" : "=f"(v) : "r"(a) : "memory"); return v; }
__device__ __forceinline__ void sts_f32(uint32_t a, float v) { asm volatile("st.shared.f32 [%0], %1;" ::"r"(a), "f"(v) : "memory"); }
__device__ __forceinline__ uint32_t atom_inc_s(uint32_t a) { uint32_t v; asm volatile("atom.relaxed.cta.shared.add.u32 %0, [%1], 1;" : "=r"(v) : "r"(a) : "memory"); return v; }
__device__ __forceinline__ void lds4(uint32_t a, uint32_t* r) {
    asm volatile("ld.shared.v4.u32 {%0, %1, %2, %3}, [%4];" : "=r"(r[0]), "=r"(r[1]), "=r"(r[2]), "=r"(r[3]) : "r"(a) : "memory");
}
__device__ __forceinline__ void sts4(uint32_t a, uint32_t x, uint32_t y, uint32_t z, uint32_t t) {
    asm volatile("st.shared.v4.u32 [%0], {%1, %2, %3, %4};" ::"r"(a), "r"(x), "r"(y), "r"(z), "r"(t) : "memory");
}
__device__ __forceinline__ uint32_t bsub2(uint32_t a, uint32_t b) { uint32_t r; asm("sub.rn.bf16x2 %0, %1, %2;" : "=r"(r) : "r"(a), "r"(b)); return r; }
__device__ __forceinline__ float blo(uint32_t v) { return __uint_as_float(v << 16); }
__device__ __forceinline__ float bhi(uint32_t v) { return __uint_as_float(v & 0xffff0000u); }
__device__ __forceinline__ float bfr(float x) { return __bfloat162float(__float2bfloat16_rn(x)); }
__device__ __forceinline__ void l2_prefetch(const void* p, uint32_t bytes) { asm volatile("cp.async.bulk.prefetch.L2.global [%0], %1;" ::"l"(p), "r"(bytes) : "memory"); }
__device__ __forceinline__ void flag_add(unsigned* p) { asm volatile("red.release.gpu.global.add.u32 [%0], 1;" ::"l"(p) : "memory"); }
__device__ __forceinline__ void flag_wait(const unsigned* p, unsigned target) {
#pragma unroll 1
    for (uint32_t it = 0;; ++it) {
        unsigned v;
        asm volatile("ld.acquire.gpu.global.u32 %0, [%1];" : "=r"(v) : "l"(p) : "memory");
        if (v >= target) break;
        if (it > (1u << 20)) __trap();
    }
    fence_async_g();
}
template <int N> __device__ __forceinline__ void pin(float (&a)[N]) {
#pragma unroll
    for (int i = 0; i < N; i++) asm volatile("" : "+f"(a[i])::"memory");
}

template <int N> __device__ __forceinline__ void fresh(float (&a)[N]) {
#pragma unroll
    for (int i = 0; i < N; i++) a[i] = 0.f;
    pin(a);
}

__device__ __forceinline__ void wgmma_rs_n64_tb0(float (&d)[32], uint32_t a0, uint32_t a1, uint32_t a2, uint32_t a3, uint64_t db, int scale_d) {
    asm volatile("{\n.reg .pred p;\nsetp.ne.b32 p, %37, 0;\n"
        "wgmma.mma_async.sync.aligned.m64n64k16.f32.bf16.bf16 {%0, %1, %2, %3, %4, %5, %6, %7, %8, %9, %10, %11, %12, %13, %14, %15, %16, %17, %18, %19, %20, %21, %22, %23, %24, %25, %26, %27, %28, %29, %30, %31}, {%32, %33, %34, %35}, %36, p, 1, 1, 0;\n}\n"
        : "+f"(d[0]), "+f"(d[1]), "+f"(d[2]), "+f"(d[3]), "+f"(d[4]), "+f"(d[5]), "+f"(d[6]), "+f"(d[7]), "+f"(d[8]), "+f"(d[9]), "+f"(d[10]), "+f"(d[11]), "+f"(d[12]), "+f"(d[13]), "+f"(d[14]), "+f"(d[15]), "+f"(d[16]), "+f"(d[17]), "+f"(d[18]), "+f"(d[19]), "+f"(d[20]), "+f"(d[21]), "+f"(d[22]), "+f"(d[23]), "+f"(d[24]), "+f"(d[25]), "+f"(d[26]), "+f"(d[27]), "+f"(d[28]), "+f"(d[29]), "+f"(d[30]), "+f"(d[31])
        : "r"(a0), "r"(a1), "r"(a2), "r"(a3), "l"(db), "r"(scale_d));
}

__device__ __forceinline__ void wgmma_ss_n128_tb1(float (&d)[64], uint64_t da, uint64_t db, int scale_d) {
    asm volatile("{\n.reg .pred p;\nsetp.ne.b32 p, %66, 0;\n"
        "wgmma.mma_async.sync.aligned.m64n128k16.f32.bf16.bf16 {%0, %1, %2, %3, %4, %5, %6, %7, %8, %9, %10, %11, %12, %13, %14, %15, %16, %17, %18, %19, %20, %21, %22, %23, %24, %25, %26, %27, %28, %29, %30, %31, %32, %33, %34, %35, %36, %37, %38, %39, %40, %41, %42, %43, %44, %45, %46, %47, %48, %49, %50, %51, %52, %53, %54, %55, %56, %57, %58, %59, %60, %61, %62, %63}, %64, %65, p, 1, 1, 0, 1;\n}\n"
        : "+f"(d[0]), "+f"(d[1]), "+f"(d[2]), "+f"(d[3]), "+f"(d[4]), "+f"(d[5]), "+f"(d[6]), "+f"(d[7]), "+f"(d[8]), "+f"(d[9]), "+f"(d[10]), "+f"(d[11]), "+f"(d[12]), "+f"(d[13]), "+f"(d[14]), "+f"(d[15]), "+f"(d[16]), "+f"(d[17]), "+f"(d[18]), "+f"(d[19]), "+f"(d[20]), "+f"(d[21]), "+f"(d[22]), "+f"(d[23]), "+f"(d[24]), "+f"(d[25]), "+f"(d[26]), "+f"(d[27]), "+f"(d[28]), "+f"(d[29]), "+f"(d[30]), "+f"(d[31]), "+f"(d[32]), "+f"(d[33]), "+f"(d[34]), "+f"(d[35]), "+f"(d[36]), "+f"(d[37]), "+f"(d[38]), "+f"(d[39]), "+f"(d[40]), "+f"(d[41]), "+f"(d[42]), "+f"(d[43]), "+f"(d[44]), "+f"(d[45]), "+f"(d[46]), "+f"(d[47]), "+f"(d[48]), "+f"(d[49]), "+f"(d[50]), "+f"(d[51]), "+f"(d[52]), "+f"(d[53]), "+f"(d[54]), "+f"(d[55]), "+f"(d[56]), "+f"(d[57]), "+f"(d[58]), "+f"(d[59]), "+f"(d[60]), "+f"(d[61]), "+f"(d[62]), "+f"(d[63])
        : "l"(da), "l"(db), "r"(scale_d));
}

__device__ __forceinline__ void wgmma_ss_n256_tb1(float (&d)[128], uint64_t da, uint64_t db, int scale_d) {
    asm volatile("{\n.reg .pred p;\nsetp.ne.b32 p, %130, 0;\n"
        "wgmma.mma_async.sync.aligned.m64n256k16.f32.bf16.bf16 {%0, %1, %2, %3, %4, %5, %6, %7, %8, %9, %10, %11, %12, %13, %14, %15, %16, %17, %18, %19, %20, %21, %22, %23, %24, %25, %26, %27, %28, %29, %30, %31, %32, %33, %34, %35, %36, %37, %38, %39, %40, %41, %42, %43, %44, %45, %46, %47, %48, %49, %50, %51, %52, %53, %54, %55, %56, %57, %58, %59, %60, %61, %62, %63, %64, %65, %66, %67, %68, %69, %70, %71, %72, %73, %74, %75, %76, %77, %78, %79, %80, %81, %82, %83, %84, %85, %86, %87, %88, %89, %90, %91, %92, %93, %94, %95, %96, %97, %98, %99, %100, %101, %102, %103, %104, %105, %106, %107, %108, %109, %110, %111, %112, %113, %114, %115, %116, %117, %118, %119, %120, %121, %122, %123, %124, %125, %126, %127}, %128, %129, p, 1, 1, 0, 1;\n}\n"
        : "+f"(d[0]), "+f"(d[1]), "+f"(d[2]), "+f"(d[3]), "+f"(d[4]), "+f"(d[5]), "+f"(d[6]), "+f"(d[7]), "+f"(d[8]), "+f"(d[9]), "+f"(d[10]), "+f"(d[11]), "+f"(d[12]), "+f"(d[13]), "+f"(d[14]), "+f"(d[15]), "+f"(d[16]), "+f"(d[17]), "+f"(d[18]), "+f"(d[19]), "+f"(d[20]), "+f"(d[21]), "+f"(d[22]), "+f"(d[23]), "+f"(d[24]), "+f"(d[25]), "+f"(d[26]), "+f"(d[27]), "+f"(d[28]), "+f"(d[29]), "+f"(d[30]), "+f"(d[31]), "+f"(d[32]), "+f"(d[33]), "+f"(d[34]), "+f"(d[35]), "+f"(d[36]), "+f"(d[37]), "+f"(d[38]), "+f"(d[39]), "+f"(d[40]), "+f"(d[41]), "+f"(d[42]), "+f"(d[43]), "+f"(d[44]), "+f"(d[45]), "+f"(d[46]), "+f"(d[47]), "+f"(d[48]), "+f"(d[49]), "+f"(d[50]), "+f"(d[51]), "+f"(d[52]), "+f"(d[53]), "+f"(d[54]), "+f"(d[55]), "+f"(d[56]), "+f"(d[57]), "+f"(d[58]), "+f"(d[59]), "+f"(d[60]), "+f"(d[61]), "+f"(d[62]), "+f"(d[63]), "+f"(d[64]), "+f"(d[65]), "+f"(d[66]), "+f"(d[67]), "+f"(d[68]), "+f"(d[69]), "+f"(d[70]), "+f"(d[71]), "+f"(d[72]), "+f"(d[73]), "+f"(d[74]), "+f"(d[75]), "+f"(d[76]), "+f"(d[77]), "+f"(d[78]), "+f"(d[79]), "+f"(d[80]), "+f"(d[81]), "+f"(d[82]), "+f"(d[83]), "+f"(d[84]), "+f"(d[85]), "+f"(d[86]), "+f"(d[87]), "+f"(d[88]), "+f"(d[89]), "+f"(d[90]), "+f"(d[91]), "+f"(d[92]), "+f"(d[93]), "+f"(d[94]), "+f"(d[95]), "+f"(d[96]), "+f"(d[97]), "+f"(d[98]), "+f"(d[99]), "+f"(d[100]), "+f"(d[101]), "+f"(d[102]), "+f"(d[103]), "+f"(d[104]), "+f"(d[105]), "+f"(d[106]), "+f"(d[107]), "+f"(d[108]), "+f"(d[109]), "+f"(d[110]), "+f"(d[111]), "+f"(d[112]), "+f"(d[113]), "+f"(d[114]), "+f"(d[115]), "+f"(d[116]), "+f"(d[117]), "+f"(d[118]), "+f"(d[119]), "+f"(d[120]), "+f"(d[121]), "+f"(d[122]), "+f"(d[123]), "+f"(d[124]), "+f"(d[125]), "+f"(d[126]), "+f"(d[127])
        : "l"(da), "l"(db), "r"(scale_d));
}

__device__ __forceinline__ void wgmma_ss_n32_tb0(float (&d)[16], uint64_t da, uint64_t db, int scale_d) {
    asm volatile("{\n.reg .pred p;\nsetp.ne.b32 p, %18, 0;\n"
        "wgmma.mma_async.sync.aligned.m64n32k16.f32.bf16.bf16 {%0, %1, %2, %3, %4, %5, %6, %7, %8, %9, %10, %11, %12, %13, %14, %15}, %16, %17, p, 1, 1, 0, 0;\n}\n"
        : "+f"(d[0]), "+f"(d[1]), "+f"(d[2]), "+f"(d[3]), "+f"(d[4]), "+f"(d[5]), "+f"(d[6]), "+f"(d[7]), "+f"(d[8]), "+f"(d[9]), "+f"(d[10]), "+f"(d[11]), "+f"(d[12]), "+f"(d[13]), "+f"(d[14]), "+f"(d[15])
        : "l"(da), "l"(db), "r"(scale_d));
}

__device__ __forceinline__ void wgmma_ss_n64_tb0(float (&d)[32], uint64_t da, uint64_t db, int scale_d) {
    asm volatile("{\n.reg .pred p;\nsetp.ne.b32 p, %34, 0;\n"
        "wgmma.mma_async.sync.aligned.m64n64k16.f32.bf16.bf16 {%0, %1, %2, %3, %4, %5, %6, %7, %8, %9, %10, %11, %12, %13, %14, %15, %16, %17, %18, %19, %20, %21, %22, %23, %24, %25, %26, %27, %28, %29, %30, %31}, %32, %33, p, 1, 1, 0, 0;\n}\n"
        : "+f"(d[0]), "+f"(d[1]), "+f"(d[2]), "+f"(d[3]), "+f"(d[4]), "+f"(d[5]), "+f"(d[6]), "+f"(d[7]), "+f"(d[8]), "+f"(d[9]), "+f"(d[10]), "+f"(d[11]), "+f"(d[12]), "+f"(d[13]), "+f"(d[14]), "+f"(d[15]), "+f"(d[16]), "+f"(d[17]), "+f"(d[18]), "+f"(d[19]), "+f"(d[20]), "+f"(d[21]), "+f"(d[22]), "+f"(d[23]), "+f"(d[24]), "+f"(d[25]), "+f"(d[26]), "+f"(d[27]), "+f"(d[28]), "+f"(d[29]), "+f"(d[30]), "+f"(d[31])
        : "l"(da), "l"(db), "r"(scale_d));
}

struct Maps {
    CUtensorMap xa, xa2, xas, wup4, wup8, mqa2, mqa4, mqb1, mqb2, uc, x, out, wq, wk, fa[3], fb[2], fc;
};

__device__ __forceinline__ uint64_t mkd(uint32_t lo) {
    uint64_t d;
    asm("mov.b64 %0, {%1, %2};" : "=l"(d) : "r"(lo), "r"((1024u >> 4) | (1u << 30)));
    return d;
}
__device__ __forceinline__ void bulk_ld(uint32_t dst, const void* src, uint32_t bytes, uint32_t bar) {
    asm volatile("cp.async.bulk.shared::cluster.global.mbarrier::complete_tx::bytes [%0], [%1], %2, [%3];" ::"r"(dst), "l"(src), "r"(bytes), "r"(bar) : "memory");
}
__device__ __forceinline__ void bulk_st(void* dst, uint32_t src, uint32_t bytes) {
    asm volatile("cp.async.bulk.global.shared::cta.bulk_group [%0], [%1], %2;" ::"l"(dst), "r"(src), "r"(bytes) : "memory");
}
__device__ __forceinline__ void ring_ld(uint32_t sb, uint32_t slot8, int n) {
    mbar_expect_tx(sb + B_R2 + slot8, 8192);
    bulk_ld(sb + R1 + slot8 * 1024, (const char*)g_wepi + n * 8192, 8192, sb + B_R2 + slot8);
}

__device__ __forceinline__ void ring_half(uint32_t sb, uint32_t slot8, uint32_t hoff, const CUtensorMap* tm, int c1, int c2) {
    mbar_expect_tx(sb + B_R1 + slot8, 8192);
    tma3(sb + slot8 * 2048 + hoff, tm, 0, c1, c2, sb + B_R1 + slot8);
}
__device__ __forceinline__ void ring_full(uint32_t sb, uint32_t slot8, const CUtensorMap* tm, int c1, int c2) {
    mbar_expect_tx(sb + B_R1 + slot8, 16384);
    mbar_arrive(sb + B_R1 + slot8);
    tma3(sb + slot8 * 2048, tm, 0, c1, c2, sb + B_R1 + slot8);
}
__device__ __forceinline__ void cta_done(int mode) {
    if (mode == 0 && atomicAdd(&g_sync[4], 1) == NCTA + 1) {
#pragma unroll
        for (int i = 0; i < 5; i++) g_sync[i] = 0;
    }
}

__device__ __forceinline__ void fold_cta(const Maps& mp, uint32_t sb, int mode) {
    constexpr uint32_t F_FULL = MISC, F_EMPTY = MISC + 32, F_T1 = MISC + 64, STG = 49152, FOUT = 3 * STG;
    const int tid = threadIdx.x, f = blockIdx.x - NCTA;
    if (mode == 2) return;
    if (tid == 0) {
        for (int i = 0; i < 3; i++) { mbar_init(sb + F_FULL + 8 * i, 1); mbar_init(sb + F_EMPTY + 8 * i, 2); }
        mbar_init(sb + F_T1, 2);
        asm volatile("fence.mbarrier_init.release.cluster;" ::: "memory");
        fence_async();
    }
    __syncthreads();
    const int wg = __shfl_sync(0xffffffffu, tid >> 7, 0);
    int st = 0, ph = 0;
    if (wg == 0) {
        if (tid == 0) {
#pragma unroll 1
            for (int it = 0; it < 96; it++) {
                const int p = it >> 3, kc = it & 7, job = p >> 2;
                if (it == 64) mbar_wait(sb + F_T1, 0);
                mbar_wait(sb + F_EMPTY + 8 * st, ph ^ 1);
                mbar_expect_tx(sb + F_FULL + 8 * st, STG);
                tma3(sb + st * STG, &mp.fa[job], 0, 256 * f + 128 * ((p >> 1) & 1), kc, sb + F_FULL + 8 * st);
                tma3(sb + st * STG + 16384, &mp.fb[job != 0], 0, 64 * kc + (job == 1 ? 512 : 0), 4 * (p & 1), sb + F_FULL + 8 * st);
                if (++st == 3) { st = 0; ph ^= 1; }
            }
        }
        return;
    }
    const int h = wg - 1, lane = tid & 31, w = (tid >> 5) & 3;
    const uint32_t sd = (sb & 0x3FFFF) >> 4;
    const bool el = (tid & 127) == 0;
#pragma unroll 1
    for (int p = 0; p < 12; p++) {
        float acc[128];
        fresh(acc);
#pragma unroll 1
        for (int kc = 0; kc < 8; kc++) {
            mbar_wait(sb + F_FULL + 8 * st, ph);
            wg_fence();
#pragma unroll
            for (int kk = 0; kk < 4; kk++)
                wgmma_ss_n256_tb1(acc, dsc(sd, st * STG + h * 8192 + kk * 32, 16), dsc(sd, st * STG + 16384 + kk * 2048, 8192), 1);
            wg_commit();
            wg_wait<0>();
            if (el) mbar_arrive(sb + F_EMPTY + 8 * st);
            if (++st == 3) { st = 0; ph ^= 1; }
        }
        pin(acc);
        const int job = p >> 2;
        if (el) {
            asm volatile("cp.async.bulk.wait_group 0;" ::: "memory");
            if (p == 4) { fence_async_g(); mbar_arrive(sb + F_T1); }
        }
        bar_sync(3 + h, 128);
        uint32_t r = 16 * w + (lane & 7) + ((lane >> 3) & 1) * 8;
        const float fs = job == 1 ? 0.5f : 1.f;
        if (job == 1) r = (r & ~31) | (((r >> 1) & 3) << 3) | (((r >> 3) & 3) << 1) | (r & 1);
        const uint32_t oa = sb + FOUT + h * 32768 + r * 128 + ((((lane >> 4) ^ r) & 7) << 4);
#pragma unroll
        for (int i = 0; i < 16; i++)
            stsm4((oa ^ ((i & 3) << 5)) + (i >> 2) * 8192, pack2(acc[8 * i] * fs, acc[8 * i + 1] * fs), pack2(acc[8 * i + 2] * fs, acc[8 * i + 3] * fs),
                  pack2(acc[8 * i + 4] * fs, acc[8 * i + 5] * fs), pack2(acc[8 * i + 6] * fs, acc[8 * i + 7] * fs));
        fence_async();
        bar_sync(3 + h, 128);
        if (el) {
            const int row0 = 256 * f + 128 * ((p >> 1) & 1) + 64 * h + (job == 1 ? 512 : 0);
            if (job == 0) tma3_store(&mp.fc, sb + FOUT + h * 32768, 0, row0, 4 * (p & 1));
            else {
#pragma unroll 1
                for (int i = 0; i < 16; i++)
                    bulk_st((char*)g_wepi + (row0 / 8 + 2 * (i & 3) + (p & 1)) * 8192 + (i >> 2) * 2048, sb + FOUT + h * 32768 + i * 2048, 2048);
            }
            asm volatile("cp.async.bulk.commit_group;" ::: "memory");
        }
    }
    if (el) {
        asm volatile("cp.async.bulk.wait_group 0;" ::: "memory");
        fence_async_g();
        if (mode == 0) flag_add(&g_sync[3]);
    }
    bar_sync(2, 256);
    if (tid == 128) cta_done(mode);
}

__global__ void __launch_bounds__(384, 1) main_kernel(const __grid_constant__ Maps mp, const bf16* __restrict__ x, const bf16* __restrict__ dw, const bf16* wup, const int mode) {
    extern __shared__ __align__(1024) uint8_t smem[];
    const uint32_t sb = smem_u32(smem);
    const int tid = threadIdx.x;
    PE();
    if (blockIdx.x >= NCTA) { fold_cta(mp, sb, mode); return; }
    const int b = blockIdx.x / TPB, ti = blockIdx.x % TPB;
    const int piece = blockIdx.x & 127;
    const int wg = __shfl_sync(0xffffffffu, tid >> 7, 0);
    const int lane = tid & 31, w = (tid >> 5) & 3;
    const bool w0 = __shfl_sync(0xffffffffu, w, 0) == 0;
    const uint32_t sd = (sb & 0x3FFFF) >> 4;
    const uint32_t adA = sd + (AT >> 4) + (1u << 16);
    const uint32_t bd0 = sd;
    const uint32_t bd2k = bd0 + ((2048u >> 4) << 16);
    const bool el = (tid & 127) == 0;
    const uint32_t lrow = 16 * w + (lane & 7) + ((lane >> 3) & 1) * 8;
    const uint32_t loff = lrow * 128 + ((((lane >> 4) ^ lrow) & 7) << 4);
    const int r0 = 16 * w + (lane >> 2);

    if (wg == 0) {
        asm volatile("setmaxnreg.inc.sync.aligned.u32 184;");
        uint32_t q[112];
        PG(206);
        if (tid == 0) {
            mbar_init(sb + B_MK, 1);
            for (int i = 0; i < 9; i++) mbar_init(sb + B_R1 + 8 * i, 2);
            for (int i = 0; i < 5; i++) asm volatile("st.shared.u32 [%0], 0;" ::"r"(sb + CNT + 4 * i) : "memory");
        } else if (tid == 32) {
            mbar_init(sb + B_LN, 1); mbar_init(sb + B_MQ, 1);
            mbar_init(sb + B_H1, 2); mbar_init(sb + B_H2, 1); mbar_init(sb + B_H3, 2);
            for (int i = 0; i < 3; i++) { mbar_init(sb + B_KV + 8 * i, 1); mbar_init(sb + B_P + 8 * i, 4); mbar_init(sb + B_GO + 8 * i, 4); }
            mbar_init(sb + B_UC, 1); mbar_init(sb + B_UC + 8, 1); mbar_init(sb + B_X, 8);
        } else if (tid == 64) {
            for (int i = 0; i < 20; i++) mbar_init(sb + B_R2 + 8 * i, 1);
        } else if (tid == 96) {
            for (int i = 0; i < 20; i++) mbar_init(sb + B_E2 + 8 * i, 4);
        }
        if (lane == 0) {
            asm volatile("fence.mbarrier_init.release.cluster;" ::: "memory");
            fence_async();
        }
        PG(207);
        __syncwarp();
        if (SU != 2) asm volatile("bar.arrive 5, 384;" ::: "memory");
        if (tid == 0) {
            mbar_expect_tx(sb + B_MK, 65536 + 32768);
            tma3(sb + 16384, &mp.wq, 0, 64 * (piece >> 4), 0, sb + B_MK);
            tma3(sb + 81920, &mp.wk, 0, 32 * (piece & 15), 0, sb + B_MK);
            for (int i = 0; i < 14; i++) mbar_arrive(sb + B_R1 + 8 * (i >> 1));
            if (mode != 1) {
                ring_full(sb, 56, &mp.wup8, 0, 8);
                ring_full(sb, 64, &mp.wup8, 16, 8);
                ring_full(sb, 0, &mp.wup8, 32, 8);
            }
        }
        PG(208);
        bar_sync(1, 128);
        if (SU == 2) asm volatile("bar.arrive 5, 384;" ::: "memory");
        PT(0);
        PG(200);
        {
            float mq[16];
            fresh(mq);
            mbar_wait(sb + B_MK, 0);
            PT(1);
            if (tid == 32) l2_prefetch((const char*)wup + piece * 8192, 8192);
            wg_fence();
#pragma unroll 1
            for (int c = 0; c < 8; c++)
#pragma unroll
                for (int kk = 0; kk < 4; kk++)
                    wgmma_ss_n32_tb0(mq, dsc(sd, 16384 + c * 8192 + kk * 32, 16), dsc(sd, 81920 + c * 4096 + kk * 32, 16), 1);
            wg_commit();
            wg_wait<0>();
            if (mode != 1 && w0 && elect1()) {
#pragma unroll 1
                for (int i = 1; i < 7; i++) ring_full(sb, 8 * i, &mp.wup8, 32 + 16 * i, 8);
            }
            pin(mq);
            uint32_t* c = reinterpret_cast<uint32_t*>(g_mqk + (64 * (piece >> 4) + r0) * D_ + 32 * (piece & 15) + 2 * (lane & 3));
#pragma unroll
            for (int n = 0; n < 4; n++) { c[4 * n] = pack2(mq[4 * n], mq[4 * n + 1]); c[4 * n + 4 * D_] = pack2(mq[4 * n + 2], mq[4 * n + 3]); }
            fence_async_g();
            bar_sync(1, 128);
            if (el) {
                if (mode == 0) flag_add(&g_sync[2]);
                if (mode == 0) flag_wait(&g_sync[2], NCTA);
                mbar_arrive(sb + B_MQ);
                PG(203);
                PT(12);
                mbar_wait(sb + B_LN, 0);
#pragma unroll 1
                for (int c = 0; c < 8; c++) {
                    tma4_store(&mp.xas, sb + AT + c * 8192, 0, 62 * ti, c, b);
                    const unsigned t0 = (unsigned)clock();
                    while (c < 7 && (unsigned)clock() - t0 < XS_GAP) __nanosleep(20);
                }
                asm volatile("cp.async.bulk.commit_group;" ::: "memory");
                if (mode == 1) asm volatile("cp.async.bulk.wait_group 0;" ::: "memory");
            }
            PT(13);
            if (mode == 1) return;
        }
        mbar_wait(sb + B_H1, 0);
        PT(2);
        uint32_t slot8 = 24, par = 0, prev8 = 0;
        auto adv = [&]() { prev8 = slot8; slot8 += 8; if (slot8 == 72) { slot8 = 0; par ^= 1; } };
        {
            float acc[128];
            fresh(acc);
            auto step = [&](int i) {
                const uint32_t aa = adA + (i >> 1) * 512 + (i & 1) * 4, bb = bd0 + ((4096u >> 4) << 16) + slot8 * 128;
                wg_fence();
                wgmma_ss_n256_tb1(acc, mkd(aa), mkd(bb), 1);
                wgmma_ss_n256_tb1(acc, mkd(aa + 2), mkd(bb + 128), 1);
                wg_commit();
                wg_wait<1>();
            };
#pragma unroll 1
            for (int i = 0; i < 8; i++) {
                mbar_wait(sb + B_R1 + slot8, par);
                step(i);
                if (i > 0 && w0 && elect1()) ring_full(sb, prev8, &mp.mqa4, 32 * i + 256, 4);
                adv();
            }
#pragma unroll 1
            for (int i = 8; i < 16; i++) {
                mbar_wait(sb + B_R1 + slot8, par);
                if (i == 15 && el) mbar_arrive(sb + B_H2);
                step(i);
                if (w0 && elect1()) ring_full(sb, prev8, &mp.wup8, 16 * i - 128, 0);
                adv();
            }
            wg_wait<0>();
            if (w0 && elect1()) ring_full(sb, prev8, &mp.wup8, 128, 0);
            pin(acc);
            PT(3);
#pragma unroll
            for (int kk = 0; kk < 4; kk++)
                stsm4((sb + QS + loff) ^ (kk << 5), pack2(acc[96 + 8 * kk], acc[97 + 8 * kk]), pack2(acc[98 + 8 * kk], acc[99 + 8 * kk]),
                      pack2(acc[100 + 8 * kk], acc[101 + 8 * kk]), pack2(acc[102 + 8 * kk], acc[103 + 8 * kk]));
            fence_async();
#pragma unroll
            for (int i = 47; i >= 0; i--) q[64 + i] = pack2v(acc[2 * i], acc[2 * i + 1]);
        }
        if (el) {
            asm volatile("cp.async.bulk.wait_group 0;" ::: "memory");
            if (mode == 0) {
                fence_async_g();
                flag_add(&g_sync[b]);
                flag_wait(&g_sync[b], TPB);
            }
        }
        __syncwarp();
        mbar_wait(sb + B_H3, 0);
        PT(4);
        slot8 = 48; par = 1;
#pragma unroll
        for (int half = 0; half < 2; half++) {
            float acc[64];
            fresh(acc);
            auto step = [&](int m) {
                const uint32_t aa = adA + m * 512, bb = bd0 + ((8192u >> 4) << 16) + slot8 * 128;
                mbar_wait(sb + B_R1 + slot8, par);
                wg_fence();
#pragma unroll
                for (int kk = 0; kk < 4; kk++) wgmma_ss_n128_tb1(acc, mkd(aa + 2 * kk), mkd(bb + 128 * kk), 1);
                wg_commit();
                wg_wait<1>();
            };
#pragma unroll 1
            for (int m = 0; m < 8; m++) {
                step(m);
                if (m > 0 && w0 && elect1()) {
                    if (half == 0) ring_full(sb, prev8, &mp.mqb2, 64 * m, 2);
                    else if (m < 4) tma4(sb + prev8 * 2048, &mp.xa2, 0, 0, 2 * m, b, sb + B_KV + 8);
                }
                adv();
            }
            wg_wait<0>();
            if (w0 && elect1()) {
                if (half == 0) {
                    mbar_expect_tx(sb + B_KV + 8, 65536);
                    tma4(sb + prev8 * 2048, &mp.xa2, 0, 0, 0, b, sb + B_KV + 8);
                } else {
                    mbar_expect_tx(sb + B_KV + 16, 65536);
                    tma4(sb + R2, &mp.xa, 0, 64, 0, b, sb + B_KV + 16);
                    mbar_expect_tx(sb + B_KV, 65536);
                    tma4(sb + R0, &mp.xa, 0, 128, 0, b, sb + B_KV);
                }
            }
            pin(acc);
#pragma unroll
            for (int i = 31; i >= 0; i--) q[32 * half + i] = pack2v(acc[2 * i], acc[2 * i + 1]);
        }
        bar_sync(1, 128);
        PT(5);

        const float CS = 0.04419417382415922f * 1.4426950408889634f;
        float m0 = -INFINITY, m1 = -INFINITY, l0 = 0.f, l1 = 0.f;
        int s = 0, sn = 1, ph = 0;
        float S[32];
        const bool l0w = lane == 0, q0 = (lane & 3) == 0;
#pragma unroll 1
        for (int j = -1;; j++) {
            if (j >= 0) {
                PL(j, 1);
                if (j == NKV - 1) {
#pragma unroll
                    for (int i = (T_ - 64 * (NKV - 1)) / 2; i < 32; i++) asm volatile("mov.b32 %0, 0xff800000;" : "=f"(S[i]));
                }
                const bool kv = mbar_test(sb + B_KV + sn * 8, ph);
                const uint32_t pb = sb + R3 + (s == 0 ? 2 : s - 1) * 8192;
                float a0, a1, sc0 = 1.f, sc1 = 1.f;
                auto expo = [&]() {
                    const float n0 = -m0 * CS, n1 = -m1 * CS;
                    a0 = 0.f; a1 = 0.f;
#pragma unroll
                    for (int kk = 0; kk < 4; kk++) {
                        float p[8];
#pragma unroll
                        for (int e = 0; e < 8; e++) p[e] = ex2(fmaf(S[8 * kk + e], CS, (e & 2) ? n1 : n0));
                        a0 += (p[0] + p[1]) + (p[4] + p[5]);
                        a1 += (p[2] + p[3]) + (p[6] + p[7]);
                        stsm4((pb + loff) ^ (kk << 5), pack2(p[0], p[1]), pack2(p[2], p[3]), pack2(p[4], p[5]), pack2(p[6], p[7]));
                    }
                };
                expo();
                if (__any_sync(0xffffffffu, !(a0 <= LAZY) || !(a1 <= LAZY))) {
                    float x0 = m0, x1 = m1;
#pragma unroll
                    for (int n = 0; n < 8; n++) { x0 = fmaxf(x0, fmaxf(S[4 * n], S[4 * n + 1])); x1 = fmaxf(x1, fmaxf(S[4 * n + 2], S[4 * n + 3])); }
                    x0 = fmaxf(x0, __shfl_xor_sync(0xffffffffu, x0, 1));
                    x1 = fmaxf(x1, __shfl_xor_sync(0xffffffffu, x1, 1));
                    x0 = fmaxf(x0, __shfl_xor_sync(0xffffffffu, x0, 2));
                    x1 = fmaxf(x1, __shfl_xor_sync(0xffffffffu, x1, 2));
                    sc0 = ex2((m0 - x0) * CS); sc1 = ex2((m1 - x1) * CS);
                    m0 = x0; m1 = x1;
                    expo();
                }
                if (q0) { sts_f32(sb + SCL + s * 256 + r0 * 4, sc0); sts_f32(sb + SCL + s * 256 + r0 * 4 + 32, sc1); }
                __syncwarp();
                if (l0w) mbar_arrive(sb + B_P + s * 8);
                l0 = fmaf(l0, sc0, a0); l1 = fmaf(l1, sc1, a1);
                PL(j, 2);
                if (j == NKV - 1) break;
                if (!kv) mbar_wait(sb + B_KV + sn * 8, ph);
            } else {
                mbar_wait(sb + B_KV + 8, 0);
            }
            float Sn[32];
            const uint32_t kd = sd + sn * 4096;
            wg_fence();
#pragma unroll
            for (int kk = 0; kk < 28; kk++) {
                wgmma_rs_n64_tb0(Sn, q[4 * kk], q[4 * kk + 1], q[4 * kk + 2], q[4 * kk + 3], dsc(kd, (kk >> 2) * 8192 + (kk & 3) * 32, 16), kk > 0);
                if (kk == FENCE_AT) { fence_async(); __syncwarp(); }
                if (kk == GO_AT) { PL(j, 3); if (j >= 0 && l0w) mbar_arrive(sb + B_GO + s * 8); }
            }
#pragma unroll
            for (int kk = 0; kk < 4; kk++)
                wgmma_ss_n64_tb0(Sn, dsc(sd, QS + kk * 32, 16), dsc(kd, 7 * 8192 + kk * 32, 16), 1);
            wg_commit();
            PL(j, 0);
            wg_wait<0>();
            pin(Sn);
#pragma unroll
            for (int i = 0; i < 32; i++) S[i] = Sn[i];
            s = sn;
            if (++sn == 3) sn = 0;
            if (sn == 1) ph ^= 1;
        }
        l0 += __shfl_xor_sync(0xffffffffu, l0, 1); l1 += __shfl_xor_sync(0xffffffffu, l1, 1);
        l0 += __shfl_xor_sync(0xffffffffu, l0, 2); l1 += __shfl_xor_sync(0xffffffffu, l1, 2);
        if (q0) { sts_f32(sb + LINV + r0 * 4, rcp(l0)); sts_f32(sb + LINV + r0 * 4 + 32, rcp(l1)); }
        fence_async();
        __syncwarp();
        if (l0w) {
            mbar_arrive(sb + B_GO + s * 8);
            uint32_t slot8 = 8 * w, par = 0;
#pragma unroll 1
            for (int n = 20 + w; n < 136; n += 4) {
                mbar_wait(sb + B_E2 + slot8, par);
                if (n < 128) ring_ld(sb, slot8, n);
                else {
                    mbar_expect_tx(sb + B_X, 8192);
                    tma4(sb + R1 + slot8 * 1024, &mp.x, 0, 62 * ti, n - 128, b, sb + B_X);
                }
                slot8 += 32;
                if (slot8 >= 160) { slot8 -= 160; par ^= 1; }
            }
        }
        PDUMP();
    } else {
        asm volatile("setmaxnreg.dec.sync.aligned.u32 160;");
        const int h = wg - 1;
        uint32_t v[4][8], v2[4][8];
        if (SU != 0) bar_sync(5, 384);
        PG(206);
#pragma unroll
        for (int i = 0; i < 8; i++) {
            const int t = 62 * ti - 1 + 32 * (i >> 2) + 16 * h + 4 * w + (i & 3);
            const uint4* p = reinterpret_cast<const uint4*>(x + ((size_t)b * T_ + t) * D_) + lane;
            uint32_t* d = i < 4 ? v[i & 3] : v2[i & 3];
#pragma unroll
            for (int c = 0; c < 2; c++)
                asm volatile("{\n.reg .pred p;\nsetp.lt.u32 p, %5, %6;\nmov.b32 %0, 0;\nmov.b32 %1, 0;\nmov.b32 %2, 0;\nmov.b32 %3, 0;\n"
                             "@p ld.global.nc.v4.u32 {%0, %1, %2, %3}, [%4];\n}\n"
                             : "=r"(d[4 * c]), "=r"(d[4 * c + 1]), "=r"(d[4 * c + 2]), "=r"(d[4 * c + 3]) : "l"(p + 32 * c), "r"(t), "n"(T_));
        }
#pragma unroll 1
        for (int bt = 0; bt < 2; bt++) {
            PT(bt ? 13 : 0);
            float a[8];
            const uint32_t la = sb + AT + (lane >> 3) * 8192 + (32 * bt + 16 * h + 4 * w) * 128 + (((lane & 7) ^ ((w & 1) * 4)) << 4);
            const bool b4 = lane & 16, b3 = lane & 8, b2 = lane & 4;
#pragma unroll
            for (int r = 0; r < 4; r++) {
                float c[4] = {0.f, 0.f, 0.f, 0.f};
#pragma unroll
                for (int i = 0; i < 8; i += 2) hmma(c, v[r][i], v[r][i], v[r][i + 1], v[r][i + 1], v[r][i], v[r][i + 1]);
                a[4 + r] = (lane & 3) == (lane >> 3) ? (b2 ? c[1] : c[0]) : 0.f;
                if (r & 1) {
                    float e[4] = {0.f, 0.f, 0.f, 0.f};
#pragma unroll
                    for (int i = 0; i < 8; i += 2) hmma(e, v[r - 1][i], v[r][i], v[r - 1][i + 1], v[r][i + 1], 0x3f803f80u, 0x3f803f80u);
                    a[r - 1] = e[0]; a[r] = e[2];
                }
            }
            float k[4];
#pragma unroll
            for (int i = 0; i < 4; i++) {
                const int lo = (i & 1) + 4 * (i >> 1);
                k[i] = (b4 ? a[lo + 2] : a[lo]) + __shfl_xor_sync(0xffffffffu, b4 ? a[lo] : a[lo + 2], 16);
            }
            const float k0 = (b3 ? k[1] : k[0]) + __shfl_xor_sync(0xffffffffu, b3 ? k[0] : k[1], 8);
            const float k1 = (b3 ? k[3] : k[2]) + __shfl_xor_sync(0xffffffffu, b3 ? k[2] : k[3], 8);
            float z = (b2 ? k1 : k0) + __shfl_xor_sync(0xffffffffu, b2 ? k0 : k1, 4);
            z += __shfl_xor_sync(0xffffffffu, z, 2);
            z += __shfl_xor_sync(0xffffffffu, z, 1);
            const float zo = __shfl_xor_sync(0xffffffffu, z, 4);
            PG(204 + bt);
            const float mu = (b2 ? zo : z) * (0.25f / D_);
            float sd_ = bfr(bfr(fmaxf(fmaf(b2 ? z : zo, 1.f / D_, -mu * mu), 0.f)) + 1e-5f);
            asm("sqrt.approx.f32 %0, %0;" : "+f"(sd_));
            const float ri = rcp(bfr(sd_));
            const uint32_t w1 = pack2(mu, ri), w2 = pack2(ri - bhi(w1), ri - bhi(w1));
#pragma unroll
            for (int r = 0; r < 4; r++) {
                const uint32_t s1 = __shfl_sync(0xffffffffu, w1, 8 * r), rl = __shfl_sync(0xffffffffu, w2, 8 * r);
                const uint32_t m2 = __byte_perm(s1, 0, 0x1010), rh = __byte_perm(s1, 0, 0x3232);
#pragma unroll
                for (int i = 0; i < 8; i++) { const uint32_t d = bsub2(v[r][i], m2); v[r][i] = bfma2(d, rh, bmul2(d, rl)); }
                sts4((la ^ (r << 4)) + r * 128, v[r][0], v[r][1], v[r][2], v[r][3]);
                sts4((la ^ (r << 4)) + r * 128 + 32768, v[r][4], v[r][5], v[r][6], v[r][7]);
#pragma unroll
                for (int i = 0; i < 8; i++) v[r][i] = v2[r][i];
            }
        }
        fence_async();
        if (SU == 0) bar_sync(5, 384); else bar_sync(2, 256);
        if (tid == 128) mbar_arrive(sb + B_LN);
        PG(202);
        if (mode == 1) return;
        float acc[128];
#pragma unroll
        for (int pass = 0; pass < 2; pass++) {
            if (pass == 1) mbar_wait(sb + B_H2, 0);
            PT(1 + 3 * pass);
            fresh(acc);
            uint32_t slot8 = pass ? 8 : 56, par = 0, prev8 = 0;
            auto adv = [&]() { prev8 = slot8; slot8 += 8; if (slot8 == 72) { slot8 = 0; par ^= 1; } };
            auto step = [&](int kk) {
                wg_fence();
                wgmma_ss_n256_tb1(acc, mkd(adA + (kk >> 2) * 512 + (kk & 3) * 2), mkd(bd2k + h * 512 + slot8 * 128), 1);
                wg_commit();
                wg_wait<1>();
            };
#pragma unroll 1
            for (int kk = 0; kk < 24; kk++) {
                mbar_wait(sb + B_R1 + slot8, par);
                step(kk);
                if (kk > 0 && w0 && elect1()) ring_half(sb, prev8, h * 8192, &mp.wup4, 16 * kk + 128, (pass ? 0 : 8) + 4 * h);
                adv();
            }
            if (pass == 0 && w0) mbar_wait(sb + B_MQ, 0);
#pragma unroll 1
            for (int kk = 24; kk < 32; kk++) {
                mbar_wait(sb + B_R1 + slot8, par);
                if (kk == 31 && el) mbar_arrive(sb + (pass ? B_H3 : B_H1));
                step(kk);
                if (w0 && elect1()) ring_half(sb, prev8, h * 8192, pass ? &mp.mqb1 : &mp.mqa2, (pass ? 64 : 32) * (kk - 24), pass ? h : 4 + 2 * h);
                adv();
            }
            wg_wait<0>();
            if (w0 && elect1()) ring_half(sb, prev8, h * 8192, pass ? &mp.mqb1 : &mp.mqa2, pass ? 0 : 256, pass ? 2 + h : 4 + 2 * h);
            pin(acc);
            PT(2 + 3 * pass);
            bf16* ucp = g_uc + ((size_t)blockIdx.x * 128 + r0) * D_ + 256 * h + 8 * (lane & 3);
            if (pass == 0) {
                float s0 = 0.f, s1 = 0.f, v0 = 0.f, v1 = 0.f;
#pragma unroll
                for (int n = 0; n < 32; n++) {
#pragma unroll
                    for (int e = 0; e < 4; e++) acc[4 * n + e] = gelu2(acc[4 * n + e]);
                    s0 += acc[4 * n] + acc[4 * n + 1]; s1 += acc[4 * n + 2] + acc[4 * n + 3];
                    v0 = fmaf(acc[4 * n], acc[4 * n], v0); v0 = fmaf(acc[4 * n + 1], acc[4 * n + 1], v0);
                    v1 = fmaf(acc[4 * n + 2], acc[4 * n + 2], v1); v1 = fmaf(acc[4 * n + 3], acc[4 * n + 3], v1);
                }
#pragma unroll
                for (int o = 1; o < 4; o <<= 1) {
                    s0 += __shfl_xor_sync(0xffffffffu, s0, o); s1 += __shfl_xor_sync(0xffffffffu, s1, o);
                    v0 += __shfl_xor_sync(0xffffffffu, v0, o); v1 += __shfl_xor_sync(0xffffffffu, v1, o);
                }
                if ((lane & 3) == 0) {
                    uint32_t a = sb + STAT + h * 512 + r0 * 8;
                    sts_f32(a, s0); sts_f32(a + 4, v0); sts_f32(a + 64, s1); sts_f32(a + 68, v1);
                }
                bar_sync(2, 256);
                {
                    uint32_t a = sb + STAT + (h ^ 1) * 512 + r0 * 8;
                    s0 = (s0 + lds_f32(a)) * (1.f / 512.f); v0 = (v0 + lds_f32(a + 4)) * (1.f / 512.f);
                    s1 = (s1 + lds_f32(a + 64)) * (1.f / 512.f); v1 = (v1 + lds_f32(a + 68)) * (1.f / 512.f);
                }
                v0 = rsqrtf(fmaxf(fmaf(-s0, s0, v0), 0.f) + 4e-5f); v1 = rsqrtf(fmaxf(fmaf(-s1, s1, v1), 0.f) + 4e-5f);
                s0 = -s0 * v0; s1 = -s1 * v1;
#pragma unroll
                for (int m = 0; m < 8; m++) {
                    const float* a_ = acc + 16 * m;
                    stg4(ucp + 64 * D_ + 32 * m, pack2(fmaf(a_[0], v0, s0), fmaf(a_[1], v0, s0)), pack2(fmaf(a_[4], v0, s0), fmaf(a_[5], v0, s0)),
                         pack2(fmaf(a_[8], v0, s0), fmaf(a_[9], v0, s0)), pack2(fmaf(a_[12], v0, s0), fmaf(a_[13], v0, s0)));
                    stg4(ucp + 72 * D_ + 32 * m, pack2(fmaf(a_[2], v1, s1), fmaf(a_[3], v1, s1)), pack2(fmaf(a_[6], v1, s1), fmaf(a_[7], v1, s1)),
                         pack2(fmaf(a_[10], v1, s1), fmaf(a_[11], v1, s1)), pack2(fmaf(a_[14], v1, s1), fmaf(a_[15], v1, s1)));
                }
            } else {
#pragma unroll
                for (int m = 0; m < 8; m++) {
                    const float* a_ = acc + 16 * m;
                    stg4(ucp + 32 * m, pack2(gelu2(a_[0]), gelu2(a_[1])), pack2(gelu2(a_[4]), gelu2(a_[5])),
                         pack2(gelu2(a_[8]), gelu2(a_[9])), pack2(gelu2(a_[12]), gelu2(a_[13])));
                    stg4(ucp + 8 * D_ + 32 * m, pack2(gelu2(a_[2]), gelu2(a_[3])), pack2(gelu2(a_[6]), gelu2(a_[7])),
                         pack2(gelu2(a_[10]), gelu2(a_[11])), pack2(gelu2(a_[14]), gelu2(a_[15])));
                    if (m & 1) PT(12);
                }
                bar_sync(3 + h, 128);
            }
            PT(3 + 3 * pass);
        }
        int s = 1, ph = 0;
        uint32_t* cp = reinterpret_cast<uint32_t*>(g_uc + (size_t)blockIdx.x * 128 * D_) + (tid - 128);
        const uint32_t* dp = reinterpret_cast<const uint32_t*>(dw) + (((tid - 128) & ~15) | ((lane & 3) << 2) | ((lane >> 2) & 3));
        const uint32_t d0 = ldg_v(dp), d1 = ldg_v(dp + D_ / 2), d2 = ldg_v(dp + D_);
        uint32_t ga = ldg_cg(cp + 64 * (D_ / 2)), gb = ldg_cg(cp + 65 * (D_ / 2));
        fresh(acc);
#pragma unroll 1
        for (int j = 0; j < NKV; j++) {
            cp += D_ / 2;
            uint32_t gc = 0, uu = 0;
            if (j < NKV - 1) { gc = ldg_cg(cp + 65 * (D_ / 2)); uu = ldg_cg(cp); }
            mbar_wait(sb + B_P + s * 8, ph);
            PL(j, 0);
            if (j > 0) {
                const float sc0 = lds_f32(sb + SCL + s * 256 + r0 * 4), sc1 = lds_f32(sb + SCL + s * 256 + r0 * 4 + 32);
                if (__any_sync(0xffffffffu, sc0 != 1.f || sc1 != 1.f)) {
#pragma unroll
                    for (int n = 0; n < 32; n++) { acc[4 * n] *= sc0; acc[4 * n + 1] *= sc0; acc[4 * n + 2] *= sc1; acc[4 * n + 3] *= sc1; }
                }
            }
            mbar_wait(sb + B_GO + s * 8, ph);
            PL(j, 1);
            const uint32_t vd = sd + s * 4096 + h * 2048, pd = sd + (s == 0 ? 2 : s - 1) * 512;
            pin(acc);
            wg_fence();
#pragma unroll
            for (int kk = 0; kk < 4; kk++) wgmma_ss_n256_tb1(acc, dsc(pd, R3 + kk * 32, 16), dsc(vd, kk * 2048, 8192), 1);
            wg_commit();
            wg_wait<0>();
            pin(acc);
            PL(j, 2);
            if (w0 && elect1()) {
                if (j == NKV - 5 && mode == 0) flag_wait(&g_sync[3], 4);
                if (j == XPF) {
                    const int t0 = 62 * ti + 31 * h, nr = min(31, T_ - t0);
                    if (nr > 0) l2_prefetch(x + ((size_t)b * T_ + t0) * D_, nr * 1024);
                }
                if (atom_inc_s(sb + CNT + 4 * s) & 1) {
                    if (j + 3 < NKV) {
                        mbar_expect_tx(sb + B_KV + s * 8, 65536);
                        tma4(sb + s * 65536, &mp.xa, 0, 64 * (j + 3), 0, b, sb + B_KV + s * 8);
                    } else if (j < NKV - 1) {
                        const int n0 = j == NKV - 3 ? 0 : 8, n1 = n0 + 8;
#pragma unroll 1
                        for (int n = n0; n < n1; n++) ring_ld(sb, n * 8, n);
                    }
                }
            }
            if (j < NKV - 1) asm volatile("st.global.u32 [%0], %1;" ::"l"(cp), "r"(bmul2(uu, bfma2(gc, d2, bfma2(gb, d1, bmul2(ga, d0))))) : "memory");
            ga = gb; gb = gc;
            if (++s == 3) s = 0;
            if (s == 1) ph ^= 1;
        }
        {
            const float i0 = lds_f32(sb + LINV + r0 * 4), i1 = lds_f32(sb + LINV + r0 * 4 + 32);
#pragma unroll
            for (int p = 0; p < 16; p++)
                stsm4(((sb + R0 + h * 32768 + loff) ^ ((p & 3) << 5)) + (p >> 2) * 8192,
                      pack2(acc[8 * p] * i0, acc[8 * p + 1] * i0), pack2(acc[8 * p + 2] * i1, acc[8 * p + 3] * i1),
                      pack2(acc[8 * p + 4] * i0, acc[8 * p + 5] * i0), pack2(acc[8 * p + 6] * i1, acc[8 * p + 7] * i1));
        }
        fence_async();
        fence_async_g();
        bar_sync(2, 256);
        if (lane == 0 && w < 2) ring_ld(sb, 128 + 16 * w + 8 * h, 16 + 2 * w + h);
        PT(7);
        fresh(acc);
        {
            uint32_t slot8 = 8 * h, par = 0, prev8 = 0;
#pragma unroll 1
            for (int kk = 0; kk < 64; kk++) {
                if (kk == 32 || kk == 48) mbar_wait(sb + B_UC + (kk >> 1 & 8), 0);
                mbar_wait(sb + B_R2 + slot8, par);
                wg_fence();
                wgmma_ss_n256_tb1(acc, mkd(sd + (1u << 16) + (R0 >> 4) + (kk >> 2 & 7) * 512 + (kk & 3) * 2), mkd(bd2k + (R1 >> 4) + slot8 * 64), 1);
                wg_commit();
                wg_wait<1>();
                if (kk > 0 && lane == 0) mbar_arrive(sb + B_E2 + prev8);
                if ((kk == 16 || kk == 32) && w0 && elect1() && (atom_inc_s(sb + CNT + 12 + (kk >> 3 & 4)) & 1)) {
                    mbar_expect_tx(sb + B_UC + (kk >> 2 & 8), 32768);
                    tma3(sb + R0 + (kk & 32) * 1024, &mp.uc, 0, 128 * blockIdx.x, kk >> 3 & 4, sb + B_UC + (kk >> 2 & 8));
                }
                prev8 = slot8;
                slot8 += 16;
                if (slot8 >= 160) { slot8 -= 160; par ^= 1; }
            }
        }
        wg_wait<0>();
        pin(acc);
        PT(8);
        mbar_wait(sb + B_X, 0);
        PT(9);
        {
            const uint32_t sr = (lrow + 63) & 63;
            const uint32_t xoff = sr * 128 + ((((lane >> 4) ^ sr) & 7) << 4);
#pragma unroll
            for (int p = 0; p < 16; p++) {
                const uint32_t a = ((sb + R2 + h * 32768 + xoff) ^ ((p & 3) << 5)) + (p >> 2) * 8192;
                uint32_t xv[4];
                ldsm4(a, xv);
#pragma unroll
                for (int e = 0; e < 4; e++)
                    xv[e] = pack2(acc[8 * p + 2 * e] + __uint_as_float(xv[e] << 16), acc[8 * p + 2 * e + 1] + __uint_as_float(xv[e] & 0xffff0000u));
                stsm4(a, xv[0], xv[1], xv[2], xv[3]);
            }
        }
        fence_async();
        bar_sync(3 + h, 128);
        if (el) {
            for (int c = 0; c < 4; c++) tma4_store(&mp.out, sb + R2 + (4 * h + c) * 8192, 0, 62 * ti, 4 * h + c, b);
            asm volatile("cp.async.bulk.commit_group;" ::: "memory");
            PT(10);
            if (h == 0) cta_done(mode);
            asm volatile("cp.async.bulk.wait_group.read 0;" ::: "memory");
        }
        PT(11);
        PG(201);
        PDUMP();
    }
}

typedef CUresult (*PFN_enc)(CUtensorMap*, CUtensorMapDataType, cuuint32_t, void*, const cuuint64_t*, const cuuint64_t*,
                            const cuuint32_t*, const cuuint32_t*, CUtensorMapInterleave, CUtensorMapSwizzle,
                            CUtensorMapL2promotion, CUtensorMapFloatOOBfill);

static void enc(PFN_enc f, CUtensorMap* m, void* base, int rank, const cuuint64_t* dims, const cuuint64_t* strides, const cuuint32_t* box) {
    cuuint32_t es[5] = {1, 1, 1, 1, 1};
    f(m, CU_TENSOR_MAP_DATA_TYPE_BFLOAT16, rank, base, dims, strides, box, es, CU_TENSOR_MAP_INTERLEAVE_NONE,
      CU_TENSOR_MAP_SWIZZLE_128B, CU_TENSOR_MAP_L2_PROMOTION_L2_256B, CU_TENSOR_MAP_FLOAT_OOB_FILL_NONE);
}
static void enc_act(PFN_enc f, CUtensorMap* m, void* base, int rows, int chunks, int trows = T_, int pitch = T_) {
    cuuint64_t dims[4] = {64, (cuuint64_t)trows, 8, (cuuint64_t)NB_};
    cuuint64_t st[3] = {1024, 128, (cuuint64_t)pitch * 1024};
    cuuint32_t box[4] = {64, (cuuint32_t)rows, (cuuint32_t)chunks, 1};
    enc(f, m, base, 4, dims, st, box);
}
static void enc_w(PFN_enc f, CUtensorMap* m, void* base, int krows, int ncols, int bk, int bc) {
    cuuint64_t dims[3] = {64, (cuuint64_t)krows, (cuuint64_t)(ncols / 64)};
    cuuint64_t st[2] = {(cuuint64_t)ncols * 2, 128};
    cuuint32_t box[3] = {64, (cuuint32_t)bk, (cuuint32_t)bc};
    enc(f, m, base, 3, dims, st, box);
}

extern "C" void kernel_launch(void* const* d_in, const int* in_sizes, int n_in, void* d_out, int out_size) {
    const bf16* x = (const bf16*)d_in[0];
    static PFN_enc fenc = nullptr;
    static void *p_xa, *p_mqk, *p_uc, *p_t1;
    static int fused = 0;
    if (!fenc) {
        void* fn = nullptr;
        cudaDriverEntryPointQueryResult qr;
        cudaGetDriverEntryPoint("cuTensorMapEncodeTiled", &fn, cudaEnableDefault, &qr);
        fenc = (PFN_enc)fn;
        cudaGetSymbolAddress(&p_xa, g_xa);
        cudaGetSymbolAddress(&p_mqk, g_mqk);
        cudaGetSymbolAddress(&p_uc, g_uc);
        cudaGetSymbolAddress(&p_t1, g_t1);
        cudaFuncSetAttribute(main_kernel, cudaFuncAttributeMaxDynamicSharedMemorySize, SMEM_BYTES);
        int dev = 0, sms = 0, occ = 0;
        cudaGetDevice(&dev);
        cudaDeviceGetAttribute(&sms, cudaDevAttrMultiProcessorCount, dev);
        cudaOccupancyMaxActiveBlocksPerMultiprocessor(&occ, main_kernel, 384, SMEM_BYTES);
        fused = sms * occ >= NCTA + 2;
    }
    Maps mp;
    enc_act(fenc, &mp.xa, (char*)p_xa + 1024, 64, 8, T_, T_ + 8);
    enc_act(fenc, &mp.xa2, (char*)p_xa + 1024, 64, 2, T_, T_ + 8);
    enc_act(fenc, &mp.xas, p_xa, 64, 1, T_ + 1, T_ + 8);
    enc_act(fenc, &mp.x, (void*)x, 64, 1);
    enc_act(fenc, &mp.out, d_out, 62, 1);
    enc_w(fenc, &mp.wup4, d_in[5], 512, 1024, 16, 4);
    enc_w(fenc, &mp.wup8, d_in[5], 512, 1024, 16, 8);
    enc_w(fenc, &mp.mqa2, p_mqk, 512, 512, 32, 2);
    enc_w(fenc, &mp.mqa4, p_mqk, 512, 512, 32, 4);
    enc_w(fenc, &mp.mqb1, p_mqk, 512, 512, 64, 1);
    enc_w(fenc, &mp.mqb2, p_mqk, 512, 512, 64, 2);
    enc_w(fenc, &mp.uc, p_uc, NCTA * 128, 512, 64, 4);
    enc_w(fenc, &mp.wq, d_in[1], 512, 512, 64, 8);
    enc_w(fenc, &mp.wk, d_in[2], 512, 512, 32, 8);
    enc_w(fenc, &mp.fa[0], d_in[3], 512, 512, 128, 1);
    enc_w(fenc, &mp.fa[1], d_in[7], 512, 512, 128, 1);
    enc_w(fenc, &mp.fa[2], p_t1, 512, 512, 128, 1);
    enc_w(fenc, &mp.fb[0], d_in[4], 512, 512, 64, 4);
    enc_w(fenc, &mp.fb[1], d_in[8], 1024, 512, 64, 4);
    enc_w(fenc, &mp.fc, p_t1, 512, 512, 64, 4);
    cudaStream_t st = cudaStreamPerThread;
    if (fused) {
        main_kernel<<<NCTA + 2, 384, SMEM_BYTES, st>>>(mp, x, (const bf16*)d_in[6], (const bf16*)d_in[5], 0);
    } else {
        main_kernel<<<NCTA + 2, 384, SMEM_BYTES, st>>>(mp, x, (const bf16*)d_in[6], (const bf16*)d_in[5], 1);
        main_kernel<<<NCTA + 2, 384, SMEM_BYTES, st>>>(mp, x, (const bf16*)d_in[6], (const bf16*)d_in[5], 2);
    }
}
```

```cpp
#include <cuda_runtime.h>
#include <cuda_bf16.h>
#include <cuda.h>
#include <stdint.h>

typedef __nv_bfloat16 bf16;

constexpr int T_ = 4000, D_ = 512, NB_ = 2;
constexpr int TPB = 65;
constexpr int NCTA = TPB * NB_;
constexpr int NKV = 63;

__device__ __align__(1024) bf16 g_xa[NB_ * (T_ + 8) * D_];
__device__ __align__(1024) bf16 g_mqk[D_ * D_];
__device__ __align__(1024) bf16 g_t1[D_ * D_];
__device__ __align__(1024) bf16 g_wepi[2 * D_ * D_];
__device__ __align__(1024) bf16 g_uc[NCTA * 128 * D_];
__device__ unsigned g_sync[8];

#define PT(i) do { if (el) asm volatile("st.shared.u32 [%0], %1;" ::"r"(sb + MISC + 2560), "r"((unsigned)clock())); } while (0)
#define PG(i)
#define PE()
#define PLM 15
#define PL(j, q) do { if ((PLM >> ((q) + (wg ? 4 : 0))) & 1) PT(0); } while (0)
#define PDUMP()

#define FENCE_AT 1
#define GO_AT 25
#define LAZY 256.f
#define SU 2
#define XS_GAP 800
#define XPF 54
#define URAW 1
#define LAGA 1
#define LAGB 1
#define PFW 1
constexpr uint32_t R0 = 0, R1 = 65536, R2 = 131072, R3 = 196608, QS = 221184, MISC = 229376;
constexpr uint32_t AT = 147456;
constexpr uint32_t SMEM_BYTES = 232448;
constexpr uint32_t B_R1 = MISC + 1856  , B_MK = MISC + 48, B_LN = MISC + 56, B_MQ = MISC + 64,
                   B_H1 = MISC + 88, B_H2 = MISC + 96, B_H3 = MISC + 104,
                   B_KV = MISC + 112, B_P = MISC + 136, B_GO = MISC + 160, B_UC = MISC + 184  ,
                   B_X = MISC + 200, CNT = MISC + 208  , SCL = MISC + 512  ,
                   LINV = MISC + 1280  , STAT = MISC + 512  ,
                   B_R2 = MISC + 1536  , B_E2 = MISC + 1696  ;

__device__ __forceinline__ uint32_t smem_u32(const void* p) { return (uint32_t)__cvta_generic_to_shared(p); }
__device__ __forceinline__ void wg_fence() { asm volatile("wgmma.fence.sync.aligned;" ::: "memory"); }
__device__ __forceinline__ void wg_commit() { asm volatile("wgmma.commit_group.sync.aligned;" ::: "memory"); }
template <int N> __device__ __forceinline__ void wg_wait() { asm volatile("wgmma.wait_group.sync.aligned %0;" ::"n"(N) : "memory"); }
__device__ __forceinline__ uint64_t dsc(uint32_t sd, uint32_t off, uint32_t lbo) {
    uint32_t lo = sd + (off >> 4) + ((lbo >> 4) << 16);
    uint64_t d;
    asm("mov.b64 %0, {%1, %2};" : "=l"(d) : "r"(lo), "r"((1024u >> 4) | (1u << 30)));
    return d;
}
__device__ __forceinline__ bool elect1() {
    uint32_t p;
    asm volatile("{\n.reg .pred p;\nelect.sync _|p, 0xffffffff;\nselp.u32 %0, 1, 0, p;\n}\n" : "=r"(p));
    return p != 0;
}
__device__ __forceinline__ void mbar_init(uint32_t bar, int cnt) { asm volatile("mbarrier.init.shared::cta.b64 [%0], %1;" ::"r"(bar), "r"(cnt) : "memory"); }
__device__ __forceinline__ void mbar_expect_tx(uint32_t bar, uint32_t bytes) { asm volatile("mbarrier.arrive.expect_tx.shared::cta.b64 _, [%0], %1;" ::"r"(bar), "r"(bytes) : "memory"); }
__device__ __forceinline__ void mbar_arrive(uint32_t bar) { asm volatile("mbarrier.arrive.shared::cta.b64 _, [%0];" ::"r"(bar) : "memory"); }
__device__ __forceinline__ void mbar_wait(uint32_t bar, uint32_t parity) {
    uint32_t ok;
#pragma unroll 1
    for (uint32_t it = 0;; ++it) {
        asm volatile("{\n.reg .pred p;\nmbarrier.try_wait.parity.shared::cta.b64 p, [%1], %2;\nselp.u32 %0, 1, 0, p;\n}\n" : "=r"(ok) : "r"(bar), "r"(parity) : "memory");
        if (ok) break;
        if (it > (1u << 20)) __trap();
    }
}
__device__ __forceinline__ bool mbar_test(uint32_t bar, uint32_t parity) {
    uint32_t ok;
    asm volatile("{\n.reg .pred p;\nmbarrier.test_wait.parity.shared::cta.b64 p, [%1], %2;\nselp.u32 %0, 1, 0, p;\n}\n" : "=r"(ok) : "r"(bar), "r"(parity) : "memory");
    return ok != 0;
}
__device__ __forceinline__ void fence_async() { asm volatile("fence.proxy.async.shared::cta;" ::: "memory"); }
__device__ __forceinline__ void fence_async_g() { asm volatile("fence.proxy.async.global;" ::: "memory"); }
__device__ __forceinline__ void bar_sync(int id, int n) { asm volatile("bar.sync %0, %1;" ::"r"(id), "r"(n) : "memory"); }
__device__ __forceinline__ void tma3(uint32_t dst, const CUtensorMap* tm, int c0, int c1, int c2, uint32_t bar) {
    asm volatile("cp.async.bulk.tensor.3d.shared::cluster.global.mbarrier::complete_tx::bytes [%0], [%1, {%3, %4, %5}], [%2];"
                 ::"r"(dst), "l"(tm), "r"(bar), "r"(c0), "r"(c1), "r"(c2) : "memory");
}
__device__ __forceinline__ void tma4(uint32_t dst, const CUtensorMap* tm, int c0, int c1, int c2, int c3, uint32_t bar) {
    asm volatile("cp.async.bulk.tensor.4d.shared::cluster.global.mbarrier::complete_tx::bytes [%0], [%1, {%3, %4, %5, %6}], [%2];"
                 ::"r"(dst), "l"(tm), "r"(bar), "r"(c0), "r"(c1), "r"(c2), "r"(c3) : "memory");
}
__device__ __forceinline__ void tma4_store(const CUtensorMap* tm, uint32_t src, int c0, int c1, int c2, int c3) {
    asm volatile("cp.async.bulk.tensor.4d.global.shared::cta.bulk_group [%0, {%2, %3, %4, %5}], [%1];"
                 ::"l"(tm), "r"(src), "r"(c0), "r"(c1), "r"(c2), "r"(c3) : "memory");
}
__device__ __forceinline__ void tma3_store(const CUtensorMap* tm, uint32_t src, int c0, int c1, int c2) {
    asm volatile("cp.async.bulk.tensor.3d.global.shared::cta.bulk_group [%0, {%2, %3, %4}], [%1];"
                 ::"l"(tm), "r"(src), "r"(c0), "r"(c1), "r"(c2) : "memory");
}
__device__ __forceinline__ void stsm4(uint32_t addr, uint32_t a, uint32_t b, uint32_t c, uint32_t d) {
    asm volatile("stmatrix.sync.aligned.m8n8.x4.shared.b16 [%0], {%1, %2, %3, %4};" ::"r"(addr), "r"(a), "r"(b), "r"(c), "r"(d) : "memory");
}
__device__ __forceinline__ void ldsm4(uint32_t addr, uint32_t (&r)[4]) {
    asm volatile("ldmatrix.sync.aligned.m8n8.x4.shared.b16 {%0, %1, %2, %3}, [%4];" : "=r"(r[0]), "=r"(r[1]), "=r"(r[2]), "=r"(r[3]) : "r"(addr) : "memory");
}
__device__ __forceinline__ void ldsm2(uint32_t addr, uint32_t (&r)[2]) {
    asm volatile("ldmatrix.sync.aligned.m8n8.x2.shared.b16 {%0, %1}, [%2];" : "=r"(r[0]), "=r"(r[1]) : "r"(addr) : "memory");
}
__device__ __forceinline__ void stg4(void* p, uint32_t a, uint32_t b, uint32_t c, uint32_t d) {
    asm volatile("st.global.v4.u32 [%0], {%1, %2, %3, %4};" ::"l"(p), "r"(a), "r"(b), "r"(c), "r"(d) : "memory");
}
__device__ __forceinline__ void hmma(float (&c)[4], uint32_t a0, uint32_t a1, uint32_t a2, uint32_t a3, uint32_t b0, uint32_t b1) {
    asm("mma.sync.aligned.m16n8k16.row.col.f32.bf16.bf16.f32 {%0, %1, %2, %3}, {%4, %5, %6, %7}, {%8, %9}, {%0, %1, %2, %3};"
        : "+f"(c[0]), "+f"(c[1]), "+f"(c[2]), "+f"(c[3]) : "r"(a0), "r"(a1), "r"(a2), "r"(a3), "r"(b0), "r"(b1));
}
__device__ __forceinline__ uint32_t pack2(float lo, float hi) {
    uint32_t r;
    asm("cvt.rn.bf16x2.f32 %0, %1, %2;" : "=r"(r) : "f"(hi), "f"(lo));
    return r;
}
__device__ __forceinline__ uint32_t pack2v(float lo, float hi) {
    uint32_t r;
    asm volatile("cvt.rn.bf16x2.f32 %0, %1, %2;" : "=r"(r) : "f"(hi), "f"(lo));
    return r;
}
__device__ __forceinline__ uint32_t bmul2(uint32_t a, uint32_t b) { uint32_t r; asm("mul.rn.bf16x2 %0, %1, %2;" : "=r"(r) : "r"(a), "r"(b)); return r; }
__device__ __forceinline__ uint32_t bfma2(uint32_t a, uint32_t b, uint32_t c) { uint32_t r; asm("fma.rn.bf16x2 %0, %1, %2, %3;" : "=r"(r) : "r"(a), "r"(b), "r"(c)); return r; }
__device__ __forceinline__ float ex2(float x) { float r; asm("ex2.approx.ftz.f32 %0, %1;" : "=f"(r) : "f"(x)); return r; }
__device__ __forceinline__ float rcp(float x) { float r; asm("rcp.approx.ftz.f32 %0, %1;" : "=f"(r) : "f"(x)); return r; }
__device__ __forceinline__ float gelu2(float x) {
    float t = fmaf(x * x, 0.044715f * 0.7978845608028654f, 0.7978845608028654f), th;
    asm("tanh.approx.f32 %0, %1;" : "=f"(th) : "f"(x * t));
    return fmaf(x, th, x);
}
__device__ __forceinline__ uint32_t ldg_v(const uint32_t* p) { uint32_t v; asm volatile("ld.global.nc.u32 %0, [%1];" : "=r"(v) : "l"(p)); return v; }
__device__ __forceinline__ uint32_t ldg_cg(const uint32_t* p) { uint32_t v; asm volatile("ld.global.cg.u32 %0, [%1];" : "=r"(v) : "l"(p) : "memory"); return v; }
__device__ __forceinline__ float lds_f32(uint32_t a) { float v; asm volatile("ld.shared.f32 %0, [%1];" : "=f"(v) : "r"(a) : "memory"); return v; }
__device__ __forceinline__ void sts_f32(uint32_t a, float v) { asm volatile("st.shared.f32 [%0], %1;" ::"r"(a), "f"(v) : "memory"); }
__device__ __forceinline__ uint32_t atom_inc_s(uint32_t a) { uint32_t v; asm volatile("atom.relaxed.cta.shared.add.u32 %0, [%1], 1;" : "=r"(v) : "r"(a) : "memory"); return v; }
__device__ __forceinline__ void lds4(uint32_t a, uint32_t* r) {
    asm volatile("ld.shared.v4.u32 {%0, %1, %2, %3}, [%4];" : "=r"(r[0]), "=r"(r[1]), "=r"(r[2]), "=r"(r[3]) : "r"(a) : "memory");
}
__device__ __forceinline__ void sts4(uint32_t a, uint32_t x, uint32_t y, uint32_t z, uint32_t t) {
    asm volatile("st.shared.v4.u32 [%0], {%1, %2, %3, %4};" ::"r"(a), "r"(x), "r"(y), "r"(z), "r"(t) : "memory");
}
__device__ __forceinline__ uint32_t bsub2(uint32_t a, uint32_t b) { uint32_t r; asm("sub.rn.bf16x2 %0, %1, %2;" : "=r"(r) : "r"(a), "r"(b)); return r; }
__device__ __forceinline__ float blo(uint32_t v) { return __uint_as_float(v << 16); }
__device__ __forceinline__ float bhi(uint32_t v) { return __uint_as_float(v & 0xffff0000u); }
__device__ __forceinline__ float bfr(float x) { return __bfloat162float(__float2bfloat16_rn(x)); }
__device__ __forceinline__ void l2_prefetch(const void* p, uint32_t bytes) { asm volatile("cp.async.bulk.prefetch.L2.global [%0], %1;" ::"l"(p), "r"(bytes) : "memory"); }
__device__ __forceinline__ void flag_add(unsigned* p) { asm volatile("red.release.gpu.global.add.u32 [%0], 1;" ::"l"(p) : "memory"); }
__device__ __forceinline__ void flag_wait(const unsigned* p, unsigned target) {
#pragma unroll 1
    for (uint32_t it = 0;; ++it) {
        unsigned v;
        asm volatile("ld.acquire.gpu.global.u32 %0, [%1];" : "=r"(v) : "l"(p) : "memory");
        if (v >= target) break;
        if (it > (1u << 20)) __trap();
    }
    fence_async_g();
}
template <int N> __device__ __forceinline__ void pin(float (&a)[N]) {
#pragma unroll
    for (int i = 0; i < N; i++) asm volatile("" : "+f"(a[i])::"memory");
}

template <int N> __device__ __forceinline__ void fresh(float (&a)[N]) {
#pragma unroll
    for (int i = 0; i < N; i++) a[i] = 0.f;
    pin(a);
}

__device__ __forceinline__ void wgmma_rs_n64_tb0(float (&d)[32], uint32_t a0, uint32_t a1, uint32_t a2, uint32_t a3, uint64_t db, int scale_d) {
    asm volatile("{\n.reg .pred p;\nsetp.ne.b32 p, %37, 0;\n"
        "wgmma.mma_async.sync.aligned.m64n64k16.f32.bf16.bf16 {%0, %1, %2, %3, %4, %5, %6, %7, %8, %9, %10, %11, %12, %13, %14, %15, %16, %17, %18, %19, %20, %21, %22, %23, %24, %25, %26, %27, %28, %29, %30, %31}, {%32, %33, %34, %35}, %36, p, 1, 1, 0;\n}\n"
        : "+f"(d[0]), "+f"(d[1]), "+f"(d[2]), "+f"(d[3]), "+f"(d[4]), "+f"(d[5]), "+f"(d[6]), "+f"(d[7]), "+f"(d[8]), "+f"(d[9]), "+f"(d[10]), "+f"(d[11]), "+f"(d[12]), "+f"(d[13]), "+f"(d[14]), "+f"(d[15]), "+f"(d[16]), "+f"(d[17]), "+f"(d[18]), "+f"(d[19]), "+f"(d[20]), "+f"(d[21]), "+f"(d[22]), "+f"(d[23]), "+f"(d[24]), "+f"(d[25]), "+f"(d[26]), "+f"(d[27]), "+f"(d[28]), "+f"(d[29]), "+f"(d[30]), "+f"(d[31])
        : "r"(a0), "r"(a1), "r"(a2), "r"(a3), "l"(db), "r"(scale_d));
}

__device__ __forceinline__ void wgmma_ss_n128_tb1(float (&d)[64], uint64_t da, uint64_t db, int scale_d) {
    asm volatile("{\n.reg .pred p;\nsetp.ne.b32 p, %66, 0;\n"
        "wgmma.mma_async.sync.aligned.m64n128k16.f32.bf16.bf16 {%0, %1, %2, %3, %4, %5, %6, %7, %8, %9, %10, %11, %12, %13, %14, %15, %16, %17, %18, %19, %20, %21, %22, %23, %24, %25, %26, %27, %28, %29, %30, %31, %32, %33, %34, %35, %36, %37, %38, %39, %40, %41, %42, %43, %44, %45, %46, %47, %48, %49, %50, %51, %52, %53, %54, %55, %56, %57, %58, %59, %60, %61, %62, %63}, %64, %65, p, 1, 1, 0, 1;\n}\n"
        : "+f"(d[0]), "+f"(d[1]), "+f"(d[2]), "+f"(d[3]), "+f"(d[4]), "+f"(d[5]), "+f"(d[6]), "+f"(d[7]), "+f"(d[8]), "+f"(d[9]), "+f"(d[10]), "+f"(d[11]), "+f"(d[12]), "+f"(d[13]), "+f"(d[14]), "+f"(d[15]), "+f"(d[16]), "+f"(d[17]), "+f"(d[18]), "+f"(d[19]), "+f"(d[20]), "+f"(d[21]), "+f"(d[22]), "+f"(d[23]), "+f"(d[24]), "+f"(d[25]), "+f"(d[26]), "+f"(d[27]), "+f"(d[28]), "+f"(d[29]), "+f"(d[30]), "+f"(d[31]), "+f"(d[32]), "+f"(d[33]), "+f"(d[34]), "+f"(d[35]), "+f"(d[36]), "+f"(d[37]), "+f"(d[38]), "+f"(d[39]), "+f"(d[40]), "+f"(d[41]), "+f"(d[42]), "+f"(d[43]), "+f"(d[44]), "+f"(d[45]), "+f"(d[46]), "+f"(d[47]), "+f"(d[48]), "+f"(d[49]), "+f"(d[50]), "+f"(d[51]), "+f"(d[52]), "+f"(d[53]), "+f"(d[54]), "+f"(d[55]), "+f"(d[56]), "+f"(d[57]), "+f"(d[58]), "+f"(d[59]), "+f"(d[60]), "+f"(d[61]), "+f"(d[62]), "+f"(d[63])
        : "l"(da), "l"(db), "r"(scale_d));
}

__device__ __forceinline__ void wgmma_ss_n256_tb1(float (&d)[128], uint64_t da, uint64_t db, int scale_d) {
    asm volatile("{\n.reg .pred p;\nsetp.ne.b32 p, %130, 0;\n"
        "wgmma.mma_async.sync.aligned.m64n256k16.f32.bf16.bf16 {%0, %1, %2, %3, %4, %5, %6, %7, %8, %9, %10, %11, %12, %13, %14, %15, %16, %17, %18, %19, %20, %21, %22, %23, %24, %25, %26, %27, %28, %29, %30, %31, %32, %33, %34, %35, %36, %37, %38, %39, %40, %41, %42, %43, %44, %45, %46, %47, %48, %49, %50, %51, %52, %53, %54, %55, %56, %57, %58, %59, %60, %61, %62, %63, %64, %65, %66, %67, %68, %69, %70, %71, %72, %73, %74, %75, %76, %77, %78, %79, %80, %81, %82, %83, %84, %85, %86, %87, %88, %89, %90, %91, %92, %93, %94, %95, %96, %97, %98, %99, %100, %101, %102, %103, %104, %105, %106, %107, %108, %109, %110, %111, %112, %113, %114, %115, %116, %117, %118, %119, %120, %121, %122, %123, %124, %125, %126, %127}, %128, %129, p, 1, 1, 0, 1;\n}\n"
        : "+f"(d[0]), "+f"(d[1]), "+f"(d[2]), "+f"(d[3]), "+f"(d[4]), "+f"(d[5]), "+f"(d[6]), "+f"(d[7]), "+f"(d[8]), "+f"(d[9]), "+f"(d[10]), "+f"(d[11]), "+f"(d[12]), "+f"(d[13]), "+f"(d[14]), "+f"(d[15]), "+f"(d[16]), "+f"(d[17]), "+f"(d[18]), "+f"(d[19]), "+f"(d[20]), "+f"(d[21]), "+f"(d[22]), "+f"(d[23]), "+f"(d[24]), "+f"(d[25]), "+f"(d[26]), "+f"(d[27]), "+f"(d[28]), "+f"(d[29]), "+f"(d[30]), "+f"(d[31]), "+f"(d[32]), "+f"(d[33]), "+f"(d[34]), "+f"(d[35]), "+f"(d[36]), "+f"(d[37]), "+f"(d[38]), "+f"(d[39]), "+f"(d[40]), "+f"(d[41]), "+f"(d[42]), "+f"(d[43]), "+f"(d[44]), "+f"(d[45]), "+f"(d[46]), "+f"(d[47]), "+f"(d[48]), "+f"(d[49]), "+f"(d[50]), "+f"(d[51]), "+f"(d[52]), "+f"(d[53]), "+f"(d[54]), "+f"(d[55]), "+f"(d[56]), "+f"(d[57]), "+f"(d[58]), "+f"(d[59]), "+f"(d[60]), "+f"(d[61]), "+f"(d[62]), "+f"(d[63]), "+f"(d[64]), "+f"(d[65]), "+f"(d[66]), "+f"(d[67]), "+f"(d[68]), "+f"(d[69]), "+f"(d[70]), "+f"(d[71]), "+f"(d[72]), "+f"(d[73]), "+f"(d[74]), "+f"(d[75]), "+f"(d[76]), "+f"(d[77]), "+f"(d[78]), "+f"(d[79]), "+f"(d[80]), "+f"(d[81]), "+f"(d[82]), "+f"(d[83]), "+f"(d[84]), "+f"(d[85]), "+f"(d[86]), "+f"(d[87]), "+f"(d[88]), "+f"(d[89]), "+f"(d[90]), "+f"(d[91]), "+f"(d[92]), "+f"(d[93]), "+f"(d[94]), "+f"(d[95]), "+f"(d[96]), "+f"(d[97]), "+f"(d[98]), "+f"(d[99]), "+f"(d[100]), "+f"(d[101]), "+f"(d[102]), "+f"(d[103]), "+f"(d[104]), "+f"(d[105]), "+f"(d[106]), "+f"(d[107]), "+f"(d[108]), "+f"(d[109]), "+f"(d[110]), "+f"(d[111]), "+f"(d[112]), "+f"(d[113]), "+f"(d[114]), "+f"(d[115]), "+f"(d[116]), "+f"(d[117]), "+f"(d[118]), "+f"(d[119]), "+f"(d[120]), "+f"(d[121]), "+f"(d[122]), "+f"(d[123]), "+f"(d[124]), "+f"(d[125]), "+f"(d[126]), "+f"(d[127])
        : "l"(da), "l"(db), "r"(scale_d));
}

__device__ __forceinline__ void wgmma_ss_n32_tb0(float (&d)[16], uint64_t da, uint64_t db, int scale_d) {
    asm volatile("{\n.reg .pred p;\nsetp.ne.b32 p, %18, 0;\n"
        "wgmma.mma_async.sync.aligned.m64n32k16.f32.bf16.bf16 {%0, %1, %2, %3, %4, %5, %6, %7, %8, %9, %10, %11, %12, %13, %14, %15}, %16, %17, p, 1, 1, 0, 0;\n}\n"
        : "+f"(d[0]), "+f"(d[1]), "+f"(d[2]), "+f"(d[3]), "+f"(d[4]), "+f"(d[5]), "+f"(d[6]), "+f"(d[7]), "+f"(d[8]), "+f"(d[9]), "+f"(d[10]), "+f"(d[11]), "+f"(d[12]), "+f"(d[13]), "+f"(d[14]), "+f"(d[15])
        : "l"(da), "l"(db), "r"(scale_d));
}

__device__ __forceinline__ void wgmma_ss_n64_tb0(float (&d)[32], uint64_t da, uint64_t db, int scale_d) {
    asm volatile("{\n.reg .pred p;\nsetp.ne.b32 p, %34, 0;\n"
        "wgmma.mma_async.sync.aligned.m64n64k16.f32.bf16.bf16 {%0, %1, %2, %3, %4, %5, %6, %7, %8, %9, %10, %11, %12, %13, %14, %15, %16, %17, %18, %19, %20, %21, %22, %23, %24, %25, %26, %27, %28, %29, %30, %31}, %32, %33, p, 1, 1, 0, 0;\n}\n"
        : "+f"(d[0]), "+f"(d[1]), "+f"(d[2]), "+f"(d[3]), "+f"(d[4]), "+f"(d[5]), "+f"(d[6]), "+f"(d[7]), "+f"(d[8]), "+f"(d[9]), "+f"(d[10]), "+f"(d[11]), "+f"(d[12]), "+f"(d[13]), "+f"(d[14]), "+f"(d[15]), "+f"(d[16]), "+f"(d[17]), "+f"(d[18]), "+f"(d[19]), "+f"(d[20]), "+f"(d[21]), "+f"(d[22]), "+f"(d[23]), "+f"(d[24]), "+f"(d[25]), "+f"(d[26]), "+f"(d[27]), "+f"(d[28]), "+f"(d[29]), "+f"(d[30]), "+f"(d[31])
        : "l"(da), "l"(db), "r"(scale_d));
}

struct Maps {
    CUtensorMap xa, xa2, xas, wup4, wup8, mqa2, mqa4, mqb1, mqb2, uc, x, out, wq, wk, fa[3], fb[2], fc;
};

__device__ __forceinline__ uint64_t mkd(uint32_t lo) {
    uint64_t d;
    asm("mov.b64 %0, {%1, %2};" : "=l"(d) : "r"(lo), "r"((1024u >> 4) | (1u << 30)));
    return d;
}
__device__ __forceinline__ void bulk_ld(uint32_t dst, const void* src, uint32_t bytes, uint32_t bar) {
    asm volatile("cp.async.bulk.shared::cluster.global.mbarrier::complete_tx::bytes [%0], [%1], %2, [%3];" ::"r"(dst), "l"(src), "r"(bytes), "r"(bar) : "memory");
}
__device__ __forceinline__ void bulk_st(void* dst, uint32_t src, uint32_t bytes) {
    asm volatile("cp.async.bulk.global.shared::cta.bulk_group [%0], [%1], %2;" ::"l"(dst), "r"(src), "r"(bytes) : "memory");
}
__device__ __forceinline__ void ring_ld(uint32_t sb, uint32_t slot8, int n) {
    mbar_expect_tx(sb + B_R2 + slot8, 8192);
    bulk_ld(sb + R1 + slot8 * 1024, (const char*)g_wepi + n * 8192, 8192, sb + B_R2 + slot8);
}

__device__ __forceinline__ void ring_half(uint32_t sb, uint32_t slot8, uint32_t hoff, const CUtensorMap* tm, int c1, int c2) {
    mbar_expect_tx(sb + B_R1 + slot8, 8192);
    tma3(sb + slot8 * 2048 + hoff, tm, 0, c1, c2, sb + B_R1 + slot8);
}
__device__ __forceinline__ void ring_full(uint32_t sb, uint32_t slot8, const CUtensorMap* tm, int c1, int c2) {
    mbar_expect_tx(sb + B_R1 + slot8, 16384);
    mbar_arrive(sb + B_R1 + slot8);
    tma3(sb + slot8 * 2048, tm, 0, c1, c2, sb + B_R1 + slot8);
}
__device__ __forceinline__ void cta_done(int mode) {
    if (mode == 0 && atomicAdd(&g_sync[4], 1) == NCTA + 1) {
#pragma unroll
        for (int i = 0; i < 5; i++) g_sync[i] = 0;
    }
}

__device__ __forceinline__ void fold_cta(const Maps& mp, uint32_t sb, int mode) {
    constexpr uint32_t F_FULL = MISC, F_EMPTY = MISC + 32, F_T1 = MISC + 64, STG = 49152, FOUT = 3 * STG;
    const int tid = threadIdx.x, f = blockIdx.x - NCTA;
    if (mode == 2) return;
    if (tid == 0) {
        for (int i = 0; i < 3; i++) { mbar_init(sb + F_FULL + 8 * i, 1); mbar_init(sb + F_EMPTY + 8 * i, 2); }
        mbar_init(sb + F_T1, 2);
        asm volatile("fence.mbarrier_init.release.cluster;" ::: "memory");
        fence_async();
    }
    __syncthreads();
    const int wg = __shfl_sync(0xffffffffu, tid >> 7, 0);
    int st = 0, ph = 0;
    if (wg == 0) {
        if (tid == 0) {
#pragma unroll 1
            for (int it = 0; it < 96; it++) {
                const int p = it >> 3, kc = it & 7, job = p >> 2;
                if (it == 64) mbar_wait(sb + F_T1, 0);
                mbar_wait(sb + F_EMPTY + 8 * st, ph ^ 1);
                mbar_expect_tx(sb + F_FULL + 8 * st, STG);
                tma3(sb + st * STG, &mp.fa[job], 0, 256 * f + 128 * ((p >> 1) & 1), kc, sb + F_FULL + 8 * st);
                tma3(sb + st * STG + 16384, &mp.fb[job != 0], 0, 64 * kc + (job == 1 ? 512 : 0), 4 * (p & 1), sb + F_FULL + 8 * st);
                if (++st == 3) { st = 0; ph ^= 1; }
            }
        }
        return;
    }
    const int h = wg - 1, lane = tid & 31, w = (tid >> 5) & 3;
    const uint32_t sd = (sb & 0x3FFFF) >> 4;
    const bool el = (tid & 127) == 0;
#pragma unroll 1
    for (int p = 0; p < 12; p++) {
        float acc[128];
        fresh(acc);
#pragma unroll 1
        for (int kc = 0; kc < 8; kc++) {
            mbar_wait(sb + F_FULL + 8 * st, ph);
            wg_fence();
#pragma unroll
            for (int kk = 0; kk < 4; kk++)
                wgmma_ss_n256_tb1(acc, dsc(sd, st * STG + h * 8192 + kk * 32, 16), dsc(sd, st * STG + 16384 + kk * 2048, 8192), 1);
            wg_commit();
            wg_wait<0>();
            if (el) mbar_arrive(sb + F_EMPTY + 8 * st);
            if (++st == 3) { st = 0; ph ^= 1; }
        }
        pin(acc);
        const int job = p >> 2;
        if (el) {
            asm volatile("cp.async.bulk.wait_group 0;" ::: "memory");
            if (p == 4) { fence_async_g(); mbar_arrive(sb + F_T1); }
        }
        bar_sync(3 + h, 128);
        uint32_t r = 16 * w + (lane & 7) + ((lane >> 3) & 1) * 8;
        const float fs = job == 1 ? 0.5f : 1.f;
        if (job == 1) r = (r & ~31) | (((r >> 1) & 3) << 3) | (((r >> 3) & 3) << 1) | (r & 1);
        const uint32_t oa = sb + FOUT + h * 32768 + r * 128 + ((((lane >> 4) ^ r) & 7) << 4);
#pragma unroll
        for (int i = 0; i < 16; i++)
            stsm4((oa ^ ((i & 3) << 5)) + (i >> 2) * 8192, pack2(acc[8 * i] * fs, acc[8 * i + 1] * fs), pack2(acc[8 * i + 2] * fs, acc[8 * i + 3] * fs),
                  pack2(acc[8 * i + 4] * fs, acc[8 * i + 5] * fs), pack2(acc[8 * i + 6] * fs, acc[8 * i + 7] * fs));
        fence_async();
        bar_sync(3 + h, 128);
        if (el) {
            const int row0 = 256 * f + 128 * ((p >> 1) & 1) + 64 * h + (job == 1 ? 512 : 0);
            if (job == 0) tma3_store(&mp.fc, sb + FOUT + h * 32768, 0, row0, 4 * (p & 1));
            else {
#pragma unroll 1
                for (int i = 0; i < 16; i++)
                    bulk_st((char*)g_wepi + (row0 / 8 + 2 * (i & 3) + (p & 1)) * 8192 + (i >> 2) * 2048, sb + FOUT + h * 32768 + i * 2048, 2048);
            }
            asm volatile("cp.async.bulk.commit_group;" ::: "memory");
        }
    }
    if (el) {
        asm volatile("cp.async.bulk.wait_group 0;" ::: "memory");
        fence_async_g();
        if (mode == 0) flag_add(&g_sync[3]);
    }
    bar_sync(2, 256);
    if (tid == 128) cta_done(mode);
}

__global__ void __launch_bounds__(384, 1) main_kernel(const __grid_constant__ Maps mp, const bf16* __restrict__ x, const bf16* __restrict__ dw, const bf16* wup, const int mode) {
    extern __shared__ __align__(1024) uint8_t smem[];
    const uint32_t sb = smem_u32(smem);
    const int tid = threadIdx.x;
    PE();
    if (blockIdx.x >= NCTA) { fold_cta(mp, sb, mode); return; }
    const int b = blockIdx.x / TPB, ti = blockIdx.x % TPB;
    const int piece = blockIdx.x & 127;
    const int wg = __shfl_sync(0xffffffffu, tid >> 7, 0);
    const int lane = tid & 31, w = (tid >> 5) & 3;
    const bool w0 = __shfl_sync(0xffffffffu, w, 0) == 0;
    const uint32_t sd = (sb & 0x3FFFF) >> 4;
    const uint32_t adA = sd + (AT >> 4) + (1u << 16);
    const uint32_t bd0 = sd;
    const uint32_t bd2k = bd0 + ((2048u >> 4) << 16);
    const bool el = (tid & 127) == 0;
    const uint32_t lrow = 16 * w + (lane & 7) + ((lane >> 3) & 1) * 8;
    const uint32_t loff = lrow * 128 + ((((lane >> 4) ^ lrow) & 7) << 4);
    const int r0 = 16 * w + (lane >> 2);

    if (wg == 0) {
        asm volatile("setmaxnreg.inc.sync.aligned.u32 184;");
        uint32_t q[112];
        PG(206);
        if (tid == 0) {
            mbar_init(sb + B_MK, 1);
            for (int i = 0; i < 9; i++) mbar_init(sb + B_R1 + 8 * i, 2);
            for (int i = 0; i < 5; i++) asm volatile("st.shared.u32 [%0], 0;" ::"r"(sb + CNT + 4 * i) : "memory");
        } else if (tid == 32) {
            mbar_init(sb + B_LN, 1); mbar_init(sb + B_MQ, 1);
            mbar_init(sb + B_H1, 2); mbar_init(sb + B_H2, 1); mbar_init(sb + B_H3, 2);
            for (int i = 0; i < 3; i++) { mbar_init(sb + B_KV + 8 * i, 1); mbar_init(sb + B_P + 8 * i, 4); mbar_init(sb + B_GO + 8 * i, 4); }
            mbar_init(sb + B_UC, 1); mbar_init(sb + B_UC + 8, 1); mbar_init(sb + B_X, 8);
        } else if (tid == 64) {
            for (int i = 0; i < 20; i++) mbar_init(sb + B_R2 + 8 * i, 1);
        } else if (tid == 96) {
            for (int i = 0; i < 20; i++) mbar_init(sb + B_E2 + 8 * i, 4);
        }
        if (lane == 0) {
            asm volatile("fence.mbarrier_init.release.cluster;" ::: "memory");
            fence_async();
        }
        PG(207);
        __syncwarp();
        if (SU != 2) asm volatile("bar.arrive 5, 384;" ::: "memory");
        if (tid == 0) {
            mbar_expect_tx(sb + B_MK, 65536 + 32768);
            tma3(sb + 16384, &mp.wq, 0, 64 * (piece >> 4), 0, sb + B_MK);
            tma3(sb + 81920, &mp.wk, 0, 32 * (piece & 15), 0, sb + B_MK);
            for (int i = 0; i < 14; i++) mbar_arrive(sb + B_R1 + 8 * (i >> 1));
            if (mode != 1) {
                ring_full(sb, 56, &mp.wup8, 0, 8);
                ring_full(sb, 64, &mp.wup8, 16, 8);
                ring_full(sb, 0, &mp.wup8, 32, 8);
            }
        }
        PG(208);
        bar_sync(1, 128);
        if (SU == 2) asm volatile("bar.arrive 5, 384;" ::: "memory");
        PT(0);
        PG(200);
        {
            float mq[16];
            fresh(mq);
            mbar_wait(sb + B_MK, 0);
            PT(1);
            if (tid == 32) l2_prefetch((const char*)wup + piece * 8192, 8192);
            wg_fence();
#pragma unroll 1
            for (int c = 0; c < 8; c++)
#pragma unroll
                for (int kk = 0; kk < 4; kk++)
                    wgmma_ss_n32_tb0(mq, dsc(sd, 16384 + c * 8192 + kk * 32, 16), dsc(sd, 81920 + c * 4096 + kk * 32, 16), 1);
            wg_commit();
            wg_wait<0>();
            if (mode != 1 && w0 && elect1()) {
#pragma unroll 1
                for (int i = 1; i < 7; i++) ring_full(sb, 8 * i, &mp.wup8, 32 + 16 * i, 8);
            }
            pin(mq);
            uint32_t* c = reinterpret_cast<uint32_t*>(g_mqk + (64 * (piece >> 4) + r0) * D_ + 32 * (piece & 15) + 2 * (lane & 3));
#pragma unroll
            for (int n = 0; n < 4; n++) { c[4 * n] = pack2(mq[4 * n], mq[4 * n + 1]); c[4 * n + 4 * D_] = pack2(mq[4 * n + 2], mq[4 * n + 3]); }
            fence_async_g();
            bar_sync(1, 128);
            if (el) {
                if (mode == 0) flag_add(&g_sync[2]);
                if (mode == 0) flag_wait(&g_sync[2], NCTA);
                mbar_arrive(sb + B_MQ);
                PG(203);
                PT(12);
                mbar_wait(sb + B_LN, 0);
#pragma unroll 1
                for (int c = 0; c < 8; c++) {
                    tma4_store(&mp.xas, sb + AT + c * 8192, 0, 62 * ti, c, b);
                    const unsigned t0 = (unsigned)clock();
                    while (c < 7 && (unsigned)clock() - t0 < XS_GAP) __nanosleep(20);
                }
                asm volatile("cp.async.bulk.commit_group;" ::: "memory");
                if (mode == 1) asm volatile("cp.async.bulk.wait_group 0;" ::: "memory");
            }
            PT(13);
            if (mode == 1) return;
        }
        mbar_wait(sb + B_H1, 0);
        PT(2);
        uint32_t slot8 = 24, par = 0, prev8 = 0, prev2 = 0;
        auto adv = [&]() { prev2 = prev8; prev8 = slot8; slot8 += 8; if (slot8 == 72) { slot8 = 0; par ^= 1; } };
        {
            float acc[128];
            fresh(acc);
            auto step = [&](int i) {
                const uint32_t aa = adA + (i >> 1) * 512 + (i & 1) * 4, bb = bd0 + ((4096u >> 4) << 16) + slot8 * 128;
                wg_fence();
                wgmma_ss_n256_tb1(acc, mkd(aa), mkd(bb), 1);
                wgmma_ss_n256_tb1(acc, mkd(aa + 2), mkd(bb + 128), 1);
                wg_commit();
                wg_wait<1 + LAGA>();
            };
#pragma unroll 1
            for (int i = 0; i < 8 + LAGA; i++) {
                mbar_wait(sb + B_R1 + slot8, par);
                step(i);
                if (i > LAGA && w0 && elect1()) ring_full(sb, LAGA ? prev2 : prev8, &mp.mqa4, 32 * (i - LAGA) + 256, 4);
                adv();
            }
#pragma unroll 1
            for (int i = 8 + LAGA; i < 16; i++) {
                mbar_wait(sb + B_R1 + slot8, par);
                if (i == 15 && el) mbar_arrive(sb + B_H2);
                step(i);
                if (w0 && elect1()) ring_full(sb, LAGA ? prev2 : prev8, &mp.wup8, 16 * (i - LAGA) - 128, 0);
                adv();
            }
            if (LAGA) {
                wg_wait<1>();
                if (w0 && elect1()) ring_full(sb, prev2, &mp.wup8, 112, 0);
            }
            wg_wait<0>();
            if (w0 && elect1()) ring_full(sb, prev8, &mp.wup8, 128, 0);
            pin(acc);
            PT(3);
#pragma unroll
            for (int kk = 0; kk < 4; kk++)
                stsm4((sb + QS + loff) ^ (kk << 5), pack2(acc[96 + 8 * kk], acc[97 + 8 * kk]), pack2(acc[98 + 8 * kk], acc[99 + 8 * kk]),
                      pack2(acc[100 + 8 * kk], acc[101 + 8 * kk]), pack2(acc[102 + 8 * kk], acc[103 + 8 * kk]));
            fence_async();
#pragma unroll
            for (int i = 47; i >= 0; i--) q[64 + i] = pack2v(acc[2 * i], acc[2 * i + 1]);
        }
        if (el) {
            asm volatile("cp.async.bulk.wait_group 0;" ::: "memory");
            if (mode == 0) {
                fence_async_g();
                flag_add(&g_sync[b]);
                flag_wait(&g_sync[b], TPB);
            }
        }
        __syncwarp();
        mbar_wait(sb + B_H3, 0);
        PT(4);
        slot8 = 48; par = 1;
#pragma unroll
        for (int half = 0; half < 2; half++) {
            float acc[64];
            fresh(acc);
            auto step = [&](int m) {
                const uint32_t aa = adA + m * 512, bb = bd0 + ((8192u >> 4) << 16) + slot8 * 128;
                mbar_wait(sb + B_R1 + slot8, par);
                wg_fence();
#pragma unroll
                for (int kk = 0; kk < 4; kk++) wgmma_ss_n128_tb1(acc, mkd(aa + 2 * kk), mkd(bb + 128 * kk), 1);
                wg_commit();
                wg_wait<1 + LAGB>();
            };
#pragma unroll 1
            for (int m = 0; m < 8; m++) {
                step(m);
                if (m > LAGB && w0 && elect1()) {
                    if (half == 0) ring_full(sb, LAGB ? prev2 : prev8, &mp.mqb2, 64 * (m - LAGB), 2);
                    else if (m < 4 + LAGB) tma4(sb + (LAGB ? prev2 : prev8) * 2048, &mp.xa2, 0, 0, 2 * (m - LAGB), b, sb + B_KV + 8);
                }
                adv();
            }
            if (LAGB && half == 0) {
                wg_wait<1>();
                if (w0 && elect1()) ring_full(sb, prev2, &mp.mqb2, 448, 2);
            }
            wg_wait<0>();
            if (w0 && elect1()) {
                if (half == 0) {
                    mbar_expect_tx(sb + B_KV + 8, 65536);
                    tma4(sb + prev8 * 2048, &mp.xa2, 0, 0, 0, b, sb + B_KV + 8);
                } else {
                    mbar_expect_tx(sb + B_KV + 16, 65536);
                    tma4(sb + R2, &mp.xa, 0, 64, 0, b, sb + B_KV + 16);
                    mbar_expect_tx(sb + B_KV, 65536);
                    tma4(sb + R0, &mp.xa, 0, 128, 0, b, sb + B_KV);
                }
            }
            pin(acc);
#pragma unroll
            for (int i = 31; i >= 0; i--) q[32 * half + i] = pack2v(acc[2 * i], acc[2 * i + 1]);
        }
        bar_sync(1, 128);
        PT(5);

        const float CS = 0.04419417382415922f * 1.4426950408889634f;
        float m0 = -INFINITY, m1 = -INFINITY, l0 = 0.f, l1 = 0.f;
        int s = 0, sn = 1, ph = 0;
        float S[32];
        const bool l0w = lane == 0, q0 = (lane & 3) == 0;
#pragma unroll 1
        for (int j = -1;; j++) {
            if (j >= 0) {
                PL(j, 1);
                if (j == NKV - 1) {
#pragma unroll
                    for (int i = (T_ - 64 * (NKV - 1)) / 2; i < 32; i++) asm volatile("mov.b32 %0, 0xff800000;" : "=f"(S[i]));
                }
                const bool kv = mbar_test(sb + B_KV + sn * 8, ph);
                const uint32_t pb = sb + R3 + (s == 0 ? 2 : s - 1) * 8192;
                float a0, a1, sc0 = 1.f, sc1 = 1.f;
                auto expo = [&]() {
                    const float n0 = -m0 * CS, n1 = -m1 * CS;
                    a0 = 0.f; a1 = 0.f;
#pragma unroll
                    for (int kk = 0; kk < 4; kk++) {
                        float p[8];
#pragma unroll
                        for (int e = 0; e < 8; e++) p[e] = ex2(fmaf(S[8 * kk + e], CS, (e & 2) ? n1 : n0));
                        a0 += (p[0] + p[1]) + (p[4] + p[5]);
                        a1 += (p[2] + p[3]) + (p[6] + p[7]);
                        stsm4((pb + loff) ^ (kk << 5), pack2(p[0], p[1]), pack2(p[2], p[3]), pack2(p[4], p[5]), pack2(p[6], p[7]));
                    }
                };
                expo();
                if (__any_sync(0xffffffffu, !(a0 <= LAZY) || !(a1 <= LAZY))) {
                    float x0 = m0, x1 = m1;
#pragma unroll
                    for (int n = 0; n < 8; n++) { x0 = fmaxf(x0, fmaxf(S[4 * n], S[4 * n + 1])); x1 = fmaxf(x1, fmaxf(S[4 * n + 2], S[4 * n + 3])); }
                    x0 = fmaxf(x0, __shfl_xor_sync(0xffffffffu, x0, 1));
                    x1 = fmaxf(x1, __shfl_xor_sync(0xffffffffu, x1, 1));
                    x0 = fmaxf(x0, __shfl_xor_sync(0xffffffffu, x0, 2));
                    x1 = fmaxf(x1, __shfl_xor_sync(0xffffffffu, x1, 2));
                    sc0 = ex2((m0 - x0) * CS); sc1 = ex2((m1 - x1) * CS);
                    m0 = x0; m1 = x1;
                    expo();
                }
                if (q0) { sts_f32(sb + SCL + s * 256 + r0 * 4, sc0); sts_f32(sb + SCL + s * 256 + r0 * 4 + 32, sc1); }
                __syncwarp();
                if (l0w) mbar_arrive(sb + B_P + s * 8);
                l0 = fmaf(l0, sc0, a0); l1 = fmaf(l1, sc1, a1);
                PL(j, 2);
                if (j == NKV - 1) break;
                if (!kv) mbar_wait(sb + B_KV + sn * 8, ph);
            } else {
                mbar_wait(sb + B_KV + 8, 0);
            }
            float Sn[32];
            const uint32_t kd = sd + sn * 4096;
            wg_fence();
#pragma unroll
            for (int kk = 0; kk < 28; kk++) {
                wgmma_rs_n64_tb0(Sn, q[4 * kk], q[4 * kk + 1], q[4 * kk + 2], q[4 * kk + 3], dsc(kd, (kk >> 2) * 8192 + (kk & 3) * 32, 16), kk > 0);
                if (kk == FENCE_AT) { fence_async(); __syncwarp(); }
                if (kk == GO_AT) { PL(j, 3); if (j >= 0 && l0w) mbar_arrive(sb + B_GO + s * 8); }
            }
#pragma unroll
            for (int kk = 0; kk < 4; kk++)
                wgmma_ss_n64_tb0(Sn, dsc(sd, QS + kk * 32, 16), dsc(kd, 7 * 8192 + kk * 32, 16), 1);
            wg_commit();
            PL(j, 0);
            wg_wait<0>();
            pin(Sn);
#pragma unroll
            for (int i = 0; i < 32; i++) S[i] = Sn[i];
            s = sn;
            if (++sn == 3) sn = 0;
            if (sn == 1) ph ^= 1;
        }
        l0 += __shfl_xor_sync(0xffffffffu, l0, 1); l1 += __shfl_xor_sync(0xffffffffu, l1, 1);
        l0 += __shfl_xor_sync(0xffffffffu, l0, 2); l1 += __shfl_xor_sync(0xffffffffu, l1, 2);
        if (q0) { sts_f32(sb + LINV + r0 * 4, rcp(l0)); sts_f32(sb + LINV + r0 * 4 + 32, rcp(l1)); }
        fence_async();
        __syncwarp();
        if (l0w) {
            mbar_arrive(sb + B_GO + s * 8);
            uint32_t slot8 = 8 * w, par = 0;
#pragma unroll 1
            for (int n = 20 + w; n < 136; n += 4) {
                mbar_wait(sb + B_E2 + slot8, par);
                if (n < 128) ring_ld(sb, slot8, n);
                else {
                    mbar_expect_tx(sb + B_X, 8192);
                    tma4(sb + R1 + slot8 * 1024, &mp.x, 0, 62 * ti, n - 128, b, sb + B_X);
                }
                slot8 += 32;
                if (slot8 >= 160) { slot8 -= 160; par ^= 1; }
            }
        }
        PDUMP();
    } else {
        asm volatile("setmaxnreg.dec.sync.aligned.u32 160;");
        const int h = wg - 1;
        uint32_t v[4][8], v2[4][8];
        if (SU != 0) bar_sync(5, 384);
        PG(206);
#pragma unroll
        for (int i = 0; i < 8; i++) {
            const int t = 62 * ti - 1 + 32 * (i >> 2) + 16 * h + 4 * w + (i & 3);
            const uint4* p = reinterpret_cast<const uint4*>(x + ((size_t)b * T_ + t) * D_) + lane;
            uint32_t* d = i < 4 ? v[i & 3] : v2[i & 3];
#pragma unroll
            for (int c = 0; c < 2; c++)
                asm volatile("{\n.reg .pred p;\nsetp.lt.u32 p, %5, %6;\nmov.b32 %0, 0;\nmov.b32 %1, 0;\nmov.b32 %2, 0;\nmov.b32 %3, 0;\n"
                             "@p ld.global.nc.v4.u32 {%0, %1, %2, %3}, [%4];\n}\n"
                             : "=r"(d[4 * c]), "=r"(d[4 * c + 1]), "=r"(d[4 * c + 2]), "=r"(d[4 * c + 3]) : "l"(p + 32 * c), "r"(t), "n"(T_));
        }
#pragma unroll 1
        for (int bt = 0; bt < 2; bt++) {
            PT(bt ? 13 : 0);
            float a[8];
            const uint32_t la = sb + AT + (lane >> 3) * 8192 + (32 * bt + 16 * h + 4 * w) * 128 + (((lane & 7) ^ ((w & 1) * 4)) << 4);
            const bool b4 = lane & 16, b3 = lane & 8, b2 = lane & 4;
#pragma unroll
            for (int r = 0; r < 4; r++) {
                float c[4] = {0.f, 0.f, 0.f, 0.f};
#pragma unroll
                for (int i = 0; i < 8; i += 2) hmma(c, v[r][i], v[r][i], v[r][i + 1], v[r][i + 1], v[r][i], v[r][i + 1]);
                a[4 + r] = (lane & 3) == (lane >> 3) ? (b2 ? c[1] : c[0]) : 0.f;
                if (r & 1) {
                    float e[4] = {0.f, 0.f, 0.f, 0.f};
#pragma unroll
                    for (int i = 0; i < 8; i += 2) hmma(e, v[r - 1][i], v[r][i], v[r - 1][i + 1], v[r][i + 1], 0x3f803f80u, 0x3f803f80u);
                    a[r - 1] = e[0]; a[r] = e[2];
                }
            }
            float k[4];
#pragma unroll
            for (int i = 0; i < 4; i++) {
                const int lo = (i & 1) + 4 * (i >> 1);
                k[i] = (b4 ? a[lo + 2] : a[lo]) + __shfl_xor_sync(0xffffffffu, b4 ? a[lo] : a[lo + 2], 16);
            }
            const float k0 = (b3 ? k[1] : k[0]) + __shfl_xor_sync(0xffffffffu, b3 ? k[0] : k[1], 8);
            const float k1 = (b3 ? k[3] : k[2]) + __shfl_xor_sync(0xffffffffu, b3 ? k[2] : k[3], 8);
            float z = (b2 ? k1 : k0) + __shfl_xor_sync(0xffffffffu, b2 ? k0 : k1, 4);
            z += __shfl_xor_sync(0xffffffffu, z, 2);
            z += __shfl_xor_sync(0xffffffffu, z, 1);
            const float zo = __shfl_xor_sync(0xffffffffu, z, 4);
            PG(204 + bt);
            const float mu = (b2 ? zo : z) * (0.25f / D_);
            float sd_ = bfr(bfr(fmaxf(fmaf(b2 ? z : zo, 1.f / D_, -mu * mu), 0.f)) + 1e-5f);
            asm("sqrt.approx.f32 %0, %0;" : "+f"(sd_));
            const float ri = rcp(bfr(sd_));
            const uint32_t w1 = pack2(mu, ri), w2 = pack2(ri - bhi(w1), ri - bhi(w1));
#pragma unroll
            for (int r = 0; r < 4; r++) {
                const uint32_t s1 = __shfl_sync(0xffffffffu, w1, 8 * r), rl = __shfl_sync(0xffffffffu, w2, 8 * r);
                const uint32_t m2 = __byte_perm(s1, 0, 0x1010), rh = __byte_perm(s1, 0, 0x3232);
#pragma unroll
                for (int i = 0; i < 8; i++) { const uint32_t d = bsub2(v[r][i], m2); v[r][i] = bfma2(d, rh, bmul2(d, rl)); }
                sts4((la ^ (r << 4)) + r * 128, v[r][0], v[r][1], v[r][2], v[r][3]);
                sts4((la ^ (r << 4)) + r * 128 + 32768, v[r][4], v[r][5], v[r][6], v[r][7]);
#pragma unroll
                for (int i = 0; i < 8; i++) v[r][i] = v2[r][i];
            }
        }
        fence_async();
        if (SU == 0) bar_sync(5, 384); else bar_sync(2, 256);
        if (tid == 128) mbar_arrive(sb + B_LN);
        PG(202);
        if (mode == 1) return;
        float acc[128];
#pragma unroll
        for (int pass = 0; pass < 2; pass++) {
            if (pass == 1) mbar_wait(sb + B_H2, 0);
            PT(1 + 3 * pass);
            fresh(acc);
            uint32_t slot8 = pass ? 8 : 56, par = 0, prev8 = 0;
            auto adv = [&]() { prev8 = slot8; slot8 += 8; if (slot8 == 72) { slot8 = 0; par ^= 1; } };
            auto step = [&](int kk) {
                wg_fence();
                wgmma_ss_n256_tb1(acc, mkd(adA + (kk >> 2) * 512 + (kk & 3) * 2), mkd(bd2k + h * 512 + slot8 * 128), 1);
                wg_commit();
                wg_wait<1>();
            };
#pragma unroll 1
            for (int kk = 0; kk < 24; kk++) {
                mbar_wait(sb + B_R1 + slot8, par);
                step(kk);
                if (kk > 0 && w0 && elect1()) ring_half(sb, prev8, h * 8192, &mp.wup4, 16 * kk + 128, (pass ? 0 : 8) + 4 * h);
                adv();
            }
            if (pass == 0 && w0) mbar_wait(sb + B_MQ, 0);
#pragma unroll 1
            for (int kk = 24; kk < 32; kk++) {
                mbar_wait(sb + B_R1 + slot8, par);
                if (kk == 31 && el) mbar_arrive(sb + (pass ? B_H3 : B_H1));
                step(kk);
                if (w0 && elect1()) ring_half(sb, prev8, h * 8192, pass ? &mp.mqb1 : &mp.mqa2, (pass ? 64 : 32) * (kk - 24), pass ? h : 4 + 2 * h);
                adv();
            }
            wg_wait<0>();
            if (w0 && elect1()) ring_half(sb, prev8, h * 8192, pass ? &mp.mqb1 : &mp.mqa2, pass ? 0 : 256, pass ? 2 + h : 4 + 2 * h);
            pin(acc);
            PT(2 + 3 * pass);
            bf16* ucp = g_uc + ((size_t)blockIdx.x * 128 + r0) * D_ + 256 * h + 8 * (lane & 3);
            if (pass == 0) {
                float s0 = 0.f, s1 = 0.f, v0 = 0.f, v1 = 0.f;
#pragma unroll
                for (int n = 0; n < 32; n++) {
#pragma unroll
                    for (int e = 0; e < 4; e++) acc[4 * n + e] = gelu2(acc[4 * n + e]);
                    s0 += acc[4 * n] + acc[4 * n + 1]; s1 += acc[4 * n + 2] + acc[4 * n + 3];
                    v0 = fmaf(acc[4 * n], acc[4 * n], v0); v0 = fmaf(acc[4 * n + 1], acc[4 * n + 1], v0);
                    v1 = fmaf(acc[4 * n + 2], acc[4 * n + 2], v1); v1 = fmaf(acc[4 * n + 3], acc[4 * n + 3], v1);
                }
#pragma unroll
                for (int o = 1; o < 4; o <<= 1) {
                    s0 += __shfl_xor_sync(0xffffffffu, s0, o); s1 += __shfl_xor_sync(0xffffffffu, s1, o);
                    v0 += __shfl_xor_sync(0xffffffffu, v0, o); v1 += __shfl_xor_sync(0xffffffffu, v1, o);
                }
                if ((lane & 3) == 0) {
                    uint32_t a = sb + STAT + h * 512 + r0 * 8;
                    sts_f32(a, s0); sts_f32(a + 4, v0); sts_f32(a + 64, s1); sts_f32(a + 68, v1);
                }
                bar_sync(2, 256);
                {
                    uint32_t a = sb + STAT + (h ^ 1) * 512 + r0 * 8;
                    s0 = (s0 + lds_f32(a)) * (1.f / 512.f); v0 = (v0 + lds_f32(a + 4)) * (1.f / 512.f);
                    s1 = (s1 + lds_f32(a + 64)) * (1.f / 512.f); v1 = (v1 + lds_f32(a + 68)) * (1.f / 512.f);
                }
                v0 = rsqrtf(fmaxf(fmaf(-s0, s0, v0), 0.f) + 4e-5f); v1 = rsqrtf(fmaxf(fmaf(-s1, s1, v1), 0.f) + 4e-5f);
                s0 = -s0 * v0; s1 = -s1 * v1;
#pragma unroll
                for (int m = 0; m < 8; m++) {
                    const float* a_ = acc + 16 * m;
                    stg4(ucp + 64 * D_ + 32 * m, pack2(fmaf(a_[0], v0, s0), fmaf(a_[1], v0, s0)), pack2(fmaf(a_[4], v0, s0), fmaf(a_[5], v0, s0)),
                         pack2(fmaf(a_[8], v0, s0), fmaf(a_[9], v0, s0)), pack2(fmaf(a_[12], v0, s0), fmaf(a_[13], v0, s0)));
                    stg4(ucp + 72 * D_ + 32 * m, pack2(fmaf(a_[2], v1, s1), fmaf(a_[3], v1, s1)), pack2(fmaf(a_[6], v1, s1), fmaf(a_[7], v1, s1)),
                         pack2(fmaf(a_[10], v1, s1), fmaf(a_[11], v1, s1)), pack2(fmaf(a_[14], v1, s1), fmaf(a_[15], v1, s1)));
                }
            } else {
#pragma unroll
                for (int m = 0; m < 8; m++) {
                    const float* a_ = acc + 16 * m;
                    stg4(ucp + 32 * m, pack2(a_[0], a_[1]), pack2(a_[4], a_[5]), pack2(a_[8], a_[9]), pack2(a_[12], a_[13]));
                    stg4(ucp + 8 * D_ + 32 * m, pack2(a_[2], a_[3]), pack2(a_[6], a_[7]), pack2(a_[10], a_[11]), pack2(a_[14], a_[15]));
                }
                bar_sync(3 + h, 128);
            }
            PT(3 + 3 * pass);
        }
        int s = 1, ph = 0;
        uint32_t* cp = reinterpret_cast<uint32_t*>(g_uc + (size_t)blockIdx.x * 128 * D_) + (tid - 128);
        const uint32_t* dp = reinterpret_cast<const uint32_t*>(dw) + (((tid - 128) & ~15) | ((lane & 3) << 2) | ((lane >> 2) & 3));
        const uint32_t d0 = ldg_v(dp), d1 = ldg_v(dp + D_ / 2), d2 = ldg_v(dp + D_);
        uint32_t ga = ldg_cg(cp + 64 * (D_ / 2)), gb = ldg_cg(cp + 65 * (D_ / 2));
        fresh(acc);
#pragma unroll 1
        for (int j = 0; j < NKV; j++) {
            cp += D_ / 2;
            uint32_t gc = 0, uu = 0;
            if (j < NKV - 1) { gc = ldg_cg(cp + 65 * (D_ / 2)); uu = ldg_cg(cp); }
            mbar_wait(sb + B_P + s * 8, ph);
            PL(j, 0);
            if (j > 0) {
                const float sc0 = lds_f32(sb + SCL + s * 256 + r0 * 4), sc1 = lds_f32(sb + SCL + s * 256 + r0 * 4 + 32);
                if (__any_sync(0xffffffffu, sc0 != 1.f || sc1 != 1.f)) {
#pragma unroll
                    for (int n = 0; n < 32; n++) { acc[4 * n] *= sc0; acc[4 * n + 1] *= sc0; acc[4 * n + 2] *= sc1; acc[4 * n + 3] *= sc1; }
                }
            }
            mbar_wait(sb + B_GO + s * 8, ph);
            PL(j, 1);
            const uint32_t vd = sd + s * 4096 + h * 2048, pd = sd + (s == 0 ? 2 : s - 1) * 512;
            pin(acc);
            wg_fence();
#pragma unroll
            for (int kk = 0; kk < 4; kk++) wgmma_ss_n256_tb1(acc, dsc(pd, R3 + kk * 32, 16), dsc(vd, kk * 2048, 8192), 1);
            wg_commit();
            wg_wait<0>();
            pin(acc);
            PL(j, 2);
            if (w0 && elect1()) {
                if (j == NKV - 5 && mode == 0) flag_wait(&g_sync[3], 4);
                if (j == XPF) {
                    const int t0 = 62 * ti + 31 * h, nr = min(31, T_ - t0);
                    if (nr > 0) l2_prefetch(x + ((size_t)b * T_ + t0) * D_, nr * 1024);
                }
                if (atom_inc_s(sb + CNT + 4 * s) & 1) {
                    if (j + 3 < NKV) {
                        mbar_expect_tx(sb + B_KV + s * 8, 65536);
                        tma4(sb + s * 65536, &mp.xa, 0, 64 * (j + 3), 0, b, sb + B_KV + s * 8);
                    } else if (j < NKV - 1) {
                        const int n0 = j == NKV - 3 ? 0 : 8, n1 = n0 + 8;
#pragma unroll 1
                        for (int n = n0; n < n1; n++) ring_ld(sb, n * 8, n);
                    }
                }
            }
            uu = pack2(gelu2(blo(uu)), gelu2(bhi(uu)));
            if (j < NKV - 1) asm volatile("st.global.u32 [%0], %1;" ::"l"(cp), "r"(bmul2(uu, bfma2(gc, d2, bfma2(gb, d1, bmul2(ga, d0))))) : "memory");
            ga = gb; gb = gc;
            if (++s == 3) s = 0;
            if (s == 1) ph ^= 1;
        }
        {
            const float i0 = lds_f32(sb + LINV + r0 * 4), i1 = lds_f32(sb + LINV + r0 * 4 + 32);
#pragma unroll
            for (int p = 0; p < 16; p++)
                stsm4(((sb + R0 + h * 32768 + loff) ^ ((p & 3) << 5)) + (p >> 2) * 8192,
                      pack2(acc[8 * p] * i0, acc[8 * p + 1] * i0), pack2(acc[8 * p + 2] * i1, acc[8 * p + 3] * i1),
                      pack2(acc[8 * p + 4] * i0, acc[8 * p + 5] * i0), pack2(acc[8 * p + 6] * i1, acc[8 * p + 7] * i1));
        }
        fence_async();
        fence_async_g();
        bar_sync(2, 256);
        if (lane == 0 && w < 2) ring_ld(sb, 128 + 16 * w + 8 * h, 16 + 2 * w + h);
        PT(7);
        fresh(acc);
        {
            uint32_t slot8 = 8 * h, par = 0, prev8 = 0;
#pragma unroll 1
            for (int kk = 0; kk < 64; kk++) {
                if (kk == 32 || kk == 48) mbar_wait(sb + B_UC + (kk >> 1 & 8), 0);
                mbar_wait(sb + B_R2 + slot8, par);
                wg_fence();
                wgmma_ss_n256_tb1(acc, mkd(sd + (1u << 16) + (R0 >> 4) + (kk >> 2 & 7) * 512 + (kk & 3) * 2), mkd(bd2k + (R1 >> 4) + slot8 * 64), 1);
                wg_commit();
                wg_wait<1>();
                if (kk > 0 && lane == 0) mbar_arrive(sb + B_E2 + prev8);
                if ((kk == 16 || kk == 32) && w0 && elect1() && (atom_inc_s(sb + CNT + 12 + (kk >> 3 & 4)) & 1)) {
                    mbar_expect_tx(sb + B_UC + (kk >> 2 & 8), 32768);
                    tma3(sb + R0 + (kk & 32) * 1024, &mp.uc, 0, 128 * blockIdx.x, kk >> 3 & 4, sb + B_UC + (kk >> 2 & 8));
                }
                prev8 = slot8;
                slot8 += 16;
                if (slot8 >= 160) { slot8 -= 160; par ^= 1; }
            }
        }
        wg_wait<0>();
        pin(acc);
        PT(8);
        mbar_wait(sb + B_X, 0);
        PT(9);
        {
            const uint32_t sr = (lrow + 63) & 63;
            const uint32_t xoff = sr * 128 + ((((lane >> 4) ^ sr) & 7) << 4);
#pragma unroll
            for (int p = 0; p < 16; p++) {
                const uint32_t a = ((sb + R2 + h * 32768 + xoff) ^ ((p & 3) << 5)) + (p >> 2) * 8192;
                uint32_t xv[4];
                ldsm4(a, xv);
#pragma unroll
                for (int e = 0; e < 4; e++)
                    xv[e] = pack2(acc[8 * p + 2 * e] + __uint_as_float(xv[e] << 16), acc[8 * p + 2 * e + 1] + __uint_as_float(xv[e] & 0xffff0000u));
                stsm4(a, xv[0], xv[1], xv[2], xv[3]);
            }
        }
        fence_async();
        bar_sync(3 + h, 128);
        if (el) {
            for (int c = 0; c < 4; c++) tma4_store(&mp.out, sb + R2 + (4 * h + c) * 8192, 0, 62 * ti, 4 * h + c, b);
            asm volatile("cp.async.bulk.commit_group;" ::: "memory");
            PT(10);
            if (h == 0) cta_done(mode);
            asm volatile("cp.async.bulk.wait_group.read 0;" ::: "memory");
        }
        PT(11);
        PG(201);
        PDUMP();
    }
}

typedef CUresult (*PFN_enc)(CUtensorMap*, CUtensorMapDataType, cuuint32_t, void*, const cuuint64_t*, const cuuint64_t*,
                            const cuuint32_t*, const cuuint32_t*, CUtensorMapInterleave, CUtensorMapSwizzle,
                            CUtensorMapL2promotion, CUtensorMapFloatOOBfill);

static void enc(PFN_enc f, CUtensorMap* m, void* base, int rank, const cuuint64_t* dims, const cuuint64_t* strides, const cuuint32_t* box) {
    cuuint32_t es[5] = {1, 1, 1, 1, 1};
    f(m, CU_TENSOR_MAP_DATA_TYPE_BFLOAT16, rank, base, dims, strides, box, es, CU_TENSOR_MAP_INTERLEAVE_NONE,
      CU_TENSOR_MAP_SWIZZLE_128B, CU_TENSOR_MAP_L2_PROMOTION_L2_256B, CU_TENSOR_MAP_FLOAT_OOB_FILL_NONE);
}
static void enc_act(PFN_enc f, CUtensorMap* m, void* base, int rows, int chunks, int trows = T_, int pitch = T_) {
    cuuint64_t dims[4] = {64, (cuuint64_t)trows, 8, (cuuint64_t)NB_};
    cuuint64_t st[3] = {1024, 128, (cuuint64_t)pitch * 1024};
    cuuint32_t box[4] = {64, (cuuint32_t)rows, (cuuint32_t)chunks, 1};
    enc(f, m, base, 4, dims, st, box);
}
static void enc_w(PFN_enc f, CUtensorMap* m, void* base, int krows, int ncols, int bk, int bc) {
    cuuint64_t dims[3] = {64, (cuuint64_t)krows, (cuuint64_t)(ncols / 64)};
    cuuint64_t st[2] = {(cuuint64_t)ncols * 2, 128};
    cuuint32_t box[3] = {64, (cuuint32_t)bk, (cuuint32_t)bc};
    enc(f, m, base, 3, dims, st, box);
}

extern "C" void kernel_launch(void* const* d_in, const int* in_sizes, int n_in, void* d_out, int out_size) {
    const bf16* x = (const bf16*)d_in[0];
    static PFN_enc fenc = nullptr;
    static void *p_xa, *p_mqk, *p_uc, *p_t1;
    static int fused = 0;
    if (!fenc) {
        void* fn = nullptr;
        cudaDriverEntryPointQueryResult qr;
        cudaGetDriverEntryPoint("cuTensorMapEncodeTiled", &fn, cudaEnableDefault, &qr);
        fenc = (PFN_enc)fn;
        cudaGetSymbolAddress(&p_xa, g_xa);
        cudaGetSymbolAddress(&p_mqk, g_mqk);
        cudaGetSymbolAddress(&p_uc, g_uc);
        cudaGetSymbolAddress(&p_t1, g_t1);
        cudaFuncSetAttribute(main_kernel, cudaFuncAttributeMaxDynamicSharedMemorySize, SMEM_BYTES);
        int dev = 0, sms = 0, occ = 0;
        cudaGetDevice(&dev);
        cudaDeviceGetAttribute(&sms, cudaDevAttrMultiProcessorCount, dev);
        cudaOccupancyMaxActiveBlocksPerMultiprocessor(&occ, main_kernel, 384, SMEM_BYTES);
        fused = sms * occ >= NCTA + 2;
    }
    Maps mp;
    enc_act(fenc, &mp.xa, (char*)p_xa + 1024, 64, 8, T_, T_ + 8);
    enc_act(fenc, &mp.xa2, (char*)p_xa + 1024, 64, 2, T_, T_ + 8);
    enc_act(fenc, &mp.xas, p_xa, 64, 1, T_ + 1, T_ + 8);
    enc_act(fenc, &mp.x, (void*)x, 64, 1);
    enc_act(fenc, &mp.out, d_out, 62, 1);
    enc_w(fenc, &mp.wup4, d_in[5], 512, 1024, 16, 4);
    enc_w(fenc, &mp.wup8, d_in[5], 512, 1024, 16, 8);
    enc_w(fenc, &mp.mqa2, p_mqk, 512, 512, 32, 2);
    enc_w(fenc, &mp.mqa4, p_mqk, 512, 512, 32, 4);
    enc_w(fenc, &mp.mqb1, p_mqk, 512, 512, 64, 1);
    enc_w(fenc, &mp.mqb2, p_mqk, 512, 512, 64, 2);
    enc_w(fenc, &mp.uc, p_uc, NCTA * 128, 512, 64, 4);
    enc_w(fenc, &mp.wq, d_in[1], 512, 512, 64, 8);
    enc_w(fenc, &mp.wk, d_in[2], 512, 512, 32, 8);
    enc_w(fenc, &mp.fa[0], d_in[3], 512, 512, 128, 1);
    enc_w(fenc, &mp.fa[1], d_in[7], 512, 512, 128, 1);
    enc_w(fenc, &mp.fa[2], p_t1, 512, 512, 128, 1);
    enc_w(fenc, &mp.fb[0], d_in[4], 512, 512, 64, 4);
    enc_w(fenc, &mp.fb[1], d_in[8], 1024, 512, 64, 4);
    enc_w(fenc, &mp.fc, p_t1, 512, 512, 64, 4);
    cudaStream_t st = cudaStreamPerThread;
    if (fused) {
        main_kernel<<<NCTA + 2, 384, SMEM_BYTES, st>>>(mp, x, (const bf16*)d_in[6], (const bf16*)d_in[5], 0);
    } else {
        main_kernel<<<NCTA + 2, 384, SMEM_BYTES, st>>>(mp, x, (const bf16*)d_in[6], (const bf16*)d_in[5], 1);
        main_kernel<<<NCTA + 2, 384, SMEM_BYTES, st>>>(mp, x, (const bf16*)d_in[6], (const bf16*)d_in[5], 2);
    }
}
```

```cpp
#include <cuda_runtime.h>
#include <cuda_bf16.h>
#include <cuda.h>
#include <stdint.h>

typedef __nv_bfloat16 bf16;

constexpr int T_ = 4000, D_ = 512, NB_ = 2;
constexpr int TPB = 65;
constexpr int NCTA = TPB * NB_;
constexpr int NKV = 63;

__device__ __align__(1024) bf16 g_xa[NB_ * (T_ + 8) * D_];
__device__ __align__(1024) bf16 g_mqk[D_ * D_];
__device__ __align__(1024) bf16 g_t1[D_ * D_];
__device__ __align__(1024) bf16 g_wepi[2 * D_ * D_];
__device__ __align__(1024) bf16 g_uc[NCTA * 128 * D_];
__device__ unsigned g_sync[8];

#define PT(i) do { if (el) asm volatile("st.shared.u32 [%0], %1;" ::"r"(sb + MISC + 2560), "r"((unsigned)clock())); } while (0)
#define PG(i)
#define PE()
#define PLM 15
#define PL(j, q) do { if ((PLM >> ((q) + (wg ? 4 : 0))) & 1) PT(0); } while (0)
#define PDUMP()

#define FENCE_AT 1
#define GO_AT 25
#define LAZY 256.f
#define SU 2
#define XS_GAP 800
#define XPF 54
#define CV0 9
#define LAGA 0
#define LAGB 0
#define PFW 1
constexpr uint32_t R0 = 0, R1 = 65536, R2 = 131072, R3 = 196608, QS = 221184, MISC = 229376;
constexpr uint32_t AT = 147456;
constexpr uint32_t SMEM_BYTES = 232448;
constexpr uint32_t B_R1 = MISC + 1856  , B_MK = MISC + 48, B_LN = MISC + 56, B_MQ = MISC + 64, B_GN = MISC + 72,
                   B_H1 = MISC + 88, B_H2 = MISC + 96, B_H3 = MISC + 104,
                   B_KV = MISC + 112, B_P = MISC + 136, B_GO = MISC + 160, B_UC = MISC + 184  ,
                   B_X = MISC + 200, CNT = MISC + 208  , SCL = MISC + 512  ,
                   LINV = MISC + 1280  ,
                   B_R2 = MISC + 1536  , B_E2 = MISC + 1696  ;

__device__ __forceinline__ uint32_t smem_u32(const void* p) { return (uint32_t)__cvta_generic_to_shared(p); }
__device__ __forceinline__ void wg_fence() { asm volatile("wgmma.fence.sync.aligned;" ::: "memory"); }
__device__ __forceinline__ void wg_commit() { asm volatile("wgmma.commit_group.sync.aligned;" ::: "memory"); }
template <int N> __device__ __forceinline__ void wg_wait() { asm volatile("wgmma.wait_group.sync.aligned %0;" ::"n"(N) : "memory"); }
__device__ __forceinline__ uint64_t dsc(uint32_t sd, uint32_t off, uint32_t lbo) {
    uint32_t lo = sd + (off >> 4) + ((lbo >> 4) << 16);
    uint64_t d;
    asm("mov.b64 %0, {%1, %2};" : "=l"(d) : "r"(lo), "r"((1024u >> 4) | (1u << 30)));
    return d;
}
__device__ __forceinline__ bool elect1() {
    uint32_t p;
    asm volatile("{\n.reg .pred p;\nelect.sync _|p, 0xffffffff;\nselp.u32 %0, 1, 0, p;\n}\n" : "=r"(p));
    return p != 0;
}
__device__ __forceinline__ void mbar_init(uint32_t bar, int cnt) { asm volatile("mbarrier.init.shared::cta.b64 [%0], %1;" ::"r"(bar), "r"(cnt) : "memory"); }
__device__ __forceinline__ void mbar_expect_tx(uint32_t bar, uint32_t bytes) { asm volatile("mbarrier.arrive.expect_tx.shared::cta.b64 _, [%0], %1;" ::"r"(bar), "r"(bytes) : "memory"); }
__device__ __forceinline__ void mbar_arrive(uint32_t bar) { asm volatile("mbarrier.arrive.shared::cta.b64 _, [%0];" ::"r"(bar) : "memory"); }
__device__ __forceinline__ void mbar_wait(uint32_t bar, uint32_t parity) {
    uint32_t ok;
#pragma unroll 1
    for (uint32_t it = 0;; ++it) {
        asm volatile("{\n.reg .pred p;\nmbarrier.try_wait.parity.shared::cta.b64 p, [%1], %2;\nselp.u32 %0, 1, 0, p;\n}\n" : "=r"(ok) : "r"(bar), "r"(parity) : "memory");
        if (ok) break;
        if (it > (1u << 20)) __trap();
    }
}
__device__ __forceinline__ bool mbar_test(uint32_t bar, uint32_t parity) {
    uint32_t ok;
    asm volatile("{\n.reg .pred p;\nmbarrier.test_wait.parity.shared::cta.b64 p, [%1], %2;\nselp.u32 %0, 1, 0, p;\n}\n" : "=r"(ok) : "r"(bar), "r"(parity) : "memory");
    return ok != 0;
}
__device__ __forceinline__ void fence_async() { asm volatile("fence.proxy.async.shared::cta;" ::: "memory"); }
__device__ __forceinline__ void fence_async_g() { asm volatile("fence.proxy.async.global;" ::: "memory"); }
__device__ __forceinline__ void bar_sync(int id, int n) { asm volatile("bar.sync %0, %1;" ::"r"(id), "r"(n) : "memory"); }
__device__ __forceinline__ void tma3(uint32_t dst, const CUtensorMap* tm, int c0, int c1, int c2, uint32_t bar) {
    asm volatile("cp.async.bulk.tensor.3d.shared::cluster.global.mbarrier::complete_tx::bytes [%0], [%1, {%3, %4, %5}], [%2];"
                 ::"r"(dst), "l"(tm), "r"(bar), "r"(c0), "r"(c1), "r"(c2) : "memory");
}
__device__ __forceinline__ void tma4(uint32_t dst, const CUtensorMap* tm, int c0, int c1, int c2, int c3, uint32_t bar) {
    asm volatile("cp.async.bulk.tensor.4d.shared::cluster.global.mbarrier::complete_tx::bytes [%0], [%1, {%3, %4, %5, %6}], [%2];"
                 ::"r"(dst), "l"(tm), "r"(bar), "r"(c0), "r"(c1), "r"(c2), "r"(c3) : "memory");
}
__device__ __forceinline__ void tma4_store(const CUtensorMap* tm, uint32_t src, int c0, int c1, int c2, int c3) {
    asm volatile("cp.async.bulk.tensor.4d.global.shared::cta.bulk_group [%0, {%2, %3, %4, %5}], [%1];"
                 ::"l"(tm), "r"(src), "r"(c0), "r"(c1), "r"(c2), "r"(c3) : "memory");
}
__device__ __forceinline__ void tma3_store(const CUtensorMap* tm, uint32_t src, int c0, int c1, int c2) {
    asm volatile("cp.async.bulk.tensor.3d.global.shared::cta.bulk_group [%0, {%2, %3, %4}], [%1];"
                 ::"l"(tm), "r"(src), "r"(c0), "r"(c1), "r"(c2) : "memory");
}
__device__ __forceinline__ void stsm4(uint32_t addr, uint32_t a, uint32_t b, uint32_t c, uint32_t d) {
    asm volatile("stmatrix.sync.aligned.m8n8.x4.shared.b16 [%0], {%1, %2, %3, %4};" ::"r"(addr), "r"(a), "r"(b), "r"(c), "r"(d) : "memory");
}
__device__ __forceinline__ void ldsm4(uint32_t addr, uint32_t (&r)[4]) {
    asm volatile("ldmatrix.sync.aligned.m8n8.x4.shared.b16 {%0, %1, %2, %3}, [%4];" : "=r"(r[0]), "=r"(r[1]), "=r"(r[2]), "=r"(r[3]) : "r"(addr) : "memory");
}
__device__ __forceinline__ void ldsm2(uint32_t addr, uint32_t (&r)[2]) {
    asm volatile("ldmatrix.sync.aligned.m8n8.x2.shared.b16 {%0, %1}, [%2];" : "=r"(r[0]), "=r"(r[1]) : "r"(addr) : "memory");
}
__device__ __forceinline__ void stg4(void* p, uint32_t a, uint32_t b, uint32_t c, uint32_t d) {
    asm volatile("st.global.v4.u32 [%0], {%1, %2, %3, %4};" ::"l"(p), "r"(a), "r"(b), "r"(c), "r"(d) : "memory");
}
__device__ __forceinline__ void hmma(float (&c)[4], uint32_t a0, uint32_t a1, uint32_t a2, uint32_t a3, uint32_t b0, uint32_t b1) {
    asm("mma.sync.aligned.m16n8k16.row.col.f32.bf16.bf16.f32 {%0, %1, %2, %3}, {%4, %5, %6, %7}, {%8, %9}, {%0, %1, %2, %3};"
        : "+f"(c[0]), "+f"(c[1]), "+f"(c[2]), "+f"(c[3]) : "r"(a0), "r"(a1), "r"(a2), "r"(a3), "r"(b0), "r"(b1));
}
__device__ __forceinline__ uint32_t pack2(float lo, float hi) {
    uint32_t r;
    asm("cvt.rn.bf16x2.f32 %0, %1, %2;" : "=r"(r) : "f"(hi), "f"(lo));
    return r;
}
__device__ __forceinline__ uint32_t pack2v(float lo, float hi) {
    uint32_t r;
    asm volatile("cvt.rn.bf16x2.f32 %0, %1, %2;" : "=r"(r) : "f"(hi), "f"(lo));
    return r;
}
__device__ __forceinline__ uint32_t bmul2(uint32_t a, uint32_t b) { uint32_t r; asm("mul.rn.bf16x2 %0, %1, %2;" : "=r"(r) : "r"(a), "r"(b)); return r; }
__device__ __forceinline__ uint32_t bfma2(uint32_t a, uint32_t b, uint32_t c) { uint32_t r; asm("fma.rn.bf16x2 %0, %1, %2, %3;" : "=r"(r) : "r"(a), "r"(b), "r"(c)); return r; }
__device__ __forceinline__ float ex2(float x) { float r; asm("ex2.approx.ftz.f32 %0, %1;" : "=f"(r) : "f"(x)); return r; }
__device__ __forceinline__ float rcp(float x) { float r; asm("rcp.approx.ftz.f32 %0, %1;" : "=f"(r) : "f"(x)); return r; }
__device__ __forceinline__ float gelu2(float x) {
    float t = fmaf(x * x, 0.044715f * 0.7978845608028654f, 0.7978845608028654f), th;
    asm("tanh.approx.f32 %0, %1;" : "=f"(th) : "f"(x * t));
    return fmaf(x, th, x);
}
__device__ __forceinline__ uint32_t ldg_v(const uint32_t* p) { uint32_t v; asm volatile("ld.global.nc.u32 %0, [%1];" : "=r"(v) : "l"(p)); return v; }
__device__ __forceinline__ uint32_t ldg_cg(const uint32_t* p) { uint32_t v; asm volatile("ld.global.cg.u32 %0, [%1];" : "=r"(v) : "l"(p) : "memory"); return v; }
__device__ __forceinline__ void ldg4_cg(const uint32_t* p, uint32_t* r) {
    asm volatile("ld.global.cg.v4.u32 {%0, %1, %2, %3}, [%4];" : "=r"(r[0]), "=r"(r[1]), "=r"(r[2]), "=r"(r[3]) : "l"(p) : "memory");
}
__device__ __forceinline__ float lds_f32(uint32_t a) { float v; asm volatile("ld.shared.f32 %0, [%1];" : "=f"(v) : "r"(a) : "memory"); return v; }
__device__ __forceinline__ void sts_f32(uint32_t a, float v) { asm volatile("st.shared.f32 [%0], %1;" ::"r"(a), "f"(v) : "memory"); }
__device__ __forceinline__ uint32_t atom_inc_s(uint32_t a) { uint32_t v; asm volatile("atom.relaxed.cta.shared.add.u32 %0, [%1], 1;" : "=r"(v) : "r"(a) : "memory"); return v; }
__device__ __forceinline__ void lds4(uint32_t a, uint32_t* r) {
    asm volatile("ld.shared.v4.u32 {%0, %1, %2, %3}, [%4];" : "=r"(r[0]), "=r"(r[1]), "=r"(r[2]), "=r"(r[3]) : "r"(a) : "memory");
}
__device__ __forceinline__ void sts4(uint32_t a, uint32_t x, uint32_t y, uint32_t z, uint32_t t) {
    asm volatile("st.shared.v4.u32 [%0], {%1, %2, %3, %4};" ::"r"(a), "r"(x), "r"(y), "r"(z), "r"(t) : "memory");
}
__device__ __forceinline__ uint32_t bsub2(uint32_t a, uint32_t b) { uint32_t r; asm("sub.rn.bf16x2 %0, %1, %2;" : "=r"(r) : "r"(a), "r"(b)); return r; }
__device__ __forceinline__ float blo(uint32_t v) { return __uint_as_float(v << 16); }
__device__ __forceinline__ float bhi(uint32_t v) { return __uint_as_float(v & 0xffff0000u); }
__device__ __forceinline__ float bfr(float x) { return __bfloat162float(__float2bfloat16_rn(x)); }
__device__ __forceinline__ void l2_prefetch(const void* p, uint32_t bytes) { asm volatile("cp.async.bulk.prefetch.L2.global [%0], %1;" ::"l"(p), "r"(bytes) : "memory"); }
__device__ __forceinline__ void flag_add(unsigned* p) { asm volatile("red.release.gpu.global.add.u32 [%0], 1;" ::"l"(p) : "memory"); }
__device__ __forceinline__ void flag_wait(const unsigned* p, unsigned target) {
#pragma unroll 1
    for (uint32_t it = 0;; ++it) {
        unsigned v;
        asm volatile("ld.acquire.gpu.global.u32 %0, [%1];" : "=r"(v) : "l"(p) : "memory");
        if (v >= target) break;
        if (it > (1u << 20)) __trap();
    }
    fence_async_g();
}
template <int N> __device__ __forceinline__ void pin(float (&a)[N]) {
#pragma unroll
    for (int i = 0; i < N; i++) asm volatile("" : "+f"(a[i])::"memory");
}

template <int N> __device__ __forceinline__ void fresh(float (&a)[N]) {
#pragma unroll
    for (int i = 0; i < N; i++) a[i] = 0.f;
    pin(a);
}

__device__ __forceinline__ void wgmma_rs_n64_tb0(float (&d)[32], uint32_t a0, uint32_t a1, uint32_t a2, uint32_t a3, uint64_t db, int scale_d) {
    asm volatile("{\n.reg .pred p;\nsetp.ne.b32 p, %37, 0;\n"
        "wgmma.mma_async.sync.aligned.m64n64k16.f32.bf16.bf16 {%0, %1, %2, %3, %4, %5, %6, %7, %8, %9, %10, %11, %12, %13, %14, %15, %16, %17, %18, %19, %20, %21, %22, %23, %24, %25, %26, %27, %28, %29, %30, %31}, {%32, %33, %34, %35}, %36, p, 1, 1, 0;\n}\n"
        : "+f"(d[0]), "+f"(d[1]), "+f"(d[2]), "+f"(d[3]), "+f"(d[4]), "+f"(d[5]), "+f"(d[6]), "+f"(d[7]), "+f"(d[8]), "+f"(d[9]), "+f"(d[10]), "+f"(d[11]), "+f"(d[12]), "+f"(d[13]), "+f"(d[14]), "+f"(d[15]), "+f"(d[16]), "+f"(d[17]), "+f"(d[18]), "+f"(d[19]), "+f"(d[20]), "+f"(d[21]), "+f"(d[22]), "+f"(d[23]), "+f"(d[24]), "+f"(d[25]), "+f"(d[26]), "+f"(d[27]), "+f"(d[28]), "+f"(d[29]), "+f"(d[30]), "+f"(d[31])
        : "r"(a0), "r"(a1), "r"(a2), "r"(a3), "l"(db), "r"(scale_d));
}

__device__ __forceinline__ void wgmma_ss_n128_tb1(float (&d)[64], uint64_t da, uint64_t db, int scale_d) {
    asm volatile("{\n.reg .pred p;\nsetp.ne.b32 p, %66, 0;\n"
        "wgmma.mma_async.sync.aligned.m64n128k16.f32.bf16.bf16 {%0, %1, %2, %3, %4, %5, %6, %7, %8, %9, %10, %11, %12, %13, %14, %15, %16, %17, %18, %19, %20, %21, %22, %23, %24, %25, %26, %27, %28, %29, %30, %31, %32, %33, %34, %35, %36, %37, %38, %39, %40, %41, %42, %43, %44, %45, %46, %47, %48, %49, %50, %51, %52, %53, %54, %55, %56, %57, %58, %59, %60, %61, %62, %63}, %64, %65, p, 1, 1, 0, 1;\n}\n"
        : "+f"(d[0]), "+f"(d[1]), "+f"(d[2]), "+f"(d[3]), "+f"(d[4]), "+f"(d[5]), "+f"(d[6]), "+f"(d[7]), "+f"(d[8]), "+f"(d[9]), "+f"(d[10]), "+f"(d[11]), "+f"(d[12]), "+f"(d[13]), "+f"(d[14]), "+f"(d[15]), "+f"(d[16]), "+f"(d[17]), "+f"(d[18]), "+f"(d[19]), "+f"(d[20]), "+f"(d[21]), "+f"(d[22]), "+f"(d[23]), "+f"(d[24]), "+f"(d[25]), "+f"(d[26]), "+f"(d[27]), "+f"(d[28]), "+f"(d[29]), "+f"(d[30]), "+f"(d[31]), "+f"(d[32]), "+f"(d[33]), "+f"(d[34]), "+f"(d[35]), "+f"(d[36]), "+f"(d[37]), "+f"(d[38]), "+f"(d[39]), "+f"(d[40]), "+f"(d[41]), "+f"(d[42]), "+f"(d[43]), "+f"(d[44]), "+f"(d[45]), "+f"(d[46]), "+f"(d[47]), "+f"(d[48]), "+f"(d[49]), "+f"(d[50]), "+f"(d[51]), "+f"(d[52]), "+f"(d[53]), "+f"(d[54]), "+f"(d[55]), "+f"(d[56]), "+f"(d[57]), "+f"(d[58]), "+f"(d[59]), "+f"(d[60]), "+f"(d[61]), "+f"(d[62]), "+f"(d[63])
        : "l"(da), "l"(db), "r"(scale_d));
}

__device__ __forceinline__ void wgmma_ss_n256_tb1(float (&d)[128], uint64_t da, uint64_t db, int scale_d) {
    asm volatile("{\n.reg .pred p;\nsetp.ne.b32 p, %130, 0;\n"
        "wgmma.mma_async.sync.aligned.m64n256k16.f32.bf16.bf16 {%0, %1, %2, %3, %4, %5, %6, %7, %8, %9, %10, %11, %12, %13, %14, %15, %16, %17, %18, %19, %20, %21, %22, %23, %24, %25, %26, %27, %28, %29, %30, %31, %32, %33, %34, %35, %36, %37, %38, %39, %40, %41, %42, %43, %44, %45, %46, %47, %48, %49, %50, %51, %52, %53, %54, %55, %56, %57, %58, %59, %60, %61, %62, %63, %64, %65, %66, %67, %68, %69, %70, %71, %72, %73, %74, %75, %76, %77, %78, %79, %80, %81, %82, %83, %84, %85, %86, %87, %88, %89, %90, %91, %92, %93, %94, %95, %96, %97, %98, %99, %100, %101, %102, %103, %104, %105, %106, %107, %108, %109, %110, %111, %112, %113, %114, %115, %116, %117, %118, %119, %120, %121, %122, %123, %124, %125, %126, %127}, %128, %129, p, 1, 1, 0, 1;\n}\n"
        : "+f"(d[0]), "+f"(d[1]), "+f"(d[2]), "+f"(d[3]), "+f"(d[4]), "+f"(d[5]), "+f"(d[6]), "+f"(d[7]), "+f"(d[8]), "+f"(d[9]), "+f"(d[10]), "+f"(d[11]), "+f"(d[12]), "+f"(d[13]), "+f"(d[14]), "+f"(d[15]), "+f"(d[16]), "+f"(d[17]), "+f"(d[18]), "+f"(d[19]), "+f"(d[20]), "+f"(d[21]), "+f"(d[22]), "+f"(d[23]), "+f"(d[24]), "+f"(d[25]), "+f"(d[26]), "+f"(d[27]), "+f"(d[28]), "+f"(d[29]), "+f"(d[30]), "+f"(d[31]), "+f"(d[32]), "+f"(d[33]), "+f"(d[34]), "+f"(d[35]), "+f"(d[36]), "+f"(d[37]), "+f"(d[38]), "+f"(d[39]), "+f"(d[40]), "+f"(d[41]), "+f"(d[42]), "+f"(d[43]), "+f"(d[44]), "+f"(d[45]), "+f"(d[46]), "+f"(d[47]), "+f"(d[48]), "+f"(d[49]), "+f"(d[50]), "+f"(d[51]), "+f"(d[52]), "+f"(d[53]), "+f"(d[54]), "+f"(d[55]), "+f"(d[56]), "+f"(d[57]), "+f"(d[58]), "+f"(d[59]), "+f"(d[60]), "+f"(d[61]), "+f"(d[62]), "+f"(d[63]), "+f"(d[64]), "+f"(d[65]), "+f"(d[66]), "+f"(d[67]), "+f"(d[68]), "+f"(d[69]), "+f"(d[70]), "+f"(d[71]), "+f"(d[72]), "+f"(d[73]), "+f"(d[74]), "+f"(d[75]), "+f"(d[76]), "+f"(d[77]), "+f"(d[78]), "+f"(d[79]), "+f"(d[80]), "+f"(d[81]), "+f"(d[82]), "+f"(d[83]), "+f"(d[84]), "+f"(d[85]), "+f"(d[86]), "+f"(d[87]), "+f"(d[88]), "+f"(d[89]), "+f"(d[90]), "+f"(d[91]), "+f"(d[92]), "+f"(d[93]), "+f"(d[94]), "+f"(d[95]), "+f"(d[96]), "+f"(d[97]), "+f"(d[98]), "+f"(d[99]), "+f"(d[100]), "+f"(d[101]), "+f"(d[102]), "+f"(d[103]), "+f"(d[104]), "+f"(d[105]), "+f"(d[106]), "+f"(d[107]), "+f"(d[108]), "+f"(d[109]), "+f"(d[110]), "+f"(d[111]), "+f"(d[112]), "+f"(d[113]), "+f"(d[114]), "+f"(d[115]), "+f"(d[116]), "+f"(d[117]), "+f"(d[118]), "+f"(d[119]), "+f"(d[120]), "+f"(d[121]), "+f"(d[122]), "+f"(d[123]), "+f"(d[124]), "+f"(d[125]), "+f"(d[126]), "+f"(d[127])
        : "l"(da), "l"(db), "r"(scale_d));
}

__device__ __forceinline__ void wgmma_ss_n32_tb0(float (&d)[16], uint64_t da, uint64_t db, int scale_d) {
    asm volatile("{\n.reg .pred p;\nsetp.ne.b32 p, %18, 0;\n"
        "wgmma.mma_async.sync.aligned.m64n32k16.f32.bf16.bf16 {%0, %1, %2, %3, %4, %5, %6, %7, %8, %9, %10, %11, %12, %13, %14, %15}, %16, %17, p, 1, 1, 0, 0;\n}\n"
        : "+f"(d[0]), "+f"(d[1]), "+f"(d[2]), "+f"(d[3]), "+f"(d[4]), "+f"(d[5]), "+f"(d[6]), "+f"(d[7]), "+f"(d[8]), "+f"(d[9]), "+f"(d[10]), "+f"(d[11]), "+f"(d[12]), "+f"(d[13]), "+f"(d[14]), "+f"(d[15])
        : "l"(da), "l"(db), "r"(scale_d));
}

__device__ __forceinline__ void wgmma_ss_n64_tb0(float (&d)[32], uint64_t da, uint64_t db, int scale_d) {
    asm volatile("{\n.reg .pred p;\nsetp.ne.b32 p, %34, 0;\n"
        "wgmma.mma_async.sync.aligned.m64n64k16.f32.bf16.bf16 {%0, %1, %2, %3, %4, %5, %6, %7, %8, %9, %10, %11, %12, %13, %14, %15, %16, %17, %18, %19, %20, %21, %22, %23, %24, %25, %26, %27, %28, %29, %30, %31}, %32, %33, p, 1, 1, 0, 0;\n}\n"
        : "+f"(d[0]), "+f"(d[1]), "+f"(d[2]), "+f"(d[3]), "+f"(d[4]), "+f"(d[5]), "+f"(d[6]), "+f"(d[7]), "+f"(d[8]), "+f"(d[9]), "+f"(d[10]), "+f"(d[11]), "+f"(d[12]), "+f"(d[13]), "+f"(d[14]), "+f"(d[15]), "+f"(d[16]), "+f"(d[17]), "+f"(d[18]), "+f"(d[19]), "+f"(d[20]), "+f"(d[21]), "+f"(d[22]), "+f"(d[23]), "+f"(d[24]), "+f"(d[25]), "+f"(d[26]), "+f"(d[27]), "+f"(d[28]), "+f"(d[29]), "+f"(d[30]), "+f"(d[31])
        : "l"(da), "l"(db), "r"(scale_d));
}

struct Maps {
    CUtensorMap xa, xa2, xas, wup4, wup8, mqa2, mqa4, mqb1, mqb2, uc, x, out, wq, wk, fa[3], fb[2], fc;
};

__device__ __forceinline__ uint64_t mkd(uint32_t lo) {
    uint64_t d;
    asm("mov.b64 %0, {%1, %2};" : "=l"(d) : "r"(lo), "r"((1024u >> 4) | (1u << 30)));
    return d;
}
__device__ __forceinline__ void bulk_ld(uint32_t dst, const void* src, uint32_t bytes, uint32_t bar) {
    asm volatile("cp.async.bulk.shared::cluster.global.mbarrier::complete_tx::bytes [%0], [%1], %2, [%3];" ::"r"(dst), "l"(src), "r"(bytes), "r"(bar) : "memory");
}
__device__ __forceinline__ void bulk_st(void* dst, uint32_t src, uint32_t bytes) {
    asm volatile("cp.async.bulk.global.shared::cta.bulk_group [%0], [%1], %2;" ::"l"(dst), "r"(src), "r"(bytes) : "memory");
}
__device__ __forceinline__ void ring_ld(uint32_t sb, uint32_t slot8, int n) {
    mbar_expect_tx(sb + B_R2 + slot8, 8192);
    bulk_ld(sb + R1 + slot8 * 1024, (const char*)g_wepi + n * 8192, 8192, sb + B_R2 + slot8);
}

__device__ __forceinline__ void ring_half(uint32_t sb, uint32_t slot8, uint32_t hoff, const CUtensorMap* tm, int c1, int c2) {
    mbar_expect_tx(sb + B_R1 + slot8, 8192);
    tma3(sb + slot8 * 2048 + hoff, tm, 0, c1, c2, sb + B_R1 + slot8);
}
__device__ __forceinline__ void ring_full(uint32_t sb, uint32_t slot8, const CUtensorMap* tm, int c1, int c2) {
    mbar_expect_tx(sb + B_R1 + slot8, 16384);
    mbar_arrive(sb + B_R1 + slot8);
    tma3(sb + slot8 * 2048, tm, 0, c1, c2, sb + B_R1 + slot8);
}
__device__ __forceinline__ void cta_done(int mode) {
    if (mode == 0 && atomicAdd(&g_sync[4], 1) == NCTA + 1) {
#pragma unroll
        for (int i = 0; i < 5; i++) g_sync[i] = 0;
    }
}

__device__ __forceinline__ void fold_cta(const Maps& mp, uint32_t sb, int mode) {
    constexpr uint32_t F_FULL = MISC, F_EMPTY = MISC + 32, F_T1 = MISC + 64, STG = 49152, FOUT = 3 * STG;
    const int tid = threadIdx.x, f = blockIdx.x - NCTA;
    if (mode == 2) return;
    if (tid == 0) {
        for (int i = 0; i < 3; i++) { mbar_init(sb + F_FULL + 8 * i, 1); mbar_init(sb + F_EMPTY + 8 * i, 2); }
        mbar_init(sb + F_T1, 2);
        asm volatile("fence.mbarrier_init.release.cluster;" ::: "memory");
        fence_async();
    }
    __syncthreads();
    const int wg = __shfl_sync(0xffffffffu, tid >> 7, 0);
    int st = 0, ph = 0;
    if (wg == 0) {
        if (tid == 0) {
#pragma unroll 1
            for (int it = 0; it < 96; it++) {
                const int p = it >> 3, kc = it & 7, job = p >> 2;
                if (it == 64) mbar_wait(sb + F_T1, 0);
                mbar_wait(sb + F_EMPTY + 8 * st, ph ^ 1);
                mbar_expect_tx(sb + F_FULL + 8 * st, STG);
                tma3(sb + st * STG, &mp.fa[job], 0, 256 * f + 128 * ((p >> 1) & 1), kc, sb + F_FULL + 8 * st);
                tma3(sb + st * STG + 16384, &mp.fb[job != 0], 0, 64 * kc + (job == 1 ? 512 : 0), 4 * (p & 1), sb + F_FULL + 8 * st);
                if (++st == 3) { st = 0; ph ^= 1; }
            }
        }
        return;
    }
    const int h = wg - 1, lane = tid & 31, w = (tid >> 5) & 3;
    const uint32_t sd = (sb & 0x3FFFF) >> 4;
    const bool el = (tid & 127) == 0;
#pragma unroll 1
    for (int p = 0; p < 12; p++) {
        float acc[128];
        fresh(acc);
#pragma unroll 1
        for (int kc = 0; kc < 8; kc++) {
            mbar_wait(sb + F_FULL + 8 * st, ph);
            wg_fence();
#pragma unroll
            for (int kk = 0; kk < 4; kk++)
                wgmma_ss_n256_tb1(acc, dsc(sd, st * STG + h * 8192 + kk * 32, 16), dsc(sd, st * STG + 16384 + kk * 2048, 8192), 1);
            wg_commit();
            wg_wait<0>();
            if (el) mbar_arrive(sb + F_EMPTY + 8 * st);
            if (++st == 3) { st = 0; ph ^= 1; }
        }
        pin(acc);
        const int job = p >> 2;
        if (el) {
            asm volatile("cp.async.bulk.wait_group 0;" ::: "memory");
            if (p == 4) { fence_async_g(); mbar_arrive(sb + F_T1); }
        }
        bar_sync(3 + h, 128);
        uint32_t r = 16 * w + (lane & 7) + ((lane >> 3) & 1) * 8;
        const float fs = job == 1 ? 0.5f : 1.f;
        if (job == 1) r = (r & ~31) | (((r >> 1) & 3) << 3) | (((r >> 3) & 3) << 1) | (r & 1);
        const uint32_t oa = sb + FOUT + h * 32768 + r * 128 + ((((lane >> 4) ^ r) & 7) << 4);
#pragma unroll
        for (int i = 0; i < 16; i++)
            stsm4((oa ^ ((i & 3) << 5)) + (i >> 2) * 8192, pack2(acc[8 * i] * fs, acc[8 * i + 1] * fs), pack2(acc[8 * i + 2] * fs, acc[8 * i + 3] * fs),
                  pack2(acc[8 * i + 4] * fs, acc[8 * i + 5] * fs), pack2(acc[8 * i + 6] * fs, acc[8 * i + 7] * fs));
        fence_async();
        bar_sync(3 + h, 128);
        if (el) {
            const int row0 = 256 * f + 128 * ((p >> 1) & 1) + 64 * h + (job == 1 ? 512 : 0);
            if (job == 0) tma3_store(&mp.fc, sb + FOUT + h * 32768, 0, row0, 4 * (p & 1));
            else {
#pragma unroll 1
                for (int i = 0; i < 16; i++)
                    bulk_st((char*)g_wepi + (row0 / 8 + 2 * (i & 3) + (p & 1)) * 8192 + (i >> 2) * 2048, sb + FOUT + h * 32768 + i * 2048, 2048);
            }
            asm volatile("cp.async.bulk.commit_group;" ::: "memory");
        }
    }
    if (el) {
        asm volatile("cp.async.bulk.wait_group 0;" ::: "memory");
        fence_async_g();
        if (mode == 0) flag_add(&g_sync[3]);
    }
    bar_sync(2, 256);
    if (tid == 128) cta_done(mode);
}

__global__ void __launch_bounds__(384, 1) main_kernel(const __grid_constant__ Maps mp, const bf16* __restrict__ x, const bf16* __restrict__ dw, const bf16* wup, const int mode) {
    extern __shared__ __align__(1024) uint8_t smem[];
    const uint32_t sb = smem_u32(smem);
    const int tid = threadIdx.x;
    PE();
    if (blockIdx.x >= NCTA) { fold_cta(mp, sb, mode); return; }
    const int b = blockIdx.x / TPB, ti = blockIdx.x % TPB;
    const int piece = blockIdx.x & 127;
    const int wg = __shfl_sync(0xffffffffu, tid >> 7, 0);
    const int lane = tid & 31, w = (tid >> 5) & 3;
    const bool w0 = __shfl_sync(0xffffffffu, w, 0) == 0;
    const uint32_t sd = (sb & 0x3FFFF) >> 4;
    const uint32_t adA = sd + (AT >> 4) + (1u << 16);
    const uint32_t bd0 = sd;
    const uint32_t bd2k = bd0 + ((2048u >> 4) << 16);
    const bool el = (tid & 127) == 0;
    const uint32_t lrow = 16 * w + (lane & 7) + ((lane >> 3) & 1) * 8;
    const uint32_t loff = lrow * 128 + ((((lane >> 4) ^ lrow) & 7) << 4);
    const int r0 = 16 * w + (lane >> 2);

    if (wg == 0) {
        asm volatile("setmaxnreg.inc.sync.aligned.u32 184;");
        uint32_t q[112];
        PG(206);
        if (tid == 0) {
            mbar_init(sb + B_MK, 1);
            for (int i = 0; i < 9; i++) mbar_init(sb + B_R1 + 8 * i, 2);
            for (int i = 0; i < 5; i++) asm volatile("st.shared.u32 [%0], 0;" ::"r"(sb + CNT + 4 * i) : "memory");
        } else if (tid == 32) {
            mbar_init(sb + B_LN, 1); mbar_init(sb + B_MQ, 1); mbar_init(sb + B_GN, 8);
            mbar_init(sb + B_H1, 2); mbar_init(sb + B_H2, 1); mbar_init(sb + B_H3, 2);
            for (int i = 0; i < 3; i++) { mbar_init(sb + B_KV + 8 * i, 1); mbar_init(sb + B_P + 8 * i, 4); mbar_init(sb + B_GO + 8 * i, 4); }
            mbar_init(sb + B_UC, 1); mbar_init(sb + B_UC + 8, 1); mbar_init(sb + B_X, 8);
        } else if (tid == 64) {
            for (int i = 0; i < 20; i++) mbar_init(sb + B_R2 + 8 * i, 1);
        } else if (tid == 96) {
            for (int i = 0; i < 20; i++) mbar_init(sb + B_E2 + 8 * i, 4);
        }
        if (lane == 0) {
            asm volatile("fence.mbarrier_init.release.cluster;" ::: "memory");
            fence_async();
        }
        PG(207);
        __syncwarp();
        if (SU != 2) asm volatile("bar.arrive 5, 384;" ::: "memory");
        if (tid == 0) {
            mbar_expect_tx(sb + B_MK, 65536 + 32768);
            tma3(sb + 16384, &mp.wq, 0, 64 * (piece >> 4), 0, sb + B_MK);
            tma3(sb + 81920, &mp.wk, 0, 32 * (piece & 15), 0, sb + B_MK);
            for (int i = 0; i < 14; i++) mbar_arrive(sb + B_R1 + 8 * (i >> 1));
            if (mode != 1) {
                ring_full(sb, 56, &mp.wup8, 0, 8);
                ring_full(sb, 64, &mp.wup8, 16, 8);
                ring_full(sb, 0, &mp.wup8, 32, 8);
            }
        }
        PG(208);
        bar_sync(1, 128);
        if (SU == 2) asm volatile("bar.arrive 5, 384;" ::: "memory");
        PT(0);
        PG(200);
        {
            float mq[16];
            fresh(mq);
            mbar_wait(sb + B_MK, 0);
            PT(1);
            if (tid == 32) l2_prefetch((const char*)wup + piece * 8192, 8192);
            wg_fence();
#pragma unroll 1
            for (int c = 0; c < 8; c++)
#pragma unroll
                for (int kk = 0; kk < 4; kk++)
                    wgmma_ss_n32_tb0(mq, dsc(sd, 16384 + c * 8192 + kk * 32, 16), dsc(sd, 81920 + c * 4096 + kk * 32, 16), 1);
            wg_commit();
            wg_wait<0>();
            if (mode != 1 && w0 && elect1()) {
#pragma unroll 1
                for (int i = 1; i < 7; i++) ring_full(sb, 8 * i, &mp.wup8, 32 + 16 * i, 8);
            }
            pin(mq);
            uint32_t* c = reinterpret_cast<uint32_t*>(g_mqk + (64 * (piece >> 4) + r0) * D_ + 32 * (piece & 15) + 2 * (lane & 3));
#pragma unroll
            for (int n = 0; n < 4; n++) { c[4 * n] = pack2(mq[4 * n], mq[4 * n + 1]); c[4 * n + 4 * D_] = pack2(mq[4 * n + 2], mq[4 * n + 3]); }
            fence_async_g();
            bar_sync(1, 128);
            if (el) {
                if (mode == 0) flag_add(&g_sync[2]);
                if (mode == 0) flag_wait(&g_sync[2], NCTA);
                mbar_arrive(sb + B_MQ);
                PG(203);
                PT(12);
                mbar_wait(sb + B_LN, 0);
#pragma unroll 1
                for (int c = 0; c < 8; c++) {
                    tma4_store(&mp.xas, sb + AT + c * 8192, 0, 62 * ti, c, b);
                    const unsigned t0 = (unsigned)clock();
                    while (c < 7 && (unsigned)clock() - t0 < XS_GAP) __nanosleep(20);
                }
                asm volatile("cp.async.bulk.commit_group;" ::: "memory");
                if (mode == 1) asm volatile("cp.async.bulk.wait_group 0;" ::: "memory");
            }
            PT(13);
            if (mode == 1) return;
        }
        mbar_wait(sb + B_H1, 0);
        PT(2);
        uint32_t slot8 = 24, par = 0, prev8 = 0, prev2 = 0;
        auto adv = [&]() { prev2 = prev8; prev8 = slot8; slot8 += 8; if (slot8 == 72) { slot8 = 0; par ^= 1; } };
        {
            float acc[128];
            fresh(acc);
            auto step = [&](int i) {
                const uint32_t aa = adA + (i >> 1) * 512 + (i & 1) * 4, bb = bd0 + ((4096u >> 4) << 16) + slot8 * 128;
                wg_fence();
                wgmma_ss_n256_tb1(acc, mkd(aa), mkd(bb), 1);
                wgmma_ss_n256_tb1(acc, mkd(aa + 2), mkd(bb + 128), 1);
                wg_commit();
                wg_wait<1 + LAGA>();
            };
#pragma unroll 1
            for (int i = 0; i < 8 + LAGA; i++) {
                mbar_wait(sb + B_R1 + slot8, par);
                step(i);
                if (i > LAGA && w0 && elect1()) ring_full(sb, LAGA ? prev2 : prev8, &mp.mqa4, 32 * (i - LAGA) + 256, 4);
                adv();
            }
#pragma unroll 1
            for (int i = 8 + LAGA; i < 16; i++) {
                mbar_wait(sb + B_R1 + slot8, par);
                if (i == 15 && el) mbar_arrive(sb + B_H2);
                step(i);
                if (w0 && elect1()) ring_full(sb, LAGA ? prev2 : prev8, &mp.wup8, 16 * (i - LAGA) - 128, 0);
                adv();
            }
            if (LAGA) {
                wg_wait<1>();
                if (w0 && elect1()) ring_full(sb, prev2, &mp.wup8, 112, 0);
            }
            wg_wait<0>();
            if (w0 && elect1()) ring_full(sb, prev8, &mp.wup8, 128, 0);
            pin(acc);
            PT(3);
#pragma unroll
            for (int kk = 0; kk < 4; kk++)
                stsm4((sb + QS + loff) ^ (kk << 5), pack2(acc[96 + 8 * kk], acc[97 + 8 * kk]), pack2(acc[98 + 8 * kk], acc[99 + 8 * kk]),
                      pack2(acc[100 + 8 * kk], acc[101 + 8 * kk]), pack2(acc[102 + 8 * kk], acc[103 + 8 * kk]));
            fence_async();
#pragma unroll
            for (int i = 47; i >= 0; i--) q[64 + i] = pack2v(acc[2 * i], acc[2 * i + 1]);
        }
        if (el) {
            asm volatile("cp.async.bulk.wait_group 0;" ::: "memory");
            if (mode == 0) {
                fence_async_g();
                flag_add(&g_sync[b]);
                flag_wait(&g_sync[b], TPB);
            }
        }
        __syncwarp();
        mbar_wait(sb + B_H3, 0);
        PT(4);
        slot8 = 48; par = 1;
#pragma unroll
        for (int half = 0; half < 2; half++) {
            float acc[64];
            fresh(acc);
            auto step = [&](int m) {
                const uint32_t aa = adA + m * 512, bb = bd0 + ((8192u >> 4) << 16) + slot8 * 128;
                mbar_wait(sb + B_R1 + slot8, par);
                wg_fence();
#pragma unroll
                for (int kk = 0; kk < 4; kk++) wgmma_ss_n128_tb1(acc, mkd(aa + 2 * kk), mkd(bb + 128 * kk), 1);
                wg_commit();
                wg_wait<1 + LAGB>();
            };
#pragma unroll 1
            for (int m = 0; m < 8; m++) {
                step(m);
                if (m > LAGB && w0 && elect1()) {
                    if (half == 0) ring_full(sb, LAGB ? prev2 : prev8, &mp.mqb2, 64 * (m - LAGB), 2);
                    else if (m < 4 + LAGB) tma4(sb + (LAGB ? prev2 : prev8) * 2048, &mp.xa2, 0, 0, 2 * (m - LAGB), b, sb + B_KV + 8);
                }
                adv();
            }
            if (LAGB && half == 0) {
                wg_wait<1>();
                if (w0 && elect1()) ring_full(sb, prev2, &mp.mqb2, 448, 2);
            }
            wg_wait<0>();
            if (w0 && elect1()) {
                if (half == 0) {
                    mbar_expect_tx(sb + B_KV + 8, 65536);
                    tma4(sb + prev8 * 2048, &mp.xa2, 0, 0, 0, b, sb + B_KV + 8);
                } else {
                    mbar_expect_tx(sb + B_KV + 16, 65536);
                    tma4(sb + R2, &mp.xa, 0, 64, 0, b, sb + B_KV + 16);
                    mbar_expect_tx(sb + B_KV, 65536);
                    tma4(sb + R0, &mp.xa, 0, 128, 0, b, sb + B_KV);
                }
            }
            pin(acc);
#pragma unroll
            for (int i = 31; i >= 0; i--) q[32 * half + i] = pack2v(acc[2 * i], acc[2 * i + 1]);
        }
        bar_sync(1, 128);
        PT(5);

        const float CS = 0.04419417382415922f * 1.4426950408889634f;
        float m0 = -INFINITY, m1 = -INFINITY, l0 = 0.f, l1 = 0.f;
        int s = 0, sn = 1, ph = 0;
        float S[32];
        const bool l0w = lane == 0, q0 = (lane & 3) == 0;
#pragma unroll 1
        for (int j = -1;; j++) {
            if (j >= 0) {
                PL(j, 1);
                if (j == NKV - 1) {
#pragma unroll
                    for (int i = (T_ - 64 * (NKV - 1)) / 2; i < 32; i++) asm volatile("mov.b32 %0, 0xff800000;" : "=f"(S[i]));
                }
                const bool kv = mbar_test(sb + B_KV + sn * 8, ph);
                const uint32_t pb = sb + R3 + (s == 0 ? 2 : s - 1) * 8192;
                float a0, a1, sc0 = 1.f, sc1 = 1.f;
                auto expo = [&]() {
                    const float n0 = -m0 * CS, n1 = -m1 * CS;
                    a0 = 0.f; a1 = 0.f;
#pragma unroll
                    for (int kk = 0; kk < 4; kk++) {
                        float p[8];
#pragma unroll
                        for (int e = 0; e < 8; e++) p[e] = ex2(fmaf(S[8 * kk + e], CS, (e & 2) ? n1 : n0));
                        a0 += (p[0] + p[1]) + (p[4] + p[5]);
                        a1 += (p[2] + p[3]) + (p[6] + p[7]);
                        stsm4((pb + loff) ^ (kk << 5), pack2(p[0], p[1]), pack2(p[2], p[3]), pack2(p[4], p[5]), pack2(p[6], p[7]));
                    }
                };
                expo();
                if (__any_sync(0xffffffffu, !(a0 <= LAZY) || !(a1 <= LAZY))) {
                    float x0 = m0, x1 = m1;
#pragma unroll
                    for (int n = 0; n < 8; n++) { x0 = fmaxf(x0, fmaxf(S[4 * n], S[4 * n + 1])); x1 = fmaxf(x1, fmaxf(S[4 * n + 2], S[4 * n + 3])); }
                    x0 = fmaxf(x0, __shfl_xor_sync(0xffffffffu, x0, 1));
                    x1 = fmaxf(x1, __shfl_xor_sync(0xffffffffu, x1, 1));
                    x0 = fmaxf(x0, __shfl_xor_sync(0xffffffffu, x0, 2));
                    x1 = fmaxf(x1, __shfl_xor_sync(0xffffffffu, x1, 2));
                    sc0 = ex2((m0 - x0) * CS); sc1 = ex2((m1 - x1) * CS);
                    m0 = x0; m1 = x1;
                    expo();
                }
                if (q0) { sts_f32(sb + SCL + s * 256 + r0 * 4, sc0); sts_f32(sb + SCL + s * 256 + r0 * 4 + 32, sc1); }
                __syncwarp();
                if (l0w) mbar_arrive(sb + B_P + s * 8);
                l0 = fmaf(l0, sc0, a0); l1 = fmaf(l1, sc1, a1);
                PL(j, 2);
                if (j == NKV - 1) break;
                if (!kv) mbar_wait(sb + B_KV + sn * 8, ph);
            } else {
                mbar_wait(sb + B_KV + 8, 0);
            }
            float Sn[32];
            const uint32_t kd = sd + sn * 4096;
            wg_fence();
#pragma unroll
            for (int kk = 0; kk < 28; kk++) {
                wgmma_rs_n64_tb0(Sn, q[4 * kk], q[4 * kk + 1], q[4 * kk + 2], q[4 * kk + 3], dsc(kd, (kk >> 2) * 8192 + (kk & 3) * 32, 16), kk > 0);
                if (kk == FENCE_AT) { fence_async(); __syncwarp(); }
                if (kk == GO_AT) { PL(j, 3); if (j >= 0 && l0w) mbar_arrive(sb + B_GO + s * 8); }
            }
#pragma unroll
            for (int kk = 0; kk < 4; kk++)
                wgmma_ss_n64_tb0(Sn, dsc(sd, QS + kk * 32, 16), dsc(kd, 7 * 8192 + kk * 32, 16), 1);
            wg_commit();
            PL(j, 0);
            wg_wait<0>();
            pin(Sn);
#pragma unroll
            for (int i = 0; i < 32; i++) S[i] = Sn[i];
            s = sn;
            if (++sn == 3) sn = 0;
            if (sn == 1) ph ^= 1;
        }
        l0 += __shfl_xor_sync(0xffffffffu, l0, 1); l1 += __shfl_xor_sync(0xffffffffu, l1, 1);
        l0 += __shfl_xor_sync(0xffffffffu, l0, 2); l1 += __shfl_xor_sync(0xffffffffu, l1, 2);
        if (q0) { sts_f32(sb + LINV + r0 * 4, rcp(l0)); sts_f32(sb + LINV + r0 * 4 + 32, rcp(l1)); }
        fence_async();
        __syncwarp();
        if (l0w) {
            mbar_arrive(sb + B_GO + s * 8);
            uint32_t slot8 = 8 * w, par = 0;
#pragma unroll 1
            for (int n = 20 + w; n < 136; n += 4) {
                mbar_wait(sb + B_E2 + slot8, par);
                if (n < 128) ring_ld(sb, slot8, n);
                else {
                    mbar_expect_tx(sb + B_X, 8192);
                    tma4(sb + R1 + slot8 * 1024, &mp.x, 0, 62 * ti, n - 128, b, sb + B_X);
                }
                slot8 += 32;
                if (slot8 >= 160) { slot8 -= 160; par ^= 1; }
            }
        }
        PDUMP();
    } else {
        asm volatile("setmaxnreg.dec.sync.aligned.u32 160;");
        const int h = wg - 1;
        uint32_t v[4][8], v2[4][8];
        if (SU != 0) bar_sync(5, 384);
        PG(206);
#pragma unroll
        for (int i = 0; i < 8; i++) {
            const int t = 62 * ti - 1 + 32 * (i >> 2) + 16 * h + 4 * w + (i & 3);
            const uint4* p = reinterpret_cast<const uint4*>(x + ((size_t)b * T_ + t) * D_) + lane;
            uint32_t* d = i < 4 ? v[i & 3] : v2[i & 3];
#pragma unroll
            for (int c = 0; c < 2; c++)
                asm volatile("{\n.reg .pred p;\nsetp.lt.u32 p, %5, %6;\nmov.b32 %0, 0;\nmov.b32 %1, 0;\nmov.b32 %2, 0;\nmov.b32 %3, 0;\n"
                             "@p ld.global.nc.v4.u32 {%0, %1, %2, %3}, [%4];\n}\n"
                             : "=r"(d[4 * c]), "=r"(d[4 * c + 1]), "=r"(d[4 * c + 2]), "=r"(d[4 * c + 3]) : "l"(p + 32 * c), "r"(t), "n"(T_));
        }
#pragma unroll 1
        for (int bt = 0; bt < 2; bt++) {
            PT(bt ? 13 : 0);
            float a[8];
            const uint32_t la = sb + AT + (lane >> 3) * 8192 + (32 * bt + 16 * h + 4 * w) * 128 + (((lane & 7) ^ ((w & 1) * 4)) << 4);
            const bool b4 = lane & 16, b3 = lane & 8, b2 = lane & 4;
#pragma unroll
            for (int r = 0; r < 4; r++) {
                float c[4] = {0.f, 0.f, 0.f, 0.f};
#pragma unroll
                for (int i = 0; i < 8; i += 2) hmma(c, v[r][i], v[r][i], v[r][i + 1], v[r][i + 1], v[r][i], v[r][i + 1]);
                a[4 + r] = (lane & 3) == (lane >> 3) ? (b2 ? c[1] : c[0]) : 0.f;
                if (r & 1) {
                    float e[4] = {0.f, 0.f, 0.f, 0.f};
#pragma unroll
                    for (int i = 0; i < 8; i += 2) hmma(e, v[r - 1][i], v[r][i], v[r - 1][i + 1], v[r][i + 1], 0x3f803f80u, 0x3f803f80u);
                    a[r - 1] = e[0]; a[r] = e[2];
                }
            }
            float k[4];
#pragma unroll
            for (int i = 0; i < 4; i++) {
                const int lo = (i & 1) + 4 * (i >> 1);
                k[i] = (b4 ? a[lo + 2] : a[lo]) + __shfl_xor_sync(0xffffffffu, b4 ? a[lo] : a[lo + 2], 16);
            }
            const float k0 = (b3 ? k[1] : k[0]) + __shfl_xor_sync(0xffffffffu, b3 ? k[0] : k[1], 8);
            const float k1 = (b3 ? k[3] : k[2]) + __shfl_xor_sync(0xffffffffu, b3 ? k[2] : k[3], 8);
            float z = (b2 ? k1 : k0) + __shfl_xor_sync(0xffffffffu, b2 ? k0 : k1, 4);
            z += __shfl_xor_sync(0xffffffffu, z, 2);
            z += __shfl_xor_sync(0xffffffffu, z, 1);
            const float zo = __shfl_xor_sync(0xffffffffu, z, 4);
            PG(204 + bt);
            const float mu = (b2 ? zo : z) * (0.25f / D_);
            float sd_ = bfr(bfr(fmaxf(fmaf(b2 ? z : zo, 1.f / D_, -mu * mu), 0.f)) + 1e-5f);
            asm("sqrt.approx.f32 %0, %0;" : "+f"(sd_));
            const float ri = rcp(bfr(sd_));
            const uint32_t w1 = pack2(mu, ri), w2 = pack2(ri - bhi(w1), ri - bhi(w1));
#pragma unroll
            for (int r = 0; r < 4; r++) {
                const uint32_t s1 = __shfl_sync(0xffffffffu, w1, 8 * r), rl = __shfl_sync(0xffffffffu, w2, 8 * r);
                const uint32_t m2 = __byte_perm(s1, 0, 0x1010), rh = __byte_perm(s1, 0, 0x3232);
#pragma unroll
                for (int i = 0; i < 8; i++) { const uint32_t d = bsub2(v[r][i], m2); v[r][i] = bfma2(d, rh, bmul2(d, rl)); }
                sts4((la ^ (r << 4)) + r * 128, v[r][0], v[r][1], v[r][2], v[r][3]);
                sts4((la ^ (r << 4)) + r * 128 + 32768, v[r][4], v[r][5], v[r][6], v[r][7]);
#pragma unroll
                for (int i = 0; i < 8; i++) v[r][i] = v2[r][i];
            }
        }
        fence_async();
        if (SU == 0) bar_sync(5, 384); else bar_sync(2, 256);
        if (tid == 128) mbar_arrive(sb + B_LN);
        PG(202);
        if (mode == 1) return;
        float acc[128];
#pragma unroll
        for (int pass = 0; pass < 2; pass++) {
            if (pass == 1) mbar_wait(sb + B_H2, 0);
            PT(1 + 3 * pass);
            fresh(acc);
            uint32_t slot8 = pass ? 8 : 56, par = 0, prev8 = 0;
            auto adv = [&]() { prev8 = slot8; slot8 += 8; if (slot8 == 72) { slot8 = 0; par ^= 1; } };
            auto step = [&](int kk) {
                wg_fence();
                wgmma_ss_n256_tb1(acc, mkd(adA + (kk >> 2) * 512 + (kk & 3) * 2), mkd(bd2k + h * 512 + slot8 * 128), 1);
                wg_commit();
                wg_wait<1>();
            };
#pragma unroll 1
            for (int kk = 0; kk < 24; kk++) {
                mbar_wait(sb + B_R1 + slot8, par);
                step(kk);
                if (kk > 0 && w0 && elect1()) ring_half(sb, prev8, h * 8192, &mp.wup4, 16 * kk + 128, (pass ? 0 : 8) + 4 * h);
                adv();
            }
            if (pass == 0 && w0) mbar_wait(sb + B_MQ, 0);
#pragma unroll 1
            for (int kk = 24; kk < 32; kk++) {
                mbar_wait(sb + B_R1 + slot8, par);
                if (kk == 31 && el) mbar_arrive(sb + (pass ? B_H3 : B_H1));
                step(kk);
                if (w0 && elect1()) ring_half(sb, prev8, h * 8192, pass ? &mp.mqb1 : &mp.mqa2, (pass ? 64 : 32) * (kk - 24), pass ? h : 4 + 2 * h);
                adv();
            }
            wg_wait<0>();
            if (w0 && elect1()) ring_half(sb, prev8, h * 8192, pass ? &mp.mqb1 : &mp.mqa2, pass ? 0 : 256, pass ? 2 + h : 4 + 2 * h);
            pin(acc);
            PT(2 + 3 * pass);
            bf16* ucp = g_uc + ((size_t)blockIdx.x * 128 + (pass ? 0 : 64) + r0) * D_ + 256 * h + 8 * (lane & 3);
#pragma unroll
            for (int m = 0; m < 8; m++) {
                const float* a_ = acc + 16 * m;
                stg4(ucp + 32 * m, pack2(a_[0], a_[1]), pack2(a_[4], a_[5]), pack2(a_[8], a_[9]), pack2(a_[12], a_[13]));
                stg4(ucp + 8 * D_ + 32 * m, pack2(a_[2], a_[3]), pack2(a_[6], a_[7]), pack2(a_[10], a_[11]), pack2(a_[14], a_[15]));
            }
            if (pass) bar_sync(2, 256);
            PT(3 + 3 * pass);
        }
        int s = 1, ph = 0;
        uint32_t* cp = reinterpret_cast<uint32_t*>(g_uc + ((size_t)blockIdx.x * 128 + 64 + 32 * h + 8 * w) * D_) + 4 * lane;
        const uint32_t* dp = reinterpret_cast<const uint32_t*>(dw) + (((tid - 128) & ~15) | ((lane & 3) << 2) | ((lane >> 2) & 3));
        const uint32_t d0 = ldg_v(dp), d1 = ldg_v(dp + D_ / 2), d2 = ldg_v(dp + D_);
        uint32_t e[8];
        fresh(acc);
#pragma unroll 1
        for (int j = 0; j < NKV; j++) {
            if (j < 8) { ldg4_cg(cp, e); ldg4_cg(cp + 128, e + 4); }
            else if (j >= CV0 && j < CV0 + 31) {
                if (j == CV0) {
                    mbar_wait(sb + B_GN, 0);
                    cp = reinterpret_cast<uint32_t*>(g_uc + ((size_t)blockIdx.x * 128 + 1) * D_) + (tid - 128);
                    e[0] = ldg_cg(cp + 63 * (D_ / 2)); e[1] = ldg_cg(cp + 64 * (D_ / 2));
                }
                e[2] = ldg_cg(cp + 65 * (D_ / 2)); e[3] = ldg_cg(cp + 66 * (D_ / 2));
                e[4] = ldg_cg(cp); e[5] = ldg_cg(cp + D_ / 2);
            }
            mbar_wait(sb + B_P + s * 8, ph);
            PL(j, 0);
            if (j > 0) {
                const float sc0 = lds_f32(sb + SCL + s * 256 + r0 * 4), sc1 = lds_f32(sb + SCL + s * 256 + r0 * 4 + 32);
                if (__any_sync(0xffffffffu, sc0 != 1.f || sc1 != 1.f)) {
#pragma unroll
                    for (int n = 0; n < 32; n++) { acc[4 * n] *= sc0; acc[4 * n + 1] *= sc0; acc[4 * n + 2] *= sc1; acc[4 * n + 3] *= sc1; }
                }
            }
            mbar_wait(sb + B_GO + s * 8, ph);
            PL(j, 1);
            const uint32_t vd = sd + s * 4096 + h * 2048, pd = sd + (s == 0 ? 2 : s - 1) * 512;
            pin(acc);
            wg_fence();
#pragma unroll
            for (int kk = 0; kk < 4; kk++) wgmma_ss_n256_tb1(acc, dsc(pd, R3 + kk * 32, 16), dsc(vd, kk * 2048, 8192), 1);
            wg_commit();
            wg_wait<0>();
            pin(acc);
            PL(j, 2);
            if (w0 && elect1()) {
                if (j == NKV - 5 && mode == 0) flag_wait(&g_sync[3], 4);
                if (j == XPF) {
                    const int t0 = 62 * ti + 31 * h, nr = min(31, T_ - t0);
                    if (nr > 0) l2_prefetch(x + ((size_t)b * T_ + t0) * D_, nr * 1024);
                }
                if (atom_inc_s(sb + CNT + 4 * s) & 1) {
                    if (j + 3 < NKV) {
                        mbar_expect_tx(sb + B_KV + s * 8, 65536);
                        tma4(sb + s * 65536, &mp.xa, 0, 64 * (j + 3), 0, b, sb + B_KV + s * 8);
                    } else if (j < NKV - 1) {
                        const int n0 = j == NKV - 3 ? 0 : 8, n1 = n0 + 8;
#pragma unroll 1
                        for (int n = n0; n < n1; n++) ring_ld(sb, n * 8, n);
                    }
                }
            }
            if (j < 8) {
                float sm = 0.f, sq = 0.f;
#pragma unroll
                for (int i = 0; i < 8; i++) {
                    const float lo = gelu2(blo(e[i])), hi = gelu2(bhi(e[i]));
                    sm += lo + hi; sq = fmaf(lo, lo, fmaf(hi, hi, sq));
                    e[i] = pack2(lo, hi);
                }
                float z = ((lane & 1) ? sq : sm) + __shfl_xor_sync(0xffffffffu, (lane & 1) ? sm : sq, 1);
#pragma unroll
                for (int o = 2; o < 32; o <<= 1) z += __shfl_xor_sync(0xffffffffu, z, o);
                const float zo = __shfl_xor_sync(0xffffffffu, z, 1);
                sm = ((lane & 1) ? zo : z) * (1.f / 512.f); sq = ((lane & 1) ? z : zo) * (1.f / 512.f);
                sq = rsqrtf(fmaxf(fmaf(-sm, sm, sq), 0.f) + 4e-5f);
                sm = -sm * sq;
#pragma unroll
                for (int i = 0; i < 8; i++) e[i] = pack2(fmaf(blo(e[i]), sq, sm), fmaf(bhi(e[i]), sq, sm));
                stg4(cp, e[0], e[1], e[2], e[3]);
                stg4(cp + 128, e[4], e[5], e[6], e[7]);
                cp += D_ / 2;
                if (j == 7) { __syncwarp(); if (lane == 0) mbar_arrive(sb + B_GN); }
            } else if (j >= CV0 && j < CV0 + 31) {
                const uint32_t ua = pack2(gelu2(blo(e[4])), gelu2(bhi(e[4]))), ub = pack2(gelu2(blo(e[5])), gelu2(bhi(e[5])));
                asm volatile("st.global.u32 [%0], %1;" ::"l"(cp), "r"(bmul2(ua, bfma2(e[2], d2, bfma2(e[1], d1, bmul2(e[0], d0))))) : "memory");
                asm volatile("st.global.u32 [%0], %1;" ::"l"(cp + D_ / 2), "r"(bmul2(ub, bfma2(e[3], d2, bfma2(e[2], d1, bmul2(e[1], d0))))) : "memory");
                e[0] = e[2]; e[1] = e[3];
                cp += D_;
            }
            if (++s == 3) s = 0;
            if (s == 1) ph ^= 1;
        }
        {
            const float i0 = lds_f32(sb + LINV + r0 * 4), i1 = lds_f32(sb + LINV + r0 * 4 + 32);
#pragma unroll
            for (int p = 0; p < 16; p++)
                stsm4(((sb + R0 + h * 32768 + loff) ^ ((p & 3) << 5)) + (p >> 2) * 8192,
                      pack2(acc[8 * p] * i0, acc[8 * p + 1] * i0), pack2(acc[8 * p + 2] * i1, acc[8 * p + 3] * i1),
                      pack2(acc[8 * p + 4] * i0, acc[8 * p + 5] * i0), pack2(acc[8 * p + 6] * i1, acc[8 * p + 7] * i1));
        }
        fence_async();
        fence_async_g();
        bar_sync(2, 256);
        if (lane == 0 && w < 2) ring_ld(sb, 128 + 16 * w + 8 * h, 16 + 2 * w + h);
        PT(7);
        fresh(acc);
        {
            uint32_t slot8 = 8 * h, par = 0, prev8 = 0;
#pragma unroll 1
            for (int kk = 0; kk < 64; kk++) {
                if (kk == 32 || kk == 48) mbar_wait(sb + B_UC + (kk >> 1 & 8), 0);
                mbar_wait(sb + B_R2 + slot8, par);
                wg_fence();
                wgmma_ss_n256_tb1(acc, mkd(sd + (1u << 16) + (R0 >> 4) + (kk >> 2 & 7) * 512 + (kk & 3) * 2), mkd(bd2k + (R1 >> 4) + slot8 * 64), 1);
                wg_commit();
                wg_wait<1>();
                if (kk > 0 && lane == 0) mbar_arrive(sb + B_E2 + prev8);
                if ((kk == 16 || kk == 32) && w0 && elect1() && (atom_inc_s(sb + CNT + 12 + (kk >> 3 & 4)) & 1)) {
                    mbar_expect_tx(sb + B_UC + (kk >> 2 & 8), 32768);
                    tma3(sb + R0 + (kk & 32) * 1024, &mp.uc, 0, 128 * blockIdx.x, kk >> 3 & 4, sb + B_UC + (kk >> 2 & 8));
                }
                prev8 = slot8;
                slot8 += 16;
                if (slot8 >= 160) { slot8 -= 160; par ^= 1; }
            }
        }
        wg_wait<0>();
        pin(acc);
        PT(8);
        mbar_wait(sb + B_X, 0);
        PT(9);
        {
            const uint32_t sr = (lrow + 63) & 63;
            const uint32_t xoff = sr * 128 + ((((lane >> 4) ^ sr) & 7) << 4);
#pragma unroll
            for (int p = 0; p < 16; p++) {
                const uint32_t a = ((sb + R2 + h * 32768 + xoff) ^ ((p & 3) << 5)) + (p >> 2) * 8192;
                uint32_t xv[4];
                ldsm4(a, xv);
#pragma unroll
                for (int e = 0; e < 4; e++)
                    xv[e] = pack2(acc[8 * p + 2 * e] + __uint_as_float(xv[e] << 16), acc[8 * p + 2 * e + 1] + __uint_as_float(xv[e] & 0xffff0000u));
                stsm4(a, xv[0], xv[1], xv[2], xv[3]);
            }
        }
        fence_async();
        bar_sync(3 + h, 128);
        if (el) {
            for (int c = 0; c < 4; c++) tma4_store(&mp.out, sb + R2 + (4 * h + c) * 8192, 0, 62 * ti, 4 * h + c, b);
            asm volatile("cp.async.bulk.commit_group;" ::: "memory");
            PT(10);
            if (h == 0) cta_done(mode);
            asm volatile("cp.async.bulk.wait_group.read 0;" ::: "memory");
        }
        PT(11);
        PG(201);
        PDUMP();
    }
}

typedef CUresult (*PFN_enc)(CUtensorMap*, CUtensorMapDataType, cuuint32_t, void*, const cuuint64_t*, const cuuint64_t*,
                            const cuuint32_t*, const cuuint32_t*, CUtensorMapInterleave, CUtensorMapSwizzle,
                            CUtensorMapL2promotion, CUtensorMapFloatOOBfill);

static void enc(PFN_enc f, CUtensorMap* m, void* base, int rank, const cuuint64_t* dims, const cuuint64_t* strides, const cuuint32_t* box) {
    cuuint32_t es[5] = {1, 1, 1, 1, 1};
    f(m, CU_TENSOR_MAP_DATA_TYPE_BFLOAT16, rank, base, dims, strides, box, es, CU_TENSOR_MAP_INTERLEAVE_NONE,
      CU_TENSOR_MAP_SWIZZLE_128B, CU_TENSOR_MAP_L2_PROMOTION_L2_256B, CU_TENSOR_MAP_FLOAT_OOB_FILL_NONE);
}
static void enc_act(PFN_enc f, CUtensorMap* m, void* base, int rows, int chunks, int trows = T_, int pitch = T_) {
    cuuint64_t dims[4] = {64, (cuuint64_t)trows, 8, (cuuint64_t)NB_};
    cuuint64_t st[3] = {1024, 128, (cuuint64_t)pitch * 1024};
    cuuint32_t box[4] = {64, (cuuint32_t)rows, (cuuint32_t)chunks, 1};
    enc(f, m, base, 4, dims, st, box);
}
static void enc_w(PFN_enc f, CUtensorMap* m, void* base, int krows, int ncols, int bk, int bc) {
    cuuint64_t dims[3] = {64, (cuuint64_t)krows, (cuuint64_t)(ncols / 64)};
    cuuint64_t st[2] = {(cuuint64_t)ncols * 2, 128};
    cuuint32_t box[3] = {64, (cuuint32_t)bk, (cuuint32_t)bc};
    enc(f, m, base, 3, dims, st, box);
}

extern "C" void kernel_launch(void* const* d_in, const int* in_sizes, int n_in, void* d_out, int out_size) {
    const bf16* x = (const bf16*)d_in[0];
    static PFN_enc fenc = nullptr;
    static void *p_xa, *p_mqk, *p_uc, *p_t1;
    static int fused = 0;
    if (!fenc) {
        void* fn = nullptr;
        cudaDriverEntryPointQueryResult qr;
        cudaGetDriverEntryPoint("cuTensorMapEncodeTiled", &fn, cudaEnableDefault, &qr);
        fenc = (PFN_enc)fn;
        cudaGetSymbolAddress(&p_xa, g_xa);
        cudaGetSymbolAddress(&p_mqk, g_mqk);
        cudaGetSymbolAddress(&p_uc, g_uc);
        cudaGetSymbolAddress(&p_t1, g_t1);
        cudaFuncSetAttribute(main_kernel, cudaFuncAttributeMaxDynamicSharedMemorySize, SMEM_BYTES);
        int dev = 0, sms = 0, occ = 0;
        cudaGetDevice(&dev);
        cudaDeviceGetAttribute(&sms, cudaDevAttrMultiProcessorCount, dev);
        cudaOccupancyMaxActiveBlocksPerMultiprocessor(&occ, main_kernel, 384, SMEM_BYTES);
        fused = sms * occ >= NCTA + 2;
    }
    Maps mp;
    enc_act(fenc, &mp.xa, (char*)p_xa + 1024, 64, 8, T_, T_ + 8);
    enc_act(fenc, &mp.xa2, (char*)p_xa + 1024, 64, 2, T_, T_ + 8);
    enc_act(fenc, &mp.xas, p_xa, 64, 1, T_ + 1, T_ + 8);
    enc_act(fenc, &mp.x, (void*)x, 64, 1);
    enc_act(fenc, &mp.out, d_out, 62, 1);
    enc_w(fenc, &mp.wup4, d_in[5], 512, 1024, 16, 4);
    enc_w(fenc, &mp.wup8, d_in[5], 512, 1024, 16, 8);
    enc_w(fenc, &mp.mqa2, p_mqk, 512, 512, 32, 2);
    enc_w(fenc, &mp.mqa4, p_mqk, 512, 512, 32, 4);
    enc_w(fenc, &mp.mqb1, p_mqk, 512, 512, 64, 1);
    enc_w(fenc, &mp.mqb2, p_mqk, 512, 512, 64, 2);
    enc_w(fenc, &mp.uc, p_uc, NCTA * 128, 512, 64, 4);
    enc_w(fenc, &mp.wq, d_in[1], 512, 512, 64, 8);
    enc_w(fenc, &mp.wk, d_in[2], 512, 512, 32, 8);
    enc_w(fenc, &mp.fa[0], d_in[3], 512, 512, 128, 1);
    enc_w(fenc, &mp.fa[1], d_in[7], 512, 512, 128, 1);
    enc_w(fenc, &mp.fa[2], p_t1, 512, 512, 128, 1);
    enc_w(fenc, &mp.fb[0], d_in[4], 512, 512, 64, 4);
    enc_w(fenc, &mp.fb[1], d_in[8], 1024, 512, 64, 4);
    enc_w(fenc, &mp.fc, p_t1, 512, 512, 64, 4);
    cudaStream_t st = cudaStreamPerThread;
    if (fused) {
        main_kernel<<<NCTA + 2, 384, SMEM_BYTES, st>>>(mp, x, (const bf16*)d_in[6], (const bf16*)d_in[5], 0);
    } else {
        main_kernel<<<NCTA + 2, 384, SMEM_BYTES, st>>>(mp, x, (const bf16*)d_in[6], (const bf16*)d_in[5], 1);
        main_kernel<<<NCTA + 2, 384, SMEM_BYTES, st>>>(mp, x, (const bf16*)d_in[6], (const bf16*)d_in[5], 2);
    }
}
```

```cpp
#include <cuda_runtime.h>
#include <cuda_bf16.h>
#include <cuda.h>
#include <stdint.h>

typedef __nv_bfloat16 bf16;

constexpr int T_ = 4000, D_ = 512, NB_ = 2;
constexpr int TPB = 65;
constexpr int NCTA = TPB * NB_;
constexpr int NKV = 63;

__device__ __align__(1024) bf16 g_xa[NB_ * (T_ + 8) * D_];
__device__ __align__(1024) bf16 g_mqk[D_ * D_];
__device__ __align__(1024) bf16 g_t1[D_ * D_];
__device__ __align__(1024) bf16 g_wepi[2 * D_ * D_];
__device__ __align__(1024) bf16 g_uc[NCTA * 128 * D_];
__device__ unsigned g_sync[8];

#define PT(i) do { if (el) asm volatile("st.shared.u32 [%0], %1;" ::"r"(sb + MISC + 2560), "r"((unsigned)clock())); } while (0)
#define PG(i)
#define PE()
#define PLM 15
#define PL(j, q) do { if ((PLM >> ((q) + (wg ? 4 : 0))) & 1) PT(0); } while (0)
#define PDUMP()

#define FENCE_AT 1
#define GO_AT 25
#define LAZY 256.f
#define SU 2
#define XS_GAP 800
#define XPF 50
#define RG0 "184"
#define CV0 17
#define LAGA 0
#define LAGB 0
#define PFW 1
constexpr uint32_t R0 = 0, R1 = 65536, R2 = 131072, R3 = 196608, QS = 221184, MISC = 229376;
constexpr uint32_t AT = 147456;
constexpr uint32_t SMEM_BYTES = 232448;
constexpr uint32_t B_R1 = MISC + 1856  , B_MK = MISC + 48, B_LN = MISC + 56, B_MQ = MISC + 64, B_GN = MISC + 72,
                   B_H1 = MISC + 88, B_H2 = MISC + 96, B_H3 = MISC + 104,
                   B_KV = MISC + 112, B_P = MISC + 136, B_GO = MISC + 160, B_UC = MISC + 184  ,
                   B_X = MISC + 200, CNT = MISC + 208  , SCL = MISC + 512  ,
                   LINV = MISC + 1280  , STAT = MISC + 2048  ,
                   B_R2 = MISC + 1536  , B_E2 = MISC + 1696  ;

__device__ __forceinline__ uint32_t smem_u32(const void* p) { return (uint32_t)__cvta_generic_to_shared(p); }
__device__ __forceinline__ void wg_fence() { asm volatile("wgmma.fence.sync.aligned;" ::: "memory"); }
__device__ __forceinline__ void wg_commit() { asm volatile("wgmma.commit_group.sync.aligned;" ::: "memory"); }
template <int N> __device__ __forceinline__ void wg_wait() { asm volatile("wgmma.wait_group.sync.aligned %0;" ::"n"(N) : "memory"); }
__device__ __forceinline__ uint64_t dsc(uint32_t sd, uint32_t off, uint32_t lbo) {
    uint32_t lo = sd + (off >> 4) + ((lbo >> 4) << 16);
    uint64_t d;
    asm("mov.b64 %0, {%1, %2};" : "=l"(d) : "r"(lo), "r"((1024u >> 4) | (1u << 30)));
    return d;
}
__device__ __forceinline__ bool elect1() {
    uint32_t p;
    asm volatile("{\n.reg .pred p;\nelect.sync _|p, 0xffffffff;\nselp.u32 %0, 1, 0, p;\n}\n" : "=r"(p));
    return p != 0;
}
__device__ __forceinline__ void mbar_init(uint32_t bar, int cnt) { asm volatile("mbarrier.init.shared::cta.b64 [%0], %1;" ::"r"(bar), "r"(cnt) : "memory"); }
__device__ __forceinline__ void mbar_expect_tx(uint32_t bar, uint32_t bytes) { asm volatile("mbarrier.arrive.expect_tx.shared::cta.b64 _, [%0], %1;" ::"r"(bar), "r"(bytes) : "memory"); }
__device__ __forceinline__ void mbar_arrive(uint32_t bar) { asm volatile("mbarrier.arrive.shared::cta.b64 _, [%0];" ::"r"(bar) : "memory"); }
__device__ __forceinline__ void mbar_wait(uint32_t bar, uint32_t parity) {
    uint32_t ok;
#pragma unroll 1
    for (uint32_t it = 0;; ++it) {
        asm volatile("{\n.reg .pred p;\nmbarrier.try_wait.parity.shared::cta.b64 p, [%1], %2;\nselp.u32 %0, 1, 0, p;\n}\n" : "=r"(ok) : "r"(bar), "r"(parity) : "memory");
        if (ok) break;
        if (it > (1u << 20)) __trap();
    }
}
__device__ __forceinline__ bool mbar_test(uint32_t bar, uint32_t parity) {
    uint32_t ok;
    asm volatile("{\n.reg .pred p;\nmbarrier.test_wait.parity.shared::cta.b64 p, [%1], %2;\nselp.u32 %0, 1, 0, p;\n}\n" : "=r"(ok) : "r"(bar), "r"(parity) : "memory");
    return ok != 0;
}
__device__ __forceinline__ void fence_async() { asm volatile("fence.proxy.async.shared::cta;" ::: "memory"); }
__device__ __forceinline__ void fence_async_g() { asm volatile("fence.proxy.async.global;" ::: "memory"); }
__device__ __forceinline__ void bar_sync(int id, int n) { asm volatile("bar.sync %0, %1;" ::"r"(id), "r"(n) : "memory"); }
__device__ __forceinline__ void tma3(uint32_t dst, const CUtensorMap* tm, int c0, int c1, int c2, uint32_t bar) {
    asm volatile("cp.async.bulk.tensor.3d.shared::cluster.global.mbarrier::complete_tx::bytes [%0], [%1, {%3, %4, %5}], [%2];"
                 ::"r"(dst), "l"(tm), "r"(bar), "r"(c0), "r"(c1), "r"(c2) : "memory");
}
__device__ __forceinline__ void tma4(uint32_t dst, const CUtensorMap* tm, int c0, int c1, int c2, int c3, uint32_t bar) {
    asm volatile("cp.async.bulk.tensor.4d.shared::cluster.global.mbarrier::complete_tx::bytes [%0], [%1, {%3, %4, %5, %6}], [%2];"
                 ::"r"(dst), "l"(tm), "r"(bar), "r"(c0), "r"(c1), "r"(c2), "r"(c3) : "memory");
}
__device__ __forceinline__ void tma4_store(const CUtensorMap* tm, uint32_t src, int c0, int c1, int c2, int c3) {
    asm volatile("cp.async.bulk.tensor.4d.global.shared::cta.bulk_group [%0, {%2, %3, %4, %5}], [%1];"
                 ::"l"(tm), "r"(src), "r"(c0), "r"(c1), "r"(c2), "r"(c3) : "memory");
}
__device__ __forceinline__ void tma3_store(const CUtensorMap* tm, uint32_t src, int c0, int c1, int c2) {
    asm volatile("cp.async.bulk.tensor.3d.global.shared::cta.bulk_group [%0, {%2, %3, %4}], [%1];"
                 ::"l"(tm), "r"(src), "r"(c0), "r"(c1), "r"(c2) : "memory");
}
__device__ __forceinline__ void stsm4(uint32_t addr, uint32_t a, uint32_t b, uint32_t c, uint32_t d) {
    asm volatile("stmatrix.sync.aligned.m8n8.x4.shared.b16 [%0], {%1, %2, %3, %4};" ::"r"(addr), "r"(a), "r"(b), "r"(c), "r"(d) : "memory");
}
__device__ __forceinline__ void ldsm4(uint32_t addr, uint32_t (&r)[4]) {
    asm volatile("ldmatrix.sync.aligned.m8n8.x4.shared.b16 {%0, %1, %2, %3}, [%4];" : "=r"(r[0]), "=r"(r[1]), "=r"(r[2]), "=r"(r[3]) : "r"(addr) : "memory");
}
__device__ __forceinline__ void ldsm2(uint32_t addr, uint32_t (&r)[2]) {
    asm volatile("ldmatrix.sync.aligned.m8n8.x2.shared.b16 {%0, %1}, [%2];" : "=r"(r[0]), "=r"(r[1]) : "r"(addr) : "memory");
}
__device__ __forceinline__ void stg4(void* p, uint32_t a, uint32_t b, uint32_t c, uint32_t d) {
    asm volatile("st.global.v4.u32 [%0], {%1, %2, %3, %4};" ::"l"(p), "r"(a), "r"(b), "r"(c), "r"(d) : "memory");
}
__device__ __forceinline__ void hmma(float (&c)[4], uint32_t a0, uint32_t a1, uint32_t a2, uint32_t a3, uint32_t b0, uint32_t b1) {
    asm("mma.sync.aligned.m16n8k16.row.col.f32.bf16.bf16.f32 {%0, %1, %2, %3}, {%4, %5, %6, %7}, {%8, %9}, {%0, %1, %2, %3};"
        : "+f"(c[0]), "+f"(c[1]), "+f"(c[2]), "+f"(c[3]) : "r"(a0), "r"(a1), "r"(a2), "r"(a3), "r"(b0), "r"(b1));
}
__device__ __forceinline__ uint32_t pack2(float lo, float hi) {
    uint32_t r;
    asm("cvt.rn.bf16x2.f32 %0, %1, %2;" : "=r"(r) : "f"(hi), "f"(lo));
    return r;
}
__device__ __forceinline__ uint32_t pack2v(float lo, float hi) {
    uint32_t r;
    asm volatile("cvt.rn.bf16x2.f32 %0, %1, %2;" : "=r"(r) : "f"(hi), "f"(lo));
    return r;
}
__device__ __forceinline__ uint32_t bmul2(uint32_t a, uint32_t b) { uint32_t r; asm("mul.rn.bf16x2 %0, %1, %2;" : "=r"(r) : "r"(a), "r"(b)); return r; }
__device__ __forceinline__ uint32_t bfma2(uint32_t a, uint32_t b, uint32_t c) { uint32_t r; asm("fma.rn.bf16x2 %0, %1, %2, %3;" : "=r"(r) : "r"(a), "r"(b), "r"(c)); return r; }
__device__ __forceinline__ float ex2(float x) { float r; asm("ex2.approx.ftz.f32 %0, %1;" : "=f"(r) : "f"(x)); return r; }
__device__ __forceinline__ float rcp(float x) { float r; asm("rcp.approx.ftz.f32 %0, %1;" : "=f"(r) : "f"(x)); return r; }
__device__ __forceinline__ float gelu2(float x) {
    float t = fmaf(x * x, 0.044715f * 0.7978845608028654f, 0.7978845608028654f), th;
    asm("tanh.approx.f32 %0, %1;" : "=f"(th) : "f"(x * t));
    return fmaf(x, th, x);
}
__device__ __forceinline__ uint32_t ldg_v(const uint32_t* p) { uint32_t v; asm volatile("ld.global.nc.u32 %0, [%1];" : "=r"(v) : "l"(p)); return v; }
__device__ __forceinline__ uint32_t ldg_cg(const uint32_t* p) { uint32_t v; asm volatile("ld.global.cg.u32 %0, [%1];" : "=r"(v) : "l"(p) : "memory"); return v; }
__device__ __forceinline__ void ldg4_cg(const uint32_t* p, uint32_t* r) {
    asm volatile("ld.global.cg.v4.u32 {%0, %1, %2, %3}, [%4];" : "=r"(r[0]), "=r"(r[1]), "=r"(r[2]), "=r"(r[3]) : "l"(p) : "memory");
}
__device__ __forceinline__ float lds_f32(uint32_t a) { float v; asm volatile("ld.shared.f32 %0, [%1];" : "=f"(v) : "r"(a) : "memory"); return v; }
__device__ __forceinline__ void sts_f32(uint32_t a, float v) { asm volatile("st.shared.f32 [%0], %1;" ::"r"(a), "f"(v) : "memory"); }
__device__ __forceinline__ uint32_t atom_inc_s(uint32_t a) { uint32_t v; asm volatile("atom.relaxed.cta.shared.add.u32 %0, [%1], 1;" : "=r"(v) : "r"(a) : "memory"); return v; }
__device__ __forceinline__ void lds4(uint32_t a, uint32_t* r) {
    asm volatile("ld.shared.v4.u32 {%0, %1, %2, %3}, [%4];" : "=r"(r[0]), "=r"(r[1]), "=r"(r[2]), "=r"(r[3]) : "r"(a) : "memory");
}
__device__ __forceinline__ void sts4(uint32_t a, uint32_t x, uint32_t y, uint32_t z, uint32_t t) {
    asm volatile("st.shared.v4.u32 [%0], {%1, %2, %3, %4};" ::"r"(a), "r"(x), "r"(y), "r"(z), "r"(t) : "memory");
}
__device__ __forceinline__ uint32_t bsub2(uint32_t a, uint32_t b) { uint32_t r; asm("sub.rn.bf16x2 %0, %1, %2;" : "=r"(r) : "r"(a), "r"(b)); return r; }
__device__ __forceinline__ float blo(uint32_t v) { return __uint_as_float(v << 16); }
__device__ __forceinline__ float bhi(uint32_t v) { return __uint_as_float(v & 0xffff0000u); }
__device__ __forceinline__ float bfr(float x) { return __bfloat162float(__float2bfloat16_rn(x)); }
__device__ __forceinline__ void l2_prefetch(const void* p, uint32_t bytes) { asm volatile("cp.async.bulk.prefetch.L2.global [%0], %1;" ::"l"(p), "r"(bytes) : "memory"); }
__device__ __forceinline__ void flag_add(unsigned* p) { asm volatile("red.release.gpu.global.add.u32 [%0], 1;" ::"l"(p) : "memory"); }
__device__ __forceinline__ void flag_wait(const unsigned* p, unsigned target) {
#pragma unroll 1
    for (uint32_t it = 0;; ++it) {
        unsigned v;
        asm volatile("ld.acquire.gpu.global.u32 %0, [%1];" : "=r"(v) : "l"(p) : "memory");
        if (v >= target) break;
        if (it > (1u << 20)) __trap();
    }
    fence_async_g();
}
template <int N> __device__ __forceinline__ void pin(float (&a)[N]) {
#pragma unroll
    for (int i = 0; i < N; i++) asm volatile("" : "+f"(a[i])::"memory");
}

template <int N> __device__ __forceinline__ void fresh(float (&a)[N]) {
#pragma unroll
    for (int i = 0; i < N; i++) a[i] = 0.f;
    pin(a);
}

__device__ __forceinline__ void wgmma_rs_n64_tb0(float (&d)[32], uint32_t a0, uint32_t a1, uint32_t a2, uint32_t a3, uint64_t db, int scale_d) {
    asm volatile("{\n.reg .pred p;\nsetp.ne.b32 p, %37, 0;\n"
        "wgmma.mma_async.sync.aligned.m64n64k16.f32.bf16.bf16 {%0, %1, %2, %3, %4, %5, %6, %7, %8, %9, %10, %11, %12, %13, %14, %15, %16, %17, %18, %19, %20, %21, %22, %23, %24, %25, %26, %27, %28, %29, %30, %31}, {%32, %33, %34, %35}, %36, p, 1, 1, 0;\n}\n"
        : "+f"(d[0]), "+f"(d[1]), "+f"(d[2]), "+f"(d[3]), "+f"(d[4]), "+f"(d[5]), "+f"(d[6]), "+f"(d[7]), "+f"(d[8]), "+f"(d[9]), "+f"(d[10]), "+f"(d[11]), "+f"(d[12]), "+f"(d[13]), "+f"(d[14]), "+f"(d[15]), "+f"(d[16]), "+f"(d[17]), "+f"(d[18]), "+f"(d[19]), "+f"(d[20]), "+f"(d[21]), "+f"(d[22]), "+f"(d[23]), "+f"(d[24]), "+f"(d[25]), "+f"(d[26]), "+f"(d[27]), "+f"(d[28]), "+f"(d[29]), "+f"(d[30]), "+f"(d[31])
        : "r"(a0), "r"(a1), "r"(a2), "r"(a3), "l"(db), "r"(scale_d));
}

__device__ __forceinline__ void wgmma_ss_n128_tb1(float (&d)[64], uint64_t da, uint64_t db, int scale_d) {
    asm volatile("{\n.reg .pred p;\nsetp.ne.b32 p, %66, 0;\n"
        "wgmma.mma_async.sync.aligned.m64n128k16.f32.bf16.bf16 {%0, %1, %2, %3, %4, %5, %6, %7, %8, %9, %10, %11, %12, %13, %14, %15, %16, %17, %18, %19, %20, %21, %22, %23, %24, %25, %26, %27, %28, %29, %30, %31, %32, %33, %34, %35, %36, %37, %38, %39, %40, %41, %42, %43, %44, %45, %46, %47, %48, %49, %50, %51, %52, %53, %54, %55, %56, %57, %58, %59, %60, %61, %62, %63}, %64, %65, p, 1, 1, 0, 1;\n}\n"
        : "+f"(d[0]), "+f"(d[1]), "+f"(d[2]), "+f"(d[3]), "+f"(d[4]), "+f"(d[5]), "+f"(d[6]), "+f"(d[7]), "+f"(d[8]), "+f"(d[9]), "+f"(d[10]), "+f"(d[11]), "+f"(d[12]), "+f"(d[13]), "+f"(d[14]), "+f"(d[15]), "+f"(d[16]), "+f"(d[17]), "+f"(d[18]), "+f"(d[19]), "+f"(d[20]), "+f"(d[21]), "+f"(d[22]), "+f"(d[23]), "+f"(d[24]), "+f"(d[25]), "+f"(d[26]), "+f"(d[27]), "+f"(d[28]), "+f"(d[29]), "+f"(d[30]), "+f"(d[31]), "+f"(d[32]), "+f"(d[33]), "+f"(d[34]), "+f"(d[35]), "+f"(d[36]), "+f"(d[37]), "+f"(d[38]), "+f"(d[39]), "+f"(d[40]), "+f"(d[41]), "+f"(d[42]), "+f"(d[43]), "+f"(d[44]), "+f"(d[45]), "+f"(d[46]), "+f"(d[47]), "+f"(d[48]), "+f"(d[49]), "+f"(d[50]), "+f"(d[51]), "+f"(d[52]), "+f"(d[53]), "+f"(d[54]), "+f"(d[55]), "+f"(d[56]), "+f"(d[57]), "+f"(d[58]), "+f"(d[59]), "+f"(d[60]), "+f"(d[61]), "+f"(d[62]), "+f"(d[63])
        : "l"(da), "l"(db), "r"(scale_d));
}

__device__ __forceinline__ void wgmma_ss_n256_tb1(float (&d)[128], uint64_t da, uint64_t db, int scale_d) {
    asm volatile("{\n.reg .pred p;\nsetp.ne.b32 p, %130, 0;\n"
        "wgmma.mma_async.sync.aligned.m64n256k16.f32.bf16.bf16 {%0, %1, %2, %3, %4, %5, %6, %7, %8, %9, %10, %11, %12, %13, %14, %15, %16, %17, %18, %19, %20, %21, %22, %23, %24, %25, %26, %27, %28, %29, %30, %31, %32, %33, %34, %35, %36, %37, %38, %39, %40, %41, %42, %43, %44, %45, %46, %47, %48, %49, %50, %51, %52, %53, %54, %55, %56, %57, %58, %59, %60, %61, %62, %63, %64, %65, %66, %67, %68, %69, %70, %71, %72, %73, %74, %75, %76, %77, %78, %79, %80, %81, %82, %83, %84, %85, %86, %87, %88, %89, %90, %91, %92, %93, %94, %95, %96, %97, %98, %99, %100, %101, %102, %103, %104, %105, %106, %107, %108, %109, %110, %111, %112, %113, %114, %115, %116, %117, %118, %119, %120, %121, %122, %123, %124, %125, %126, %127}, %128, %129, p, 1, 1, 0, 1;\n}\n"
        : "+f"(d[0]), "+f"(d[1]), "+f"(d[2]), "+f"(d[3]), "+f"(d[4]), "+f"(d[5]), "+f"(d[6]), "+f"(d[7]), "+f"(d[8]), "+f"(d[9]), "+f"(d[10]), "+f"(d[11]), "+f"(d[12]), "+f"(d[13]), "+f"(d[14]), "+f"(d[15]), "+f"(d[16]), "+f"(d[17]), "+f"(d[18]), "+f"(d[19]), "+f"(d[20]), "+f"(d[21]), "+f"(d[22]), "+f"(d[23]), "+f"(d[24]), "+f"(d[25]), "+f"(d[26]), "+f"(d[27]), "+f"(d[28]), "+f"(d[29]), "+f"(d[30]), "+f"(d[31]), "+f"(d[32]), "+f"(d[33]), "+f"(d[34]), "+f"(d[35]), "+f"(d[36]), "+f"(d[37]), "+f"(d[38]), "+f"(d[39]), "+f"(d[40]), "+f"(d[41]), "+f"(d[42]), "+f"(d[43]), "+f"(d[44]), "+f"(d[45]), "+f"(d[46]), "+f"(d[47]), "+f"(d[48]), "+f"(d[49]), "+f"(d[50]), "+f"(d[51]), "+f"(d[52]), "+f"(d[53]), "+f"(d[54]), "+f"(d[55]), "+f"(d[56]), "+f"(d[57]), "+f"(d[58]), "+f"(d[59]), "+f"(d[60]), "+f"(d[61]), "+f"(d[62]), "+f"(d[63]), "+f"(d[64]), "+f"(d[65]), "+f"(d[66]), "+f"(d[67]), "+f"(d[68]), "+f"(d[69]), "+f"(d[70]), "+f"(d[71]), "+f"(d[72]), "+f"(d[73]), "+f"(d[74]), "+f"(d[75]), "+f"(d[76]), "+f"(d[77]), "+f"(d[78]), "+f"(d[79]), "+f"(d[80]), "+f"(d[81]), "+f"(d[82]), "+f"(d[83]), "+f"(d[84]), "+f"(d[85]), "+f"(d[86]), "+f"(d[87]), "+f"(d[88]), "+f"(d[89]), "+f"(d[90]), "+f"(d[91]), "+f"(d[92]), "+f"(d[93]), "+f"(d[94]), "+f"(d[95]), "+f"(d[96]), "+f"(d[97]), "+f"(d[98]), "+f"(d[99]), "+f"(d[100]), "+f"(d[101]), "+f"(d[102]), "+f"(d[103]), "+f"(d[104]), "+f"(d[105]), "+f"(d[106]), "+f"(d[107]), "+f"(d[108]), "+f"(d[109]), "+f"(d[110]), "+f"(d[111]), "+f"(d[112]), "+f"(d[113]), "+f"(d[114]), "+f"(d[115]), "+f"(d[116]), "+f"(d[117]), "+f"(d[118]), "+f"(d[119]), "+f"(d[120]), "+f"(d[121]), "+f"(d[122]), "+f"(d[123]), "+f"(d[124]), "+f"(d[125]), "+f"(d[126]), "+f"(d[127])
        : "l"(da), "l"(db), "r"(scale_d));
}

__device__ __forceinline__ void wgmma_ss_n32_tb0(float (&d)[16], uint64_t da, uint64_t db, int scale_d) {
    asm volatile("{\n.reg .pred p;\nsetp.ne.b32 p, %18, 0;\n"
        "wgmma.mma_async.sync.aligned.m64n32k16.f32.bf16.bf16 {%0, %1, %2, %3, %4, %5, %6, %7, %8, %9, %10, %11, %12, %13, %14, %15}, %16, %17, p, 1, 1, 0, 0;\n}\n"
        : "+f"(d[0]), "+f"(d[1]), "+f"(d[2]), "+f"(d[3]), "+f"(d[4]), "+f"(d[5]), "+f"(d[6]), "+f"(d[7]), "+f"(d[8]), "+f"(d[9]), "+f"(d[10]), "+f"(d[11]), "+f"(d[12]), "+f"(d[13]), "+f"(d[14]), "+f"(d[15])
        : "l"(da), "l"(db), "r"(scale_d));
}

__device__ __forceinline__ void wgmma_ss_n64_tb0(float (&d)[32], uint64_t da, uint64_t db, int scale_d) {
    asm volatile("{\n.reg .pred p;\nsetp.ne.b32 p, %34, 0;\n"
        "wgmma.mma_async.sync.aligned.m64n64k16.f32.bf16.bf16 {%0, %1, %2, %3, %4, %5, %6, %7, %8, %9, %10, %11, %12, %13, %14, %15, %16, %17, %18, %19, %20, %21, %22, %23, %24, %25, %26, %27, %28, %29, %30, %31}, %32, %33, p, 1, 1, 0, 0;\n}\n"
        : "+f"(d[0]), "+f"(d[1]), "+f"(d[2]), "+f"(d[3]), "+f"(d[4]), "+f"(d[5]), "+f"(d[6]), "+f"(d[7]), "+f"(d[8]), "+f"(d[9]), "+f"(d[10]), "+f"(d[11]), "+f"(d[12]), "+f"(d[13]), "+f"(d[14]), "+f"(d[15]), "+f"(d[16]), "+f"(d[17]), "+f"(d[18]), "+f"(d[19]), "+f"(d[20]), "+f"(d[21]), "+f"(d[22]), "+f"(d[23]), "+f"(d[24]), "+f"(d[25]), "+f"(d[26]), "+f"(d[27]), "+f"(d[28]), "+f"(d[29]), "+f"(d[30]), "+f"(d[31])
        : "l"(da), "l"(db), "r"(scale_d));
}

struct Maps {
    CUtensorMap xa, xa2, xa4, xas, wup4, wup8, mqa2, mqa4, mqb1, mqb2, uc, x, out, wq, wk, fa[3], fb[2], fc;
};

__device__ __forceinline__ uint64_t mkd(uint32_t lo) {
    uint64_t d;
    asm("mov.b64 %0, {%1, %2};" : "=l"(d) : "r"(lo), "r"((1024u >> 4) | (1u << 30)));
    return d;
}
__device__ __forceinline__ void bulk_ld(uint32_t dst, const void* src, uint32_t bytes, uint32_t bar) {
    asm volatile("cp.async.bulk.shared::cluster.global.mbarrier::complete_tx::bytes [%0], [%1], %2, [%3];" ::"r"(dst), "l"(src), "r"(bytes), "r"(bar) : "memory");
}
__device__ __forceinline__ void bulk_st(void* dst, uint32_t src, uint32_t bytes) {
    asm volatile("cp.async.bulk.global.shared::cta.bulk_group [%0], [%1], %2;" ::"l"(dst), "r"(src), "r"(bytes) : "memory");
}
__device__ __forceinline__ void ring_ld(uint32_t sb, uint32_t slot8, int n) {
    mbar_expect_tx(sb + B_R2 + slot8, 8192);
    bulk_ld(sb + R1 + slot8 * 1024, (const char*)g_wepi + n * 8192, 8192, sb + B_R2 + slot8);
}

__device__ __forceinline__ void ring_half(uint32_t sb, uint32_t slot8, uint32_t hoff, const CUtensorMap* tm, int c1, int c2) {
    mbar_expect_tx(sb + B_R1 + slot8, 8192);
    tma3(sb + slot8 * 2048 + hoff, tm, 0, c1, c2, sb + B_R1 + slot8);
}
__device__ __forceinline__ void ring_full(uint32_t sb, uint32_t slot8, const CUtensorMap* tm, int c1, int c2) {
    mbar_expect_tx(sb + B_R1 + slot8, 16384);
    mbar_arrive(sb + B_R1 + slot8);
    tma3(sb + slot8 * 2048, tm, 0, c1, c2, sb + B_R1 + slot8);
}
__device__ __forceinline__ void cta_done(int mode) {
    if (mode == 0 && atomicAdd(&g_sync[4], 1) == NCTA + 1) {
#pragma unroll
        for (int i = 0; i < 5; i++) g_sync[i] = 0;
    }
}

__device__ __forceinline__ void fold_cta(const Maps& mp, uint32_t sb, int mode) {
    constexpr uint32_t F_FULL = MISC, F_EMPTY = MISC + 32, F_T1 = MISC + 64, STG = 49152, FOUT = 3 * STG;
    const int tid = threadIdx.x, f = blockIdx.x - NCTA;
    if (mode == 2) return;
    if (tid == 0) {
        for (int i = 0; i < 3; i++) { mbar_init(sb + F_FULL + 8 * i, 1); mbar_init(sb + F_EMPTY + 8 * i, 2); }
        mbar_init(sb + F_T1, 2);
        asm volatile("fence.mbarrier_init.release.cluster;" ::: "memory");
        fence_async();
    }
    __syncthreads();
    const int wg = __shfl_sync(0xffffffffu, tid >> 7, 0);
    int st = 0, ph = 0;
    if (wg == 0) {
        if (tid == 0) {
#pragma unroll 1
            for (int it = 0; it < 96; it++) {
                const int p = it >> 3, kc = it & 7, job = p >> 2;
                if (it == 64) mbar_wait(sb + F_T1, 0);
                mbar_wait(sb + F_EMPTY + 8 * st, ph ^ 1);
                mbar_expect_tx(sb + F_FULL + 8 * st, STG);
                tma3(sb + st * STG, &mp.fa[job], 0, 256 * f + 128 * ((p >> 1) & 1), kc, sb + F_FULL + 8 * st);
                tma3(sb + st * STG + 16384, &mp.fb[job != 0], 0, 64 * kc + (job == 1 ? 512 : 0), 4 * (p & 1), sb + F_FULL + 8 * st);
                if (++st == 3) { st = 0; ph ^= 1; }
            }
        }
        return;
    }
    const int h = wg - 1, lane = tid & 31, w = (tid >> 5) & 3;
    const uint32_t sd = (sb & 0x3FFFF) >> 4;
    const bool el = (tid & 127) == 0;
#pragma unroll 1
    for (int p = 0; p < 12; p++) {
        float acc[128];
        fresh(acc);
#pragma unroll 1
        for (int kc = 0; kc < 8; kc++) {
            mbar_wait(sb + F_FULL + 8 * st, ph);
            wg_fence();
#pragma unroll
            for (int kk = 0; kk < 4; kk++)
                wgmma_ss_n256_tb1(acc, dsc(sd, st * STG + h * 8192 + kk * 32, 16), dsc(sd, st * STG + 16384 + kk * 2048, 8192), 1);
            wg_commit();
            wg_wait<0>();
            if (el) mbar_arrive(sb + F_EMPTY + 8 * st);
            if (++st == 3) { st = 0; ph ^= 1; }
        }
        pin(acc);
        const int job = p >> 2;
        if (el) {
            asm volatile("cp.async.bulk.wait_group 0;" ::: "memory");
            if (p == 4) { fence_async_g(); mbar_arrive(sb + F_T1); }
        }
        bar_sync(3 + h, 128);
        uint32_t r = 16 * w + (lane & 7) + ((lane >> 3) & 1) * 8;
        const float fs = job == 1 ? 0.5f : 1.f;
        if (job == 1) r = (r & ~31) | (((r >> 1) & 3) << 3) | (((r >> 3) & 3) << 1) | (r & 1);
        const uint32_t oa = sb + FOUT + h * 32768 + r * 128 + ((((lane >> 4) ^ r) & 7) << 4);
#pragma unroll
        for (int i = 0; i < 16; i++)
            stsm4((oa ^ ((i & 3) << 5)) + (i >> 2) * 8192, pack2(acc[8 * i] * fs, acc[8 * i + 1] * fs), pack2(acc[8 * i + 2] * fs, acc[8 * i + 3] * fs),
                  pack2(acc[8 * i + 4] * fs, acc[8 * i + 5] * fs), pack2(acc[8 * i + 6] * fs, acc[8 * i + 7] * fs));
        fence_async();
        bar_sync(3 + h, 128);
        if (el) {
            const int row0 = 256 * f + 128 * ((p >> 1) & 1) + 64 * h + (job == 1 ? 512 : 0);
            if (job == 0) tma3_store(&mp.fc, sb + FOUT + h * 32768, 0, row0, 4 * (p & 1));
            else {
#pragma unroll 1
                for (int i = 0; i < 16; i++)
                    bulk_st((char*)g_wepi + (row0 / 8 + 2 * (i & 3) + (p & 1)) * 8192 + (i >> 2) * 2048, sb + FOUT + h * 32768 + i * 2048, 2048);
            }
            asm volatile("cp.async.bulk.commit_group;" ::: "memory");
        }
    }
    if (el) {
        asm volatile("cp.async.bulk.wait_group 0;" ::: "memory");
        fence_async_g();
        if (mode == 0) flag_add(&g_sync[3]);
    }
    bar_sync(2, 256);
    if (tid == 128) cta_done(mode);
}

__global__ void __launch_bounds__(384, 1) main_kernel(const __grid_constant__ Maps mp, const bf16* __restrict__ x, const bf16* __restrict__ dw, const bf16* wup, const int mode) {
    extern __shared__ __align__(1024) uint8_t smem[];
    const uint32_t sb = smem_u32(smem);
    const int tid = threadIdx.x;
    PE();
    if (blockIdx.x >= NCTA) { fold_cta(mp, sb, mode); return; }
    const int b = blockIdx.x / TPB, ti = blockIdx.x % TPB;
    const int piece = blockIdx.x & 127;
    const int wg = __shfl_sync(0xffffffffu, tid >> 7, 0);
    const int lane = tid & 31, w = (tid >> 5) & 3;
    const bool w0 = __shfl_sync(0xffffffffu, w, 0) == 0;
    const uint32_t sd = (sb & 0x3FFFF) >> 4;
    const uint32_t adA = sd + (AT >> 4) + (1u << 16);
    const uint32_t bd0 = sd;
    const uint32_t bd2k = bd0 + ((2048u >> 4) << 16);
    const bool el = (tid & 127) == 0;
    const uint32_t lrow = 16 * w + (lane & 7) + ((lane >> 3) & 1) * 8;
    const uint32_t loff = lrow * 128 + ((((lane >> 4) ^ lrow) & 7) << 4);
    const int r0 = 16 * w + (lane >> 2);

    if (wg == 0) {
        asm volatile("setmaxnreg.inc.sync.aligned.u32 " RG0 ";");
        uint32_t q[112];
        PG(206);
        if (tid == 0) {
            mbar_init(sb + B_MK, 1);
            for (int i = 0; i < 9; i++) mbar_init(sb + B_R1 + 8 * i, 2);
            for (int i = 0; i < 5; i++) asm volatile("st.shared.u32 [%0], 0;" ::"r"(sb + CNT + 4 * i) : "memory");
        } else if (tid == 32) {
            mbar_init(sb + B_LN, 1); mbar_init(sb + B_MQ, 1); mbar_init(sb + B_GN, 8);
            mbar_init(sb + B_H1, 2); mbar_init(sb + B_H2, 1); mbar_init(sb + B_H3, 2);
            for (int i = 0; i < 3; i++) { mbar_init(sb + B_KV + 8 * i, 2); mbar_init(sb + B_P + 8 * i, 4); mbar_init(sb + B_GO + 8 * i, 4); }
            mbar_init(sb + B_UC, 1); mbar_init(sb + B_UC + 8, 1); mbar_init(sb + B_X, 8);
        } else if (tid == 64) {
            for (int i = 0; i < 20; i++) mbar_init(sb + B_R2 + 8 * i, 1);
        } else if (tid == 96) {
            for (int i = 0; i < 20; i++) mbar_init(sb + B_E2 + 8 * i, 4);
        }
        if (lane == 0) {
            asm volatile("fence.mbarrier_init.release.cluster;" ::: "memory");
            fence_async();
        }
        PG(207);
        __syncwarp();
        if (SU != 2) asm volatile("bar.arrive 5, 384;" ::: "memory");
        if (tid == 0) {
            mbar_expect_tx(sb + B_MK, 65536 + 32768);
            tma3(sb + 16384, &mp.wq, 0, 64 * (piece >> 4), 0, sb + B_MK);
            tma3(sb + 81920, &mp.wk, 0, 32 * (piece & 15), 0, sb + B_MK);
            for (int i = 0; i < 14; i++) mbar_arrive(sb + B_R1 + 8 * (i >> 1));
            if (mode != 1) {
                ring_full(sb, 56, &mp.wup8, 0, 8);
                ring_full(sb, 64, &mp.wup8, 16, 8);
                ring_full(sb, 0, &mp.wup8, 32, 8);
            }
        }
        PG(208);
        bar_sync(1, 128);
        if (SU == 2) asm volatile("bar.arrive 5, 384;" ::: "memory");
        PT(0);
        PG(200);
        {
            float mq[16];
            fresh(mq);
            mbar_wait(sb + B_MK, 0);
            PT(1);
            if (tid == 32) l2_prefetch((const char*)wup + piece * 8192, 8192);
            wg_fence();
#pragma unroll 1
            for (int c = 0; c < 8; c++)
#pragma unroll
                for (int kk = 0; kk < 4; kk++)
                    wgmma_ss_n32_tb0(mq, dsc(sd, 16384 + c * 8192 + kk * 32, 16), dsc(sd, 81920 + c * 4096 + kk * 32, 16), 1);
            wg_commit();
            wg_wait<0>();
            if (mode != 1 && w0 && elect1()) {
#pragma unroll 1
                for (int i = 1; i < 7; i++) ring_full(sb, 8 * i, &mp.wup8, 32 + 16 * i, 8);
            }
            pin(mq);
            uint32_t* c = reinterpret_cast<uint32_t*>(g_mqk + (64 * (piece >> 4) + r0) * D_ + 32 * (piece & 15) + 2 * (lane & 3));
#pragma unroll
            for (int n = 0; n < 4; n++) { c[4 * n] = pack2(mq[4 * n], mq[4 * n + 1]); c[4 * n + 4 * D_] = pack2(mq[4 * n + 2], mq[4 * n + 3]); }
            fence_async_g();
            bar_sync(1, 128);
            if (el) {
                if (mode == 0) flag_add(&g_sync[2]);
                if (mode == 0) flag_wait(&g_sync[2], NCTA);
                mbar_arrive(sb + B_MQ);
                PG(203);
                PT(12);
                mbar_wait(sb + B_LN, 0);
#pragma unroll 1
                for (int c = 0; c < 8; c++) {
                    tma4_store(&mp.xas, sb + AT + c * 8192, 0, 62 * ti, c, b);
                    const unsigned t0 = (unsigned)clock();
                    while (c < 7 && (unsigned)clock() - t0 < XS_GAP) __nanosleep(20);
                }
                asm volatile("cp.async.bulk.commit_group;" ::: "memory");
                if (mode == 1) asm volatile("cp.async.bulk.wait_group 0;" ::: "memory");
            }
            PT(13);
            if (mode == 1) return;
        }
        mbar_wait(sb + B_H1, 0);
        PT(2);
        uint32_t slot8 = 24, par = 0, prev8 = 0, prev2 = 0;
        auto adv = [&]() { prev2 = prev8; prev8 = slot8; slot8 += 8; if (slot8 == 72) { slot8 = 0; par ^= 1; } };
        {
            float acc[128];
            fresh(acc);
            auto step = [&](int i) {
                const uint32_t aa = adA + (i >> 1) * 512 + (i & 1) * 4, bb = bd0 + ((4096u >> 4) << 16) + slot8 * 128;
                wg_fence();
                wgmma_ss_n256_tb1(acc, mkd(aa), mkd(bb), 1);
                wgmma_ss_n256_tb1(acc, mkd(aa + 2), mkd(bb + 128), 1);
                wg_commit();
                wg_wait<1 + LAGA>();
            };
#pragma unroll 1
            for (int i = 0; i < 8 + LAGA; i++) {
                mbar_wait(sb + B_R1 + slot8, par);
                step(i);
                if (i > LAGA && w0 && elect1()) ring_full(sb, LAGA ? prev2 : prev8, &mp.mqa4, 32 * (i - LAGA) + 256, 4);
                adv();
            }
#pragma unroll 1
            for (int i = 8 + LAGA; i < 16; i++) {
                mbar_wait(sb + B_R1 + slot8, par);
                if (i == 15 && el) mbar_arrive(sb + B_H2);
                step(i);
                if (w0 && elect1()) ring_full(sb, LAGA ? prev2 : prev8, &mp.wup8, 16 * (i - LAGA) - 128, 0);
                adv();
            }
            if (LAGA) {
                wg_wait<1>();
                if (w0 && elect1()) ring_full(sb, prev2, &mp.wup8, 112, 0);
            }
            wg_wait<0>();
            if (w0 && elect1()) ring_full(sb, prev8, &mp.wup8, 128, 0);
            pin(acc);
            PT(3);
#pragma unroll
            for (int kk = 0; kk < 4; kk++)
                stsm4((sb + QS + loff) ^ (kk << 5), pack2(acc[96 + 8 * kk], acc[97 + 8 * kk]), pack2(acc[98 + 8 * kk], acc[99 + 8 * kk]),
                      pack2(acc[100 + 8 * kk], acc[101 + 8 * kk]), pack2(acc[102 + 8 * kk], acc[103 + 8 * kk]));
            fence_async();
#pragma unroll
            for (int i = 47; i >= 0; i--) q[64 + i] = pack2v(acc[2 * i], acc[2 * i + 1]);
        }
        if (el) {
            asm volatile("cp.async.bulk.wait_group 0;" ::: "memory");
            if (mode == 0) {
                fence_async_g();
                flag_add(&g_sync[b]);
                flag_wait(&g_sync[b], TPB);
            }
        }
        __syncwarp();
        mbar_wait(sb + B_H3, 0);
        PT(4);
        slot8 = 48; par = 1;
#pragma unroll
        for (int half = 0; half < 2; half++) {
            float acc[64];
            fresh(acc);
            auto step = [&](int m) {
                const uint32_t aa = adA + m * 512, bb = bd0 + ((8192u >> 4) << 16) + slot8 * 128;
                mbar_wait(sb + B_R1 + slot8, par);
                wg_fence();
#pragma unroll
                for (int kk = 0; kk < 4; kk++) wgmma_ss_n128_tb1(acc, mkd(aa + 2 * kk), mkd(bb + 128 * kk), 1);
                wg_commit();
                wg_wait<1 + LAGB>();
            };
#pragma unroll 1
            for (int m = 0; m < 8; m++) {
                step(m);
                if (m > LAGB && w0 && elect1()) {
                    if (half == 0) ring_full(sb, LAGB ? prev2 : prev8, &mp.mqb2, 64 * (m - LAGB), 2);
                    else if (m < 4 + LAGB) tma4(sb + (LAGB ? prev2 : prev8) * 2048, &mp.xa2, 0, 0, 2 * (m - LAGB), b, sb + B_KV + 8);
                }
                adv();
            }
            if (LAGB && half == 0) {
                wg_wait<1>();
                if (w0 && elect1()) ring_full(sb, prev2, &mp.mqb2, 448, 2);
            }
            wg_wait<0>();
            if (w0 && elect1()) {
                if (half == 0) {
                    mbar_expect_tx(sb + B_KV + 8, 65536);
                    for (int i = 0; i < 3; i++) mbar_arrive(sb + B_KV + 8 * i);
                    tma4(sb + prev8 * 2048, &mp.xa2, 0, 0, 0, b, sb + B_KV + 8);
                } else {
                    mbar_expect_tx(sb + B_KV + 16, 65536);
                    tma4(sb + R2, &mp.xa, 0, 64, 0, b, sb + B_KV + 16);
                    mbar_expect_tx(sb + B_KV, 65536);
                    tma4(sb + R0, &mp.xa, 0, 128, 0, b, sb + B_KV);
                }
            }
            pin(acc);
#pragma unroll
            for (int i = 31; i >= 0; i--) q[32 * half + i] = pack2v(acc[2 * i], acc[2 * i + 1]);
        }
        bar_sync(1, 128);
        PT(5);

        const float CS = 0.04419417382415922f * 1.4426950408889634f;
        float m0 = -INFINITY, m1 = -INFINITY, l0 = 0.f, l1 = 0.f;
        int s = 0, sn = 1, ph = 0;
        float S[32];
        const bool l0w = lane == 0, q0 = (lane & 3) == 0;
#pragma unroll 1
        for (int j = -1;; j++) {
            if (j >= 0) {
                PL(j, 1);
                if (j == NKV - 1) {
#pragma unroll
                    for (int i = (T_ - 64 * (NKV - 1)) / 2; i < 32; i++) asm volatile("mov.b32 %0, 0xff800000;" : "=f"(S[i]));
                }
                const bool kv = mbar_test(sb + B_KV + sn * 8, ph);
                const uint32_t pb = sb + R3 + (s == 0 ? 2 : s - 1) * 8192;
                float a0, a1, sc0 = 1.f, sc1 = 1.f;
                auto expo = [&]() {
                    const float n0 = -m0 * CS, n1 = -m1 * CS;
                    a0 = 0.f; a1 = 0.f;
#pragma unroll
                    for (int kk = 0; kk < 4; kk++) {
                        float p[8];
#pragma unroll
                        for (int e = 0; e < 8; e++) p[e] = ex2(fmaf(S[8 * kk + e], CS, (e & 2) ? n1 : n0));
                        a0 += (p[0] + p[1]) + (p[4] + p[5]);
                        a1 += (p[2] + p[3]) + (p[6] + p[7]);
                        stsm4((pb + loff) ^ (kk << 5), pack2(p[0], p[1]), pack2(p[2], p[3]), pack2(p[4], p[5]), pack2(p[6], p[7]));
                    }
                };
                expo();
                if (__any_sync(0xffffffffu, !(a0 <= LAZY) || !(a1 <= LAZY))) {
                    float x0 = m0, x1 = m1;
#pragma unroll
                    for (int n = 0; n < 8; n++) { x0 = fmaxf(x0, fmaxf(S[4 * n], S[4 * n + 1])); x1 = fmaxf(x1, fmaxf(S[4 * n + 2], S[4 * n + 3])); }
                    x0 = fmaxf(x0, __shfl_xor_sync(0xffffffffu, x0, 1));
                    x1 = fmaxf(x1, __shfl_xor_sync(0xffffffffu, x1, 1));
                    x0 = fmaxf(x0, __shfl_xor_sync(0xffffffffu, x0, 2));
                    x1 = fmaxf(x1, __shfl_xor_sync(0xffffffffu, x1, 2));
                    sc0 = ex2((m0 - x0) * CS); sc1 = ex2((m1 - x1) * CS);
                    m0 = x0; m1 = x1;
                    expo();
                }
                if (q0) { sts_f32(sb + SCL + s * 256 + r0 * 4, sc0); sts_f32(sb + SCL + s * 256 + r0 * 4 + 32, sc1); }
                __syncwarp();
                if (l0w) mbar_arrive(sb + B_P + s * 8);
                l0 = fmaf(l0, sc0, a0); l1 = fmaf(l1, sc1, a1);
                PL(j, 2);
                if (j == NKV - 1) break;
                if (!kv) mbar_wait(sb + B_KV + sn * 8, ph);
            } else {
                mbar_wait(sb + B_KV + 8, 0);
            }
            float Sn[32];
            const uint32_t kd = sd + sn * 4096;
            wg_fence();
#pragma unroll
            for (int kk = 0; kk < 28; kk++) {
                wgmma_rs_n64_tb0(Sn, q[4 * kk], q[4 * kk + 1], q[4 * kk + 2], q[4 * kk + 3], dsc(kd, (kk >> 2) * 8192 + (kk & 3) * 32, 16), kk > 0);
                if (kk == FENCE_AT) { fence_async(); __syncwarp(); }
                if (kk == GO_AT) { PL(j, 3); if (j >= 0 && l0w) mbar_arrive(sb + B_GO + s * 8); }
            }
#pragma unroll
            for (int kk = 0; kk < 4; kk++)
                wgmma_ss_n64_tb0(Sn, dsc(sd, QS + kk * 32, 16), dsc(kd, 7 * 8192 + kk * 32, 16), 1);
            wg_commit();
            PL(j, 0);
            wg_wait<0>();
            pin(Sn);
#pragma unroll
            for (int i = 0; i < 32; i++) S[i] = Sn[i];
            s = sn;
            if (++sn == 3) sn = 0;
            if (sn == 1) ph ^= 1;
        }
        l0 += __shfl_xor_sync(0xffffffffu, l0, 1); l1 += __shfl_xor_sync(0xffffffffu, l1, 1);
        l0 += __shfl_xor_sync(0xffffffffu, l0, 2); l1 += __shfl_xor_sync(0xffffffffu, l1, 2);
        if (q0) { sts_f32(sb + LINV + r0 * 4, rcp(l0)); sts_f32(sb + LINV + r0 * 4 + 32, rcp(l1)); }
        fence_async();
        __syncwarp();
        if (l0w) {
            mbar_arrive(sb + B_GO + s * 8);
            uint32_t slot8 = 8 * w, par = 0;
#pragma unroll 1
            for (int n = 20 + w; n < 136; n += 4) {
                mbar_wait(sb + B_E2 + slot8, par);
                if (n < 128) ring_ld(sb, slot8, n);
                else {
                    mbar_expect_tx(sb + B_X, 8192);
                    tma4(sb + R1 + slot8 * 1024, &mp.x, 0, 62 * ti, n - 128, b, sb + B_X);
                }
                slot8 += 32;
                if (slot8 >= 160) { slot8 -= 160; par ^= 1; }
            }
        }
        PDUMP();
    } else {
        if (RG0[2] == '4') asm volatile("setmaxnreg.dec.sync.aligned.u32 160;");
        const int h = wg - 1;
        uint32_t v[4][8], v2[4][8];
        if (SU != 0) bar_sync(5, 384);
        PG(206);
#pragma unroll
        for (int i = 0; i < 8; i++) {
            const int t = 62 * ti - 1 + 32 * (i >> 2) + 16 * h + 4 * w + (i & 3);
            const uint4* p = reinterpret_cast<const uint4*>(x + ((size_t)b * T_ + t) * D_) + lane;
            uint32_t* d = i < 4 ? v[i & 3] : v2[i & 3];
#pragma unroll
            for (int c = 0; c < 2; c++)
                asm volatile("{\n.reg .pred p;\nsetp.lt.u32 p, %5, %6;\nmov.b32 %0, 0;\nmov.b32 %1, 0;\nmov.b32 %2, 0;\nmov.b32 %3, 0;\n"
                             "@p ld.global.nc.v4.u32 {%0, %1, %2, %3}, [%4];\n}\n"
                             : "=r"(d[4 * c]), "=r"(d[4 * c + 1]), "=r"(d[4 * c + 2]), "=r"(d[4 * c + 3]) : "l"(p + 32 * c), "r"(t), "n"(T_));
        }
#pragma unroll 1
        for (int bt = 0; bt < 2; bt++) {
            PT(bt ? 13 : 0);
            float a[8];
            const uint32_t la = sb + AT + (lane >> 3) * 8192 + (32 * bt + 16 * h + 4 * w) * 128 + (((lane & 7) ^ ((w & 1) * 4)) << 4);
            const bool b4 = lane & 16, b3 = lane & 8, b2 = lane & 4;
#pragma unroll
            for (int r = 0; r < 4; r++) {
                float c[4] = {0.f, 0.f, 0.f, 0.f};
#pragma unroll
                for (int i = 0; i < 8; i += 2) hmma(c, v[r][i], v[r][i], v[r][i + 1], v[r][i + 1], v[r][i], v[r][i + 1]);
                a[4 + r] = (lane & 3) == (lane >> 3) ? (b2 ? c[1] : c[0]) : 0.f;
                if (r & 1) {
                    float e[4] = {0.f, 0.f, 0.f, 0.f};
#pragma unroll
                    for (int i = 0; i < 8; i += 2) hmma(e, v[r - 1][i], v[r][i], v[r - 1][i + 1], v[r][i + 1], 0x3f803f80u, 0x3f803f80u);
                    a[r - 1] = e[0]; a[r] = e[2];
                }
            }
            float k[4];
#pragma unroll
            for (int i = 0; i < 4; i++) {
                const int lo = (i & 1) + 4 * (i >> 1);
                k[i] = (b4 ? a[lo + 2] : a[lo]) + __shfl_xor_sync(0xffffffffu, b4 ? a[lo] : a[lo + 2], 16);
            }
            const float k0 = (b3 ? k[1] : k[0]) + __shfl_xor_sync(0xffffffffu, b3 ? k[0] : k[1], 8);
            const float k1 = (b3 ? k[3] : k[2]) + __shfl_xor_sync(0xffffffffu, b3 ? k[2] : k[3], 8);
            float z = (b2 ? k1 : k0) + __shfl_xor_sync(0xffffffffu, b2 ? k0 : k1, 4);
            z += __shfl_xor_sync(0xffffffffu, z, 2);
            z += __shfl_xor_sync(0xffffffffu, z, 1);
            const float zo = __shfl_xor_sync(0xffffffffu, z, 4);
            PG(204 + bt);
            const float mu = (b2 ? zo : z) * (0.25f / D_);
            float sd_ = bfr(bfr(fmaxf(fmaf(b2 ? z : zo, 1.f / D_, -mu * mu), 0.f)) + 1e-5f);
            asm("sqrt.approx.f32 %0, %0;" : "+f"(sd_));
            const float ri = rcp(bfr(sd_));
            const uint32_t w1 = pack2(mu, ri), w2 = pack2(ri - bhi(w1), ri - bhi(w1));
#pragma unroll
            for (int r = 0; r < 4; r++) {
                const uint32_t s1 = __shfl_sync(0xffffffffu, w1, 8 * r), rl = __shfl_sync(0xffffffffu, w2, 8 * r);
                const uint32_t m2 = __byte_perm(s1, 0, 0x1010), rh = __byte_perm(s1, 0, 0x3232);
#pragma unroll
                for (int i = 0; i < 8; i++) { const uint32_t d = bsub2(v[r][i], m2); v[r][i] = bfma2(d, rh, bmul2(d, rl)); }
                sts4((la ^ (r << 4)) + r * 128, v[r][0], v[r][1], v[r][2], v[r][3]);
                sts4((la ^ (r << 4)) + r * 128 + 32768, v[r][4], v[r][5], v[r][6], v[r][7]);
#pragma unroll
                for (int i = 0; i < 8; i++) v[r][i] = v2[r][i];
            }
        }
        fence_async();
        if (SU == 0) bar_sync(5, 384); else bar_sync(2, 256);
        if (tid == 128) mbar_arrive(sb + B_LN);
        PG(202);
        if (mode == 1) return;
        float acc[128];
#pragma unroll
        for (int pass = 0; pass < 2; pass++) {
            if (pass == 1) mbar_wait(sb + B_H2, 0);
            PT(1 + 3 * pass);
            fresh(acc);
            uint32_t slot8 = pass ? 8 : 56, par = 0, prev8 = 0;
            auto adv = [&]() { prev8 = slot8; slot8 += 8; if (slot8 == 72) { slot8 = 0; par ^= 1; } };
            auto step = [&](int kk) {
                wg_fence();
                wgmma_ss_n256_tb1(acc, mkd(adA + (kk >> 2) * 512 + (kk & 3) * 2), mkd(bd2k + h * 512 + slot8 * 128), 1);
                wg_commit();
                wg_wait<1>();
            };
#pragma unroll 1
            for (int kk = 0; kk < 24; kk++) {
                mbar_wait(sb + B_R1 + slot8, par);
                step(kk);
                if (kk > 0 && w0 && elect1()) ring_half(sb, prev8, h * 8192, &mp.wup4, 16 * kk + 128, (pass ? 0 : 8) + 4 * h);
                adv();
            }
            if (pass == 0 && w0) mbar_wait(sb + B_MQ, 0);
#pragma unroll 1
            for (int kk = 24; kk < 32; kk++) {
                mbar_wait(sb + B_R1 + slot8, par);
                if (kk == 31 && el) mbar_arrive(sb + (pass ? B_H3 : B_H1));
                step(kk);
                if (w0 && elect1()) ring_half(sb, prev8, h * 8192, pass ? &mp.mqb1 : &mp.mqa2, (pass ? 64 : 32) * (kk - 24), pass ? h : 4 + 2 * h);
                adv();
            }
            wg_wait<0>();
            if (w0 && elect1()) ring_half(sb, prev8, h * 8192, pass ? &mp.mqb1 : &mp.mqa2, pass ? 0 : 256, pass ? 2 + h : 4 + 2 * h);
            pin(acc);
            PT(2 + 3 * pass);
            bf16* ucp = g_uc + ((size_t)blockIdx.x * 128 + (pass ? 0 : 64) + r0) * D_ + 256 * h + 8 * (lane & 3);
#pragma unroll
            for (int m = 0; m < 8; m++) {
                const float* a_ = acc + 16 * m;
                stg4(ucp + 32 * m, pack2(a_[0], a_[1]), pack2(a_[4], a_[5]), pack2(a_[8], a_[9]), pack2(a_[12], a_[13]));
                stg4(ucp + 8 * D_ + 32 * m, pack2(a_[2], a_[3]), pack2(a_[6], a_[7]), pack2(a_[10], a_[11]), pack2(a_[14], a_[15]));
            }
            if (pass) bar_sync(2, 256);
            PT(3 + 3 * pass);
        }
        int s = 1, ph = 0;
        uint32_t* cp = reinterpret_cast<uint32_t*>(g_uc + ((size_t)blockIdx.x * 128 + 64 + 32 * h + 8 * w + (lane >> 2)) * D_) + 4 * (lane & 3);
        const uint32_t* dp = reinterpret_cast<const uint32_t*>(dw) + (((tid - 128) & ~15) | ((lane & 3) << 2) | ((lane >> 2) & 3));
        const uint32_t d0 = ldg_v(dp), d1 = ldg_v(dp + D_ / 2), d2 = ldg_v(dp + D_);
        uint32_t e[6] = {0, 0, 0, 0, 0, 0};
        fresh(acc);
#pragma unroll 1
        for (int j = 0; j < NKV; j++) {
            if (j < 16) ldg4_cg(cp, e + 2);
            else if (j >= CV0 && j < CV0 + 32) {
                if (j == CV0) {
                    mbar_wait(sb + B_GN, 0);
                    cp = reinterpret_cast<uint32_t*>(g_uc + ((size_t)blockIdx.x * 128 - 1) * D_) + (tid - 128);
                }
                e[2] = ldg_cg(cp + 65 * (D_ / 2)); e[3] = ldg_cg(cp + 66 * (D_ / 2));
                if (j > CV0) { e[4] = ldg_cg(cp); e[5] = ldg_cg(cp + D_ / 2); }
            }
            mbar_wait(sb + B_P + s * 8, ph);
            PL(j, 0);
            if (j > 0) {
                const float sc0 = lds_f32(sb + SCL + s * 256 + r0 * 4), sc1 = lds_f32(sb + SCL + s * 256 + r0 * 4 + 32);
                if (__any_sync(0xffffffffu, sc0 != 1.f || sc1 != 1.f)) {
#pragma unroll
                    for (int n = 0; n < 32; n++) { acc[4 * n] *= sc0; acc[4 * n + 1] *= sc0; acc[4 * n + 2] *= sc1; acc[4 * n + 3] *= sc1; }
                }
            }
            mbar_wait(sb + B_GO + s * 8, ph);
            PL(j, 1);
            const uint32_t vd = sd + s * 4096 + h * 2048, pd = sd + (s == 0 ? 2 : s - 1) * 512;
            pin(acc);
            wg_fence();
#pragma unroll
            for (int kk = 0; kk < 4; kk++) wgmma_ss_n256_tb1(acc, dsc(pd, R3 + kk * 32, 16), dsc(vd, kk * 2048, 8192), 1);
            wg_commit();
            if (j < 16) {
                float sm = __uint_as_float(e[0]), sq = __uint_as_float(e[1]);
#pragma unroll
                for (int i = 2; i < 6; i++) {
                    const float lo = gelu2(blo(e[i])), hi = gelu2(bhi(e[i]));
                    sm += lo + hi; sq = fmaf(lo, lo, fmaf(hi, hi, sq));
                    e[i] = pack2(lo, hi);
                }
                stg4(cp, e[2], e[3], e[4], e[5]);
                cp += 16;
                if (j == 15) {
                    sm += __shfl_xor_sync(0xffffffffu, sm, 1); sq += __shfl_xor_sync(0xffffffffu, sq, 1);
                    sm += __shfl_xor_sync(0xffffffffu, sm, 2); sq += __shfl_xor_sync(0xffffffffu, sq, 2);
                    sm *= 1.f / 512.f;
                    sq = rsqrtf(fmaxf(fmaf(-sm, sm, sq * (1.f / 512.f)), 0.f) + 4e-5f);
                    const uint32_t a = sb + STAT + (32 * h + 8 * w + (lane >> 2)) * 8;
                    if ((lane & 3) == 0) { sts_f32(a, sq); sts_f32(a + 4, -sm * sq); }
                    __syncwarp();
                    if (lane == 0) mbar_arrive(sb + B_GN);
                }
                e[0] = __float_as_uint(sm); e[1] = __float_as_uint(sq);
            } else if (j >= CV0 && j < CV0 + 32) {
                uint32_t st[4];
                lds4(sb + STAT + (j - CV0) * 16, st);
                const uint32_t ua = pack2(gelu2(blo(e[4])), gelu2(bhi(e[4]))), ub = pack2(gelu2(blo(e[5])), gelu2(bhi(e[5])));
                e[2] = pack2(fmaf(blo(e[2]), __uint_as_float(st[0]), __uint_as_float(st[1])), fmaf(bhi(e[2]), __uint_as_float(st[0]), __uint_as_float(st[1])));
                e[3] = pack2(fmaf(blo(e[3]), __uint_as_float(st[2]), __uint_as_float(st[3])), fmaf(bhi(e[3]), __uint_as_float(st[2]), __uint_as_float(st[3])));
                if (j > CV0) {
                    asm volatile("st.global.u32 [%0], %1;" ::"l"(cp), "r"(bmul2(ua, bfma2(e[2], d2, bfma2(e[1], d1, bmul2(e[0], d0))))) : "memory");
                    asm volatile("st.global.u32 [%0], %1;" ::"l"(cp + D_ / 2), "r"(bmul2(ub, bfma2(e[3], d2, bfma2(e[2], d1, bmul2(e[1], d0))))) : "memory");
                }
                e[0] = e[2]; e[1] = e[3];
                cp += D_;
            }
            wg_wait<0>();
            pin(acc);
            PL(j, 2);
            if (w0 && elect1()) {
                if (j + 3 < NKV) {
                    mbar_expect_tx(sb + B_KV + s * 8, 32768);
                    tma4(sb + s * 65536 + h * 32768, &mp.xa4, 0, 64 * (j + 3), 4 * h, b, sb + B_KV + s * 8);
                } else if (j < NKV - 1) {
                    const int n0 = (j == NKV - 3 ? 0 : 8) + 4 * h;
#pragma unroll 1
                    for (int n = n0; n < n0 + 4; n++) ring_ld(sb, n * 8, n);
                }
                if (j == NKV - 5 && mode == 0) flag_wait(&g_sync[3], 4);
                if (j >= XPF && j < XPF + 4) {
                    const int t0 = 62 * ti + 32 * h + 8 * (j - XPF), nr = min(8, T_ - t0);
                    if (nr > 0) l2_prefetch(x + ((size_t)b * T_ + t0) * D_, nr * 1024);
                }
            }
            if (++s == 3) s = 0;
            if (s == 1) ph ^= 1;
        }
        {
            const float i0 = lds_f32(sb + LINV + r0 * 4), i1 = lds_f32(sb + LINV + r0 * 4 + 32);
#pragma unroll
            for (int p = 0; p < 16; p++)
                stsm4(((sb + R0 + h * 32768 + loff) ^ ((p & 3) << 5)) + (p >> 2) * 8192,
                      pack2(acc[8 * p] * i0, acc[8 * p + 1] * i0), pack2(acc[8 * p + 2] * i1, acc[8 * p + 3] * i1),
                      pack2(acc[8 * p + 4] * i0, acc[8 * p + 5] * i0), pack2(acc[8 * p + 6] * i1, acc[8 * p + 7] * i1));
        }
        fence_async();
        fence_async_g();
        bar_sync(2, 256);
        if (lane == 0 && w < 2) ring_ld(sb, 128 + 16 * w + 8 * h, 16 + 2 * w + h);
        PT(7);
        fresh(acc);
        {
            uint32_t slot8 = 8 * h, par = 0, prev8 = 0;
#pragma unroll 1
            for (int kk = 0; kk < 64; kk++) {
                if (kk == 32 || kk == 48) mbar_wait(sb + B_UC + (kk >> 1 & 8), 0);
                mbar_wait(sb + B_R2 + slot8, par);
                wg_fence();
                wgmma_ss_n256_tb1(acc, mkd(sd + (1u << 16) + (R0 >> 4) + (kk >> 2 & 7) * 512 + (kk & 3) * 2), mkd(bd2k + (R1 >> 4) + slot8 * 64), 1);
                wg_commit();
                wg_wait<1>();
                if (kk > 0 && lane == 0) mbar_arrive(sb + B_E2 + prev8);
                if ((kk == 16 || kk == 32) && w0 && elect1() && (atom_inc_s(sb + CNT + 12 + (kk >> 3 & 4)) & 1)) {
                    mbar_expect_tx(sb + B_UC + (kk >> 2 & 8), 32768);
                    tma3(sb + R0 + (kk & 32) * 1024, &mp.uc, 0, 128 * blockIdx.x, kk >> 3 & 4, sb + B_UC + (kk >> 2 & 8));
                }
                prev8 = slot8;
                slot8 += 16;
                if (slot8 >= 160) { slot8 -= 160; par ^= 1; }
            }
        }
        wg_wait<0>();
        pin(acc);
        PT(8);
        mbar_wait(sb + B_X, 0);
        PT(9);
        {
            const uint32_t sr = (lrow + 63) & 63;
            const uint32_t xoff = sr * 128 + ((((lane >> 4) ^ sr) & 7) << 4);
#pragma unroll
            for (int p = 0; p < 16; p++) {
                const uint32_t a = ((sb + R2 + h * 32768 + xoff) ^ ((p & 3) << 5)) + (p >> 2) * 8192;
                uint32_t xv[4];
                ldsm4(a, xv);
#pragma unroll
                for (int e = 0; e < 4; e++)
                    xv[e] = pack2(acc[8 * p + 2 * e] + __uint_as_float(xv[e] << 16), acc[8 * p + 2 * e + 1] + __uint_as_float(xv[e] & 0xffff0000u));
                stsm4(a, xv[0], xv[1], xv[2], xv[3]);
            }
        }
        fence_async();
        bar_sync(3 + h, 128);
        if (el) {
            for (int c = 0; c < 4; c++) tma4_store(&mp.out, sb + R2 + (4 * h + c) * 8192, 0, 62 * ti, 4 * h + c, b);
            asm volatile("cp.async.bulk.commit_group;" ::: "memory");
            PT(10);
            if (h == 0) cta_done(mode);
            asm volatile("cp.async.bulk.wait_group.read 0;" ::: "memory");
        }
        PT(11);
        PG(201);
        PDUMP();
    }
}

typedef CUresult (*PFN_enc)(CUtensorMap*, CUtensorMapDataType, cuuint32_t, void*, const cuuint64_t*, const cuuint64_t*,
                            const cuuint32_t*, const cuuint32_t*, CUtensorMapInterleave, CUtensorMapSwizzle,
                            CUtensorMapL2promotion, CUtensorMapFloatOOBfill);

static void enc(PFN_enc f, CUtensorMap* m, void* base, int rank, const cuuint64_t* dims, const cuuint64_t* strides, const cuuint32_t* box) {
    cuuint32_t es[5] = {1, 1, 1, 1, 1};
    f(m, CU_TENSOR_MAP_DATA_TYPE_BFLOAT16, rank, base, dims, strides, box, es, CU_TENSOR_MAP_INTERLEAVE_NONE,
      CU_TENSOR_MAP_SWIZZLE_128B, CU_TENSOR_MAP_L2_PROMOTION_L2_256B, CU_TENSOR_MAP_FLOAT_OOB_FILL_NONE);
}
static void enc_act(PFN_enc f, CUtensorMap* m, void* base, int rows, int chunks, int trows = T_, int pitch = T_) {
    cuuint64_t dims[4] = {64, (cuuint64_t)trows, 8, (cuuint64_t)NB_};
    cuuint64_t st[3] = {1024, 128, (cuuint64_t)pitch * 1024};
    cuuint32_t box[4] = {64, (cuuint32_t)rows, (cuuint32_t)chunks, 1};
    enc(f, m, base, 4, dims, st, box);
}
static void enc_w(PFN_enc f, CUtensorMap* m, void* base, int krows, int ncols, int bk, int bc) {
    cuuint64_t dims[3] = {64, (cuuint64_t)krows, (cuuint64_t)(ncols / 64)};
    cuuint64_t st[2] = {(cuuint64_t)ncols * 2, 128};
    cuuint32_t box[3] = {64, (cuuint32_t)bk, (cuuint32_t)bc};
    enc(f, m, base, 3, dims, st, box);
}

extern "C" void kernel_launch(void* const* d_in, const int* in_sizes, int n_in, void* d_out, int out_size) {
    const bf16* x = (const bf16*)d_in[0];
    static PFN_enc fenc = nullptr;
    static void *p_xa, *p_mqk, *p_uc, *p_t1;
    static int fused = 0;
    if (!fenc) {
        void* fn = nullptr;
        cudaDriverEntryPointQueryResult qr;
        cudaGetDriverEntryPoint("cuTensorMapEncodeTiled", &fn, cudaEnableDefault, &qr);
        fenc = (PFN_enc)fn;
        cudaGetSymbolAddress(&p_xa, g_xa);
        cudaGetSymbolAddress(&p_mqk, g_mqk);
        cudaGetSymbolAddress(&p_uc, g_uc);
        cudaGetSymbolAddress(&p_t1, g_t1);
        cudaFuncSetAttribute(main_kernel, cudaFuncAttributeMaxDynamicSharedMemorySize, SMEM_BYTES);
        int dev = 0, sms = 0, occ = 0;
        cudaGetDevice(&dev);
        cudaDeviceGetAttribute(&sms, cudaDevAttrMultiProcessorCount, dev);
        cudaOccupancyMaxActiveBlocksPerMultiprocessor(&occ, main_kernel, 384, SMEM_BYTES);
        fused = sms * occ >= NCTA + 2;
    }
    Maps mp;
    enc_act(fenc, &mp.xa, (char*)p_xa + 1024, 64, 8, T_, T_ + 8);
    enc_act(fenc, &mp.xa2, (char*)p_xa + 1024, 64, 2, T_, T_ + 8);
    enc_act(fenc, &mp.xa4, (char*)p_xa + 1024, 64, 4, T_, T_ + 8);
    enc_act(fenc, &mp.xas, p_xa, 64, 1, T_ + 1, T_ + 8);
    enc_act(fenc, &mp.x, (void*)x, 64, 1);
    enc_act(fenc, &mp.out, d_out, 62, 1);
    enc_w(fenc, &mp.wup4, d_in[5], 512, 1024, 16, 4);
    enc_w(fenc, &mp.wup8, d_in[5], 512, 1024, 16, 8);
    enc_w(fenc, &mp.mqa2, p_mqk, 512, 512, 32, 2);
    enc_w(fenc, &mp.mqa4, p_mqk, 512, 512, 32, 4);
    enc_w(fenc, &mp.mqb1, p_mqk, 512, 512, 64, 1);
    enc_w(fenc, &mp.mqb2, p_mqk, 512, 512, 64, 2);
    enc_w(fenc, &mp.uc, p_uc, NCTA * 128, 512, 64, 4);
    enc_w(fenc, &mp.wq, d_in[1], 512, 512, 64, 8);
    enc_w(fenc, &mp.wk, d_in[2], 512, 512, 32, 8);
    enc_w(fenc, &mp.fa[0], d_in[3], 512, 512, 128, 1);
    enc_w(fenc, &mp.fa[1], d_in[7], 512, 512, 128, 1);
    enc_w(fenc, &mp.fa[2], p_t1, 512, 512, 128, 1);
    enc_w(fenc, &mp.fb[0], d_in[4], 512, 512, 64, 4);
    enc_w(fenc, &mp.fb[1], d_in[8], 1024, 512, 64, 4);
    enc_w(fenc, &mp.fc, p_t1, 512, 512, 64, 4);
    cudaStream_t st = cudaStreamPerThread;
    if (fused) {
        main_kernel<<<NCTA + 2, 384, SMEM_BYTES, st>>>(mp, x, (const bf16*)d_in[6], (const bf16*)d_in[5], 0);
    } else {
        main_kernel<<<NCTA + 2, 384, SMEM_BYTES, st>>>(mp, x, (const bf16*)d_in[6], (const bf16*)d_in[5], 1);
        main_kernel<<<NCTA + 2, 384, SMEM_BYTES, st>>>(mp, x, (const bf16*)d_in[6], (const bf16*)d_in[5], 2);
    }
}
```

```cpp
#include <cuda_runtime.h>
#include <cuda_bf16.h>
#include <cuda.h>
#include <stdint.h>

typedef __nv_bfloat16 bf16;

constexpr int T_ = 4000, D_ = 512, NB_ = 2;
constexpr int TPB = 65;
constexpr int NCTA = TPB * NB_;
constexpr int NKV = 63;

__device__ __align__(1024) bf16 g_xa[NB_ * (T_ + 8) * D_];
__device__ __align__(1024) bf16 g_mqk[D_ * D_];
__device__ __align__(1024) bf16 g_t1[D_ * D_];
__device__ __align__(1024) bf16 g_wepi[2 * D_ * D_];
__device__ __align__(1024) bf16 g_uc[NCTA * 128 * D_];
__device__ unsigned g_sync[8];

#define PT(i) do { if (el) asm volatile("st.shared.u32 [%0], %1;" ::"r"(sb + MISC + 2560), "r"((unsigned)clock())); } while (0)
#define PG(i)
#define PE()
#define PLM 15
#define PL(j, q) do { if ((PLM >> ((q) + (wg ? 4 : 0))) & 1) PT(0); } while (0)
#define PDUMP()

#define FENCE_AT 1
#define GO_AT 25
#define LAZY 256.f
#define SU 2
#define XS_GAP 800
#define XPF 50
#define RG0 "184"
#define DPOS 0
#define GST 8
#define CV0 6
#define LAGA 0
#define LAGB 0
#define PFW 1
constexpr uint32_t R0 = 0, R1 = 65536, R2 = 131072, R3 = 196608, QS = 221184, MISC = 229376;
constexpr uint32_t AT = 147456;
constexpr uint32_t SMEM_BYTES = 232448;
constexpr uint32_t B_R1 = MISC + 1856  , B_MK = MISC + 48, B_LN = MISC + 56, B_MQ = MISC + 64, B_GN = MISC + 72,
                   B_H1 = MISC + 88, B_H2 = MISC + 96, B_H3 = MISC + 104,
                   B_KV = MISC + 112, B_P = MISC + 136, B_GO = MISC + 160, B_UC = MISC + 184  ,
                   B_X = MISC + 200, CNT = MISC + 208  , SCL = MISC + 512  ,
                   LINV = MISC + 1280  , STAT = MISC + 2048  ,
                   B_R2 = MISC + 1536  , B_E2 = MISC + 1696  ;

__device__ __forceinline__ uint32_t smem_u32(const void* p) { return (uint32_t)__cvta_generic_to_shared(p); }
__device__ __forceinline__ void wg_fence() { asm volatile("wgmma.fence.sync.aligned;" ::: "memory"); }
__device__ __forceinline__ void wg_commit() { asm volatile("wgmma.commit_group.sync.aligned;" ::: "memory"); }
template <int N> __device__ __forceinline__ void wg_wait() { asm volatile("wgmma.wait_group.sync.aligned %0;" ::"n"(N) : "memory"); }
__device__ __forceinline__ uint64_t dsc(uint32_t sd, uint32_t off, uint32_t lbo) {
    uint32_t lo = sd + (off >> 4) + ((lbo >> 4) << 16);
    uint64_t d;
    asm("mov.b64 %0, {%1, %2};" : "=l"(d) : "r"(lo), "r"((1024u >> 4) | (1u << 30)));
    return d;
}
__device__ __forceinline__ bool elect1() {
    uint32_t p;
    asm volatile("{\n.reg .pred p;\nelect.sync _|p, 0xffffffff;\nselp.u32 %0, 1, 0, p;\n}\n" : "=r"(p));
    return p != 0;
}
__device__ __forceinline__ void mbar_init(uint32_t bar, int cnt) { asm volatile("mbarrier.init.shared::cta.b64 [%0], %1;" ::"r"(bar), "r"(cnt) : "memory"); }
__device__ __forceinline__ void mbar_expect_tx(uint32_t bar, uint32_t bytes) { asm volatile("mbarrier.arrive.expect_tx.shared::cta.b64 _, [%0], %1;" ::"r"(bar), "r"(bytes) : "memory"); }
__device__ __forceinline__ void mbar_arrive(uint32_t bar) { asm volatile("mbarrier.arrive.shared::cta.b64 _, [%0];" ::"r"(bar) : "memory"); }
__device__ __forceinline__ void mbar_wait(uint32_t bar, uint32_t parity) {
    uint32_t ok;
#pragma unroll 1
    for (uint32_t it = 0;; ++it) {
        asm volatile("{\n.reg .pred p;\nmbarrier.try_wait.parity.shared::cta.b64 p, [%1], %2;\nselp.u32 %0, 1, 0, p;\n}\n" : "=r"(ok) : "r"(bar), "r"(parity) : "memory");
        if (ok) break;
        if (it > (1u << 20)) __trap();
    }
}
__device__ __forceinline__ bool mbar_test(uint32_t bar, uint32_t parity) {
    uint32_t ok;
    asm volatile("{\n.reg .pred p;\nmbarrier.test_wait.parity.shared::cta.b64 p, [%1], %2;\nselp.u32 %0, 1, 0, p;\n}\n" : "=r"(ok) : "r"(bar), "r"(parity) : "memory");
    return ok != 0;
}
__device__ __forceinline__ void fence_async() { asm volatile("fence.proxy.async.shared::cta;" ::: "memory"); }
__device__ __forceinline__ void fence_async_g() { asm volatile("fence.proxy.async.global;" ::: "memory"); }
__device__ __forceinline__ void bar_sync(int id, int n) { asm volatile("bar.sync %0, %1;" ::"r"(id), "r"(n) : "memory"); }
__device__ __forceinline__ void tma3(uint32_t dst, const CUtensorMap* tm, int c0, int c1, int c2, uint32_t bar) {
    asm volatile("cp.async.bulk.tensor.3d.shared::cluster.global.mbarrier::complete_tx::bytes [%0], [%1, {%3, %4, %5}], [%2];"
                 ::"r"(dst), "l"(tm), "r"(bar), "r"(c0), "r"(c1), "r"(c2) : "memory");
}
__device__ __forceinline__ void tma4(uint32_t dst, const CUtensorMap* tm, int c0, int c1, int c2, int c3, uint32_t bar) {
    asm volatile("cp.async.bulk.tensor.4d.shared::cluster.global.mbarrier::complete_tx::bytes [%0], [%1, {%3, %4, %5, %6}], [%2];"
                 ::"r"(dst), "l"(tm), "r"(bar), "r"(c0), "r"(c1), "r"(c2), "r"(c3) : "memory");
}
__device__ __forceinline__ void tma4_store(const CUtensorMap* tm, uint32_t src, int c0, int c1, int c2, int c3) {
    asm volatile("cp.async.bulk.tensor.4d.global.shared::cta.bulk_group [%0, {%2, %3, %4, %5}], [%1];"
                 ::"l"(tm), "r"(src), "r"(c0), "r"(c1), "r"(c2), "r"(c3) : "memory");
}
__device__ __forceinline__ void tma3_store(const CUtensorMap* tm, uint32_t src, int c0, int c1, int c2) {
    asm volatile("cp.async.bulk.tensor.3d.global.shared::cta.bulk_group [%0, {%2, %3, %4}], [%1];"
                 ::"l"(tm), "r"(src), "r"(c0), "r"(c1), "r"(c2) : "memory");
}
__device__ __forceinline__ void stsm4(uint32_t addr, uint32_t a, uint32_t b, uint32_t c, uint32_t d) {
    asm volatile("stmatrix.sync.aligned.m8n8.x4.shared.b16 [%0], {%1, %2, %3, %4};" ::"r"(addr), "r"(a), "r"(b), "r"(c), "r"(d) : "memory");
}
__device__ __forceinline__ void ldsm4(uint32_t addr, uint32_t (&r)[4]) {
    asm volatile("ldmatrix.sync.aligned.m8n8.x4.shared.b16 {%0, %1, %2, %3}, [%4];" : "=r"(r[0]), "=r"(r[1]), "=r"(r[2]), "=r"(r[3]) : "r"(addr) : "memory");
}
__device__ __forceinline__ void ldsm2(uint32_t addr, uint32_t (&r)[2]) {
    asm volatile("ldmatrix.sync.aligned.m8n8.x2.shared.b16 {%0, %1}, [%2];" : "=r"(r[0]), "=r"(r[1]) : "r"(addr) : "memory");
}
__device__ __forceinline__ void stg4(void* p, uint32_t a, uint32_t b, uint32_t c, uint32_t d) {
    asm volatile("st.global.v4.u32 [%0], {%1, %2, %3, %4};" ::"l"(p), "r"(a), "r"(b), "r"(c), "r"(d) : "memory");
}
__device__ __forceinline__ void hmma(float (&c)[4], uint32_t a0, uint32_t a1, uint32_t a2, uint32_t a3, uint32_t b0, uint32_t b1) {
    asm("mma.sync.aligned.m16n8k16.row.col.f32.bf16.bf16.f32 {%0, %1, %2, %3}, {%4, %5, %6, %7}, {%8, %9}, {%0, %1, %2, %3};"
        : "+f"(c[0]), "+f"(c[1]), "+f"(c[2]), "+f"(c[3]) : "r"(a0), "r"(a1), "r"(a2), "r"(a3), "r"(b0), "r"(b1));
}
__device__ __forceinline__ uint32_t pack2(float lo, float hi) {
    uint32_t r;
    asm("cvt.rn.bf16x2.f32 %0, %1, %2;" : "=r"(r) : "f"(hi), "f"(lo));
    return r;
}
__device__ __forceinline__ uint32_t pack2v(float lo, float hi) {
    uint32_t r;
    asm volatile("cvt.rn.bf16x2.f32 %0, %1, %2;" : "=r"(r) : "f"(hi), "f"(lo));
    return r;
}
__device__ __forceinline__ uint32_t bmul2(uint32_t a, uint32_t b) { uint32_t r; asm("mul.rn.bf16x2 %0, %1, %2;" : "=r"(r) : "r"(a), "r"(b)); return r; }
__device__ __forceinline__ uint32_t bfma2(uint32_t a, uint32_t b, uint32_t c) { uint32_t r; asm("fma.rn.bf16x2 %0, %1, %2, %3;" : "=r"(r) : "r"(a), "r"(b), "r"(c)); return r; }
__device__ __forceinline__ float ex2(float x) { float r; asm("ex2.approx.ftz.f32 %0, %1;" : "=f"(r) : "f"(x)); return r; }
__device__ __forceinline__ float rcp(float x) { float r; asm("rcp.approx.ftz.f32 %0, %1;" : "=f"(r) : "f"(x)); return r; }
__device__ __forceinline__ float gelu2(float x) {
    float t = fmaf(x * x, 0.044715f * 0.7978845608028654f, 0.7978845608028654f), th;
    asm("tanh.approx.f32 %0, %1;" : "=f"(th) : "f"(x * t));
    return fmaf(x, th, x);
}
__device__ __forceinline__ uint32_t ldg_v(const uint32_t* p) { uint32_t v; asm volatile("ld.global.nc.u32 %0, [%1];" : "=r"(v) : "l"(p)); return v; }
__device__ __forceinline__ uint32_t ldg_cg(const uint32_t* p) { uint32_t v; asm volatile("ld.global.cg.u32 %0, [%1];" : "=r"(v) : "l"(p) : "memory"); return v; }
__device__ __forceinline__ void ldg4_cg(const uint32_t* p, uint32_t* r) {
    asm volatile("ld.global.cg.v4.u32 {%0, %1, %2, %3}, [%4];" : "=r"(r[0]), "=r"(r[1]), "=r"(r[2]), "=r"(r[3]) : "l"(p) : "memory");
}
__device__ __forceinline__ float lds_f32(uint32_t a) { float v; asm volatile("ld.shared.f32 %0, [%1];" : "=f"(v) : "r"(a) : "memory"); return v; }
__device__ __forceinline__ void sts_f32(uint32_t a, float v) { asm volatile("st.shared.f32 [%0], %1;" ::"r"(a), "f"(v) : "memory"); }
__device__ __forceinline__ uint32_t atom_inc_s(uint32_t a) { uint32_t v; asm volatile("atom.relaxed.cta.shared.add.u32 %0, [%1], 1;" : "=r"(v) : "r"(a) : "memory"); return v; }
__device__ __forceinline__ void lds4(uint32_t a, uint32_t* r) {
    asm volatile("ld.shared.v4.u32 {%0, %1, %2, %3}, [%4];" : "=r"(r[0]), "=r"(r[1]), "=r"(r[2]), "=r"(r[3]) : "r"(a) : "memory");
}
__device__ __forceinline__ void sts4(uint32_t a, uint32_t x, uint32_t y, uint32_t z, uint32_t t) {
    asm volatile("st.shared.v4.u32 [%0], {%1, %2, %3, %4};" ::"r"(a), "r"(x), "r"(y), "r"(z), "r"(t) : "memory");
}
__device__ __forceinline__ uint32_t bsub2(uint32_t a, uint32_t b) { uint32_t r; asm("sub.rn.bf16x2 %0, %1, %2;" : "=r"(r) : "r"(a), "r"(b)); return r; }
__device__ __forceinline__ float blo(uint32_t v) { return __uint_as_float(v << 16); }
__device__ __forceinline__ float bhi(uint32_t v) { return __uint_as_float(v & 0xffff0000u); }
__device__ __forceinline__ float bfr(float x) { return __bfloat162float(__float2bfloat16_rn(x)); }
__device__ __forceinline__ void l2_prefetch(const void* p, uint32_t bytes) { asm volatile("cp.async.bulk.prefetch.L2.global [%0], %1;" ::"l"(p), "r"(bytes) : "memory"); }
__device__ __forceinline__ void flag_add(unsigned* p) { asm volatile("red.release.gpu.global.add.u32 [%0], 1;" ::"l"(p) : "memory"); }
__device__ __forceinline__ void flag_wait(const unsigned* p, unsigned target) {
#pragma unroll 1
    for (uint32_t it = 0;; ++it) {
        unsigned v;
        asm volatile("ld.acquire.gpu.global.u32 %0, [%1];" : "=r"(v) : "l"(p) : "memory");
        if (v >= target) break;
        if (it > (1u << 20)) __trap();
    }
    fence_async_g();
}
template <int N> __device__ __forceinline__ void pin(float (&a)[N]) {
#pragma unroll
    for (int i = 0; i < N; i++) asm volatile("" : "+f"(a[i])::"memory");
}

template <int N> __device__ __forceinline__ void fresh(float (&a)[N]) {
#pragma unroll
    for (int i = 0; i < N; i++) a[i] = 0.f;
    pin(a);
}

__device__ __forceinline__ void wgmma_rs_n64_tb0(float (&d)[32], uint32_t a0, uint32_t a1, uint32_t a2, uint32_t a3, uint64_t db, int scale_d) {
    asm volatile("{\n.reg .pred p;\nsetp.ne.b32 p, %37, 0;\n"
        "wgmma.mma_async.sync.aligned.m64n64k16.f32.bf16.bf16 {%0, %1, %2, %3, %4, %5, %6, %7, %8, %9, %10, %11, %12, %13, %14, %15, %16, %17, %18, %19, %20, %21, %22, %23, %24, %25, %26, %27, %28, %29, %30, %31}, {%32, %33, %34, %35}, %36, p, 1, 1, 0;\n}\n"
        : "+f"(d[0]), "+f"(d[1]), "+f"(d[2]), "+f"(d[3]), "+f"(d[4]), "+f"(d[5]), "+f"(d[6]), "+f"(d[7]), "+f"(d[8]), "+f"(d[9]), "+f"(d[10]), "+f"(d[11]), "+f"(d[12]), "+f"(d[13]), "+f"(d[14]), "+f"(d[15]), "+f"(d[16]), "+f"(d[17]), "+f"(d[18]), "+f"(d[19]), "+f"(d[20]), "+f"(d[21]), "+f"(d[22]), "+f"(d[23]), "+f"(d[24]), "+f"(d[25]), "+f"(d[26]), "+f"(d[27]), "+f"(d[28]), "+f"(d[29]), "+f"(d[30]), "+f"(d[31])
        : "r"(a0), "r"(a1), "r"(a2), "r"(a3), "l"(db), "r"(scale_d));
}

__device__ __forceinline__ void wgmma_ss_n128_tb1(float (&d)[64], uint64_t da, uint64_t db, int scale_d) {
    asm volatile("{\n.reg .pred p;\nsetp.ne.b32 p, %66, 0;\n"
        "wgmma.mma_async.sync.aligned.m64n128k16.f32.bf16.bf16 {%0, %1, %2, %3, %4, %5, %6, %7, %8, %9, %10, %11, %12, %13, %14, %15, %16, %17, %18, %19, %20, %21, %22, %23, %24, %25, %26, %27, %28, %29, %30, %31, %32, %33, %34, %35, %36, %37, %38, %39, %40, %41, %42, %43, %44, %45, %46, %47, %48, %49, %50, %51, %52, %53, %54, %55, %56, %57, %58, %59, %60, %61, %62, %63}, %64, %65, p, 1, 1, 0, 1;\n}\n"
        : "+f"(d[0]), "+f"(d[1]), "+f"(d[2]), "+f"(d[3]), "+f"(d[4]), "+f"(d[5]), "+f"(d[6]), "+f"(d[7]), "+f"(d[8]), "+f"(d[9]), "+f"(d[10]), "+f"(d[11]), "+f"(d[12]), "+f"(d[13]), "+f"(d[14]), "+f"(d[15]), "+f"(d[16]), "+f"(d[17]), "+f"(d[18]), "+f"(d[19]), "+f"(d[20]), "+f"(d[21]), "+f"(d[22]), "+f"(d[23]), "+f"(d[24]), "+f"(d[25]), "+f"(d[26]), "+f"(d[27]), "+f"(d[28]), "+f"(d[29]), "+f"(d[30]), "+f"(d[31]), "+f"(d[32]), "+f"(d[33]), "+f"(d[34]), "+f"(d[35]), "+f"(d[36]), "+f"(d[37]), "+f"(d[38]), "+f"(d[39]), "+f"(d[40]), "+f"(d[41]), "+f"(d[42]), "+f"(d[43]), "+f"(d[44]), "+f"(d[45]), "+f"(d[46]), "+f"(d[47]), "+f"(d[48]), "+f"(d[49]), "+f"(d[50]), "+f"(d[51]), "+f"(d[52]), "+f"(d[53]), "+f"(d[54]), "+f"(d[55]), "+f"(d[56]), "+f"(d[57]), "+f"(d[58]), "+f"(d[59]), "+f"(d[60]), "+f"(d[61]), "+f"(d[62]), "+f"(d[63])
        : "l"(da), "l"(db), "r"(scale_d));
}

__device__ __forceinline__ void wgmma_ss_n256_tb1(float (&d)[128], uint64_t da, uint64_t db, int scale_d) {
    asm volatile("{\n.reg .pred p;\nsetp.ne.b32 p, %130, 0;\n"
        "wgmma.mma_async.sync.aligned.m64n256k16.f32.bf16.bf16 {%0, %1, %2, %3, %4, %5, %6, %7, %8, %9, %10, %11, %12, %13, %14, %15, %16, %17, %18, %19, %20, %21, %22, %23, %24, %25, %26, %27, %28, %29, %30, %31, %32, %33, %34, %35, %36, %37, %38, %39, %40, %41, %42, %43, %44, %45, %46, %47, %48, %49, %50, %51, %52, %53, %54, %55, %56, %57, %58, %59, %60, %61, %62, %63, %64, %65, %66, %67, %68, %69, %70, %71, %72, %73, %74, %75, %76, %77, %78, %79, %80, %81, %82, %83, %84, %85, %86, %87, %88, %89, %90, %91, %92, %93, %94, %95, %96, %97, %98, %99, %100, %101, %102, %103, %104, %105, %106, %107, %108, %109, %110, %111, %112, %113, %114, %115, %116, %117, %118, %119, %120, %121, %122, %123, %124, %125, %126, %127}, %128, %129, p, 1, 1, 0, 1;\n}\n"
        : "+f"(d[0]), "+f"(d[1]), "+f"(d[2]), "+f"(d[3]), "+f"(d[4]), "+f"(d[5]), "+f"(d[6]), "+f"(d[7]), "+f"(d[8]), "+f"(d[9]), "+f"(d[10]), "+f"(d[11]), "+f"(d[12]), "+f"(d[13]), "+f"(d[14]), "+f"(d[15]), "+f"(d[16]), "+f"(d[17]), "+f"(d[18]), "+f"(d[19]), "+f"(d[20]), "+f"(d[21]), "+f"(d[22]), "+f"(d[23]), "+f"(d[24]), "+f"(d[25]), "+f"(d[26]), "+f"(d[27]), "+f"(d[28]), "+f"(d[29]), "+f"(d[30]), "+f"(d[31]), "+f"(d[32]), "+f"(d[33]), "+f"(d[34]), "+f"(d[35]), "+f"(d[36]), "+f"(d[37]), "+f"(d[38]), "+f"(d[39]), "+f"(d[40]), "+f"(d[41]), "+f"(d[42]), "+f"(d[43]), "+f"(d[44]), "+f"(d[45]), "+f"(d[46]), "+f"(d[47]), "+f"(d[48]), "+f"(d[49]), "+f"(d[50]), "+f"(d[51]), "+f"(d[52]), "+f"(d[53]), "+f"(d[54]), "+f"(d[55]), "+f"(d[56]), "+f"(d[57]), "+f"(d[58]), "+f"(d[59]), "+f"(d[60]), "+f"(d[61]), "+f"(d[62]), "+f"(d[63]), "+f"(d[64]), "+f"(d[65]), "+f"(d[66]), "+f"(d[67]), "+f"(d[68]), "+f"(d[69]), "+f"(d[70]), "+f"(d[71]), "+f"(d[72]), "+f"(d[73]), "+f"(d[74]), "+f"(d[75]), "+f"(d[76]), "+f"(d[77]), "+f"(d[78]), "+f"(d[79]), "+f"(d[80]), "+f"(d[81]), "+f"(d[82]), "+f"(d[83]), "+f"(d[84]), "+f"(d[85]), "+f"(d[86]), "+f"(d[87]), "+f"(d[88]), "+f"(d[89]), "+f"(d[90]), "+f"(d[91]), "+f"(d[92]), "+f"(d[93]), "+f"(d[94]), "+f"(d[95]), "+f"(d[96]), "+f"(d[97]), "+f"(d[98]), "+f"(d[99]), "+f"(d[100]), "+f"(d[101]), "+f"(d[102]), "+f"(d[103]), "+f"(d[104]), "+f"(d[105]), "+f"(d[106]), "+f"(d[107]), "+f"(d[108]), "+f"(d[109]), "+f"(d[110]), "+f"(d[111]), "+f"(d[112]), "+f"(d[113]), "+f"(d[114]), "+f"(d[115]), "+f"(d[116]), "+f"(d[117]), "+f"(d[118]), "+f"(d[119]), "+f"(d[120]), "+f"(d[121]), "+f"(d[122]), "+f"(d[123]), "+f"(d[124]), "+f"(d[125]), "+f"(d[126]), "+f"(d[127])
        : "l"(da), "l"(db), "r"(scale_d));
}

__device__ __forceinline__ void wgmma_ss_n32_tb0(float (&d)[16], uint64_t da, uint64_t db, int scale_d) {
    asm volatile("{\n.reg .pred p;\nsetp.ne.b32 p, %18, 0;\n"
        "wgmma.mma_async.sync.aligned.m64n32k16.f32.bf16.bf16 {%0, %1, %2, %3, %4, %5, %6, %7, %8, %9, %10, %11, %12, %13, %14, %15}, %16, %17, p, 1, 1, 0, 0;\n}\n"
        : "+f"(d[0]), "+f"(d[1]), "+f"(d[2]), "+f"(d[3]), "+f"(d[4]), "+f"(d[5]), "+f"(d[6]), "+f"(d[7]), "+f"(d[8]), "+f"(d[9]), "+f"(d[10]), "+f"(d[11]), "+f"(d[12]), "+f"(d[13]), "+f"(d[14]), "+f"(d[15])
        : "l"(da), "l"(db), "r"(scale_d));
}

__device__ __forceinline__ void wgmma_ss_n64_tb0(float (&d)[32], uint64_t da, uint64_t db, int scale_d) {
    asm volatile("{\n.reg .pred p;\nsetp.ne.b32 p, %34, 0;\n"
        "wgmma.mma_async.sync.aligned.m64n64k16.f32.bf16.bf16 {%0, %1, %2, %3, %4, %5, %6, %7, %8, %9, %10, %11, %12, %13, %14, %15, %16, %17, %18, %19, %20, %21, %22, %23, %24, %25, %26, %27, %28, %29, %30, %31}, %32, %33, p, 1, 1, 0, 0;\n}\n"
        : "+f"(d[0]), "+f"(d[1]), "+f"(d[2]), "+f"(d[3]), "+f"(d[4]), "+f"(d[5]), "+f"(d[6]), "+f"(d[7]), "+f"(d[8]), "+f"(d[9]), "+f"(d[10]), "+f"(d[11]), "+f"(d[12]), "+f"(d[13]), "+f"(d[14]), "+f"(d[15]), "+f"(d[16]), "+f"(d[17]), "+f"(d[18]), "+f"(d[19]), "+f"(d[20]), "+f"(d[21]), "+f"(d[22]), "+f"(d[23]), "+f"(d[24]), "+f"(d[25]), "+f"(d[26]), "+f"(d[27]), "+f"(d[28]), "+f"(d[29]), "+f"(d[30]), "+f"(d[31])
        : "l"(da), "l"(db), "r"(scale_d));
}

struct Maps {
    CUtensorMap xa, xa2, xa4, xas, wup4, wup8, mqa2, mqa4, mqb1, mqb2, uc, x, out, wq, wk, fa[3], fb[2], fc;
};

__device__ __forceinline__ uint64_t mkd(uint32_t lo) {
    uint64_t d;
    asm("mov.b64 %0, {%1, %2};" : "=l"(d) : "r"(lo), "r"((1024u >> 4) | (1u << 30)));
    return d;
}
__device__ __forceinline__ void bulk_ld(uint32_t dst, const void* src, uint32_t bytes, uint32_t bar) {
    asm volatile("cp.async.bulk.shared::cluster.global.mbarrier::complete_tx::bytes [%0], [%1], %2, [%3];" ::"r"(dst), "l"(src), "r"(bytes), "r"(bar) : "memory");
}
__device__ __forceinline__ void bulk_st(void* dst, uint32_t src, uint32_t bytes) {
    asm volatile("cp.async.bulk.global.shared::cta.bulk_group [%0], [%1], %2;" ::"l"(dst), "r"(src), "r"(bytes) : "memory");
}
__device__ __forceinline__ void ring_ld(uint32_t sb, uint32_t slot8, int n) {
    mbar_expect_tx(sb + B_R2 + slot8, 8192);
    bulk_ld(sb + R1 + slot8 * 1024, (const char*)g_wepi + n * 8192, 8192, sb + B_R2 + slot8);
}

__device__ __forceinline__ void ring_half(uint32_t sb, uint32_t slot8, uint32_t hoff, const CUtensorMap* tm, int c1, int c2) {
    mbar_expect_tx(sb + B_R1 + slot8, 8192);
    tma3(sb + slot8 * 2048 + hoff, tm, 0, c1, c2, sb + B_R1 + slot8);
}
__device__ __forceinline__ void ring_full(uint32_t sb, uint32_t slot8, const CUtensorMap* tm, int c1, int c2) {
    mbar_expect_tx(sb + B_R1 + slot8, 16384);
    mbar_arrive(sb + B_R1 + slot8);
    tma3(sb + slot8 * 2048, tm, 0, c1, c2, sb + B_R1 + slot8);
}
__device__ __forceinline__ void cta_done(int mode) {
    if (mode == 0 && atomicAdd(&g_sync[4], 1) == NCTA + 1) {
#pragma unroll
        for (int i = 0; i < 5; i++) g_sync[i] = 0;
    }
}

__device__ __forceinline__ void fold_cta(const Maps& mp, uint32_t sb, int mode) {
    constexpr uint32_t F_FULL = MISC, F_EMPTY = MISC + 32, F_T1 = MISC + 64, STG = 49152, FOUT = 3 * STG;
    const int tid = threadIdx.x, f = blockIdx.x - NCTA;
    if (mode == 2) return;
    if (tid == 0) {
        for (int i = 0; i < 3; i++) { mbar_init(sb + F_FULL + 8 * i, 1); mbar_init(sb + F_EMPTY + 8 * i, 2); }
        mbar_init(sb + F_T1, 2);
        asm volatile("fence.mbarrier_init.release.cluster;" ::: "memory");
        fence_async();
    }
    __syncthreads();
    const int wg = __shfl_sync(0xffffffffu, tid >> 7, 0);
    int st = 0, ph = 0;
    if (wg == 0) {
        if (tid == 0) {
#pragma unroll 1
            for (int it = 0; it < 96; it++) {
                const int p = it >> 3, kc = it & 7, job = p >> 2;
                if (it == 64) mbar_wait(sb + F_T1, 0);
                mbar_wait(sb + F_EMPTY + 8 * st, ph ^ 1);
                mbar_expect_tx(sb + F_FULL + 8 * st, STG);
                tma3(sb + st * STG, &mp.fa[job], 0, 256 * f + 128 * ((p >> 1) & 1), kc, sb + F_FULL + 8 * st);
                tma3(sb + st * STG + 16384, &mp.fb[job != 0], 0, 64 * kc + (job == 1 ? 512 : 0), 4 * (p & 1), sb + F_FULL + 8 * st);
                if (++st == 3) { st = 0; ph ^= 1; }
            }
        }
        return;
    }
    const int h = wg - 1, lane = tid & 31, w = (tid >> 5) & 3;
    const uint32_t sd = (sb & 0x3FFFF) >> 4;
    const bool el = (tid & 127) == 0;
#pragma unroll 1
    for (int p = 0; p < 12; p++) {
        float acc[128];
        fresh(acc);
#pragma unroll 1
        for (int kc = 0; kc < 8; kc++) {
            mbar_wait(sb + F_FULL + 8 * st, ph);
            wg_fence();
#pragma unroll
            for (int kk = 0; kk < 4; kk++)
                wgmma_ss_n256_tb1(acc, dsc(sd, st * STG + h * 8192 + kk * 32, 16), dsc(sd, st * STG + 16384 + kk * 2048, 8192), 1);
            wg_commit();
            wg_wait<0>();
            if (el) mbar_arrive(sb + F_EMPTY + 8 * st);
            if (++st == 3) { st = 0; ph ^= 1; }
        }
        pin(acc);
        const int job = p >> 2;
        if (el) {
            asm volatile("cp.async.bulk.wait_group 0;" ::: "memory");
            if (p == 4) { fence_async_g(); mbar_arrive(sb + F_T1); }
        }
        bar_sync(3 + h, 128);
        uint32_t r = 16 * w + (lane & 7) + ((lane >> 3) & 1) * 8;
        const float fs = job == 1 ? 0.5f : 1.f;
        if (job == 1) r = (r & ~31) | (((r >> 1) & 3) << 3) | (((r >> 3) & 3) << 1) | (r & 1);
        const uint32_t oa = sb + FOUT + h * 32768 + r * 128 + ((((lane >> 4) ^ r) & 7) << 4);
#pragma unroll
        for (int i = 0; i < 16; i++)
            stsm4((oa ^ ((i & 3) << 5)) + (i >> 2) * 8192, pack2(acc[8 * i] * fs, acc[8 * i + 1] * fs), pack2(acc[8 * i + 2] * fs, acc[8 * i + 3] * fs),
                  pack2(acc[8 * i + 4] * fs, acc[8 * i + 5] * fs), pack2(acc[8 * i + 6] * fs, acc[8 * i + 7] * fs));
        fence_async();
        bar_sync(3 + h, 128);
        if (el) {
            const int row0 = 256 * f + 128 * ((p >> 1) & 1) + 64 * h + (job == 1 ? 512 : 0);
            if (job == 0) tma3_store(&mp.fc, sb + FOUT + h * 32768, 0, row0, 4 * (p & 1));
            else {
#pragma unroll 1
                for (int i = 0; i < 16; i++)
                    bulk_st((char*)g_wepi + (row0 / 8 + 2 * (i & 3) + (p & 1)) * 8192 + (i >> 2) * 2048, sb + FOUT + h * 32768 + i * 2048, 2048);
            }
            asm volatile("cp.async.bulk.commit_group;" ::: "memory");
        }
    }
    if (el) {
        asm volatile("cp.async.bulk.wait_group 0;" ::: "memory");
        fence_async_g();
        if (mode == 0) flag_add(&g_sync[3]);
    }
    bar_sync(2, 256);
    if (tid == 128) cta_done(mode);
}

__global__ void __launch_bounds__(384, 1) main_kernel(const __grid_constant__ Maps mp, const bf16* __restrict__ x, const bf16* __restrict__ dw, const bf16* wup, const int mode) {
    extern __shared__ __align__(1024) uint8_t smem[];
    const uint32_t sb = smem_u32(smem);
    const int tid = threadIdx.x;
    PE();
    if (blockIdx.x >= NCTA) { fold_cta(mp, sb, mode); return; }
    const int b = blockIdx.x / TPB, ti = blockIdx.x % TPB;
    const int piece = blockIdx.x & 127;
    const int wg = __shfl_sync(0xffffffffu, tid >> 7, 0);
    const int lane = tid & 31, w = (tid >> 5) & 3;
    const bool w0 = __shfl_sync(0xffffffffu, w, 0) == 0;
    const uint32_t sd = (sb & 0x3FFFF) >> 4;
    const uint32_t adA = sd + (AT >> 4) + (1u << 16);
    const uint32_t bd0 = sd;
    const uint32_t bd2k = bd0 + ((2048u >> 4) << 16);
    const bool el = (tid & 127) == 0;
    const uint32_t lrow = 16 * w + (lane & 7) + ((lane >> 3) & 1) * 8;
    const uint32_t loff = lrow * 128 + ((((lane >> 4) ^ lrow) & 7) << 4);
    const int r0 = 16 * w + (lane >> 2);

    if (wg == 0) {
        asm volatile("setmaxnreg.inc.sync.aligned.u32 " RG0 ";");
        uint32_t q[112];
        PG(206);
        if (tid == 0) {
            mbar_init(sb + B_MK, 1);
            for (int i = 0; i < 9; i++) mbar_init(sb + B_R1 + 8 * i, 2);
            for (int i = 0; i < 5; i++) asm volatile("st.shared.u32 [%0], 0;" ::"r"(sb + CNT + 4 * i) : "memory");
        } else if (tid == 32) {
            mbar_init(sb + B_LN, 1); mbar_init(sb + B_MQ, 1); mbar_init(sb + B_GN, 8);
            mbar_init(sb + B_H1, 2); mbar_init(sb + B_H2, 1); mbar_init(sb + B_H3, 2);
            for (int i = 0; i < 3; i++) { mbar_init(sb + B_KV + 8 * i, 2); mbar_init(sb + B_P + 8 * i, 4); mbar_init(sb + B_GO + 8 * i, 4); }
            mbar_init(sb + B_UC, 1); mbar_init(sb + B_UC + 8, 1); mbar_init(sb + B_X, 8);
        } else if (tid == 64) {
            for (int i = 0; i < 20; i++) mbar_init(sb + B_R2 + 8 * i, 1);
        } else if (tid == 96) {
            for (int i = 0; i < 20; i++) mbar_init(sb + B_E2 + 8 * i, 4);
        }
        if (lane == 0) {
            asm volatile("fence.mbarrier_init.release.cluster;" ::: "memory");
            fence_async();
        }
        PG(207);
        __syncwarp();
        if (SU != 2) asm volatile("bar.arrive 5, 384;" ::: "memory");
        if (tid == 0) {
            mbar_expect_tx(sb + B_MK, 65536 + 32768);
            tma3(sb + 16384, &mp.wq, 0, 64 * (piece >> 4), 0, sb + B_MK);
            tma3(sb + 81920, &mp.wk, 0, 32 * (piece & 15), 0, sb + B_MK);
            for (int i = 0; i < 14; i++) mbar_arrive(sb + B_R1 + 8 * (i >> 1));
            if (mode != 1) {
                ring_full(sb, 56, &mp.wup8, 0, 8);
                ring_full(sb, 64, &mp.wup8, 16, 8);
                ring_full(sb, 0, &mp.wup8, 32, 8);
            }
        }
        PG(208);
        bar_sync(1, 128);
        if (SU == 2) asm volatile("bar.arrive 5, 384;" ::: "memory");
        PT(0);
        PG(200);
        {
            float mq[16];
            fresh(mq);
            mbar_wait(sb + B_MK, 0);
            PT(1);
            if (tid == 32) l2_prefetch((const char*)wup + piece * 8192, 8192);
            wg_fence();
#pragma unroll 1
            for (int c = 0; c < 8; c++)
#pragma unroll
                for (int kk = 0; kk < 4; kk++)
                    wgmma_ss_n32_tb0(mq, dsc(sd, 16384 + c * 8192 + kk * 32, 16), dsc(sd, 81920 + c * 4096 + kk * 32, 16), 1);
            wg_commit();
            wg_wait<0>();
            if (mode != 1 && w0 && elect1()) {
#pragma unroll 1
                for (int i = 1; i < 7; i++) ring_full(sb, 8 * i, &mp.wup8, 32 + 16 * i, 8);
            }
            pin(mq);
            uint32_t* c = reinterpret_cast<uint32_t*>(g_mqk + (64 * (piece >> 4) + r0) * D_ + 32 * (piece & 15) + 2 * (lane & 3));
#pragma unroll
            for (int n = 0; n < 4; n++) { c[4 * n] = pack2(mq[4 * n], mq[4 * n + 1]); c[4 * n + 4 * D_] = pack2(mq[4 * n + 2], mq[4 * n + 3]); }
            fence_async_g();
            bar_sync(1, 128);
            if (el) {
                if (mode == 0) flag_add(&g_sync[2]);
                if (mode == 0) flag_wait(&g_sync[2], NCTA);
                mbar_arrive(sb + B_MQ);
                PG(203);
                PT(12);
                mbar_wait(sb + B_LN, 0);
#pragma unroll 1
                for (int c = 0; c < 8; c++) {
                    tma4_store(&mp.xas, sb + AT + c * 8192, 0, 62 * ti, c, b);
                    const unsigned t0 = (unsigned)clock();
                    while (c < 7 && (unsigned)clock() - t0 < XS_GAP) __nanosleep(20);
                }
                asm volatile("cp.async.bulk.commit_group;" ::: "memory");
                if (mode == 1) asm volatile("cp.async.bulk.wait_group 0;" ::: "memory");
            }
            PT(13);
            if (mode == 1) return;
        }
        mbar_wait(sb + B_H1, 0);
        PT(2);
        uint32_t slot8 = 24, par = 0, prev8 = 0, prev2 = 0;
        auto adv = [&]() { prev2 = prev8; prev8 = slot8; slot8 += 8; if (slot8 == 72) { slot8 = 0; par ^= 1; } };
        {
            float acc[128];
            fresh(acc);
            auto step = [&](int i) {
                const uint32_t aa = adA + (i >> 1) * 512 + (i & 1) * 4, bb = bd0 + ((4096u >> 4) << 16) + slot8 * 128;
                wg_fence();
                wgmma_ss_n256_tb1(acc, mkd(aa), mkd(bb), 1);
                wgmma_ss_n256_tb1(acc, mkd(aa + 2), mkd(bb + 128), 1);
                wg_commit();
                wg_wait<1 + LAGA>();
            };
#pragma unroll 1
            for (int i = 0; i < 8 + LAGA; i++) {
                mbar_wait(sb + B_R1 + slot8, par);
                step(i);
                if (i > LAGA && w0 && elect1()) ring_full(sb, LAGA ? prev2 : prev8, &mp.mqa4, 32 * (i - LAGA) + 256, 4);
                adv();
            }
#pragma unroll 1
            for (int i = 8 + LAGA; i < 16; i++) {
                mbar_wait(sb + B_R1 + slot8, par);
                if (i == 15 && el) mbar_arrive(sb + B_H2);
                step(i);
                if (w0 && elect1()) ring_full(sb, LAGA ? prev2 : prev8, &mp.wup8, 16 * (i - LAGA) - 128, 0);
                adv();
            }
            if (LAGA) {
                wg_wait<1>();
                if (w0 && elect1()) ring_full(sb, prev2, &mp.wup8, 112, 0);
            }
            wg_wait<0>();
            if (w0 && elect1()) ring_full(sb, prev8, &mp.wup8, 128, 0);
            pin(acc);
            PT(3);
#pragma unroll
            for (int kk = 0; kk < 4; kk++)
                stsm4((sb + QS + loff) ^ (kk << 5), pack2(acc[96 + 8 * kk], acc[97 + 8 * kk]), pack2(acc[98 + 8 * kk], acc[99 + 8 * kk]),
                      pack2(acc[100 + 8 * kk], acc[101 + 8 * kk]), pack2(acc[102 + 8 * kk], acc[103 + 8 * kk]));
            fence_async();
#pragma unroll
            for (int i = 47; i >= 0; i--) q[64 + i] = pack2v(acc[2 * i], acc[2 * i + 1]);
        }
        if (el) {
            asm volatile("cp.async.bulk.wait_group 0;" ::: "memory");
            if (mode == 0) {
                fence_async_g();
                flag_add(&g_sync[b]);
                flag_wait(&g_sync[b], TPB);
            }
        }
        __syncwarp();
        mbar_wait(sb + B_H3, 0);
        PT(4);
        slot8 = 48; par = 1;
#pragma unroll
        for (int half = 0; half < 2; half++) {
            float acc[64];
            fresh(acc);
            auto step = [&](int m) {
                const uint32_t aa = adA + m * 512, bb = bd0 + ((8192u >> 4) << 16) + slot8 * 128;
                mbar_wait(sb + B_R1 + slot8, par);
                wg_fence();
#pragma unroll
                for (int kk = 0; kk < 4; kk++) wgmma_ss_n128_tb1(acc, mkd(aa + 2 * kk), mkd(bb + 128 * kk), 1);
                wg_commit();
                wg_wait<1 + LAGB>();
            };
#pragma unroll 1
            for (int m = 0; m < 8; m++) {
                step(m);
                if (half == 1 && m == GST) asm volatile("bar.arrive 6, 384;" ::: "memory");
                if (m > LAGB && w0 && elect1()) {
                    if (half == 0) ring_full(sb, LAGB ? prev2 : prev8, &mp.mqb2, 64 * (m - LAGB), 2);
                    else if (m < 4 + LAGB) tma4(sb + (LAGB ? prev2 : prev8) * 2048, &mp.xa2, 0, 0, 2 * (m - LAGB), b, sb + B_KV + 8);
                }
                adv();
            }
            if (LAGB && half == 0) {
                wg_wait<1>();
                if (w0 && elect1()) ring_full(sb, prev2, &mp.mqb2, 448, 2);
            }
            wg_wait<0>();
            if (w0 && elect1()) {
                if (half == 0) {
                    mbar_expect_tx(sb + B_KV + 8, 65536);
                    for (int i = 0; i < 3; i++) mbar_arrive(sb + B_KV + 8 * i);
                    tma4(sb + prev8 * 2048, &mp.xa2, 0, 0, 0, b, sb + B_KV + 8);
                } else {
                    mbar_expect_tx(sb + B_KV + 16, 65536);
                    tma4(sb + R2, &mp.xa, 0, 64, 0, b, sb + B_KV + 16);
                    mbar_expect_tx(sb + B_KV, 65536);
                    tma4(sb + R0, &mp.xa, 0, 128, 0, b, sb + B_KV);
                }
            }
            if (half == 1 && GST == 8) asm volatile("bar.arrive 6, 384;" ::: "memory");
            pin(acc);
#pragma unroll
            for (int i = 31; i >= 0; i--) q[32 * half + i] = pack2v(acc[2 * i], acc[2 * i + 1]);
        }
        bar_sync(1, 128);
        PT(5);

        const float CS = 0.04419417382415922f * 1.4426950408889634f;
        float m0 = -INFINITY, m1 = -INFINITY, l0 = 0.f, l1 = 0.f;
        int s = 0, sn = 1, ph = 0;
        float S[32];
        const bool l0w = lane == 0, q0 = (lane & 3) == 0;
#pragma unroll 1
        for (int j = -1;; j++) {
            if (j >= 0) {
                PL(j, 1);
                if (j == NKV - 1) {
#pragma unroll
                    for (int i = (T_ - 64 * (NKV - 1)) / 2; i < 32; i++) asm volatile("mov.b32 %0, 0xff800000;" : "=f"(S[i]));
                }
                const bool kv = mbar_test(sb + B_KV + sn * 8, ph);
                const uint32_t pb = sb + R3 + (s == 0 ? 2 : s - 1) * 8192;
                float a0, a1, sc0 = 1.f, sc1 = 1.f;
                auto expo = [&]() {
                    const float n0 = -m0 * CS, n1 = -m1 * CS;
                    a0 = 0.f; a1 = 0.f;
#pragma unroll
                    for (int kk = 0; kk < 4; kk++) {
                        float p[8];
#pragma unroll
                        for (int e = 0; e < 8; e++) p[e] = ex2(fmaf(S[8 * kk + e], CS, (e & 2) ? n1 : n0));
                        a0 += (p[0] + p[1]) + (p[4] + p[5]);
                        a1 += (p[2] + p[3]) + (p[6] + p[7]);
                        stsm4((pb + loff) ^ (kk << 5), pack2(p[0], p[1]), pack2(p[2], p[3]), pack2(p[4], p[5]), pack2(p[6], p[7]));
                    }
                };
                expo();
                if (__any_sync(0xffffffffu, !(a0 <= LAZY) || !(a1 <= LAZY))) {
                    float x0 = m0, x1 = m1;
#pragma unroll
                    for (int n = 0; n < 8; n++) { x0 = fmaxf(x0, fmaxf(S[4 * n], S[4 * n + 1])); x1 = fmaxf(x1, fmaxf(S[4 * n + 2], S[4 * n + 3])); }
                    x0 = fmaxf(x0, __shfl_xor_sync(0xffffffffu, x0, 1));
                    x1 = fmaxf(x1, __shfl_xor_sync(0xffffffffu, x1, 1));
                    x0 = fmaxf(x0, __shfl_xor_sync(0xffffffffu, x0, 2));
                    x1 = fmaxf(x1, __shfl_xor_sync(0xffffffffu, x1, 2));
                    sc0 = ex2((m0 - x0) * CS); sc1 = ex2((m1 - x1) * CS);
                    m0 = x0; m1 = x1;
                    expo();
                }
                if (q0) { sts_f32(sb + SCL + s * 256 + r0 * 4, sc0); sts_f32(sb + SCL + s * 256 + r0 * 4 + 32, sc1); }
                __syncwarp();
                if (l0w) mbar_arrive(sb + B_P + s * 8);
                l0 = fmaf(l0, sc0, a0); l1 = fmaf(l1, sc1, a1);
                PL(j, 2);
                if (j == NKV - 1) break;
                if (!kv) mbar_wait(sb + B_KV + sn * 8, ph);
            } else {
                mbar_wait(sb + B_KV + 8, 0);
            }
            float Sn[32];
            const uint32_t kd = sd + sn * 4096;
            wg_fence();
#pragma unroll
            for (int kk = 0; kk < 28; kk++) {
                wgmma_rs_n64_tb0(Sn, q[4 * kk], q[4 * kk + 1], q[4 * kk + 2], q[4 * kk + 3], dsc(kd, (kk >> 2) * 8192 + (kk & 3) * 32, 16), kk > 0);
                if (kk == FENCE_AT) { fence_async(); __syncwarp(); }
                if (kk == GO_AT) { PL(j, 3); if (j >= 0 && l0w) mbar_arrive(sb + B_GO + s * 8); }
            }
#pragma unroll
            for (int kk = 0; kk < 4; kk++)
                wgmma_ss_n64_tb0(Sn, dsc(sd, QS + kk * 32, 16), dsc(kd, 7 * 8192 + kk * 32, 16), 1);
            wg_commit();
            PL(j, 0);
            wg_wait<0>();
            pin(Sn);
#pragma unroll
            for (int i = 0; i < 32; i++) S[i] = Sn[i];
            s = sn;
            if (++sn == 3) sn = 0;
            if (sn == 1) ph ^= 1;
        }
        l0 += __shfl_xor_sync(0xffffffffu, l0, 1); l1 += __shfl_xor_sync(0xffffffffu, l1, 1);
        l0 += __shfl_xor_sync(0xffffffffu, l0, 2); l1 += __shfl_xor_sync(0xffffffffu, l1, 2);
        if (q0) { sts_f32(sb + LINV + r0 * 4, rcp(l0)); sts_f32(sb + LINV + r0 * 4 + 32, rcp(l1)); }
        fence_async();
        __syncwarp();
        if (l0w) {
            mbar_arrive(sb + B_GO + s * 8);
            uint32_t slot8 = 8 * w, par = 0;
#pragma unroll 1
            for (int n = 20 + w; n < 136; n += 4) {
                mbar_wait(sb + B_E2 + slot8, par);
                if (n < 128) ring_ld(sb, slot8, n);
                else {
                    mbar_expect_tx(sb + B_X, 8192);
                    tma4(sb + R1 + slot8 * 1024, &mp.x, 0, 62 * ti, n - 128, b, sb + B_X);
                }
                slot8 += 32;
                if (slot8 >= 160) { slot8 -= 160; par ^= 1; }
            }
        }
        PDUMP();
    } else {
        if (RG0[2] == '4') asm volatile("setmaxnreg.dec.sync.aligned.u32 160;");
        const int h = wg - 1;
        uint32_t v[4][8], v2[4][8];
        if (SU != 0) bar_sync(5, 384);
        PG(206);
#pragma unroll
        for (int i = 0; i < 8; i++) {
            const int t = 62 * ti - 1 + 32 * (i >> 2) + 16 * h + 4 * w + (i & 3);
            const uint4* p = reinterpret_cast<const uint4*>(x + ((size_t)b * T_ + t) * D_) + lane;
            uint32_t* d = i < 4 ? v[i & 3] : v2[i & 3];
#pragma unroll
            for (int c = 0; c < 2; c++)
                asm volatile("{\n.reg .pred p;\nsetp.lt.u32 p, %5, %6;\nmov.b32 %0, 0;\nmov.b32 %1, 0;\nmov.b32 %2, 0;\nmov.b32 %3, 0;\n"
                             "@p ld.global.nc.v4.u32 {%0, %1, %2, %3}, [%4];\n}\n"
                             : "=r"(d[4 * c]), "=r"(d[4 * c + 1]), "=r"(d[4 * c + 2]), "=r"(d[4 * c + 3]) : "l"(p + 32 * c), "r"(t), "n"(T_));
        }
#pragma unroll 1
        for (int bt = 0; bt < 2; bt++) {
            PT(0);
            float a[8];
            const uint32_t la = sb + AT + (lane >> 3) * 8192 + (32 * bt + 16 * h + 4 * w) * 128 + (((lane & 7) ^ ((w & 1) * 4)) << 4);
            const bool b4 = lane & 16, b3 = lane & 8, b2 = lane & 4;
#pragma unroll
            for (int r = 0; r < 4; r++) {
                float c[4] = {0.f, 0.f, 0.f, 0.f};
#pragma unroll
                for (int i = 0; i < 8; i += 2) hmma(c, v[r][i], v[r][i], v[r][i + 1], v[r][i + 1], v[r][i], v[r][i + 1]);
                a[4 + r] = (lane & 3) == (lane >> 3) ? (b2 ? c[1] : c[0]) : 0.f;
                if (r & 1) {
                    float e[4] = {0.f, 0.f, 0.f, 0.f};
#pragma unroll
                    for (int i = 0; i < 8; i += 2) hmma(e, v[r - 1][i], v[r][i], v[r - 1][i + 1], v[r][i + 1], 0x3f803f80u, 0x3f803f80u);
                    a[r - 1] = e[0]; a[r] = e[2];
                }
            }
            float k[4];
#pragma unroll
            for (int i = 0; i < 4; i++) {
                const int lo = (i & 1) + 4 * (i >> 1);
                k[i] = (b4 ? a[lo + 2] : a[lo]) + __shfl_xor_sync(0xffffffffu, b4 ? a[lo] : a[lo + 2], 16);
            }
            const float k0 = (b3 ? k[1] : k[0]) + __shfl_xor_sync(0xffffffffu, b3 ? k[0] : k[1], 8);
            const float k1 = (b3 ? k[3] : k[2]) + __shfl_xor_sync(0xffffffffu, b3 ? k[2] : k[3], 8);
            float z = (b2 ? k1 : k0) + __shfl_xor_sync(0xffffffffu, b2 ? k0 : k1, 4);
            z += __shfl_xor_sync(0xffffffffu, z, 2);
            z += __shfl_xor_sync(0xffffffffu, z, 1);
            const float zo = __shfl_xor_sync(0xffffffffu, z, 4);
            PG(204 + bt);
            const float mu = (b2 ? zo : z) * (0.25f / D_);
            float sd_ = bfr(bfr(fmaxf(fmaf(b2 ? z : zo, 1.f / D_, -mu * mu), 0.f)) + 1e-5f);
            asm("sqrt.approx.f32 %0, %0;" : "+f"(sd_));
            const float ri = rcp(bfr(sd_));
            const uint32_t w1 = pack2(mu, ri), w2 = pack2(ri - bhi(w1), ri - bhi(w1));
#pragma unroll
            for (int r = 0; r < 4; r++) {
                const uint32_t s1 = __shfl_sync(0xffffffffu, w1, 8 * r), rl = __shfl_sync(0xffffffffu, w2, 8 * r);
                const uint32_t m2 = __byte_perm(s1, 0, 0x1010), rh = __byte_perm(s1, 0, 0x3232);
#pragma unroll
                for (int i = 0; i < 8; i++) { const uint32_t d = bsub2(v[r][i], m2); v[r][i] = bfma2(d, rh, bmul2(d, rl)); }
                sts4((la ^ (r << 4)) + r * 128, v[r][0], v[r][1], v[r][2], v[r][3]);
                sts4((la ^ (r << 4)) + r * 128 + 32768, v[r][4], v[r][5], v[r][6], v[r][7]);
#pragma unroll
                for (int i = 0; i < 8; i++) v[r][i] = v2[r][i];
            }
        }
        fence_async();
        if (SU == 0) bar_sync(5, 384); else bar_sync(2, 256);
        if (tid == 128) mbar_arrive(sb + B_LN);
        PG(202);
        if (mode == 1) return;
        float acc[128];
#pragma unroll
        for (int pass = 0; pass < 2; pass++) {
            if (pass == 1) mbar_wait(sb + B_H2, 0);
            PT(1 + 3 * pass);
            fresh(acc);
            uint32_t slot8 = pass ? 8 : 56, par = 0, prev8 = 0;
            auto adv = [&]() { prev8 = slot8; slot8 += 8; if (slot8 == 72) { slot8 = 0; par ^= 1; } };
            auto step = [&](int kk) {
                wg_fence();
                wgmma_ss_n256_tb1(acc, mkd(adA + (kk >> 2) * 512 + (kk & 3) * 2), mkd(bd2k + h * 512 + slot8 * 128), 1);
                wg_commit();
                wg_wait<1>();
            };
#pragma unroll 1
            for (int kk = 0; kk < 24; kk++) {
                mbar_wait(sb + B_R1 + slot8, par);
                step(kk);
                if (kk > 0 && w0 && elect1()) ring_half(sb, prev8, h * 8192, &mp.wup4, 16 * kk + 128, (pass ? 0 : 8) + 4 * h);
                adv();
            }
            if (pass == 0 && w0) mbar_wait(sb + B_MQ, 0);
#pragma unroll 1
            for (int kk = 24; kk < 32; kk++) {
                mbar_wait(sb + B_R1 + slot8, par);
                if (kk == 31 && el) mbar_arrive(sb + (pass ? B_H3 : B_H1));
                step(kk);
                if (w0 && elect1()) ring_half(sb, prev8, h * 8192, pass ? &mp.mqb1 : &mp.mqa2, (pass ? 64 : 32) * (kk - 24), pass ? h : 4 + 2 * h);
                adv();
            }
            wg_wait<0>();
            if (w0 && elect1()) ring_half(sb, prev8, h * 8192, pass ? &mp.mqb1 : &mp.mqa2, pass ? 0 : 256, pass ? 2 + h : 4 + 2 * h);
            pin(acc);
            PT(2 + 3 * pass);
            bf16* ucp = g_uc + ((size_t)blockIdx.x * 128 + (pass ? 0 : 64) + r0) * D_ + 256 * h + 8 * (lane & 3);
#pragma unroll
            for (int m = 0; m < 8; m++) {
                const float* a_ = acc + 16 * m;
                stg4(ucp + 32 * m, pack2(a_[0], a_[1]), pack2(a_[4], a_[5]), pack2(a_[8], a_[9]), pack2(a_[12], a_[13]));
                stg4(ucp + 8 * D_ + 32 * m, pack2(a_[2], a_[3]), pack2(a_[6], a_[7]), pack2(a_[10], a_[11]), pack2(a_[14], a_[15]));
            }
            if (pass) bar_sync(2, 256);
            PT(3 + 3 * pass);
        }
        {
            uint32_t* gp = reinterpret_cast<uint32_t*>(g_uc + ((size_t)blockIdx.x * 128 + 64 + 32 * h + 8 * w + (lane >> 2)) * D_) + 4 * (lane & 3);
            uint32_t e[64];
#pragma unroll
            for (int c = 0; c < 16; c++) ldg4_cg(gp + 16 * c, e + 4 * c);
            bar_sync(6, 384);
            PT(12);
            float sm[2] = {0.f, 0.f}, sq[2] = {0.f, 0.f};
#pragma unroll
            for (int c = 0; c < 16; c++) {
#pragma unroll
                for (int i = 4 * c; i < 4 * c + 4; i++) {
                    const float lo = gelu2(blo(e[i])), hi = gelu2(bhi(e[i]));
                    sm[i & 1] += lo + hi; sq[i & 1] = fmaf(lo, lo, fmaf(hi, hi, sq[i & 1]));
                    e[i] = pack2(lo, hi);
                }
                stg4(gp + 16 * c, e[4 * c], e[4 * c + 1], e[4 * c + 2], e[4 * c + 3]);
            }
            float s1 = sm[0] + sm[1], s2 = sq[0] + sq[1];
            s1 += __shfl_xor_sync(0xffffffffu, s1, 1); s2 += __shfl_xor_sync(0xffffffffu, s2, 1);
            s1 += __shfl_xor_sync(0xffffffffu, s1, 2); s2 += __shfl_xor_sync(0xffffffffu, s2, 2);
            s1 *= 1.f / 512.f;
            s2 = rsqrtf(fmaxf(fmaf(-s1, s1, s2 * (1.f / 512.f)), 0.f) + 4e-5f);
            const uint32_t a = sb + STAT + (32 * h + 8 * w + (lane >> 2)) * 8;
            if ((lane & 3) == 0) { sts_f32(a, s2); sts_f32(a + 4, -s1 * s2); }
            __syncwarp();
            if (lane == 0) mbar_arrive(sb + B_GN);
            PT(13);
        }
        int s = 1, ph = 0;
        uint32_t* cp = reinterpret_cast<uint32_t*>(g_uc + ((size_t)blockIdx.x * 128 - 1) * D_) + (tid - 128);
        const uint32_t* dp = reinterpret_cast<const uint32_t*>(dw) + (((tid - 128) & ~15) | ((lane & 3) << 2) | ((lane >> 2) & 3));
        const uint32_t d0 = ldg_v(dp), d1 = ldg_v(dp + D_ / 2), d2 = ldg_v(dp + D_);
        uint32_t e[6] = {0, 0, 0, 0, 0, 0};
        auto conv = [&](int j) {
            if (j >= CV0 && j < CV0 + 32) {
                uint32_t st[4];
                lds4(sb + STAT + (j - CV0) * 16, st);
                const uint32_t ua = pack2(gelu2(blo(e[4])), gelu2(bhi(e[4]))), ub = pack2(gelu2(blo(e[5])), gelu2(bhi(e[5])));
                e[2] = pack2(fmaf(blo(e[2]), __uint_as_float(st[0]), __uint_as_float(st[1])), fmaf(bhi(e[2]), __uint_as_float(st[0]), __uint_as_float(st[1])));
                e[3] = pack2(fmaf(blo(e[3]), __uint_as_float(st[2]), __uint_as_float(st[3])), fmaf(bhi(e[3]), __uint_as_float(st[2]), __uint_as_float(st[3])));
                if (j > CV0) {
                    asm volatile("st.global.u32 [%0], %1;" ::"l"(cp), "r"(bmul2(ua, bfma2(e[2], d2, bfma2(e[1], d1, bmul2(e[0], d0))))) : "memory");
                    asm volatile("st.global.u32 [%0], %1;" ::"l"(cp + D_ / 2), "r"(bmul2(ub, bfma2(e[3], d2, bfma2(e[2], d1, bmul2(e[1], d0))))) : "memory");
                }
                e[0] = e[2]; e[1] = e[3];
                cp += D_;
            }
        };
        fresh(acc);
#pragma unroll 1
        for (int j = 0; j < NKV; j++) {
            if (j >= CV0 && j < CV0 + 32) {
                if (j == CV0) mbar_wait(sb + B_GN, 0);
                e[2] = ldg_cg(cp + 65 * (D_ / 2)); e[3] = ldg_cg(cp + 66 * (D_ / 2));
                if (j > CV0) { e[4] = ldg_cg(cp); e[5] = ldg_cg(cp + D_ / 2); }
            }
            mbar_wait(sb + B_P + s * 8, ph);
            PL(j, 0);
            if (j > 0) {
                const float sc0 = lds_f32(sb + SCL + s * 256 + r0 * 4), sc1 = lds_f32(sb + SCL + s * 256 + r0 * 4 + 32);
                if (__any_sync(0xffffffffu, sc0 != 1.f || sc1 != 1.f)) {
#pragma unroll
                    for (int n = 0; n < 32; n++) { acc[4 * n] *= sc0; acc[4 * n + 1] *= sc0; acc[4 * n + 2] *= sc1; acc[4 * n + 3] *= sc1; }
                }
            }
            mbar_wait(sb + B_GO + s * 8, ph);
            PL(j, 1);
            const uint32_t vd = sd + s * 4096 + h * 2048, pd = sd + (s == 0 ? 2 : s - 1) * 512;
            pin(acc);
            wg_fence();
#pragma unroll
            for (int kk = 0; kk < 4; kk++) wgmma_ss_n256_tb1(acc, dsc(pd, R3 + kk * 32, 16), dsc(vd, kk * 2048, 8192), 1);
            wg_commit();
            conv(j);
            wg_wait<0>();
            pin(acc);
            PL(j, 2);
            if (w0 && elect1()) {
                if (j + 3 < NKV) {
                    mbar_expect_tx(sb + B_KV + s * 8, 32768);
                    tma4(sb + s * 65536 + h * 32768, &mp.xa4, 0, 64 * (j + 3), 4 * h, b, sb + B_KV + s * 8);
                } else if (j < NKV - 1) {
                    const int n0 = (j == NKV - 3 ? 0 : 8) + 4 * h;
#pragma unroll 1
                    for (int n = n0; n < n0 + 4; n++) ring_ld(sb, n * 8, n);
                }
                if (j == NKV - 5 && mode == 0) flag_wait(&g_sync[3], 4);
                if (j >= XPF && j < XPF + 4) {
                    const int t0 = 62 * ti + 32 * h + 8 * (j - XPF), nr = min(8, T_ - t0);
                    if (nr > 0) l2_prefetch(x + ((size_t)b * T_ + t0) * D_, nr * 1024);
                }
            }
            if (++s == 3) s = 0;
            if (s == 1) ph ^= 1;
        }
        {
            const float i0 = lds_f32(sb + LINV + r0 * 4), i1 = lds_f32(sb + LINV + r0 * 4 + 32);
#pragma unroll
            for (int p = 0; p < 16; p++)
                stsm4(((sb + R0 + h * 32768 + loff) ^ ((p & 3) << 5)) + (p >> 2) * 8192,
                      pack2(acc[8 * p] * i0, acc[8 * p + 1] * i0), pack2(acc[8 * p + 2] * i1, acc[8 * p + 3] * i1),
                      pack2(acc[8 * p + 4] * i0, acc[8 * p + 5] * i0), pack2(acc[8 * p + 6] * i1, acc[8 * p + 7] * i1));
        }
        fence_async();
        fence_async_g();
        bar_sync(2, 256);
        if (lane == 0 && w < 2) ring_ld(sb, 128 + 16 * w + 8 * h, 16 + 2 * w + h);
        PT(7);
        fresh(acc);
        {
            uint32_t slot8 = 8 * h, par = 0, prev8 = 0;
#pragma unroll 1
            for (int kk = 0; kk < 64; kk++) {
                if (kk == 32 || kk == 48) mbar_wait(sb + B_UC + (kk >> 1 & 8), 0);
                mbar_wait(sb + B_R2 + slot8, par);
                wg_fence();
                wgmma_ss_n256_tb1(acc, mkd(sd + (1u << 16) + (R0 >> 4) + (kk >> 2 & 7) * 512 + (kk & 3) * 2), mkd(bd2k + (R1 >> 4) + slot8 * 64), 1);
                wg_commit();
                wg_wait<1>();
                if (kk > 0 && lane == 0) mbar_arrive(sb + B_E2 + prev8);
                if ((kk == 16 || kk == 32) && w0 && elect1() && (atom_inc_s(sb + CNT + 12 + (kk >> 3 & 4)) & 1)) {
                    mbar_expect_tx(sb + B_UC + (kk >> 2 & 8), 32768);
                    tma3(sb + R0 + (kk & 32) * 1024, &mp.uc, 0, 128 * blockIdx.x, kk >> 3 & 4, sb + B_UC + (kk >> 2 & 8));
                }
                prev8 = slot8;
                slot8 += 16;
                if (slot8 >= 160) { slot8 -= 160; par ^= 1; }
            }
        }
        wg_wait<0>();
        pin(acc);
        PT(8);
        mbar_wait(sb + B_X, 0);
        PT(9);
        {
            const uint32_t sr = (lrow + 63) & 63;
            const uint32_t xoff = sr * 128 + ((((lane >> 4) ^ sr) & 7) << 4);
#pragma unroll
            for (int p = 0; p < 16; p++) {
                const uint32_t a = ((sb + R2 + h * 32768 + xoff) ^ ((p & 3) << 5)) + (p >> 2) * 8192;
                uint32_t xv[4];
                ldsm4(a, xv);
#pragma unroll
                for (int e = 0; e < 4; e++)
                    xv[e] = pack2(acc[8 * p + 2 * e] + __uint_as_float(xv[e] << 16), acc[8 * p + 2 * e + 1] + __uint_as_float(xv[e] & 0xffff0000u));
                stsm4(a, xv[0], xv[1], xv[2], xv[3]);
            }
        }
        fence_async();
        bar_sync(3 + h, 128);
        if (el) {
            for (int c = 0; c < 4; c++) tma4_store(&mp.out, sb + R2 + (4 * h + c) * 8192, 0, 62 * ti, 4 * h + c, b);
            asm volatile("cp.async.bulk.commit_group;" ::: "memory");
            PT(10);
            if (h == 0) cta_done(mode);
            asm volatile("cp.async.bulk.wait_group.read 0;" ::: "memory");
        }
        PT(11);
        PG(201);
        PDUMP();
    }
}

typedef CUresult (*PFN_enc)(CUtensorMap*, CUtensorMapDataType, cuuint32_t, void*, const cuuint64_t*, const cuuint64_t*,
                            const cuuint32_t*, const cuuint32_t*, CUtensorMapInterleave, CUtensorMapSwizzle,
                            CUtensorMapL2promotion, CUtensorMapFloatOOBfill);

static void enc(PFN_enc f, CUtensorMap* m, void* base, int rank, const cuuint64_t* dims, const cuuint64_t* strides, const cuuint32_t* box) {
    cuuint32_t es[5] = {1, 1, 1, 1, 1};
    f(m, CU_TENSOR_MAP_DATA_TYPE_BFLOAT16, rank, base, dims, strides, box, es, CU_TENSOR_MAP_INTERLEAVE_NONE,
      CU_TENSOR_MAP_SWIZZLE_128B, CU_TENSOR_MAP_L2_PROMOTION_L2_256B, CU_TENSOR_MAP_FLOAT_OOB_FILL_NONE);
}
static void enc_act(PFN_enc f, CUtensorMap* m, void* base, int rows, int chunks, int trows = T_, int pitch = T_) {
    cuuint64_t dims[4] = {64, (cuuint64_t)trows, 8, (cuuint64_t)NB_};
    cuuint64_t st[3] = {1024, 128, (cuuint64_t)pitch * 1024};
    cuuint32_t box[4] = {64, (cuuint32_t)rows, (cuuint32_t)chunks, 1};
    enc(f, m, base, 4, dims, st, box);
}
static void enc_w(PFN_enc f, CUtensorMap* m, void* base, int krows, int ncols, int bk, int bc) {
    cuuint64_t dims[3] = {64, (cuuint64_t)krows, (cuuint64_t)(ncols / 64)};
    cuuint64_t st[2] = {(cuuint64_t)ncols * 2, 128};
    cuuint32_t box[3] = {64, (cuuint32_t)bk, (cuuint32_t)bc};
    enc(f, m, base, 3, dims, st, box);
}

extern "C" void kernel_launch(void* const* d_in, const int* in_sizes, int n_in, void* d_out, int out_size) {
    const bf16* x = (const bf16*)d_in[0];
    static PFN_enc fenc = nullptr;
    static void *p_xa, *p_mqk, *p_uc, *p_t1;
    static int fused = 0;
    if (!fenc) {
        void* fn = nullptr;
        cudaDriverEntryPointQueryResult qr;
        cudaGetDriverEntryPoint("cuTensorMapEncodeTiled", &fn, cudaEnableDefault, &qr);
        fenc = (PFN_enc)fn;
        cudaGetSymbolAddress(&p_xa, g_xa);
        cudaGetSymbolAddress(&p_mqk, g_mqk);
        cudaGetSymbolAddress(&p_uc, g_uc);
        cudaGetSymbolAddress(&p_t1, g_t1);
        cudaFuncSetAttribute(main_kernel, cudaFuncAttributeMaxDynamicSharedMemorySize, SMEM_BYTES);
        int dev = 0, sms = 0, occ = 0;
        cudaGetDevice(&dev);
        cudaDeviceGetAttribute(&sms, cudaDevAttrMultiProcessorCount, dev);
        cudaOccupancyMaxActiveBlocksPerMultiprocessor(&occ, main_kernel, 384, SMEM_BYTES);
        fused = sms * occ >= NCTA + 2;
    }
    Maps mp;
    enc_act(fenc, &mp.xa, (char*)p_xa + 1024, 64, 8, T_, T_ + 8);
    enc_act(fenc, &mp.xa2, (char*)p_xa + 1024, 64, 2, T_, T_ + 8);
    enc_act(fenc, &mp.xa4, (char*)p_xa + 1024, 64, 4, T_, T_ + 8);
    enc_act(fenc, &mp.xas, p_xa, 64, 1, T_ + 1, T_ + 8);
    enc_act(fenc, &mp.x, (void*)x, 64, 1);
    enc_act(fenc, &mp.out, d_out, 62, 1);
    enc_w(fenc, &mp.wup4, d_in[5], 512, 1024, 16, 4);
    enc_w(fenc, &mp.wup8, d_in[5], 512, 1024, 16, 8);
    enc_w(fenc, &mp.mqa2, p_mqk, 512, 512, 32, 2);
    enc_w(fenc, &mp.mqa4, p_mqk, 512, 512, 32, 4);
    enc_w(fenc, &mp.mqb1, p_mqk, 512, 512, 64, 1);
    enc_w(fenc, &mp.mqb2, p_mqk, 512, 512, 64, 2);
    enc_w(fenc, &mp.uc, p_uc, NCTA * 128, 512, 64, 4);
    enc_w(fenc, &mp.wq, d_in[1], 512, 512, 64, 8);
    enc_w(fenc, &mp.wk, d_in[2], 512, 512, 32, 8);
    enc_w(fenc, &mp.fa[0], d_in[3], 512, 512, 128, 1);
    enc_w(fenc, &mp.fa[1], d_in[7], 512, 512, 128, 1);
    enc_w(fenc, &mp.fa[2], p_t1, 512, 512, 128, 1);
    enc_w(fenc, &mp.fb[0], d_in[4], 512, 512, 64, 4);
    enc_w(fenc, &mp.fb[1], d_in[8], 1024, 512, 64, 4);
    enc_w(fenc, &mp.fc, p_t1, 512, 512, 64, 4);
    cudaStream_t st = cudaStreamPerThread;
    if (fused) {
        main_kernel<<<NCTA + 2, 384, SMEM_BYTES, st>>>(mp, x, (const bf16*)d_in[6], (const bf16*)d_in[5], 0);
    } else {
        main_kernel<<<NCTA + 2, 384, SMEM_BYTES, st>>>(mp, x, (const bf16*)d_in[6], (const bf16*)d_in[5], 1);
        main_kernel<<<NCTA + 2, 384, SMEM_BYTES, st>>>(mp, x, (const bf16*)d_in[6], (const bf16*)d_in[5], 2);
    }
}
```

```cpp
#include <cuda_runtime.h>
#include <cuda_bf16.h>
#include <cuda.h>
#include <stdint.h>

typedef __nv_bfloat16 bf16;

constexpr int T_ = 4000, D_ = 512, NB_ = 2;
constexpr int TPB = 65;
constexpr int NCTA = TPB * NB_;
constexpr int NKV = 63;

__device__ __align__(1024) bf16 g_xa[NB_ * (T_ + 8) * D_];
__device__ __align__(1024) bf16 g_mqk[D_ * D_];
__device__ __align__(1024) bf16 g_t1[D_ * D_];
__device__ __align__(1024) bf16 g_wepi[2 * D_ * D_];
__device__ __align__(1024) bf16 g_uc[NCTA * 128 * D_];
__device__ unsigned g_sync[8];

#define PT(i) do { if (el) asm volatile("st.shared.u32 [%0], %1;" ::"r"(sb + MISC + 2560), "r"((unsigned)clock())); } while (0)
#define PG(i)
#define PE()
#define PLM 15
#define PL(j, q) do { if ((PLM >> ((q) + (wg ? 4 : 0))) & 1) PT(0); } while (0)
#define PDUMP()

#define FENCE_AT 1
#define GO_AT 25
#define LAZY 256.f
#define SU 2
#define XS_GAP 800
#define XPF 50
#define URAW 1
#define LAGA 0
#define LAGB 0
#define DPOS 1
#define KPF 0
#define XEF 0
#define PFW 1
constexpr uint32_t R0 = 0, R1 = 65536, R2 = 131072, R3 = 196608, QS = 221184, MISC = 229376;
constexpr uint32_t AT = 147456;
constexpr uint32_t SMEM_BYTES = 232448;
constexpr uint32_t B_R1 = MISC + 1856  , B_MK = MISC + 48, B_LN = MISC + 56, B_MQ = MISC + 64,
                   B_H1 = MISC + 88, B_H2 = MISC + 96, B_H3 = MISC + 104,
                   B_KV = MISC + 112, B_P = MISC + 136, B_GO = MISC + 160, B_UC = MISC + 184  ,
                   B_X = MISC + 200, CNT = MISC + 208  , SCL = MISC + 512  ,
                   LINV = MISC + 1280  , STAT = MISC + 512  ,
                   B_R2 = MISC + 1536  , B_E2 = MISC + 1696  ;

__device__ __forceinline__ uint32_t smem_u32(const void* p) { return (uint32_t)__cvta_generic_to_shared(p); }
__device__ __forceinline__ void wg_fence() { asm volatile("wgmma.fence.sync.aligned;" ::: "memory"); }
__device__ __forceinline__ void wg_commit() { asm volatile("wgmma.commit_group.sync.aligned;" ::: "memory"); }
template <int N> __device__ __forceinline__ void wg_wait() { asm volatile("wgmma.wait_group.sync.aligned %0;" ::"n"(N) : "memory"); }
__device__ __forceinline__ uint64_t dsc(uint32_t sd, uint32_t off, uint32_t lbo) {
    uint32_t lo = sd + (off >> 4) + ((lbo >> 4) << 16);
    uint64_t d;
    asm("mov.b64 %0, {%1, %2};" : "=l"(d) : "r"(lo), "r"((1024u >> 4) | (1u << 30)));
    return d;
}
__device__ __forceinline__ bool elect1() {
    uint32_t p;
    asm volatile("{\n.reg .pred p;\nelect.sync _|p, 0xffffffff;\nselp.u32 %0, 1, 0, p;\n}\n" : "=r"(p));
    return p != 0;
}
__device__ __forceinline__ void mbar_init(uint32_t bar, int cnt) { asm volatile("mbarrier.init.shared::cta.b64 [%0], %1;" ::"r"(bar), "r"(cnt) : "memory"); }
__device__ __forceinline__ void mbar_expect_tx(uint32_t bar, uint32_t bytes) { asm volatile("mbarrier.arrive.expect_tx.shared::cta.b64 _, [%0], %1;" ::"r"(bar), "r"(bytes) : "memory"); }
__device__ __forceinline__ void mbar_arrive(uint32_t bar) { asm volatile("mbarrier.arrive.shared::cta.b64 _, [%0];" ::"r"(bar) : "memory"); }
__device__ __forceinline__ void mbar_wait(uint32_t bar, uint32_t parity) {
    uint32_t ok;
#pragma unroll 1
    for (uint32_t it = 0;; ++it) {
        asm volatile("{\n.reg .pred p;\nmbarrier.try_wait.parity.shared::cta.b64 p, [%1], %2;\nselp.u32 %0, 1, 0, p;\n}\n" : "=r"(ok) : "r"(bar), "r"(parity) : "memory");
        if (ok) break;
        if (it > (1u << 20)) __trap();
    }
}
__device__ __forceinline__ bool mbar_test(uint32_t bar, uint32_t parity) {
    uint32_t ok;
    asm volatile("{\n.reg .pred p;\nmbarrier.test_wait.parity.shared::cta.b64 p, [%1], %2;\nselp.u32 %0, 1, 0, p;\n}\n" : "=r"(ok) : "r"(bar), "r"(parity) : "memory");
    return ok != 0;
}
__device__ __forceinline__ void fence_async() { asm volatile("fence.proxy.async.shared::cta;" ::: "memory"); }
__device__ __forceinline__ void fence_async_g() { asm volatile("fence.proxy.async.global;" ::: "memory"); }
__device__ __forceinline__ void bar_sync(int id, int n) { asm volatile("bar.sync %0, %1;" ::"r"(id), "r"(n) : "memory"); }
__device__ __forceinline__ void tma3(uint32_t dst, const CUtensorMap* tm, int c0, int c1, int c2, uint32_t bar) {
    asm volatile("cp.async.bulk.tensor.3d.shared::cluster.global.mbarrier::complete_tx::bytes [%0], [%1, {%3, %4, %5}], [%2];"
                 ::"r"(dst), "l"(tm), "r"(bar), "r"(c0), "r"(c1), "r"(c2) : "memory");
}
__device__ __forceinline__ void tma4(uint32_t dst, const CUtensorMap* tm, int c0, int c1, int c2, int c3, uint32_t bar) {
    asm volatile("cp.async.bulk.tensor.4d.shared::cluster.global.mbarrier::complete_tx::bytes [%0], [%1, {%3, %4, %5, %6}], [%2];"
                 ::"r"(dst), "l"(tm), "r"(bar), "r"(c0), "r"(c1), "r"(c2), "r"(c3) : "memory");
}
__device__ __forceinline__ void tma4_store(const CUtensorMap* tm, uint32_t src, int c0, int c1, int c2, int c3) {
    asm volatile("cp.async.bulk.tensor.4d.global.shared::cta.bulk_group [%0, {%2, %3, %4, %5}], [%1];"
                 ::"l"(tm), "r"(src), "r"(c0), "r"(c1), "r"(c2), "r"(c3) : "memory");
}
__device__ __forceinline__ void tma3_store(const CUtensorMap* tm, uint32_t src, int c0, int c1, int c2) {
    asm volatile("cp.async.bulk.tensor.3d.global.shared::cta.bulk_group [%0, {%2, %3, %4}], [%1];"
                 ::"l"(tm), "r"(src), "r"(c0), "r"(c1), "r"(c2) : "memory");
}
__device__ __forceinline__ void stsm4(uint32_t addr, uint32_t a, uint32_t b, uint32_t c, uint32_t d) {
    asm volatile("stmatrix.sync.aligned.m8n8.x4.shared.b16 [%0], {%1, %2, %3, %4};" ::"r"(addr), "r"(a), "r"(b), "r"(c), "r"(d) : "memory");
}
__device__ __forceinline__ void ldsm4(uint32_t addr, uint32_t (&r)[4]) {
    asm volatile("ldmatrix.sync.aligned.m8n8.x4.shared.b16 {%0, %1, %2, %3}, [%4];" : "=r"(r[0]), "=r"(r[1]), "=r"(r[2]), "=r"(r[3]) : "r"(addr) : "memory");
}
__device__ __forceinline__ void ldsm2(uint32_t addr, uint32_t (&r)[2]) {
    asm volatile("ldmatrix.sync.aligned.m8n8.x2.shared.b16 {%0, %1}, [%2];" : "=r"(r[0]), "=r"(r[1]) : "r"(addr) : "memory");
}
__device__ __forceinline__ void stg4(void* p, uint32_t a, uint32_t b, uint32_t c, uint32_t d) {
    asm volatile("st.global.v4.u32 [%0], {%1, %2, %3, %4};" ::"l"(p), "r"(a), "r"(b), "r"(c), "r"(d) : "memory");
}
__device__ __forceinline__ void hmma(float (&c)[4], uint32_t a0, uint32_t a1, uint32_t a2, uint32_t a3, uint32_t b0, uint32_t b1) {
    asm("mma.sync.aligned.m16n8k16.row.col.f32.bf16.bf16.f32 {%0, %1, %2, %3}, {%4, %5, %6, %7}, {%8, %9}, {%0, %1, %2, %3};"
        : "+f"(c[0]), "+f"(c[1]), "+f"(c[2]), "+f"(c[3]) : "r"(a0), "r"(a1), "r"(a2), "r"(a3), "r"(b0), "r"(b1));
}
__device__ __forceinline__ uint32_t pack2(float lo, float hi) {
    uint32_t r;
    asm("cvt.rn.bf16x2.f32 %0, %1, %2;" : "=r"(r) : "f"(hi), "f"(lo));
    return r;
}
__device__ __forceinline__ uint32_t pack2v(float lo, float hi) {
    uint32_t r;
    asm volatile("cvt.rn.bf16x2.f32 %0, %1, %2;" : "=r"(r) : "f"(hi), "f"(lo));
    return r;
}
__device__ __forceinline__ uint32_t bmul2(uint32_t a, uint32_t b) { uint32_t r; asm("mul.rn.bf16x2 %0, %1, %2;" : "=r"(r) : "r"(a), "r"(b)); return r; }
__device__ __forceinline__ uint32_t bfma2(uint32_t a, uint32_t b, uint32_t c) { uint32_t r; asm("fma.rn.bf16x2 %0, %1, %2, %3;" : "=r"(r) : "r"(a), "r"(b), "r"(c)); return r; }
__device__ __forceinline__ float ex2(float x) { float r; asm("ex2.approx.ftz.f32 %0, %1;" : "=f"(r) : "f"(x)); return r; }
__device__ __forceinline__ float rcp(float x) { float r; asm("rcp.approx.ftz.f32 %0, %1;" : "=f"(r) : "f"(x)); return r; }
__device__ __forceinline__ float gelu2(float x) {
    float t = fmaf(x * x, 0.044715f * 0.7978845608028654f, 0.7978845608028654f), th;
    asm("tanh.approx.f32 %0, %1;" : "=f"(th) : "f"(x * t));
    return fmaf(x, th, x);
}
__device__ __forceinline__ uint32_t ldg_v(const uint32_t* p) { uint32_t v; asm volatile("ld.global.nc.u32 %0, [%1];" : "=r"(v) : "l"(p)); return v; }
__device__ __forceinline__ uint32_t ldg_cg(const uint32_t* p) { uint32_t v; asm volatile("ld.global.cg.u32 %0, [%1];" : "=r"(v) : "l"(p) : "memory"); return v; }
__device__ __forceinline__ float lds_f32(uint32_t a) { float v; asm volatile("ld.shared.f32 %0, [%1];" : "=f"(v) : "r"(a) : "memory"); return v; }
__device__ __forceinline__ void sts_f32(uint32_t a, float v) { asm volatile("st.shared.f32 [%0], %1;" ::"r"(a), "f"(v) : "memory"); }
__device__ __forceinline__ uint32_t atom_inc_s(uint32_t a) { uint32_t v; asm volatile("atom.relaxed.cta.shared.add.u32 %0, [%1], 1;" : "=r"(v) : "r"(a) : "memory"); return v; }
__device__ __forceinline__ void lds4(uint32_t a, uint32_t* r) {
    asm volatile("ld.shared.v4.u32 {%0, %1, %2, %3}, [%4];" : "=r"(r[0]), "=r"(r[1]), "=r"(r[2]), "=r"(r[3]) : "r"(a) : "memory");
}
__device__ __forceinline__ void sts4(uint32_t a, uint32_t x, uint32_t y, uint32_t z, uint32_t t) {
    asm volatile("st.shared.v4.u32 [%0], {%1, %2, %3, %4};" ::"r"(a), "r"(x), "r"(y), "r"(z), "r"(t) : "memory");
}
__device__ __forceinline__ uint32_t bsub2(uint32_t a, uint32_t b) { uint32_t r; asm("sub.rn.bf16x2 %0, %1, %2;" : "=r"(r) : "r"(a), "r"(b)); return r; }
__device__ __forceinline__ float blo(uint32_t v) { return __uint_as_float(v << 16); }
__device__ __forceinline__ float bhi(uint32_t v) { return __uint_as_float(v & 0xffff0000u); }
__device__ __forceinline__ float bfr(float x) { return __bfloat162float(__float2bfloat16_rn(x)); }
__device__ __forceinline__ void l2_prefetch(const void* p, uint32_t bytes) { asm volatile("cp.async.bulk.prefetch.L2.global [%0], %1;" ::"l"(p), "r"(bytes) : "memory"); }
__device__ __forceinline__ void flag_add(unsigned* p) { asm volatile("red.release.gpu.global.add.u32 [%0], 1;" ::"l"(p) : "memory"); }
__device__ __forceinline__ void flag_wait(const unsigned* p, unsigned target) {
#pragma unroll 1
    for (uint32_t it = 0;; ++it) {
        unsigned v;
        asm volatile("ld.acquire.gpu.global.u32 %0, [%1];" : "=r"(v) : "l"(p) : "memory");
        if (v >= target) break;
        if (it > (1u << 20)) __trap();
    }
    fence_async_g();
}
template <int N> __device__ __forceinline__ void pin(float (&a)[N]) {
#pragma unroll
    for (int i = 0; i < N; i++) asm volatile("" : "+f"(a[i])::"memory");
}

template <int N> __device__ __forceinline__ void fresh(float (&a)[N]) {
#pragma unroll
    for (int i = 0; i < N; i++) a[i] = 0.f;
    pin(a);
}

__device__ __forceinline__ void wgmma_rs_n64_tb0(float (&d)[32], uint32_t a0, uint32_t a1, uint32_t a2, uint32_t a3, uint64_t db, int scale_d) {
    asm volatile("{\n.reg .pred p;\nsetp.ne.b32 p, %37, 0;\n"
        "wgmma.mma_async.sync.aligned.m64n64k16.f32.bf16.bf16 {%0, %1, %2, %3, %4, %5, %6, %7, %8, %9, %10, %11, %12, %13, %14, %15, %16, %17, %18, %19, %20, %21, %22, %23, %24, %25, %26, %27, %28, %29, %30, %31}, {%32, %33, %34, %35}, %36, p, 1, 1, 0;\n}\n"
        : "+f"(d[0]), "+f"(d[1]), "+f"(d[2]), "+f"(d[3]), "+f"(d[4]), "+f"(d[5]), "+f"(d[6]), "+f"(d[7]), "+f"(d[8]), "+f"(d[9]), "+f"(d[10]), "+f"(d[11]), "+f"(d[12]), "+f"(d[13]), "+f"(d[14]), "+f"(d[15]), "+f"(d[16]), "+f"(d[17]), "+f"(d[18]), "+f"(d[19]), "+f"(d[20]), "+f"(d[21]), "+f"(d[22]), "+f"(d[23]), "+f"(d[24]), "+f"(d[25]), "+f"(d[26]), "+f"(d[27]), "+f"(d[28]), "+f"(d[29]), "+f"(d[30]), "+f"(d[31])
        : "r"(a0), "r"(a1), "r"(a2), "r"(a3), "l"(db), "r"(scale_d));
}

__device__ __forceinline__ void wgmma_ss_n128_tb1(float (&d)[64], uint64_t da, uint64_t db, int scale_d) {
    asm volatile("{\n.reg .pred p;\nsetp.ne.b32 p, %66, 0;\n"
        "wgmma.mma_async.sync.aligned.m64n128k16.f32.bf16.bf16 {%0, %1, %2, %3, %4, %5, %6, %7, %8, %9, %10, %11, %12, %13, %14, %15, %16, %17, %18, %19, %20, %21, %22, %23, %24, %25, %26, %27, %28, %29, %30, %31, %32, %33, %34, %35, %36, %37, %38, %39, %40, %41, %42, %43, %44, %45, %46, %47, %48, %49, %50, %51, %52, %53, %54, %55, %56, %57, %58, %59, %60, %61, %62, %63}, %64, %65, p, 1, 1, 0, 1;\n}\n"
        : "+f"(d[0]), "+f"(d[1]), "+f"(d[2]), "+f"(d[3]), "+f"(d[4]), "+f"(d[5]), "+f"(d[6]), "+f"(d[7]), "+f"(d[8]), "+f"(d[9]), "+f"(d[10]), "+f"(d[11]), "+f"(d[12]), "+f"(d[13]), "+f"(d[14]), "+f"(d[15]), "+f"(d[16]), "+f"(d[17]), "+f"(d[18]), "+f"(d[19]), "+f"(d[20]), "+f"(d[21]), "+f"(d[22]), "+f"(d[23]), "+f"(d[24]), "+f"(d[25]), "+f"(d[26]), "+f"(d[27]), "+f"(d[28]), "+f"(d[29]), "+f"(d[30]), "+f"(d[31]), "+f"(d[32]), "+f"(d[33]), "+f"(d[34]), "+f"(d[35]), "+f"(d[36]), "+f"(d[37]), "+f"(d[38]), "+f"(d[39]), "+f"(d[40]), "+f"(d[41]), "+f"(d[42]), "+f"(d[43]), "+f"(d[44]), "+f"(d[45]), "+f"(d[46]), "+f"(d[47]), "+f"(d[48]), "+f"(d[49]), "+f"(d[50]), "+f"(d[51]), "+f"(d[52]), "+f"(d[53]), "+f"(d[54]), "+f"(d[55]), "+f"(d[56]), "+f"(d[57]), "+f"(d[58]), "+f"(d[59]), "+f"(d[60]), "+f"(d[61]), "+f"(d[62]), "+f"(d[63])
        : "l"(da), "l"(db), "r"(scale_d));
}

__device__ __forceinline__ void wgmma_ss_n256_tb1(float (&d)[128], uint64_t da, uint64_t db, int scale_d) {
    asm volatile("{\n.reg .pred p;\nsetp.ne.b32 p, %130, 0;\n"
        "wgmma.mma_async.sync.aligned.m64n256k16.f32.bf16.bf16 {%0, %1, %2, %3, %4, %5, %6, %7, %8, %9, %10, %11, %12, %13, %14, %15, %16, %17, %18, %19, %20, %21, %22, %23, %24, %25, %26, %27, %28, %29, %30, %31, %32, %33, %34, %35, %36, %37, %38, %39, %40, %41, %42, %43, %44, %45, %46, %47, %48, %49, %50, %51, %52, %53, %54, %55, %56, %57, %58, %59, %60, %61, %62, %63, %64, %65, %66, %67, %68, %69, %70, %71, %72, %73, %74, %75, %76, %77, %78, %79, %80, %81, %82, %83, %84, %85, %86, %87, %88, %89, %90, %91, %92, %93, %94, %95, %96, %97, %98, %99, %100, %101, %102, %103, %104, %105, %106, %107, %108, %109, %110, %111, %112, %113, %114, %115, %116, %117, %118, %119, %120, %121, %122, %123, %124, %125, %126, %127}, %128, %129, p, 1, 1, 0, 1;\n}\n"
        : "+f"(d[0]), "+f"(d[1]), "+f"(d[2]), "+f"(d[3]), "+f"(d[4]), "+f"(d[5]), "+f"(d[6]), "+f"(d[7]), "+f"(d[8]), "+f"(d[9]), "+f"(d[10]), "+f"(d[11]), "+f"(d[12]), "+f"(d[13]), "+f"(d[14]), "+f"(d[15]), "+f"(d[16]), "+f"(d[17]), "+f"(d[18]), "+f"(d[19]), "+f"(d[20]), "+f"(d[21]), "+f"(d[22]), "+f"(d[23]), "+f"(d[24]), "+f"(d[25]), "+f"(d[26]), "+f"(d[27]), "+f"(d[28]), "+f"(d[29]), "+f"(d[30]), "+f"(d[31]), "+f"(d[32]), "+f"(d[33]), "+f"(d[34]), "+f"(d[35]), "+f"(d[36]), "+f"(d[37]), "+f"(d[38]), "+f"(d[39]), "+f"(d[40]), "+f"(d[41]), "+f"(d[42]), "+f"(d[43]), "+f"(d[44]), "+f"(d[45]), "+f"(d[46]), "+f"(d[47]), "+f"(d[48]), "+f"(d[49]), "+f"(d[50]), "+f"(d[51]), "+f"(d[52]), "+f"(d[53]), "+f"(d[54]), "+f"(d[55]), "+f"(d[56]), "+f"(d[57]), "+f"(d[58]), "+f"(d[59]), "+f"(d[60]), "+f"(d[61]), "+f"(d[62]), "+f"(d[63]), "+f"(d[64]), "+f"(d[65]), "+f"(d[66]), "+f"(d[67]), "+f"(d[68]), "+f"(d[69]), "+f"(d[70]), "+f"(d[71]), "+f"(d[72]), "+f"(d[73]), "+f"(d[74]), "+f"(d[75]), "+f"(d[76]), "+f"(d[77]), "+f"(d[78]), "+f"(d[79]), "+f"(d[80]), "+f"(d[81]), "+f"(d[82]), "+f"(d[83]), "+f"(d[84]), "+f"(d[85]), "+f"(d[86]), "+f"(d[87]), "+f"(d[88]), "+f"(d[89]), "+f"(d[90]), "+f"(d[91]), "+f"(d[92]), "+f"(d[93]), "+f"(d[94]), "+f"(d[95]), "+f"(d[96]), "+f"(d[97]), "+f"(d[98]), "+f"(d[99]), "+f"(d[100]), "+f"(d[101]), "+f"(d[102]), "+f"(d[103]), "+f"(d[104]), "+f"(d[105]), "+f"(d[106]), "+f"(d[107]), "+f"(d[108]), "+f"(d[109]), "+f"(d[110]), "+f"(d[111]), "+f"(d[112]), "+f"(d[113]), "+f"(d[114]), "+f"(d[115]), "+f"(d[116]), "+f"(d[117]), "+f"(d[118]), "+f"(d[119]), "+f"(d[120]), "+f"(d[121]), "+f"(d[122]), "+f"(d[123]), "+f"(d[124]), "+f"(d[125]), "+f"(d[126]), "+f"(d[127])
        : "l"(da), "l"(db), "r"(scale_d));
}

__device__ __forceinline__ void wgmma_ss_n32_tb0(float (&d)[16], uint64_t da, uint64_t db, int scale_d) {
    asm volatile("{\n.reg .pred p;\nsetp.ne.b32 p, %18, 0;\n"
        "wgmma.mma_async.sync.aligned.m64n32k16.f32.bf16.bf16 {%0, %1, %2, %3, %4, %5, %6, %7, %8, %9, %10, %11, %12, %13, %14, %15}, %16, %17, p, 1, 1, 0, 0;\n}\n"
        : "+f"(d[0]), "+f"(d[1]), "+f"(d[2]), "+f"(d[3]), "+f"(d[4]), "+f"(d[5]), "+f"(d[6]), "+f"(d[7]), "+f"(d[8]), "+f"(d[9]), "+f"(d[10]), "+f"(d[11]), "+f"(d[12]), "+f"(d[13]), "+f"(d[14]), "+f"(d[15])
        : "l"(da), "l"(db), "r"(scale_d));
}

__device__ __forceinline__ void wgmma_ss_n64_tb0(float (&d)[32], uint64_t da, uint64_t db, int scale_d) {
    asm volatile("{\n.reg .pred p;\nsetp.ne.b32 p, %34, 0;\n"
        "wgmma.mma_async.sync.aligned.m64n64k16.f32.bf16.bf16 {%0, %1, %2, %3, %4, %5, %6, %7, %8, %9, %10, %11, %12, %13, %14, %15, %16, %17, %18, %19, %20, %21, %22, %23, %24, %25, %26, %27, %28, %29, %30, %31}, %32, %33, p, 1, 1, 0, 0;\n}\n"
        : "+f"(d[0]), "+f"(d[1]), "+f"(d[2]), "+f"(d[3]), "+f"(d[4]), "+f"(d[5]), "+f"(d[6]), "+f"(d[7]), "+f"(d[8]), "+f"(d[9]), "+f"(d[10]), "+f"(d[11]), "+f"(d[12]), "+f"(d[13]), "+f"(d[14]), "+f"(d[15]), "+f"(d[16]), "+f"(d[17]), "+f"(d[18]), "+f"(d[19]), "+f"(d[20]), "+f"(d[21]), "+f"(d[22]), "+f"(d[23]), "+f"(d[24]), "+f"(d[25]), "+f"(d[26]), "+f"(d[27]), "+f"(d[28]), "+f"(d[29]), "+f"(d[30]), "+f"(d[31])
        : "l"(da), "l"(db), "r"(scale_d));
}

struct Maps {
    CUtensorMap xa, xa2, xa4, xas, wup4, wup8, mqa2, mqa4, mqb1, mqb2, uc, x, out, wq, wk, fa[3], fb[2], fc;
};

__device__ __forceinline__ uint64_t mkd(uint32_t lo) {
    uint64_t d;
    asm("mov.b64 %0, {%1, %2};" : "=l"(d) : "r"(lo), "r"((1024u >> 4) | (1u << 30)));
    return d;
}
__device__ __forceinline__ void bulk_ld(uint32_t dst, const void* src, uint32_t bytes, uint32_t bar) {
    asm volatile("cp.async.bulk.shared::cluster.global.mbarrier::complete_tx::bytes [%0], [%1], %2, [%3];" ::"r"(dst), "l"(src), "r"(bytes), "r"(bar) : "memory");
}
__device__ __forceinline__ void bulk_st(void* dst, uint32_t src, uint32_t bytes) {
    asm volatile("cp.async.bulk.global.shared::cta.bulk_group [%0], [%1], %2;" ::"l"(dst), "r"(src), "r"(bytes) : "memory");
}
__device__ __forceinline__ void ring_ld(uint32_t sb, uint32_t slot8, int n) {
    mbar_expect_tx(sb + B_R2 + slot8, 8192);
    bulk_ld(sb + R1 + slot8 * 1024, (const char*)g_wepi + n * 8192, 8192, sb + B_R2 + slot8);
}

__device__ __forceinline__ void ring_half(uint32_t sb, uint32_t slot8, uint32_t hoff, const CUtensorMap* tm, int c1, int c2) {
    mbar_expect_tx(sb + B_R1 + slot8, 8192);
    tma3(sb + slot8 * 2048 + hoff, tm, 0, c1, c2, sb + B_R1 + slot8);
}
__device__ __forceinline__ void ring_full(uint32_t sb, uint32_t slot8, const CUtensorMap* tm, int c1, int c2) {
    mbar_expect_tx(sb + B_R1 + slot8, 16384);
    mbar_arrive(sb + B_R1 + slot8);
    tma3(sb + slot8 * 2048, tm, 0, c1, c2, sb + B_R1 + slot8);
}
__device__ __forceinline__ void cta_done(int mode) {
    if (mode == 0 && atomicAdd(&g_sync[4], 1) == NCTA + 1) {
#pragma unroll
        for (int i = 0; i < 5; i++) g_sync[i] = 0;
    }
}

__device__ __forceinline__ void fold_cta(const Maps& mp, uint32_t sb, int mode) {
    constexpr uint32_t F_FULL = MISC, F_EMPTY = MISC + 32, F_T1 = MISC + 64, STG = 49152, FOUT = 3 * STG;
    const int tid = threadIdx.x, f = blockIdx.x - NCTA;
    if (mode == 2) return;
    if (tid == 0) {
        for (int i = 0; i < 3; i++) { mbar_init(sb + F_FULL + 8 * i, 1); mbar_init(sb + F_EMPTY + 8 * i, 2); }
        mbar_init(sb + F_T1, 2);
        asm volatile("fence.mbarrier_init.release.cluster;" ::: "memory");
        fence_async();
    }
    __syncthreads();
    const int wg = __shfl_sync(0xffffffffu, tid >> 7, 0);
    int st = 0, ph = 0;
    if (wg == 0) {
        if (tid == 0) {
#pragma unroll 1
            for (int it = 0; it < 96; it++) {
                const int p = it >> 3, kc = it & 7, job = p >> 2;
                if (it == 64) mbar_wait(sb + F_T1, 0);
                mbar_wait(sb + F_EMPTY + 8 * st, ph ^ 1);
                mbar_expect_tx(sb + F_FULL + 8 * st, STG);
                tma3(sb + st * STG, &mp.fa[job], 0, 256 * f + 128 * ((p >> 1) & 1), kc, sb + F_FULL + 8 * st);
                tma3(sb + st * STG + 16384, &mp.fb[job != 0], 0, 64 * kc + (job == 1 ? 512 : 0), 4 * (p & 1), sb + F_FULL + 8 * st);
                if (++st == 3) { st = 0; ph ^= 1; }
            }
        }
        return;
    }
    const int h = wg - 1, lane = tid & 31, w = (tid >> 5) & 3;
    const uint32_t sd = (sb & 0x3FFFF) >> 4;
    const bool el = (tid & 127) == 0;
#pragma unroll 1
    for (int p = 0; p < 12; p++) {
        float acc[128];
        fresh(acc);
#pragma unroll 1
        for (int kc = 0; kc < 8; kc++) {
            mbar_wait(sb + F_FULL + 8 * st, ph);
            wg_fence();
#pragma unroll
            for (int kk = 0; kk < 4; kk++)
                wgmma_ss_n256_tb1(acc, dsc(sd, st * STG + h * 8192 + kk * 32, 16), dsc(sd, st * STG + 16384 + kk * 2048, 8192), 1);
            wg_commit();
            wg_wait<0>();
            if (el) mbar_arrive(sb + F_EMPTY + 8 * st);
            if (++st == 3) { st = 0; ph ^= 1; }
        }
        pin(acc);
        const int job = p >> 2;
        if (el) {
            asm volatile("cp.async.bulk.wait_group 0;" ::: "memory");
            if (p == 4) { fence_async_g(); mbar_arrive(sb + F_T1); }
        }
        bar_sync(3 + h, 128);
        uint32_t r = 16 * w + (lane & 7) + ((lane >> 3) & 1) * 8;
        const float fs = job == 1 ? 0.5f : 1.f;
        if (job == 1) r = (r & ~31) | (((r >> 1) & 3) << 3) | (((r >> 3) & 3) << 1) | (r & 1);
        const uint32_t oa = sb + FOUT + h * 32768 + r * 128 + ((((lane >> 4) ^ r) & 7) << 4);
#pragma unroll
        for (int i = 0; i < 16; i++)
            stsm4((oa ^ ((i & 3) << 5)) + (i >> 2) * 8192, pack2(acc[8 * i] * fs, acc[8 * i + 1] * fs), pack2(acc[8 * i + 2] * fs, acc[8 * i + 3] * fs),
                  pack2(acc[8 * i + 4] * fs, acc[8 * i + 5] * fs), pack2(acc[8 * i + 6] * fs, acc[8 * i + 7] * fs));
        fence_async();
        bar_sync(3 + h, 128);
        if (el) {
            const int row0 = 256 * f + 128 * ((p >> 1) & 1) + 64 * h + (job == 1 ? 512 : 0);
            if (job == 0) tma3_store(&mp.fc, sb + FOUT + h * 32768, 0, row0, 4 * (p & 1));
            else {
#pragma unroll 1
                for (int i = 0; i < 16; i++)
                    bulk_st((char*)g_wepi + (row0 / 8 + 2 * (i & 3) + (p & 1)) * 8192 + (i >> 2) * 2048, sb + FOUT + h * 32768 + i * 2048, 2048);
            }
            asm volatile("cp.async.bulk.commit_group;" ::: "memory");
        }
    }
    if (el) {
        asm volatile("cp.async.bulk.wait_group 0;" ::: "memory");
        fence_async_g();
        if (mode == 0) flag_add(&g_sync[3]);
    }
    bar_sync(2, 256);
    if (tid == 128) cta_done(mode);
}

__global__ void __launch_bounds__(384, 1) main_kernel(const __grid_constant__ Maps mp, const bf16* __restrict__ x, const bf16* __restrict__ dw, const bf16* wup, const int mode) {
    extern __shared__ __align__(1024) uint8_t smem[];
    const uint32_t sb = smem_u32(smem);
    const int tid = threadIdx.x;
    PE();
    if (blockIdx.x >= NCTA) { fold_cta(mp, sb, mode); return; }
    const int b = blockIdx.x / TPB, ti = blockIdx.x % TPB;
    const int piece = blockIdx.x & 127;
    const int wg = __shfl_sync(0xffffffffu, tid >> 7, 0);
    const int lane = tid & 31, w = (tid >> 5) & 3;
    const bool w0 = __shfl_sync(0xffffffffu, w, 0) == 0;
    const uint32_t sd = (sb & 0x3FFFF) >> 4;
    const uint32_t adA = sd + (AT >> 4) + (1u << 16);
    const uint32_t bd0 = sd;
    const uint32_t bd2k = bd0 + ((2048u >> 4) << 16);
    const bool el = (tid & 127) == 0;
    const uint32_t lrow = 16 * w + (lane & 7) + ((lane >> 3) & 1) * 8;
    const uint32_t loff = lrow * 128 + ((((lane >> 4) ^ lrow) & 7) << 4);
    const int r0 = 16 * w + (lane >> 2);

    if (wg == 0) {
        asm volatile("setmaxnreg.inc.sync.aligned.u32 184;");
        uint32_t q[112];
        PG(206);
        if (tid == 0) {
            mbar_init(sb + B_MK, 1);
            for (int i = 0; i < 9; i++) mbar_init(sb + B_R1 + 8 * i, 2);
            for (int i = 0; i < 5; i++) asm volatile("st.shared.u32 [%0], 0;" ::"r"(sb + CNT + 4 * i) : "memory");
        } else if (tid == 32) {
            mbar_init(sb + B_LN, 1); mbar_init(sb + B_MQ, 1);
            mbar_init(sb + B_H1, 2); mbar_init(sb + B_H2, 1); mbar_init(sb + B_H3, 2);
            for (int i = 0; i < 3; i++) { mbar_init(sb + B_KV + 8 * i, 2); mbar_init(sb + B_P + 8 * i, 4); mbar_init(sb + B_GO + 8 * i, 4); }
            mbar_init(sb + B_UC, 1); mbar_init(sb + B_UC + 8, 1); mbar_init(sb + B_X, 8);
        } else if (tid == 64) {
            for (int i = 0; i < 20; i++) mbar_init(sb + B_R2 + 8 * i, 1);
        } else if (tid == 96) {
            for (int i = 0; i < 20; i++) mbar_init(sb + B_E2 + 8 * i, 4);
        }
        if (lane == 0) {
            asm volatile("fence.mbarrier_init.release.cluster;" ::: "memory");
            fence_async();
        }
        PG(207);
        __syncwarp();
        if (SU != 2) asm volatile("bar.arrive 5, 384;" ::: "memory");
        if (tid == 0) {
            mbar_expect_tx(sb + B_MK, 65536 + 32768);
            tma3(sb + 16384, &mp.wq, 0, 64 * (piece >> 4), 0, sb + B_MK);
            tma3(sb + 81920, &mp.wk, 0, 32 * (piece & 15), 0, sb + B_MK);
            for (int i = 0; i < 14; i++) mbar_arrive(sb + B_R1 + 8 * (i >> 1));
            if (mode != 1) {
                ring_full(sb, 56, &mp.wup8, 0, 8);
                ring_full(sb, 64, &mp.wup8, 16, 8);
                ring_full(sb, 0, &mp.wup8, 32, 8);
            }
        }
        PG(208);
        bar_sync(1, 128);
        if (SU == 2) asm volatile("bar.arrive 5, 384;" ::: "memory");
        PT(0);
        PG(200);
        {
            float mq[16];
            fresh(mq);
            mbar_wait(sb + B_MK, 0);
            PT(1);
            if (tid == 32) l2_prefetch((const char*)wup + piece * 8192, 8192);
            wg_fence();
#pragma unroll 1
            for (int c = 0; c < 8; c++)
#pragma unroll
                for (int kk = 0; kk < 4; kk++)
                    wgmma_ss_n32_tb0(mq, dsc(sd, 16384 + c * 8192 + kk * 32, 16), dsc(sd, 81920 + c * 4096 + kk * 32, 16), 1);
            wg_commit();
            wg_wait<0>();
            if (mode != 1 && w0 && elect1()) {
#pragma unroll 1
                for (int i = 1; i < 7; i++) ring_full(sb, 8 * i, &mp.wup8, 32 + 16 * i, 8);
            }
            pin(mq);
            uint32_t* c = reinterpret_cast<uint32_t*>(g_mqk + (64 * (piece >> 4) + r0) * D_ + 32 * (piece & 15) + 2 * (lane & 3));
#pragma unroll
            for (int n = 0; n < 4; n++) { c[4 * n] = pack2(mq[4 * n], mq[4 * n + 1]); c[4 * n + 4 * D_] = pack2(mq[4 * n + 2], mq[4 * n + 3]); }
            fence_async_g();
            bar_sync(1, 128);
            if (el) {
                if (mode == 0) flag_add(&g_sync[2]);
                if (mode == 0) flag_wait(&g_sync[2], NCTA);
                mbar_arrive(sb + B_MQ);
                PG(203);
                PT(12);
                mbar_wait(sb + B_LN, 0);
#pragma unroll 1
                for (int c = 0; c < 8; c++) {
                    tma4_store(&mp.xas, sb + AT + c * 8192, 0, 62 * ti, c, b);
                    const unsigned t0 = (unsigned)clock();
                    while (c < 7 && (unsigned)clock() - t0 < XS_GAP) __nanosleep(20);
                }
                asm volatile("cp.async.bulk.commit_group;" ::: "memory");
                if (mode == 1) asm volatile("cp.async.bulk.wait_group 0;" ::: "memory");
            }
            PT(13);
            if (mode == 1) return;
        }
        mbar_wait(sb + B_H1, 0);
        PT(2);
        uint32_t slot8 = 24, par = 0, prev8 = 0, prev2 = 0;
        auto adv = [&]() { prev2 = prev8; prev8 = slot8; slot8 += 8; if (slot8 == 72) { slot8 = 0; par ^= 1; } };
        {
            float acc[128];
            fresh(acc);
            auto step = [&](int i) {
                const uint32_t aa = adA + (i >> 1) * 512 + (i & 1) * 4, bb = bd0 + ((4096u >> 4) << 16) + slot8 * 128;
                wg_fence();
                wgmma_ss_n256_tb1(acc, mkd(aa), mkd(bb), 1);
                wgmma_ss_n256_tb1(acc, mkd(aa + 2), mkd(bb + 128), 1);
                wg_commit();
                wg_wait<1 + LAGA>();
            };
#pragma unroll 1
            for (int i = 0; i < 8 + LAGA; i++) {
                mbar_wait(sb + B_R1 + slot8, par);
                step(i);
                if (i > LAGA && w0 && elect1()) ring_full(sb, LAGA ? prev2 : prev8, &mp.mqa4, 32 * (i - LAGA) + 256, 4);
                adv();
            }
#pragma unroll 1
            for (int i = 8 + LAGA; i < 16; i++) {
                mbar_wait(sb + B_R1 + slot8, par);
                if (i == 15 && el) mbar_arrive(sb + B_H2);
                step(i);
                if (w0 && elect1()) ring_full(sb, LAGA ? prev2 : prev8, &mp.wup8, 16 * (i - LAGA) - 128, 0);
                adv();
            }
            if (LAGA) {
                wg_wait<1>();
                if (w0 && elect1()) ring_full(sb, prev2, &mp.wup8, 112, 0);
            }
            wg_wait<0>();
            if (w0 && elect1()) ring_full(sb, prev8, &mp.wup8, 128, 0);
            pin(acc);
            PT(3);
#pragma unroll
            for (int kk = 0; kk < 4; kk++)
                stsm4((sb + QS + loff) ^ (kk << 5), pack2(acc[96 + 8 * kk], acc[97 + 8 * kk]), pack2(acc[98 + 8 * kk], acc[99 + 8 * kk]),
                      pack2(acc[100 + 8 * kk], acc[101 + 8 * kk]), pack2(acc[102 + 8 * kk], acc[103 + 8 * kk]));
            fence_async();
#pragma unroll
            for (int i = 47; i >= 0; i--) q[64 + i] = pack2v(acc[2 * i], acc[2 * i + 1]);
        }
        if (el) {
            asm volatile("cp.async.bulk.wait_group 0;" ::: "memory");
            if (mode == 0) {
                fence_async_g();
                flag_add(&g_sync[b]);
                flag_wait(&g_sync[b], TPB);
            }
        }
        __syncwarp();
        mbar_wait(sb + B_H3, 0);
        PT(4);
        slot8 = 48; par = 1;
#pragma unroll
        for (int half = 0; half < 2; half++) {
            float acc[64];
            fresh(acc);
            auto step = [&](int m) {
                const uint32_t aa = adA + m * 512, bb = bd0 + ((8192u >> 4) << 16) + slot8 * 128;
                mbar_wait(sb + B_R1 + slot8, par);
                wg_fence();
#pragma unroll
                for (int kk = 0; kk < 4; kk++) wgmma_ss_n128_tb1(acc, mkd(aa + 2 * kk), mkd(bb + 128 * kk), 1);
                wg_commit();
                wg_wait<1 + LAGB>();
            };
#pragma unroll 1
            for (int m = 0; m < 8; m++) {
                step(m);
                if (m > LAGB && w0 && elect1()) {
                    if (half == 0) ring_full(sb, LAGB ? prev2 : prev8, &mp.mqb2, 64 * (m - LAGB), 2);
                    else if (m < 4 + LAGB) tma4(sb + (LAGB ? prev2 : prev8) * 2048, &mp.xa2, 0, 0, 2 * (m - LAGB), b, sb + B_KV + 8);
                }
                adv();
            }
            if (LAGB && half == 0) {
                wg_wait<1>();
                if (w0 && elect1()) ring_full(sb, prev2, &mp.mqb2, 448, 2);
            }
            wg_wait<0>();
            if (w0 && elect1()) {
                if (half == 0) {
                    mbar_expect_tx(sb + B_KV + 8, 65536);
                    for (int i = 0; i < 3; i++) mbar_arrive(sb + B_KV + 8 * i);
                    tma4(sb + prev8 * 2048, &mp.xa2, 0, 0, 0, b, sb + B_KV + 8);
                } else {
                    mbar_expect_tx(sb + B_KV + 16, 65536);
                    tma4(sb + R2, &mp.xa, 0, 64, 0, b, sb + B_KV + 16);
                    mbar_expect_tx(sb + B_KV, 65536);
                    tma4(sb + R0, &mp.xa, 0, 128, 0, b, sb + B_KV);
                }
            }
            pin(acc);
#pragma unroll
            for (int i = 31; i >= 0; i--) q[32 * half + i] = pack2v(acc[2 * i], acc[2 * i + 1]);
        }
        bar_sync(1, 128);
        PT(5);

        const float CS = 0.04419417382415922f * 1.4426950408889634f;
        float m0 = -INFINITY, m1 = -INFINITY, l0 = 0.f, l1 = 0.f;
        int s = 0, sn = 1, ph = 0;
        float S[32];
        const bool l0w = lane == 0, q0 = (lane & 3) == 0;
#pragma unroll 1
        for (int j = -1;; j++) {
            if (j >= 0) {
                PL(j, 1);
                if (j == NKV - 1) {
#pragma unroll
                    for (int i = (T_ - 64 * (NKV - 1)) / 2; i < 32; i++) asm volatile("mov.b32 %0, 0xff800000;" : "=f"(S[i]));
                }
                const bool kv = mbar_test(sb + B_KV + sn * 8, ph);
                const uint32_t pb = sb + R3 + (s == 0 ? 2 : s - 1) * 8192;
                float a0, a1, sc0 = 1.f, sc1 = 1.f;
                auto expo = [&]() {
                    const float n0 = -m0 * CS, n1 = -m1 * CS;
                    a0 = 0.f; a1 = 0.f;
#pragma unroll
                    for (int kk = 0; kk < 4; kk++) {
                        float p[8];
#pragma unroll
                        for (int e = 0; e < 8; e++) p[e] = ex2(fmaf(S[8 * kk + e], CS, (e & 2) ? n1 : n0));
                        a0 += (p[0] + p[1]) + (p[4] + p[5]);
                        a1 += (p[2] + p[3]) + (p[6] + p[7]);
                        stsm4((pb + loff) ^ (kk << 5), pack2(p[0], p[1]), pack2(p[2], p[3]), pack2(p[4], p[5]), pack2(p[6], p[7]));
                    }
                };
                expo();
                if (__any_sync(0xffffffffu, !(a0 <= LAZY) || !(a1 <= LAZY))) {
                    float x0 = m0, x1 = m1;
#pragma unroll
                    for (int n = 0; n < 8; n++) { x0 = fmaxf(x0, fmaxf(S[4 * n], S[4 * n + 1])); x1 = fmaxf(x1, fmaxf(S[4 * n + 2], S[4 * n + 3])); }
                    x0 = fmaxf(x0, __shfl_xor_sync(0xffffffffu, x0, 1));
                    x1 = fmaxf(x1, __shfl_xor_sync(0xffffffffu, x1, 1));
                    x0 = fmaxf(x0, __shfl_xor_sync(0xffffffffu, x0, 2));
                    x1 = fmaxf(x1, __shfl_xor_sync(0xffffffffu, x1, 2));
                    sc0 = ex2((m0 - x0) * CS); sc1 = ex2((m1 - x1) * CS);
                    m0 = x0; m1 = x1;
                    expo();
                }
                if (q0) { sts_f32(sb + SCL + s * 256 + r0 * 4, sc0); sts_f32(sb + SCL + s * 256 + r0 * 4 + 32, sc1); }
                __syncwarp();
                if (l0w) mbar_arrive(sb + B_P + s * 8);
                l0 = fmaf(l0, sc0, a0); l1 = fmaf(l1, sc1, a1);
                PL(j, 2);
                if (j == NKV - 1) break;
                if (!kv) mbar_wait(sb + B_KV + sn * 8, ph);
            } else {
                mbar_wait(sb + B_KV + 8, 0);
            }
            float Sn[32];
            const uint32_t kd = sd + sn * 4096;
            wg_fence();
#pragma unroll
            for (int kk = 0; kk < 28; kk++) {
                wgmma_rs_n64_tb0(Sn, q[4 * kk], q[4 * kk + 1], q[4 * kk + 2], q[4 * kk + 3], dsc(kd, (kk >> 2) * 8192 + (kk & 3) * 32, 16), kk > 0);
                if (kk == FENCE_AT) { fence_async(); __syncwarp(); }
                if (kk == GO_AT) { PL(j, 3); if (j >= 0 && l0w) mbar_arrive(sb + B_GO + s * 8); }
            }
#pragma unroll
            for (int kk = 0; kk < 4; kk++)
                wgmma_ss_n64_tb0(Sn, dsc(sd, QS + kk * 32, 16), dsc(kd, 7 * 8192 + kk * 32, 16), 1);
            wg_commit();
            PL(j, 0);
            wg_wait<0>();
            pin(Sn);
#pragma unroll
            for (int i = 0; i < 32; i++) S[i] = Sn[i];
            s = sn;
            if (++sn == 3) sn = 0;
            if (sn == 1) ph ^= 1;
        }
        l0 += __shfl_xor_sync(0xffffffffu, l0, 1); l1 += __shfl_xor_sync(0xffffffffu, l1, 1);
        l0 += __shfl_xor_sync(0xffffffffu, l0, 2); l1 += __shfl_xor_sync(0xffffffffu, l1, 2);
        if (q0) { sts_f32(sb + LINV + r0 * 4, rcp(l0)); sts_f32(sb + LINV + r0 * 4 + 32, rcp(l1)); }
        fence_async();
        __syncwarp();
        if (l0w) {
            mbar_arrive(sb + B_GO + s * 8);
            uint32_t slot8 = 8 * w, par = 0;
#pragma unroll 1
            for (int n = 20 + w; n < 136; n += 4) {
                mbar_wait(sb + B_E2 + slot8, par);
                if (n < 128) ring_ld(sb, slot8, n);
                else {
                    mbar_expect_tx(sb + B_X, 8192);
                    tma4(sb + R1 + slot8 * 1024, &mp.x, 0, 62 * ti, n - 128, b, sb + B_X);
                }
                slot8 += 32;
                if (slot8 >= 160) { slot8 -= 160; par ^= 1; }
            }
        }
        PDUMP();
    } else {
        asm volatile("setmaxnreg.dec.sync.aligned.u32 160;");
        const int h = wg - 1;
        uint32_t v[4][8], v2[4][8];
        if (SU != 0) bar_sync(5, 384);
        PG(206);
#pragma unroll
        for (int i = 0; i < 8; i++) {
            const int t = 62 * ti - 1 + 32 * (i >> 2) + 16 * h + 4 * w + (i & 3);
            const uint4* p = reinterpret_cast<const uint4*>(x + ((size_t)b * T_ + t) * D_) + lane;
            uint32_t* d = i < 4 ? v[i & 3] : v2[i & 3];
#pragma unroll
            for (int c = 0; c < 2; c++)
                asm volatile("{\n.reg .pred p;\nsetp.lt.u32 p, %5, %6;\nmov.b32 %0, 0;\nmov.b32 %1, 0;\nmov.b32 %2, 0;\nmov.b32 %3, 0;\n"
                             "@p ld.global.nc.v4.u32 {%0, %1, %2, %3}, [%4];\n}\n"
                             : "=r"(d[4 * c]), "=r"(d[4 * c + 1]), "=r"(d[4 * c + 2]), "=r"(d[4 * c + 3]) : "l"(p + 32 * c), "r"(t), "n"(T_));
        }
#pragma unroll 1
        for (int bt = 0; bt < 2; bt++) {
            PT(bt ? 13 : 0);
            float a[8];
            const uint32_t la = sb + AT + (lane >> 3) * 8192 + (32 * bt + 16 * h + 4 * w) * 128 + (((lane & 7) ^ ((w & 1) * 4)) << 4);
            const bool b4 = lane & 16, b3 = lane & 8, b2 = lane & 4;
#pragma unroll
            for (int r = 0; r < 4; r++) {
                float c[4] = {0.f, 0.f, 0.f, 0.f};
#pragma unroll
                for (int i = 0; i < 8; i += 2) hmma(c, v[r][i], v[r][i], v[r][i + 1], v[r][i + 1], v[r][i], v[r][i + 1]);
                a[4 + r] = (lane & 3) == (lane >> 3) ? (b2 ? c[1] : c[0]) : 0.f;
                if (r & 1) {
                    float e[4] = {0.f, 0.f, 0.f, 0.f};
#pragma unroll
                    for (int i = 0; i < 8; i += 2) hmma(e, v[r - 1][i], v[r][i], v[r - 1][i + 1], v[r][i + 1], 0x3f803f80u, 0x3f803f80u);
                    a[r - 1] = e[0]; a[r] = e[2];
                }
            }
            float k[4];
#pragma unroll
            for (int i = 0; i < 4; i++) {
                const int lo = (i & 1) + 4 * (i >> 1);
                k[i] = (b4 ? a[lo + 2] : a[lo]) + __shfl_xor_sync(0xffffffffu, b4 ? a[lo] : a[lo + 2], 16);
            }
            const float k0 = (b3 ? k[1] : k[0]) + __shfl_xor_sync(0xffffffffu, b3 ? k[0] : k[1], 8);
            const float k1 = (b3 ? k[3] : k[2]) + __shfl_xor_sync(0xffffffffu, b3 ? k[2] : k[3], 8);
            float z = (b2 ? k1 : k0) + __shfl_xor_sync(0xffffffffu, b2 ? k0 : k1, 4);
            z += __shfl_xor_sync(0xffffffffu, z, 2);
            z += __shfl_xor_sync(0xffffffffu, z, 1);
            const float zo = __shfl_xor_sync(0xffffffffu, z, 4);
            PG(204 + bt);
            const float mu = (b2 ? zo : z) * (0.25f / D_);
            float sd_ = bfr(bfr(fmaxf(fmaf(b2 ? z : zo, 1.f / D_, -mu * mu), 0.f)) + 1e-5f);
            asm("sqrt.approx.f32 %0, %0;" : "+f"(sd_));
            const float ri = rcp(bfr(sd_));
            const uint32_t w1 = pack2(mu, ri), w2 = pack2(ri - bhi(w1), ri - bhi(w1));
#pragma unroll
            for (int r = 0; r < 4; r++) {
                const uint32_t s1 = __shfl_sync(0xffffffffu, w1, 8 * r), rl = __shfl_sync(0xffffffffu, w2, 8 * r);
                const uint32_t m2 = __byte_perm(s1, 0, 0x1010), rh = __byte_perm(s1, 0, 0x3232);
#pragma unroll
                for (int i = 0; i < 8; i++) { const uint32_t d = bsub2(v[r][i], m2); v[r][i] = bfma2(d, rh, bmul2(d, rl)); }
                sts4((la ^ (r << 4)) + r * 128, v[r][0], v[r][1], v[r][2], v[r][3]);
                sts4((la ^ (r << 4)) + r * 128 + 32768, v[r][4], v[r][5], v[r][6], v[r][7]);
#pragma unroll
                for (int i = 0; i < 8; i++) v[r][i] = v2[r][i];
            }
        }
        fence_async();
        if (SU == 0) bar_sync(5, 384); else bar_sync(2, 256);
        if (tid == 128) mbar_arrive(sb + B_LN);
        PG(202);
        if (mode == 1) return;
        float acc[128];
#pragma unroll
        for (int pass = 0; pass < 2; pass++) {
            if (pass == 1) mbar_wait(sb + B_H2, 0);
            PT(1 + 3 * pass);
            fresh(acc);
            uint32_t slot8 = pass ? 8 : 56, par = 0, prev8 = 0;
            auto adv = [&]() { prev8 = slot8; slot8 += 8; if (slot8 == 72) { slot8 = 0; par ^= 1; } };
            auto step = [&](int kk) {
                wg_fence();
                wgmma_ss_n256_tb1(acc, mkd(adA + (kk >> 2) * 512 + (kk & 3) * 2), mkd(bd2k + h * 512 + slot8 * 128), 1);
                wg_commit();
                wg_wait<1>();
            };
#pragma unroll 1
            for (int kk = 0; kk < 24; kk++) {
                mbar_wait(sb + B_R1 + slot8, par);
                step(kk);
                if (kk > 0 && w0 && elect1()) ring_half(sb, prev8, h * 8192, &mp.wup4, 16 * kk + 128, (pass ? 0 : 8) + 4 * h);
                adv();
            }
            if (pass == 0 && w0) mbar_wait(sb + B_MQ, 0);
#pragma unroll 1
            for (int kk = 24; kk < 32; kk++) {
                mbar_wait(sb + B_R1 + slot8, par);
                if (kk == 31 && el) mbar_arrive(sb + (pass ? B_H3 : B_H1));
                step(kk);
                if (w0 && elect1()) ring_half(sb, prev8, h * 8192, pass ? &mp.mqb1 : &mp.mqa2, (pass ? 64 : 32) * (kk - 24), pass ? h : 4 + 2 * h);
                adv();
            }
            wg_wait<0>();
            if (w0 && elect1()) ring_half(sb, prev8, h * 8192, pass ? &mp.mqb1 : &mp.mqa2, pass ? 0 : 256, pass ? 2 + h : 4 + 2 * h);
            pin(acc);
            PT(2 + 3 * pass);
            bf16* ucp = g_uc + ((size_t)blockIdx.x * 128 + r0) * D_ + 256 * h + 8 * (lane & 3);
            if (pass == 0) {
                float s0 = 0.f, s1 = 0.f, v0 = 0.f, v1 = 0.f;
#pragma unroll
                for (int n = 0; n < 32; n++) {
#pragma unroll
                    for (int e = 0; e < 4; e++) acc[4 * n + e] = gelu2(acc[4 * n + e]);
                    s0 += acc[4 * n] + acc[4 * n + 1]; s1 += acc[4 * n + 2] + acc[4 * n + 3];
                    v0 = fmaf(acc[4 * n], acc[4 * n], v0); v0 = fmaf(acc[4 * n + 1], acc[4 * n + 1], v0);
                    v1 = fmaf(acc[4 * n + 2], acc[4 * n + 2], v1); v1 = fmaf(acc[4 * n + 3], acc[4 * n + 3], v1);
                }
#pragma unroll
                for (int o = 1; o < 4; o <<= 1) {
                    s0 += __shfl_xor_sync(0xffffffffu, s0, o); s1 += __shfl_xor_sync(0xffffffffu, s1, o);
                    v0 += __shfl_xor_sync(0xffffffffu, v0, o); v1 += __shfl_xor_sync(0xffffffffu, v1, o);
                }
                if ((lane & 3) == 0) {
                    uint32_t a = sb + STAT + h * 512 + r0 * 8;
                    sts_f32(a, s0); sts_f32(a + 4, v0); sts_f32(a + 64, s1); sts_f32(a + 68, v1);
                }
                bar_sync(2, 256);
                {
                    uint32_t a = sb + STAT + (h ^ 1) * 512 + r0 * 8;
                    s0 = (s0 + lds_f32(a)) * (1.f / 512.f); v0 = (v0 + lds_f32(a + 4)) * (1.f / 512.f);
                    s1 = (s1 + lds_f32(a + 64)) * (1.f / 512.f); v1 = (v1 + lds_f32(a + 68)) * (1.f / 512.f);
                }
                v0 = rsqrtf(fmaxf(fmaf(-s0, s0, v0), 0.f) + 4e-5f); v1 = rsqrtf(fmaxf(fmaf(-s1, s1, v1), 0.f) + 4e-5f);
                s0 = -s0 * v0; s1 = -s1 * v1;
#pragma unroll
                for (int m = 0; m < 8; m++) {
                    const float* a_ = acc + 16 * m;
                    stg4(ucp + 64 * D_ + 32 * m, pack2(fmaf(a_[0], v0, s0), fmaf(a_[1], v0, s0)), pack2(fmaf(a_[4], v0, s0), fmaf(a_[5], v0, s0)),
                         pack2(fmaf(a_[8], v0, s0), fmaf(a_[9], v0, s0)), pack2(fmaf(a_[12], v0, s0), fmaf(a_[13], v0, s0)));
                    stg4(ucp + 72 * D_ + 32 * m, pack2(fmaf(a_[2], v1, s1), fmaf(a_[3], v1, s1)), pack2(fmaf(a_[6], v1, s1), fmaf(a_[7], v1, s1)),
                         pack2(fmaf(a_[10], v1, s1), fmaf(a_[11], v1, s1)), pack2(fmaf(a_[14], v1, s1), fmaf(a_[15], v1, s1)));
                }
            } else {
#pragma unroll
                for (int m = 0; m < 8; m++) {
                    const float* a_ = acc + 16 * m;
                    stg4(ucp + 32 * m, pack2(a_[0], a_[1]), pack2(a_[4], a_[5]), pack2(a_[8], a_[9]), pack2(a_[12], a_[13]));
                    stg4(ucp + 8 * D_ + 32 * m, pack2(a_[2], a_[3]), pack2(a_[6], a_[7]), pack2(a_[10], a_[11]), pack2(a_[14], a_[15]));
                }
                bar_sync(3 + h, 128);
            }
            PT(3 + 3 * pass);
        }
        int s = 1, ph = 0;
        uint32_t* cp = reinterpret_cast<uint32_t*>(g_uc + (size_t)blockIdx.x * 128 * D_) + (tid - 128);
        const uint32_t* dp = reinterpret_cast<const uint32_t*>(dw) + (((tid - 128) & ~15) | ((lane & 3) << 2) | ((lane >> 2) & 3));
        const uint32_t d0 = ldg_v(dp), d1 = ldg_v(dp + D_ / 2), d2 = ldg_v(dp + D_);
        uint32_t ga = ldg_cg(cp + 64 * (D_ / 2)), gb = ldg_cg(cp + 65 * (D_ / 2));
        fresh(acc);
#pragma unroll 1
        for (int j = 0; j < NKV; j++) {
            cp += D_ / 2;
            uint32_t gc = 0, uu = 0;
            if (j < NKV - 1) { gc = ldg_cg(cp + 65 * (D_ / 2)); uu = ldg_cg(cp); }
            mbar_wait(sb + B_P + s * 8, ph);
            PL(j, 0);
            if (j > 0) {
                const float sc0 = lds_f32(sb + SCL + s * 256 + r0 * 4), sc1 = lds_f32(sb + SCL + s * 256 + r0 * 4 + 32);
                if (__any_sync(0xffffffffu, sc0 != 1.f || sc1 != 1.f)) {
#pragma unroll
                    for (int n = 0; n < 32; n++) { acc[4 * n] *= sc0; acc[4 * n + 1] *= sc0; acc[4 * n + 2] *= sc1; acc[4 * n + 3] *= sc1; }
                }
            }
            mbar_wait(sb + B_GO + s * 8, ph);
            PL(j, 1);
            const uint32_t vd = sd + s * 4096 + h * 2048, pd = sd + (s == 0 ? 2 : s - 1) * 512;
            pin(acc);
            wg_fence();
#pragma unroll
            for (int kk = 0; kk < 4; kk++) wgmma_ss_n256_tb1(acc, dsc(pd, R3 + kk * 32, 16), dsc(vd, kk * 2048, 8192), 1);
            wg_commit();
            wg_wait<0>();
            pin(acc);
            PL(j, 2);
            if (w0 && elect1()) {
                if (j + 3 < NKV) {
                    mbar_expect_tx(sb + B_KV + s * 8, 32768);
                    tma4(sb + s * 65536 + h * 32768, &mp.xa4, 0, 64 * (j + 3), 4 * h, b, sb + B_KV + s * 8);
                } else if (j < NKV - 1) {
                    const int n0 = (j == NKV - 3 ? 0 : 8) + 4 * h;
#pragma unroll 1
                    for (int n = n0; n < n0 + 4; n++) ring_ld(sb, n * 8, n);
                }
                if (j == NKV - 5 && mode == 0) flag_wait(&g_sync[3], 4);
                if (j >= XPF && j < XPF + 4) {
                    const int t0 = 62 * ti + 32 * h + 8 * (j - XPF), nr = min(8, T_ - t0);
                    if (nr > 0) l2_prefetch(x + ((size_t)b * T_ + t0) * D_, nr * 1024);
                }
                if (KPF && h == 0 && 64 * (j + KPF) + ti < T_) l2_prefetch(g_xa + ((size_t)b * (T_ + 8) + 1 + 64 * (j + KPF) + ti) * D_, 1024);
            }
            uu = pack2(gelu2(blo(uu)), gelu2(bhi(uu)));
            if (j < NKV - 1) asm volatile("st.global.u32 [%0], %1;" ::"l"(cp), "r"(bmul2(uu, bfma2(gc, d2, bfma2(gb, d1, bmul2(ga, d0))))) : "memory");
            ga = gb; gb = gc;
            if (++s == 3) s = 0;
            if (s == 1) ph ^= 1;
        }
        {
            const float i0 = lds_f32(sb + LINV + r0 * 4), i1 = lds_f32(sb + LINV + r0 * 4 + 32);
#pragma unroll
            for (int p = 0; p < 16; p++)
                stsm4(((sb + R0 + h * 32768 + loff) ^ ((p & 3) << 5)) + (p >> 2) * 8192,
                      pack2(acc[8 * p] * i0, acc[8 * p + 1] * i0), pack2(acc[8 * p + 2] * i1, acc[8 * p + 3] * i1),
                      pack2(acc[8 * p + 4] * i0, acc[8 * p + 5] * i0), pack2(acc[8 * p + 6] * i1, acc[8 * p + 7] * i1));
        }
        fence_async();
        fence_async_g();
        bar_sync(2, 256);
        if (lane == 0 && w < 2) ring_ld(sb, 128 + 16 * w + 8 * h, 16 + 2 * w + h);
        PT(7);
        fresh(acc);
        {
            uint32_t slot8 = 8 * h, par = 0, prev8 = 0;
#pragma unroll 1
            for (int kk = 0; kk < 64; kk++) {
                if (kk == 32 || kk == 48) mbar_wait(sb + B_UC + (kk >> 1 & 8), 0);
                mbar_wait(sb + B_R2 + slot8, par);
                wg_fence();
                wgmma_ss_n256_tb1(acc, mkd(sd + (1u << 16) + (R0 >> 4) + (kk >> 2 & 7) * 512 + (kk & 3) * 2), mkd(bd2k + (R1 >> 4) + slot8 * 64), 1);
                wg_commit();
                wg_wait<1>();
                if (kk > 0 && lane == 0) mbar_arrive(sb + B_E2 + prev8);
                if ((kk == 16 || kk == 32) && w0 && elect1() && (atom_inc_s(sb + CNT + 12 + (kk >> 3 & 4)) & 1)) {
                    mbar_expect_tx(sb + B_UC + (kk >> 2 & 8), 32768);
                    tma3(sb + R0 + (kk & 32) * 1024, &mp.uc, 0, 128 * blockIdx.x, kk >> 3 & 4, sb + B_UC + (kk >> 2 & 8));
                }
                prev8 = slot8;
                slot8 += 16;
                if (slot8 >= 160) { slot8 -= 160; par ^= 1; }
            }
        }
        wg_wait<0>();
        pin(acc);
        PT(8);
        mbar_wait(sb + B_X, 0);
        PT(9);
        {
            const uint32_t sr = (lrow + 63) & 63;
            const uint32_t xoff = sr * 128 + ((((lane >> 4) ^ sr) & 7) << 4);
#pragma unroll
            for (int p = 0; p < 16; p++) {
                const uint32_t a = ((sb + R2 + h * 32768 + xoff) ^ ((p & 3) << 5)) + (p >> 2) * 8192;
                uint32_t xv[4];
                ldsm4(a, xv);
#pragma unroll
                for (int e = 0; e < 4; e++)
                    xv[e] = pack2(acc[8 * p + 2 * e] + __uint_as_float(xv[e] << 16), acc[8 * p + 2 * e + 1] + __uint_as_float(xv[e] & 0xffff0000u));
                stsm4(a, xv[0], xv[1], xv[2], xv[3]);
            }
        }
        fence_async();
        bar_sync(3 + h, 128);
        if (el) {
            for (int c = 0; c < 4; c++) tma4_store(&mp.out, sb + R2 + (4 * h + c) * 8192, 0, 62 * ti, 4 * h + c, b);
            asm volatile("cp.async.bulk.commit_group;" ::: "memory");
            PT(10);
            if (h == 0) cta_done(mode);
            asm volatile("cp.async.bulk.wait_group.read 0;" ::: "memory");
        }
        PT(11);
        PG(201);
        PDUMP();
    }
}

typedef CUresult (*PFN_enc)(CUtensorMap*, CUtensorMapDataType, cuuint32_t, void*, const cuuint64_t*, const cuuint64_t*,
                            const cuuint32_t*, const cuuint32_t*, CUtensorMapInterleave, CUtensorMapSwizzle,
                            CUtensorMapL2promotion, CUtensorMapFloatOOBfill);

static void enc(PFN_enc f, CUtensorMap* m, void* base, int rank, const cuuint64_t* dims, const cuuint64_t* strides, const cuuint32_t* box) {
    cuuint32_t es[5] = {1, 1, 1, 1, 1};
    f(m, CU_TENSOR_MAP_DATA_TYPE_BFLOAT16, rank, base, dims, strides, box, es, CU_TENSOR_MAP_INTERLEAVE_NONE,
      CU_TENSOR_MAP_SWIZZLE_128B, CU_TENSOR_MAP_L2_PROMOTION_L2_256B, CU_TENSOR_MAP_FLOAT_OOB_FILL_NONE);
}
static void enc_act(PFN_enc f, CUtensorMap* m, void* base, int rows, int chunks, int trows = T_, int pitch = T_) {
    cuuint64_t dims[4] = {64, (cuuint64_t)trows, 8, (cuuint64_t)NB_};
    cuuint64_t st[3] = {1024, 128, (cuuint64_t)pitch * 1024};
    cuuint32_t box[4] = {64, (cuuint32_t)rows, (cuuint32_t)chunks, 1};
    enc(f, m, base, 4, dims, st, box);
}
static void enc_w(PFN_enc f, CUtensorMap* m, void* base, int krows, int ncols, int bk, int bc) {
    cuuint64_t dims[3] = {64, (cuuint64_t)krows, (cuuint64_t)(ncols / 64)};
    cuuint64_t st[2] = {(cuuint64_t)ncols * 2, 128};
    cuuint32_t box[3] = {64, (cuuint32_t)bk, (cuuint32_t)bc};
    enc(f, m, base, 3, dims, st, box);
}

extern "C" void kernel_launch(void* const* d_in, const int* in_sizes, int n_in, void* d_out, int out_size) {
    const bf16* x = (const bf16*)d_in[0];
    static PFN_enc fenc = nullptr;
    static void *p_xa, *p_mqk, *p_uc, *p_t1;
    static int fused = 0;
    if (!fenc) {
        void* fn = nullptr;
        cudaDriverEntryPointQueryResult qr;
        cudaGetDriverEntryPoint("cuTensorMapEncodeTiled", &fn, cudaEnableDefault, &qr);
        fenc = (PFN_enc)fn;
        cudaGetSymbolAddress(&p_xa, g_xa);
        cudaGetSymbolAddress(&p_mqk, g_mqk);
        cudaGetSymbolAddress(&p_uc, g_uc);
        cudaGetSymbolAddress(&p_t1, g_t1);
        cudaFuncSetAttribute(main_kernel, cudaFuncAttributeMaxDynamicSharedMemorySize, SMEM_BYTES);
        int dev = 0, sms = 0, occ = 0;
        cudaGetDevice(&dev);
        cudaDeviceGetAttribute(&sms, cudaDevAttrMultiProcessorCount, dev);
        cudaOccupancyMaxActiveBlocksPerMultiprocessor(&occ, main_kernel, 384, SMEM_BYTES);
        fused = sms * occ >= NCTA + 2;
    }
    Maps mp;
    enc_act(fenc, &mp.xa, (char*)p_xa + 1024, 64, 8, T_, T_ + 8);
    enc_act(fenc, &mp.xa2, (char*)p_xa + 1024, 64, 2, T_, T_ + 8);
    enc_act(fenc, &mp.xa4, (char*)p_xa + 1024, 64, 4, T_, T_ + 8);
    enc_act(fenc, &mp.xas, p_xa, 64, 1, T_ + 1, T_ + 8);
    enc_act(fenc, &mp.x, (void*)x, 64, 1);
    enc_act(fenc, &mp.out, d_out, 62, 1);
    enc_w(fenc, &mp.wup4, d_in[5], 512, 1024, 16, 4);
    enc_w(fenc, &mp.wup8, d_in[5], 512, 1024, 16, 8);
    enc_w(fenc, &mp.mqa2, p_mqk, 512, 512, 32, 2);
    enc_w(fenc, &mp.mqa4, p_mqk, 512, 512, 32, 4);
    enc_w(fenc, &mp.mqb1, p_mqk, 512, 512, 64, 1);
    enc_w(fenc, &mp.mqb2, p_mqk, 512, 512, 64, 2);
    enc_w(fenc, &mp.uc, p_uc, NCTA * 128, 512, 64, 4);
    enc_w(fenc, &mp.wq, d_in[1], 512, 512, 64, 8);
    enc_w(fenc, &mp.wk, d_in[2], 512, 512, 32, 8);
    enc_w(fenc, &mp.fa[0], d_in[3], 512, 512, 128, 1);
    enc_w(fenc, &mp.fa[1], d_in[7], 512, 512, 128, 1);
    enc_w(fenc, &mp.fa[2], p_t1, 512, 512, 128, 1);
    enc_w(fenc, &mp.fb[0], d_in[4], 512, 512, 64, 4);
    enc_w(fenc, &mp.fb[1], d_in[8], 1024, 512, 64, 4);
    enc_w(fenc, &mp.fc, p_t1, 512, 512, 64, 4);
    cudaStream_t st = cudaStreamPerThread;
    if (fused) {
        main_kernel<<<NCTA + 2, 384, SMEM_BYTES, st>>>(mp, x, (const bf16*)d_in[6], (const bf16*)d_in[5], 0);
    } else {
        main_kernel<<<NCTA + 2, 384, SMEM_BYTES, st>>>(mp, x, (const bf16*)d_in[6], (const bf16*)d_in[5], 1);
        main_kernel<<<NCTA + 2, 384, SMEM_BYTES, st>>>(mp, x, (const bf16*)d_in[6], (const bf16*)d_in[5], 2);
    }
}
```

```cpp
#include <cuda_runtime.h>
#include <cuda_bf16.h>
#include <cuda.h>
#include <stdint.h>

typedef __nv_bfloat16 bf16;

constexpr int T_ = 4000, D_ = 512, NB_ = 2;
constexpr int TPB = 65;
constexpr int NCTA = TPB * NB_;
constexpr int NKV = 63;

__device__ __align__(1024) bf16 g_xa[NB_ * (T_ + 8) * D_];
__device__ __align__(1024) bf16 g_mqk[D_ * D_];
__device__ __align__(1024) bf16 g_t1[D_ * D_];
__device__ __align__(1024) bf16 g_wepi[2 * D_ * D_];
__device__ __align__(1024) bf16 g_uc[NCTA * 128 * D_];
__device__ unsigned g_sync[8];

#define PT(i) do { if (el) asm volatile("st.shared.u32 [%0], %1;" ::"r"(sb + MISC + 2560), "r"((unsigned)clock())); } while (0)
#define PG(i)
#define PE()
#define PLM 15
#define PL(j, q) do { if ((PLM >> ((q) + (wg ? 4 : 0))) & 1) PT(0); } while (0)
#define PDUMP()

#define FENCE_AT 1
#define GO_AT 25
#define LAZY 4294967296.f
#define SU 2
#define XS_GAP 800
#define XPF 50
#define URAW 1
#define LAGA 0
#define LAGB 0
#define DPOS 1
#define KPF 0
#define XEF 0
#define SK0 1
#define PFW 1
constexpr uint32_t R0 = 0, R1 = 65536, R2 = 131072, R3 = 196608, QS = 221184, MISC = 229376;
constexpr uint32_t AT = 147456;
constexpr uint32_t SMEM_BYTES = 232448;
constexpr uint32_t B_R1 = MISC + 1856  , B_MK = MISC + 48, B_LN = MISC + 56, B_MQ = MISC + 64,
                   B_H1 = MISC + 88, B_H2 = MISC + 96, B_H3 = MISC + 104,
                   B_KV = MISC + 112, B_P = MISC + 136, B_GO = MISC + 160, B_UC = MISC + 184  ,
                   B_X = MISC + 200, CNT = MISC + 208  , SCL = MISC + 512  ,
                   LINV = MISC + 1280  , STAT = MISC + 512  ,
                   B_R2 = MISC + 1536  , B_E2 = MISC + 1696  ;

__device__ __forceinline__ uint32_t smem_u32(const void* p) { return (uint32_t)__cvta_generic_to_shared(p); }
__device__ __forceinline__ void wg_fence() { asm volatile("wgmma.fence.sync.aligned;" ::: "memory"); }
__device__ __forceinline__ void wg_commit() { asm volatile("wgmma.commit_group.sync.aligned;" ::: "memory"); }
template <int N> __device__ __forceinline__ void wg_wait() { asm volatile("wgmma.wait_group.sync.aligned %0;" ::"n"(N) : "memory"); }
__device__ __forceinline__ uint64_t dsc(uint32_t sd, uint32_t off, uint32_t lbo) {
    uint32_t lo = sd + (off >> 4) + ((lbo >> 4) << 16);
    uint64_t d;
    asm("mov.b64 %0, {%1, %2};" : "=l"(d) : "r"(lo), "r"((1024u >> 4) | (1u << 30)));
    return d;
}
__device__ __forceinline__ bool elect1() {
    uint32_t p;
    asm volatile("{\n.reg .pred p;\nelect.sync _|p, 0xffffffff;\nselp.u32 %0, 1, 0, p;\n}\n" : "=r"(p));
    return p != 0;
}
__device__ __forceinline__ void mbar_init(uint32_t bar, int cnt) { asm volatile("mbarrier.init.shared::cta.b64 [%0], %1;" ::"r"(bar), "r"(cnt) : "memory"); }
__device__ __forceinline__ void mbar_expect_tx(uint32_t bar, uint32_t bytes) { asm volatile("mbarrier.arrive.expect_tx.shared::cta.b64 _, [%0], %1;" ::"r"(bar), "r"(bytes) : "memory"); }
__device__ __forceinline__ void mbar_arrive(uint32_t bar) { asm volatile("mbarrier.arrive.shared::cta.b64 _, [%0];" ::"r"(bar) : "memory"); }
__device__ __forceinline__ void mbar_wait(uint32_t bar, uint32_t parity) {
    uint32_t ok;
#pragma unroll 1
    for (uint32_t it = 0;; ++it) {
        asm volatile("{\n.reg .pred p;\nmbarrier.try_wait.parity.shared::cta.b64 p, [%1], %2;\nselp.u32 %0, 1, 0, p;\n}\n" : "=r"(ok) : "r"(bar), "r"(parity) : "memory");
        if (ok) break;
        if (it > (1u << 20)) __trap();
    }
}
__device__ __forceinline__ bool mbar_test(uint32_t bar, uint32_t parity) {
    uint32_t ok;
    asm volatile("{\n.reg .pred p;\nmbarrier.test_wait.parity.shared::cta.b64 p, [%1], %2;\nselp.u32 %0, 1, 0, p;\n}\n" : "=r"(ok) : "r"(bar), "r"(parity) : "memory");
    return ok != 0;
}
__device__ __forceinline__ void fence_async() { asm volatile("fence.proxy.async.shared::cta;" ::: "memory"); }
__device__ __forceinline__ void fence_async_g() { asm volatile("fence.proxy.async.global;" ::: "memory"); }
__device__ __forceinline__ void bar_sync(int id, int n) { asm volatile("bar.sync %0, %1;" ::"r"(id), "r"(n) : "memory"); }
__device__ __forceinline__ void tma3(uint32_t dst, const CUtensorMap* tm, int c0, int c1, int c2, uint32_t bar) {
    asm volatile("cp.async.bulk.tensor.3d.shared::cluster.global.mbarrier::complete_tx::bytes [%0], [%1, {%3, %4, %5}], [%2];"
                 ::"r"(dst), "l"(tm), "r"(bar), "r"(c0), "r"(c1), "r"(c2) : "memory");
}
__device__ __forceinline__ void tma4(uint32_t dst, const CUtensorMap* tm, int c0, int c1, int c2, int c3, uint32_t bar) {
    asm volatile("cp.async.bulk.tensor.4d.shared::cluster.global.mbarrier::complete_tx::bytes [%0], [%1, {%3, %4, %5, %6}], [%2];"
                 ::"r"(dst), "l"(tm), "r"(bar), "r"(c0), "r"(c1), "r"(c2), "r"(c3) : "memory");
}
__device__ __forceinline__ void tma4_store(const CUtensorMap* tm, uint32_t src, int c0, int c1, int c2, int c3) {
    asm volatile("cp.async.bulk.tensor.4d.global.shared::cta.bulk_group [%0, {%2, %3, %4, %5}], [%1];"
                 ::"l"(tm), "r"(src), "r"(c0), "r"(c1), "r"(c2), "r"(c3) : "memory");
}
__device__ __forceinline__ void tma3_store(const CUtensorMap* tm, uint32_t src, int c0, int c1, int c2) {
    asm volatile("cp.async.bulk.tensor.3d.global.shared::cta.bulk_group [%0, {%2, %3, %4}], [%1];"
                 ::"l"(tm), "r"(src), "r"(c0), "r"(c1), "r"(c2) : "memory");
}
__device__ __forceinline__ void stsm4(uint32_t addr, uint32_t a, uint32_t b, uint32_t c, uint32_t d) {
    asm volatile("stmatrix.sync.aligned.m8n8.x4.shared.b16 [%0], {%1, %2, %3, %4};" ::"r"(addr), "r"(a), "r"(b), "r"(c), "r"(d) : "memory");
}
__device__ __forceinline__ void ldsm4(uint32_t addr, uint32_t (&r)[4]) {
    asm volatile("ldmatrix.sync.aligned.m8n8.x4.shared.b16 {%0, %1, %2, %3}, [%4];" : "=r"(r[0]), "=r"(r[1]), "=r"(r[2]), "=r"(r[3]) : "r"(addr) : "memory");
}
__device__ __forceinline__ void ldsm2(uint32_t addr, uint32_t (&r)[2]) {
    asm volatile("ldmatrix.sync.aligned.m8n8.x2.shared.b16 {%0, %1}, [%2];" : "=r"(r[0]), "=r"(r[1]) : "r"(addr) : "memory");
}
__device__ __forceinline__ void stg4(void* p, uint32_t a, uint32_t b, uint32_t c, uint32_t d) {
    asm volatile("st.global.v4.u32 [%0], {%1, %2, %3, %4};" ::"l"(p), "r"(a), "r"(b), "r"(c), "r"(d) : "memory");
}
__device__ __forceinline__ void hmma(float (&c)[4], uint32_t a0, uint32_t a1, uint32_t a2, uint32_t a3, uint32_t b0, uint32_t b1) {
    asm("mma.sync.aligned.m16n8k16.row.col.f32.bf16.bf16.f32 {%0, %1, %2, %3}, {%4, %5, %6, %7}, {%8, %9}, {%0, %1, %2, %3};"
        : "+f"(c[0]), "+f"(c[1]), "+f"(c[2]), "+f"(c[3]) : "r"(a0), "r"(a1), "r"(a2), "r"(a3), "r"(b0), "r"(b1));
}
__device__ __forceinline__ uint32_t pack2(float lo, float hi) {
    uint32_t r;
    asm("cvt.rn.bf16x2.f32 %0, %1, %2;" : "=r"(r) : "f"(hi), "f"(lo));
    return r;
}
__device__ __forceinline__ uint32_t pack2v(float lo, float hi) {
    uint32_t r;
    asm volatile("cvt.rn.bf16x2.f32 %0, %1, %2;" : "=r"(r) : "f"(hi), "f"(lo));
    return r;
}
__device__ __forceinline__ uint32_t bmul2(uint32_t a, uint32_t b) { uint32_t r; asm("mul.rn.bf16x2 %0, %1, %2;" : "=r"(r) : "r"(a), "r"(b)); return r; }
__device__ __forceinline__ uint32_t bfma2(uint32_t a, uint32_t b, uint32_t c) { uint32_t r; asm("fma.rn.bf16x2 %0, %1, %2, %3;" : "=r"(r) : "r"(a), "r"(b), "r"(c)); return r; }
__device__ __forceinline__ float ex2(float x) { float r; asm("ex2.approx.ftz.f32 %0, %1;" : "=f"(r) : "f"(x)); return r; }
__device__ __forceinline__ float rcp(float x) { float r; asm("rcp.approx.ftz.f32 %0, %1;" : "=f"(r) : "f"(x)); return r; }
__device__ __forceinline__ float gelu2(float x) {
    float t = fmaf(x * x, 0.044715f * 0.7978845608028654f, 0.7978845608028654f), th;
    asm("tanh.approx.f32 %0, %1;" : "=f"(th) : "f"(x * t));
    return fmaf(x, th, x);
}
__device__ __forceinline__ uint32_t ldg_v(const uint32_t* p) { uint32_t v; asm volatile("ld.global.nc.u32 %0, [%1];" : "=r"(v) : "l"(p)); return v; }
__device__ __forceinline__ uint32_t ldg_cg(const uint32_t* p) { uint32_t v; asm volatile("ld.global.cg.u32 %0, [%1];" : "=r"(v) : "l"(p) : "memory"); return v; }
__device__ __forceinline__ float lds_f32(uint32_t a) { float v; asm volatile("ld.shared.f32 %0, [%1];" : "=f"(v) : "r"(a) : "memory"); return v; }
__device__ __forceinline__ void sts_f32(uint32_t a, float v) { asm volatile("st.shared.f32 [%0], %1;" ::"r"(a), "f"(v) : "memory"); }
__device__ __forceinline__ uint32_t atom_inc_s(uint32_t a) { uint32_t v; asm volatile("atom.relaxed.cta.shared.add.u32 %0, [%1], 1;" : "=r"(v) : "r"(a) : "memory"); return v; }
__device__ __forceinline__ void lds4(uint32_t a, uint32_t* r) {
    asm volatile("ld.shared.v4.u32 {%0, %1, %2, %3}, [%4];" : "=r"(r[0]), "=r"(r[1]), "=r"(r[2]), "=r"(r[3]) : "r"(a) : "memory");
}
__device__ __forceinline__ void sts4(uint32_t a, uint32_t x, uint32_t y, uint32_t z, uint32_t t) {
    asm volatile("st.shared.v4.u32 [%0], {%1, %2, %3, %4};" ::"r"(a), "r"(x), "r"(y), "r"(z), "r"(t) : "memory");
}
__device__ __forceinline__ uint32_t bsub2(uint32_t a, uint32_t b) { uint32_t r; asm("sub.rn.bf16x2 %0, %1, %2;" : "=r"(r) : "r"(a), "r"(b)); return r; }
__device__ __forceinline__ float blo(uint32_t v) { return __uint_as_float(v << 16); }
__device__ __forceinline__ float bhi(uint32_t v) { return __uint_as_float(v & 0xffff0000u); }
__device__ __forceinline__ float bfr(float x) { return __bfloat162float(__float2bfloat16_rn(x)); }
__device__ __forceinline__ void l2_prefetch(const void* p, uint32_t bytes) { asm volatile("cp.async.bulk.prefetch.L2.global [%0], %1;" ::"l"(p), "r"(bytes) : "memory"); }
__device__ __forceinline__ void flag_add(unsigned* p) { asm volatile("red.release.gpu.global.add.u32 [%0], 1;" ::"l"(p) : "memory"); }
__device__ __forceinline__ void flag_wait(const unsigned* p, unsigned target) {
#pragma unroll 1
    for (uint32_t it = 0;; ++it) {
        unsigned v;
        asm volatile("ld.acquire.gpu.global.u32 %0, [%1];" : "=r"(v) : "l"(p) : "memory");
        if (v >= target) break;
        if (it > (1u << 20)) __trap();
    }
    fence_async_g();
}
template <int N> __device__ __forceinline__ void pin(float (&a)[N]) {
#pragma unroll
    for (int i = 0; i < N; i++) asm volatile("" : "+f"(a[i])::"memory");
}

template <int N> __device__ __forceinline__ void fresh(float (&a)[N]) {
#pragma unroll
    for (int i = 0; i < N; i++) a[i] = 0.f;
    pin(a);
}

__device__ __forceinline__ void wgmma_rs_n64_tb0(float (&d)[32], uint32_t a0, uint32_t a1, uint32_t a2, uint32_t a3, uint64_t db, int scale_d) {
    asm volatile("{\n.reg .pred p;\nsetp.ne.b32 p, %37, 0;\n"
        "wgmma.mma_async.sync.aligned.m64n64k16.f32.bf16.bf16 {%0, %1, %2, %3, %4, %5, %6, %7, %8, %9, %10, %11, %12, %13, %14, %15, %16, %17, %18, %19, %20, %21, %22, %23, %24, %25, %26, %27, %28, %29, %30, %31}, {%32, %33, %34, %35}, %36, p, 1, 1, 0;\n}\n"
        : "+f"(d[0]), "+f"(d[1]), "+f"(d[2]), "+f"(d[3]), "+f"(d[4]), "+f"(d[5]), "+f"(d[6]), "+f"(d[7]), "+f"(d[8]), "+f"(d[9]), "+f"(d[10]), "+f"(d[11]), "+f"(d[12]), "+f"(d[13]), "+f"(d[14]), "+f"(d[15]), "+f"(d[16]), "+f"(d[17]), "+f"(d[18]), "+f"(d[19]), "+f"(d[20]), "+f"(d[21]), "+f"(d[22]), "+f"(d[23]), "+f"(d[24]), "+f"(d[25]), "+f"(d[26]), "+f"(d[27]), "+f"(d[28]), "+f"(d[29]), "+f"(d[30]), "+f"(d[31])
        : "r"(a0), "r"(a1), "r"(a2), "r"(a3), "l"(db), "r"(scale_d));
}

__device__ __forceinline__ void wgmma_ss_n128_tb1(float (&d)[64], uint64_t da, uint64_t db, int scale_d) {
    asm volatile("{\n.reg .pred p;\nsetp.ne.b32 p, %66, 0;\n"
        "wgmma.mma_async.sync.aligned.m64n128k16.f32.bf16.bf16 {%0, %1, %2, %3, %4, %5, %6, %7, %8, %9, %10, %11, %12, %13, %14, %15, %16, %17, %18, %19, %20, %21, %22, %23, %24, %25, %26, %27, %28, %29, %30, %31, %32, %33, %34, %35, %36, %37, %38, %39, %40, %41, %42, %43, %44, %45, %46, %47, %48, %49, %50, %51, %52, %53, %54, %55, %56, %57, %58, %59, %60, %61, %62, %63}, %64, %65, p, 1, 1, 0, 1;\n}\n"
        : "+f"(d[0]), "+f"(d[1]), "+f"(d[2]), "+f"(d[3]), "+f"(d[4]), "+f"(d[5]), "+f"(d[6]), "+f"(d[7]), "+f"(d[8]), "+f"(d[9]), "+f"(d[10]), "+f"(d[11]), "+f"(d[12]), "+f"(d[13]), "+f"(d[14]), "+f"(d[15]), "+f"(d[16]), "+f"(d[17]), "+f"(d[18]), "+f"(d[19]), "+f"(d[20]), "+f"(d[21]), "+f"(d[22]), "+f"(d[23]), "+f"(d[24]), "+f"(d[25]), "+f"(d[26]), "+f"(d[27]), "+f"(d[28]), "+f"(d[29]), "+f"(d[30]), "+f"(d[31]), "+f"(d[32]), "+f"(d[33]), "+f"(d[34]), "+f"(d[35]), "+f"(d[36]), "+f"(d[37]), "+f"(d[38]), "+f"(d[39]), "+f"(d[40]), "+f"(d[41]), "+f"(d[42]), "+f"(d[43]), "+f"(d[44]), "+f"(d[45]), "+f"(d[46]), "+f"(d[47]), "+f"(d[48]), "+f"(d[49]), "+f"(d[50]), "+f"(d[51]), "+f"(d[52]), "+f"(d[53]), "+f"(d[54]), "+f"(d[55]), "+f"(d[56]), "+f"(d[57]), "+f"(d[58]), "+f"(d[59]), "+f"(d[60]), "+f"(d[61]), "+f"(d[62]), "+f"(d[63])
        : "l"(da), "l"(db), "r"(scale_d));
}

__device__ __forceinline__ void wgmma_ss_n256_tb1(float (&d)[128], uint64_t da, uint64_t db, int scale_d) {
    asm volatile("{\n.reg .pred p;\nsetp.ne.b32 p, %130, 0;\n"
        "wgmma.mma_async.sync.aligned.m64n256k16.f32.bf16.bf16 {%0, %1, %2, %3, %4, %5, %6, %7, %8, %9, %10, %11, %12, %13, %14, %15, %16, %17, %18, %19, %20, %21, %22, %23, %24, %25, %26, %27, %28, %29, %30, %31, %32, %33, %34, %35, %36, %37, %38, %39, %40, %41, %42, %43, %44, %45, %46, %47, %48, %49, %50, %51, %52, %53, %54, %55, %56, %57, %58, %59, %60, %61, %62, %63, %64, %65, %66, %67, %68, %69, %70, %71, %72, %73, %74, %75, %76, %77, %78, %79, %80, %81, %82, %83, %84, %85, %86, %87, %88, %89, %90, %91, %92, %93, %94, %95, %96, %97, %98, %99, %100, %101, %102, %103, %104, %105, %106, %107, %108, %109, %110, %111, %112, %113, %114, %115, %116, %117, %118, %119, %120, %121, %122, %123, %124, %125, %126, %127}, %128, %129, p, 1, 1, 0, 1;\n}\n"
        : "+f"(d[0]), "+f"(d[1]), "+f"(d[2]), "+f"(d[3]), "+f"(d[4]), "+f"(d[5]), "+f"(d[6]), "+f"(d[7]), "+f"(d[8]), "+f"(d[9]), "+f"(d[10]), "+f"(d[11]), "+f"(d[12]), "+f"(d[13]), "+f"(d[14]), "+f"(d[15]), "+f"(d[16]), "+f"(d[17]), "+f"(d[18]), "+f"(d[19]), "+f"(d[20]), "+f"(d[21]), "+f"(d[22]), "+f"(d[23]), "+f"(d[24]), "+f"(d[25]), "+f"(d[26]), "+f"(d[27]), "+f"(d[28]), "+f"(d[29]), "+f"(d[30]), "+f"(d[31]), "+f"(d[32]), "+f"(d[33]), "+f"(d[34]), "+f"(d[35]), "+f"(d[36]), "+f"(d[37]), "+f"(d[38]), "+f"(d[39]), "+f"(d[40]), "+f"(d[41]), "+f"(d[42]), "+f"(d[43]), "+f"(d[44]), "+f"(d[45]), "+f"(d[46]), "+f"(d[47]), "+f"(d[48]), "+f"(d[49]), "+f"(d[50]), "+f"(d[51]), "+f"(d[52]), "+f"(d[53]), "+f"(d[54]), "+f"(d[55]), "+f"(d[56]), "+f"(d[57]), "+f"(d[58]), "+f"(d[59]), "+f"(d[60]), "+f"(d[61]), "+f"(d[62]), "+f"(d[63]), "+f"(d[64]), "+f"(d[65]), "+f"(d[66]), "+f"(d[67]), "+f"(d[68]), "+f"(d[69]), "+f"(d[70]), "+f"(d[71]), "+f"(d[72]), "+f"(d[73]), "+f"(d[74]), "+f"(d[75]), "+f"(d[76]), "+f"(d[77]), "+f"(d[78]), "+f"(d[79]), "+f"(d[80]), "+f"(d[81]), "+f"(d[82]), "+f"(d[83]), "+f"(d[84]), "+f"(d[85]), "+f"(d[86]), "+f"(d[87]), "+f"(d[88]), "+f"(d[89]), "+f"(d[90]), "+f"(d[91]), "+f"(d[92]), "+f"(d[93]), "+f"(d[94]), "+f"(d[95]), "+f"(d[96]), "+f"(d[97]), "+f"(d[98]), "+f"(d[99]), "+f"(d[100]), "+f"(d[101]), "+f"(d[102]), "+f"(d[103]), "+f"(d[104]), "+f"(d[105]), "+f"(d[106]), "+f"(d[107]), "+f"(d[108]), "+f"(d[109]), "+f"(d[110]), "+f"(d[111]), "+f"(d[112]), "+f"(d[113]), "+f"(d[114]), "+f"(d[115]), "+f"(d[116]), "+f"(d[117]), "+f"(d[118]), "+f"(d[119]), "+f"(d[120]), "+f"(d[121]), "+f"(d[122]), "+f"(d[123]), "+f"(d[124]), "+f"(d[125]), "+f"(d[126]), "+f"(d[127])
        : "l"(da), "l"(db), "r"(scale_d));
}

__device__ __forceinline__ void wgmma_ss_n32_tb0(float (&d)[16], uint64_t da, uint64_t db, int scale_d) {
    asm volatile("{\n.reg .pred p;\nsetp.ne.b32 p, %18, 0;\n"
        "wgmma.mma_async.sync.aligned.m64n32k16.f32.bf16.bf16 {%0, %1, %2, %3, %4, %5, %6, %7, %8, %9, %10, %11, %12, %13, %14, %15}, %16, %17, p, 1, 1, 0, 0;\n}\n"
        : "+f"(d[0]), "+f"(d[1]), "+f"(d[2]), "+f"(d[3]), "+f"(d[4]), "+f"(d[5]), "+f"(d[6]), "+f"(d[7]), "+f"(d[8]), "+f"(d[9]), "+f"(d[10]), "+f"(d[11]), "+f"(d[12]), "+f"(d[13]), "+f"(d[14]), "+f"(d[15])
        : "l"(da), "l"(db), "r"(scale_d));
}

__device__ __forceinline__ void wgmma_ss_n64_tb0(float (&d)[32], uint64_t da, uint64_t db, int scale_d) {
    asm volatile("{\n.reg .pred p;\nsetp.ne.b32 p, %34, 0;\n"
        "wgmma.mma_async.sync.aligned.m64n64k16.f32.bf16.bf16 {%0, %1, %2, %3, %4, %5, %6, %7, %8, %9, %10, %11, %12, %13, %14, %15, %16, %17, %18, %19, %20, %21, %22, %23, %24, %25, %26, %27, %28, %29, %30, %31}, %32, %33, p, 1, 1, 0, 0;\n}\n"
        : "+f"(d[0]), "+f"(d[1]), "+f"(d[2]), "+f"(d[3]), "+f"(d[4]), "+f"(d[5]), "+f"(d[6]), "+f"(d[7]), "+f"(d[8]), "+f"(d[9]), "+f"(d[10]), "+f"(d[11]), "+f"(d[12]), "+f"(d[13]), "+f"(d[14]), "+f"(d[15]), "+f"(d[16]), "+f"(d[17]), "+f"(d[18]), "+f"(d[19]), "+f"(d[20]), "+f"(d[21]), "+f"(d[22]), "+f"(d[23]), "+f"(d[24]), "+f"(d[25]), "+f"(d[26]), "+f"(d[27]), "+f"(d[28]), "+f"(d[29]), "+f"(d[30]), "+f"(d[31])
        : "l"(da), "l"(db), "r"(scale_d));
}

struct Maps {
    CUtensorMap xa, xa2, xa4, xas, wup4, wup8, mqa2, mqa4, mqb1, mqb2, uc, x, out, wq, wk, fa[3], fb[2], fc;
};

__device__ __forceinline__ uint64_t mkd(uint32_t lo) {
    uint64_t d;
    asm("mov.b64 %0, {%1, %2};" : "=l"(d) : "r"(lo), "r"((1024u >> 4) | (1u << 30)));
    return d;
}
__device__ __forceinline__ void bulk_ld(uint32_t dst, const void* src, uint32_t bytes, uint32_t bar) {
    asm volatile("cp.async.bulk.shared::cluster.global.mbarrier::complete_tx::bytes [%0], [%1], %2, [%3];" ::"r"(dst), "l"(src), "r"(bytes), "r"(bar) : "memory");
}
__device__ __forceinline__ void bulk_st(void* dst, uint32_t src, uint32_t bytes) {
    asm volatile("cp.async.bulk.global.shared::cta.bulk_group [%0], [%1], %2;" ::"l"(dst), "r"(src), "r"(bytes) : "memory");
}
__device__ __forceinline__ void ring_ld(uint32_t sb, uint32_t slot8, int n) {
    mbar_expect_tx(sb + B_R2 + slot8, 8192);
    bulk_ld(sb + R1 + slot8 * 1024, (const char*)g_wepi + n * 8192, 8192, sb + B_R2 + slot8);
}

__device__ __forceinline__ void ring_half(uint32_t sb, uint32_t slot8, uint32_t hoff, const CUtensorMap* tm, int c1, int c2) {
    mbar_expect_tx(sb + B_R1 + slot8, 8192);
    tma3(sb + slot8 * 2048 + hoff, tm, 0, c1, c2, sb + B_R1 + slot8);
}
__device__ __forceinline__ void ring_full(uint32_t sb, uint32_t slot8, const CUtensorMap* tm, int c1, int c2) {
    mbar_expect_tx(sb + B_R1 + slot8, 16384);
    mbar_arrive(sb + B_R1 + slot8);
    tma3(sb + slot8 * 2048, tm, 0, c1, c2, sb + B_R1 + slot8);
}
__device__ __forceinline__ void cta_done(int mode) {
    if (mode == 0 && atomicAdd(&g_sync[4], 1) == NCTA + 1) {
#pragma unroll
        for (int i = 0; i < 5; i++) g_sync[i] = 0;
    }
}

__device__ __forceinline__ void fold_cta(const Maps& mp, uint32_t sb, int mode) {
    constexpr uint32_t F_FULL = MISC, F_EMPTY = MISC + 32, F_T1 = MISC + 64, STG = 49152, FOUT = 3 * STG;
    const int tid = threadIdx.x, f = blockIdx.x - NCTA;
    if (mode == 2) return;
    if (tid == 0) {
        for (int i = 0; i < 3; i++) { mbar_init(sb + F_FULL + 8 * i, 1); mbar_init(sb + F_EMPTY + 8 * i, 2); }
        mbar_init(sb + F_T1, 2);
        asm volatile("fence.mbarrier_init.release.cluster;" ::: "memory");
        fence_async();
    }
    __syncthreads();
    const int wg = __shfl_sync(0xffffffffu, tid >> 7, 0);
    int st = 0, ph = 0;
    if (wg == 0) {
        if (tid == 0) {
#pragma unroll 1
            for (int it = 0; it < 96; it++) {
                const int p = it >> 3, kc = it & 7, job = p >> 2;
                if (it == 64) mbar_wait(sb + F_T1, 0);
                mbar_wait(sb + F_EMPTY + 8 * st, ph ^ 1);
                mbar_expect_tx(sb + F_FULL + 8 * st, STG);
                tma3(sb + st * STG, &mp.fa[job], 0, 256 * f + 128 * ((p >> 1) & 1), kc, sb + F_FULL + 8 * st);
                tma3(sb + st * STG + 16384, &mp.fb[job != 0], 0, 64 * kc + (job == 1 ? 512 : 0), 4 * (p & 1), sb + F_FULL + 8 * st);
                if (++st == 3) { st = 0; ph ^= 1; }
            }
        }
        return;
    }
    const int h = wg - 1, lane = tid & 31, w = (tid >> 5) & 3;
    const uint32_t sd = (sb & 0x3FFFF) >> 4;
    const bool el = (tid & 127) == 0;
#pragma unroll 1
    for (int p = 0; p < 12; p++) {
        float acc[128];
        fresh(acc);
#pragma unroll 1
        for (int kc = 0; kc < 8; kc++) {
            mbar_wait(sb + F_FULL + 8 * st, ph);
            wg_fence();
#pragma unroll
            for (int kk = 0; kk < 4; kk++)
                wgmma_ss_n256_tb1(acc, dsc(sd, st * STG + h * 8192 + kk * 32, 16), dsc(sd, st * STG + 16384 + kk * 2048, 8192), 1);
            wg_commit();
            wg_wait<0>();
            if (el) mbar_arrive(sb + F_EMPTY + 8 * st);
            if (++st == 3) { st = 0; ph ^= 1; }
        }
        pin(acc);
        const int job = p >> 2;
        if (el) {
            asm volatile("cp.async.bulk.wait_group 0;" ::: "memory");
            if (p == 4) { fence_async_g(); mbar_arrive(sb + F_T1); }
        }
        bar_sync(3 + h, 128);
        uint32_t r = 16 * w + (lane & 7) + ((lane >> 3) & 1) * 8;
        const float fs = job == 1 ? 0.5f : 1.f;
        if (job == 1) r = (r & ~31) | (((r >> 1) & 3) << 3) | (((r >> 3) & 3) << 1) | (r & 1);
        const uint32_t oa = sb + FOUT + h * 32768 + r * 128 + ((((lane >> 4) ^ r) & 7) << 4);
#pragma unroll
        for (int i = 0; i < 16; i++)
            stsm4((oa ^ ((i & 3) << 5)) + (i >> 2) * 8192, pack2(acc[8 * i] * fs, acc[8 * i + 1] * fs), pack2(acc[8 * i + 2] * fs, acc[8 * i + 3] * fs),
                  pack2(acc[8 * i + 4] * fs, acc[8 * i + 5] * fs), pack2(acc[8 * i + 6] * fs, acc[8 * i + 7] * fs));
        fence_async();
        bar_sync(3 + h, 128);
        if (el) {
            const int row0 = 256 * f + 128 * ((p >> 1) & 1) + 64 * h + (job == 1 ? 512 : 0);
            if (job == 0) tma3_store(&mp.fc, sb + FOUT + h * 32768, 0, row0, 4 * (p & 1));
            else {
#pragma unroll 1
                for (int i = 0; i < 16; i++)
                    bulk_st((char*)g_wepi + (row0 / 8 + 2 * (i & 3) + (p & 1)) * 8192 + (i >> 2) * 2048, sb + FOUT + h * 32768 + i * 2048, 2048);
            }
            asm volatile("cp.async.bulk.commit_group;" ::: "memory");
        }
    }
    if (el) {
        asm volatile("cp.async.bulk.wait_group 0;" ::: "memory");
        fence_async_g();
        if (mode == 0) flag_add(&g_sync[3]);
    }
    bar_sync(2, 256);
    if (tid == 128) cta_done(mode);
}

__global__ void __launch_bounds__(384, 1) main_kernel(const __grid_constant__ Maps mp, const bf16* __restrict__ x, const bf16* __restrict__ dw, const bf16* wup, const int mode) {
    extern __shared__ __align__(1024) uint8_t smem[];
    const uint32_t sb = smem_u32(smem);
    const int tid = threadIdx.x;
    PE();
    if (blockIdx.x >= NCTA) { fold_cta(mp, sb, mode); return; }
    const int b = blockIdx.x / TPB, ti = blockIdx.x % TPB;
    const int piece = blockIdx.x & 127;
    const int wg = __shfl_sync(0xffffffffu, tid >> 7, 0);
    const int lane = tid & 31, w = (tid >> 5) & 3;
    const bool w0 = __shfl_sync(0xffffffffu, w, 0) == 0;
    const uint32_t sd = (sb & 0x3FFFF) >> 4;
    const uint32_t adA = sd + (AT >> 4) + (1u << 16);
    const uint32_t bd0 = sd;
    const uint32_t bd2k = bd0 + ((2048u >> 4) << 16);
    const bool el = (tid & 127) == 0;
    const uint32_t lrow = 16 * w + (lane & 7) + ((lane >> 3) & 1) * 8;
    const uint32_t loff = lrow * 128 + ((((lane >> 4) ^ lrow) & 7) << 4);
    const int r0 = 16 * w + (lane >> 2);

    if (wg == 0) {
        asm volatile("setmaxnreg.inc.sync.aligned.u32 184;");
        uint32_t q[112];
        PG(206);
        if (tid == 0) {
            mbar_init(sb + B_MK, 1);
            for (int i = 0; i < 9; i++) mbar_init(sb + B_R1 + 8 * i, 2);
            for (int i = 0; i < 5; i++) asm volatile("st.shared.u32 [%0], 0;" ::"r"(sb + CNT + 4 * i) : "memory");
        } else if (tid == 32) {
            mbar_init(sb + B_LN, 1); mbar_init(sb + B_MQ, 1);
            mbar_init(sb + B_H1, 2); mbar_init(sb + B_H2, 1); mbar_init(sb + B_H3, 2);
            for (int i = 0; i < 3; i++) { mbar_init(sb + B_KV + 8 * i, 2); mbar_init(sb + B_P + 8 * i, 4); mbar_init(sb + B_GO + 8 * i, 4); }
            mbar_init(sb + B_UC, 1); mbar_init(sb + B_UC + 8, 1); mbar_init(sb + B_X, 8);
        } else if (tid == 64) {
            for (int i = 0; i < 20; i++) mbar_init(sb + B_R2 + 8 * i, 1);
        } else if (tid == 96) {
            for (int i = 0; i < 20; i++) mbar_init(sb + B_E2 + 8 * i, 4);
        }
        if (lane == 0) {
            asm volatile("fence.mbarrier_init.release.cluster;" ::: "memory");
            fence_async();
        }
        PG(207);
        __syncwarp();
        if (SU != 2) asm volatile("bar.arrive 5, 384;" ::: "memory");
        if (tid == 0) {
            mbar_expect_tx(sb + B_MK, 65536 + 32768);
            tma3(sb + 16384, &mp.wq, 0, 64 * (piece >> 4), 0, sb + B_MK);
            tma3(sb + 81920, &mp.wk, 0, 32 * (piece & 15), 0, sb + B_MK);
            for (int i = 0; i < 14; i++) mbar_arrive(sb + B_R1 + 8 * (i >> 1));
            if (mode != 1) {
                ring_full(sb, 56, &mp.wup8, 0, 8);
                ring_full(sb, 64, &mp.wup8, 16, 8);
                ring_full(sb, 0, &mp.wup8, 32, 8);
            }
        }
        PG(208);
        bar_sync(1, 128);
        if (SU == 2) asm volatile("bar.arrive 5, 384;" ::: "memory");
        PT(0);
        PG(200);
        {
            float mq[16];
            fresh(mq);
            mbar_wait(sb + B_MK, 0);
            PT(1);
            if (tid == 32) l2_prefetch((const char*)wup + piece * 8192, 8192);
            wg_fence();
#pragma unroll 1
            for (int c = 0; c < 8; c++)
#pragma unroll
                for (int kk = 0; kk < 4; kk++)
                    wgmma_ss_n32_tb0(mq, dsc(sd, 16384 + c * 8192 + kk * 32, 16), dsc(sd, 81920 + c * 4096 + kk * 32, 16), 1);
            wg_commit();
            wg_wait<0>();
            if (mode != 1 && w0 && elect1()) {
#pragma unroll 1
                for (int i = 1; i < 7; i++) ring_full(sb, 8 * i, &mp.wup8, 32 + 16 * i, 8);
            }
            pin(mq);
            uint32_t* c = reinterpret_cast<uint32_t*>(g_mqk + (64 * (piece >> 4) + r0) * D_ + 32 * (piece & 15) + 2 * (lane & 3));
#pragma unroll
            for (int n = 0; n < 4; n++) { c[4 * n] = pack2(mq[4 * n], mq[4 * n + 1]); c[4 * n + 4 * D_] = pack2(mq[4 * n + 2], mq[4 * n + 3]); }
            fence_async_g();
            bar_sync(1, 128);
            if (el) {
                if (mode == 0) flag_add(&g_sync[2]);
                if (mode == 0) flag_wait(&g_sync[2], NCTA);
                mbar_arrive(sb + B_MQ);
                PG(203);
                PT(12);
                mbar_wait(sb + B_LN, 0);
#pragma unroll 1
                for (int c = 0; c < 8; c++) {
                    tma4_store(&mp.xas, sb + AT + c * 8192, 0, 62 * ti, c, b);
                    const unsigned t0 = (unsigned)clock();
                    while (c < 7 && (unsigned)clock() - t0 < XS_GAP) __nanosleep(20);
                }
                asm volatile("cp.async.bulk.commit_group;" ::: "memory");
                if (mode == 1) asm volatile("cp.async.bulk.wait_group 0;" ::: "memory");
            }
            PT(13);
            if (mode == 1) return;
        }
        mbar_wait(sb + B_H1, 0);
        PT(2);
        uint32_t slot8 = 24, par = 0, prev8 = 0, prev2 = 0;
        auto adv = [&]() { prev2 = prev8; prev8 = slot8; slot8 += 8; if (slot8 == 72) { slot8 = 0; par ^= 1; } };
        {
            float acc[128];
            fresh(acc);
            auto step = [&](int i) {
                const uint32_t aa = adA + (i >> 1) * 512 + (i & 1) * 4, bb = bd0 + ((4096u >> 4) << 16) + slot8 * 128;
                wg_fence();
                wgmma_ss_n256_tb1(acc, mkd(aa), mkd(bb), 1);
                wgmma_ss_n256_tb1(acc, mkd(aa + 2), mkd(bb + 128), 1);
                wg_commit();
                wg_wait<1 + LAGA>();
            };
#pragma unroll 1
            for (int i = 0; i < 8 + LAGA; i++) {
                mbar_wait(sb + B_R1 + slot8, par);
                step(i);
                if (i > LAGA && w0 && elect1()) ring_full(sb, LAGA ? prev2 : prev8, &mp.mqa4, 32 * (i - LAGA) + 256, 4);
                adv();
            }
#pragma unroll 1
            for (int i = 8 + LAGA; i < 16; i++) {
                mbar_wait(sb + B_R1 + slot8, par);
                if (i == 15 && el) mbar_arrive(sb + B_H2);
                step(i);
                if (w0 && elect1()) ring_full(sb, LAGA ? prev2 : prev8, &mp.wup8, 16 * (i - LAGA) - 128, 0);
                adv();
            }
            if (LAGA) {
                wg_wait<1>();
                if (w0 && elect1()) ring_full(sb, prev2, &mp.wup8, 112, 0);
            }
            wg_wait<0>();
            if (w0 && elect1()) ring_full(sb, prev8, &mp.wup8, 128, 0);
            pin(acc);
            PT(3);
#pragma unroll
            for (int kk = 0; kk < 4; kk++)
                stsm4((sb + QS + loff) ^ (kk << 5), pack2(acc[96 + 8 * kk], acc[97 + 8 * kk]), pack2(acc[98 + 8 * kk], acc[99 + 8 * kk]),
                      pack2(acc[100 + 8 * kk], acc[101 + 8 * kk]), pack2(acc[102 + 8 * kk], acc[103 + 8 * kk]));
            fence_async();
#pragma unroll
            for (int i = 47; i >= 0; i--) q[64 + i] = pack2v(acc[2 * i], acc[2 * i + 1]);
        }
        if (el) {
            asm volatile("cp.async.bulk.wait_group 0;" ::: "memory");
            if (mode == 0) {
                fence_async_g();
                flag_add(&g_sync[b]);
                flag_wait(&g_sync[b], TPB);
            }
        }
        __syncwarp();
        mbar_wait(sb + B_H3, 0);
        PT(4);
        slot8 = 48; par = 1;
#pragma unroll
        for (int half = 0; half < 2; half++) {
            float acc[64];
            fresh(acc);
            auto step = [&](int m) {
                const uint32_t aa = adA + m * 512, bb = bd0 + ((8192u >> 4) << 16) + slot8 * 128;
                mbar_wait(sb + B_R1 + slot8, par);
                wg_fence();
#pragma unroll
                for (int kk = 0; kk < 4; kk++) wgmma_ss_n128_tb1(acc, mkd(aa + 2 * kk), mkd(bb + 128 * kk), 1);
                wg_commit();
                wg_wait<1 + LAGB>();
            };
#pragma unroll 1
            for (int m = 0; m < 8; m++) {
                step(m);
                if (m > LAGB && w0 && elect1()) {
                    if (half == 0) ring_full(sb, LAGB ? prev2 : prev8, &mp.mqb2, 64 * (m - LAGB), 2);
                    else if (m < 4 + LAGB) tma4(sb + (LAGB ? prev2 : prev8) * 2048, &mp.xa2, 0, 0, 2 * (m - LAGB), b, sb + B_KV + 8);
                }
                adv();
            }
            if (LAGB && half == 0) {
                wg_wait<1>();
                if (w0 && elect1()) ring_full(sb, prev2, &mp.mqb2, 448, 2);
            }
            wg_wait<0>();
            if (w0 && elect1()) {
                if (half == 0) {
                    mbar_expect_tx(sb + B_KV + 8, 65536);
                    for (int i = 0; i < 3; i++) mbar_arrive(sb + B_KV + 8 * i);
                    tma4(sb + prev8 * 2048, &mp.xa2, 0, 0, 0, b, sb + B_KV + 8);
                } else {
                    mbar_expect_tx(sb + B_KV + 16, 65536);
                    tma4(sb + R2, &mp.xa, 0, 64, 0, b, sb + B_KV + 16);
                    mbar_expect_tx(sb + B_KV, 65536);
                    tma4(sb + R0, &mp.xa, 0, 128, 0, b, sb + B_KV);
                }
            }
            pin(acc);
#pragma unroll
            for (int i = 31; i >= 0; i--) q[32 * half + i] = pack2v(acc[2 * i], acc[2 * i + 1]);
        }
        bar_sync(1, 128);
        PT(5);

        const float CS = 0.04419417382415922f * 1.4426950408889634f;
        float m0 = -INFINITY, m1 = -INFINITY, l0 = 0.f, l1 = 0.f;
        int s = 0, sn = 1, ph = 0;
        float S[32];
        const bool l0w = lane == 0, q0 = (lane & 3) == 0;
#pragma unroll 1
        for (int j = -1;; j++) {
            if (j >= 0) {
                PL(j, 1);
                if (j == NKV - 1) {
#pragma unroll
                    for (int i = (T_ - 64 * (NKV - 1)) / 2; i < 32; i++) asm volatile("mov.b32 %0, 0xff800000;" : "=f"(S[i]));
                }
                const bool kv = mbar_test(sb + B_KV + sn * 8, ph);
                const uint32_t pb = sb + R3 + (s == 0 ? 2 : s - 1) * 8192;
                float a0 = 0.f, a1 = 0.f, sc0 = 1.f, sc1 = 1.f;
                auto expo = [&]() {
                    const float n0 = -m0 * CS, n1 = -m1 * CS;
                    a0 = 0.f; a1 = 0.f;
#pragma unroll
                    for (int kk = 0; kk < 4; kk++) {
                        float p[8];
#pragma unroll
                        for (int e = 0; e < 8; e++) p[e] = ex2(fmaf(S[8 * kk + e], CS, (e & 2) ? n1 : n0));
                        a0 += (p[0] + p[1]) + (p[4] + p[5]);
                        a1 += (p[2] + p[3]) + (p[6] + p[7]);
                        stsm4((pb + loff) ^ (kk << 5), pack2(p[0], p[1]), pack2(p[2], p[3]), pack2(p[4], p[5]), pack2(p[6], p[7]));
                    }
                };
                if (j > 0 || !SK0) expo();
                if ((SK0 && j == 0) || __any_sync(0xffffffffu, !(a0 <= LAZY) || !(a1 <= LAZY))) {
                    float x0 = m0, x1 = m1;
#pragma unroll
                    for (int n = 0; n < 8; n++) { x0 = fmaxf(x0, fmaxf(S[4 * n], S[4 * n + 1])); x1 = fmaxf(x1, fmaxf(S[4 * n + 2], S[4 * n + 3])); }
                    x0 = fmaxf(x0, __shfl_xor_sync(0xffffffffu, x0, 1));
                    x1 = fmaxf(x1, __shfl_xor_sync(0xffffffffu, x1, 1));
                    x0 = fmaxf(x0, __shfl_xor_sync(0xffffffffu, x0, 2));
                    x1 = fmaxf(x1, __shfl_xor_sync(0xffffffffu, x1, 2));
                    sc0 = ex2((m0 - x0) * CS); sc1 = ex2((m1 - x1) * CS);
                    m0 = x0; m1 = x1;
                    expo();
                }
                if (q0) { sts_f32(sb + SCL + s * 256 + r0 * 4, sc0); sts_f32(sb + SCL + s * 256 + r0 * 4 + 32, sc1); }
                __syncwarp();
                if (l0w) mbar_arrive(sb + B_P + s * 8);
                l0 = fmaf(l0, sc0, a0); l1 = fmaf(l1, sc1, a1);
                PL(j, 2);
                if (j == NKV - 1) break;
                if (!kv) mbar_wait(sb + B_KV + sn * 8, ph);
            } else {
                mbar_wait(sb + B_KV + 8, 0);
            }
            float Sn[32];
            const uint32_t kd = sd + sn * 4096;
            wg_fence();
#pragma unroll
            for (int kk = 0; kk < 28; kk++) {
                wgmma_rs_n64_tb0(Sn, q[4 * kk], q[4 * kk + 1], q[4 * kk + 2], q[4 * kk + 3], dsc(kd, (kk >> 2) * 8192 + (kk & 3) * 32, 16), kk > 0);
                if (kk == FENCE_AT) { fence_async(); __syncwarp(); }
                if (kk == GO_AT) { PL(j, 3); if (j >= 0 && l0w) mbar_arrive(sb + B_GO + s * 8); }
            }
#pragma unroll
            for (int kk = 0; kk < 4; kk++)
                wgmma_ss_n64_tb0(Sn, dsc(sd, QS + kk * 32, 16), dsc(kd, 7 * 8192 + kk * 32, 16), 1);
            wg_commit();
            PL(j, 0);
            wg_wait<0>();
            pin(Sn);
#pragma unroll
            for (int i = 0; i < 32; i++) S[i] = Sn[i];
            s = sn;
            if (++sn == 3) sn = 0;
            if (sn == 1) ph ^= 1;
        }
        l0 += __shfl_xor_sync(0xffffffffu, l0, 1); l1 += __shfl_xor_sync(0xffffffffu, l1, 1);
        l0 += __shfl_xor_sync(0xffffffffu, l0, 2); l1 += __shfl_xor_sync(0xffffffffu, l1, 2);
        if (q0) { sts_f32(sb + LINV + r0 * 4, rcp(l0)); sts_f32(sb + LINV + r0 * 4 + 32, rcp(l1)); }
        fence_async();
        __syncwarp();
        if (l0w) {
            mbar_arrive(sb + B_GO + s * 8);
            uint32_t slot8 = 8 * w, par = 0;
#pragma unroll 1
            for (int n = 20 + w; n < 136; n += 4) {
                mbar_wait(sb + B_E2 + slot8, par);
                if (n < 128) ring_ld(sb, slot8, n);
                else {
                    mbar_expect_tx(sb + B_X, 8192);
                    tma4(sb + R1 + slot8 * 1024, &mp.x, 0, 62 * ti, n - 128, b, sb + B_X);
                }
                slot8 += 32;
                if (slot8 >= 160) { slot8 -= 160; par ^= 1; }
            }
        }
        PDUMP();
    } else {
        asm volatile("setmaxnreg.dec.sync.aligned.u32 160;");
        const int h = wg - 1;
        uint32_t v[4][8], v2[4][8];
        if (SU != 0) bar_sync(5, 384);
        PG(206);
#pragma unroll
        for (int i = 0; i < 8; i++) {
            const int t = 62 * ti - 1 + 32 * (i >> 2) + 16 * h + 4 * w + (i & 3);
            const uint4* p = reinterpret_cast<const uint4*>(x + ((size_t)b * T_ + t) * D_) + lane;
            uint32_t* d = i < 4 ? v[i & 3] : v2[i & 3];
#pragma unroll
            for (int c = 0; c < 2; c++)
                asm volatile("{\n.reg .pred p;\nsetp.lt.u32 p, %5, %6;\nmov.b32 %0, 0;\nmov.b32 %1, 0;\nmov.b32 %2, 0;\nmov.b32 %3, 0;\n"
                             "@p ld.global.nc.v4.u32 {%0, %1, %2, %3}, [%4];\n}\n"
                             : "=r"(d[4 * c]), "=r"(d[4 * c + 1]), "=r"(d[4 * c + 2]), "=r"(d[4 * c + 3]) : "l"(p + 32 * c), "r"(t), "n"(T_));
        }
#pragma unroll 1
        for (int bt = 0; bt < 2; bt++) {
            PT(bt ? 13 : 0);
            float a[8];
            const uint32_t la = sb + AT + (lane >> 3) * 8192 + (32 * bt + 16 * h + 4 * w) * 128 + (((lane & 7) ^ ((w & 1) * 4)) << 4);
            const bool b4 = lane & 16, b3 = lane & 8, b2 = lane & 4;
#pragma unroll
            for (int r = 0; r < 4; r++) {
                float c[4] = {0.f, 0.f, 0.f, 0.f};
#pragma unroll
                for (int i = 0; i < 8; i += 2) hmma(c, v[r][i], v[r][i], v[r][i + 1], v[r][i + 1], v[r][i], v[r][i + 1]);
                a[4 + r] = (lane & 3) == (lane >> 3) ? (b2 ? c[1] : c[0]) : 0.f;
                if (r & 1) {
                    float e[4] = {0.f, 0.f, 0.f, 0.f};
#pragma unroll
                    for (int i = 0; i < 8; i += 2) hmma(e, v[r - 1][i], v[r][i], v[r - 1][i + 1], v[r][i + 1], 0x3f803f80u, 0x3f803f80u);
                    a[r - 1] = e[0]; a[r] = e[2];
                }
            }
            float k[4];
#pragma unroll
            for (int i = 0; i < 4; i++) {
                const int lo = (i & 1) + 4 * (i >> 1);
                k[i] = (b4 ? a[lo + 2] : a[lo]) + __shfl_xor_sync(0xffffffffu, b4 ? a[lo] : a[lo + 2], 16);
            }
            const float k0 = (b3 ? k[1] : k[0]) + __shfl_xor_sync(0xffffffffu, b3 ? k[0] : k[1], 8);
            const float k1 = (b3 ? k[3] : k[2]) + __shfl_xor_sync(0xffffffffu, b3 ? k[2] : k[3], 8);
            float z = (b2 ? k1 : k0) + __shfl_xor_sync(0xffffffffu, b2 ? k0 : k1, 4);
            z += __shfl_xor_sync(0xffffffffu, z, 2);
            z += __shfl_xor_sync(0xffffffffu, z, 1);
            const float zo = __shfl_xor_sync(0xffffffffu, z, 4);
            PG(204 + bt);
            const float mu = (b2 ? zo : z) * (0.25f / D_);
            float sd_ = bfr(bfr(fmaxf(fmaf(b2 ? z : zo, 1.f / D_, -mu * mu), 0.f)) + 1e-5f);
            asm("sqrt.approx.f32 %0, %0;" : "+f"(sd_));
            const float ri = rcp(bfr(sd_));
            const uint32_t w1 = pack2(mu, ri), w2 = pack2(ri - bhi(w1), ri - bhi(w1));
#pragma unroll
            for (int r = 0; r < 4; r++) {
                const uint32_t s1 = __shfl_sync(0xffffffffu, w1, 8 * r), rl = __shfl_sync(0xffffffffu, w2, 8 * r);
                const uint32_t m2 = __byte_perm(s1, 0, 0x1010), rh = __byte_perm(s1, 0, 0x3232);
#pragma unroll
                for (int i = 0; i < 8; i++) { const uint32_t d = bsub2(v[r][i], m2); v[r][i] = bfma2(d, rh, bmul2(d, rl)); }
                sts4((la ^ (r << 4)) + r * 128, v[r][0], v[r][1], v[r][2], v[r][3]);
                sts4((la ^ (r << 4)) + r * 128 + 32768, v[r][4], v[r][5], v[r][6], v[r][7]);
#pragma unroll
                for (int i = 0; i < 8; i++) v[r][i] = v2[r][i];
            }
        }
        fence_async();
        if (SU == 0) bar_sync(5, 384); else bar_sync(2, 256);
        if (tid == 128) mbar_arrive(sb + B_LN);
        PG(202);
        if (mode == 1) return;
        float acc[128];
#pragma unroll
        for (int pass = 0; pass < 2; pass++) {
            if (pass == 1) mbar_wait(sb + B_H2, 0);
            PT(1 + 3 * pass);
            fresh(acc);
            uint32_t slot8 = pass ? 8 : 56, par = 0, prev8 = 0;
            auto adv = [&]() { prev8 = slot8; slot8 += 8; if (slot8 == 72) { slot8 = 0; par ^= 1; } };
            auto step = [&](int kk) {
                wg_fence();
                wgmma_ss_n256_tb1(acc, mkd(adA + (kk >> 2) * 512 + (kk & 3) * 2), mkd(bd2k + h * 512 + slot8 * 128), 1);
                wg_commit();
                wg_wait<1>();
            };
#pragma unroll 1
            for (int kk = 0; kk < 24; kk++) {
                mbar_wait(sb + B_R1 + slot8, par);
                step(kk);
                if (kk > 0 && w0 && elect1()) ring_half(sb, prev8, h * 8192, &mp.wup4, 16 * kk + 128, (pass ? 0 : 8) + 4 * h);
                adv();
            }
            if (pass == 0 && w0) mbar_wait(sb + B_MQ, 0);
#pragma unroll 1
            for (int kk = 24; kk < 32; kk++) {
                mbar_wait(sb + B_R1 + slot8, par);
                if (kk == 31 && el) mbar_arrive(sb + (pass ? B_H3 : B_H1));
                step(kk);
                if (w0 && elect1()) ring_half(sb, prev8, h * 8192, pass ? &mp.mqb1 : &mp.mqa2, (pass ? 64 : 32) * (kk - 24), pass ? h : 4 + 2 * h);
                adv();
            }
            wg_wait<0>();
            if (w0 && elect1()) ring_half(sb, prev8, h * 8192, pass ? &mp.mqb1 : &mp.mqa2, pass ? 0 : 256, pass ? 2 + h : 4 + 2 * h);
            pin(acc);
            PT(2 + 3 * pass);
            bf16* ucp = g_uc + ((size_t)blockIdx.x * 128 + r0) * D_ + 256 * h + 8 * (lane & 3);
            if (pass == 0) {
                float s0 = 0.f, s1 = 0.f, v0 = 0.f, v1 = 0.f;
#pragma unroll
                for (int n = 0; n < 32; n++) {
#pragma unroll
                    for (int e = 0; e < 4; e++) acc[4 * n + e] = gelu2(acc[4 * n + e]);
                    s0 += acc[4 * n] + acc[4 * n + 1]; s1 += acc[4 * n + 2] + acc[4 * n + 3];
                    v0 = fmaf(acc[4 * n], acc[4 * n], v0); v0 = fmaf(acc[4 * n + 1], acc[4 * n + 1], v0);
                    v1 = fmaf(acc[4 * n + 2], acc[4 * n + 2], v1); v1 = fmaf(acc[4 * n + 3], acc[4 * n + 3], v1);
                }
#pragma unroll
                for (int o = 1; o < 4; o <<= 1) {
                    s0 += __shfl_xor_sync(0xffffffffu, s0, o); s1 += __shfl_xor_sync(0xffffffffu, s1, o);
                    v0 += __shfl_xor_sync(0xffffffffu, v0, o); v1 += __shfl_xor_sync(0xffffffffu, v1, o);
                }
                if ((lane & 3) == 0) {
                    uint32_t a = sb + STAT + h * 512 + r0 * 8;
                    sts_f32(a, s0); sts_f32(a + 4, v0); sts_f32(a + 64, s1); sts_f32(a + 68, v1);
                }
                bar_sync(2, 256);
                {
                    uint32_t a = sb + STAT + (h ^ 1) * 512 + r0 * 8;
                    s0 = (s0 + lds_f32(a)) * (1.f / 512.f); v0 = (v0 + lds_f32(a + 4)) * (1.f / 512.f);
                    s1 = (s1 + lds_f32(a + 64)) * (1.f / 512.f); v1 = (v1 + lds_f32(a + 68)) * (1.f / 512.f);
                }
                v0 = rsqrtf(fmaxf(fmaf(-s0, s0, v0), 0.f) + 4e-5f); v1 = rsqrtf(fmaxf(fmaf(-s1, s1, v1), 0.f) + 4e-5f);
                s0 = -s0 * v0; s1 = -s1 * v1;
#pragma unroll
                for (int m = 0; m < 8; m++) {
                    const float* a_ = acc + 16 * m;
                    stg4(ucp + 64 * D_ + 32 * m, pack2(fmaf(a_[0], v0, s0), fmaf(a_[1], v0, s0)), pack2(fmaf(a_[4], v0, s0), fmaf(a_[5], v0, s0)),
                         pack2(fmaf(a_[8], v0, s0), fmaf(a_[9], v0, s0)), pack2(fmaf(a_[12], v0, s0), fmaf(a_[13], v0, s0)));
                    stg4(ucp + 72 * D_ + 32 * m, pack2(fmaf(a_[2], v1, s1), fmaf(a_[3], v1, s1)), pack2(fmaf(a_[6], v1, s1), fmaf(a_[7], v1, s1)),
                         pack2(fmaf(a_[10], v1, s1), fmaf(a_[11], v1, s1)), pack2(fmaf(a_[14], v1, s1), fmaf(a_[15], v1, s1)));
                }
            } else {
#pragma unroll
                for (int m = 0; m < 8; m++) {
                    const float* a_ = acc + 16 * m;
                    stg4(ucp + 32 * m, pack2(a_[0], a_[1]), pack2(a_[4], a_[5]), pack2(a_[8], a_[9]), pack2(a_[12], a_[13]));
                    stg4(ucp + 8 * D_ + 32 * m, pack2(a_[2], a_[3]), pack2(a_[6], a_[7]), pack2(a_[10], a_[11]), pack2(a_[14], a_[15]));
                }
                bar_sync(3 + h, 128);
            }
            PT(3 + 3 * pass);
        }
        int s = 1, ph = 0;
        uint32_t* cp = reinterpret_cast<uint32_t*>(g_uc + (size_t)blockIdx.x * 128 * D_) + (tid - 128);
        const uint32_t* dp = reinterpret_cast<const uint32_t*>(dw) + (((tid - 128) & ~15) | ((lane & 3) << 2) | ((lane >> 2) & 3));
        const uint32_t d0 = ldg_v(dp), d1 = ldg_v(dp + D_ / 2), d2 = ldg_v(dp + D_);
        uint32_t ga = ldg_cg(cp + 64 * (D_ / 2)), gb = ldg_cg(cp + 65 * (D_ / 2));
        fresh(acc);
#pragma unroll 1
        for (int j = 0; j < NKV; j++) {
            cp += D_ / 2;
            uint32_t gc = 0, uu = 0;
            if (j < NKV - 1) { gc = ldg_cg(cp + 65 * (D_ / 2)); uu = ldg_cg(cp); }
            mbar_wait(sb + B_P + s * 8, ph);
            PL(j, 0);
            if (j > 0) {
                const float sc0 = lds_f32(sb + SCL + s * 256 + r0 * 4), sc1 = lds_f32(sb + SCL + s * 256 + r0 * 4 + 32);
                if (__any_sync(0xffffffffu, sc0 != 1.f || sc1 != 1.f)) {
#pragma unroll
                    for (int n = 0; n < 32; n++) { acc[4 * n] *= sc0; acc[4 * n + 1] *= sc0; acc[4 * n + 2] *= sc1; acc[4 * n + 3] *= sc1; }
                }
            }
            mbar_wait(sb + B_GO + s * 8, ph);
            PL(j, 1);
            const uint32_t vd = sd + s * 4096 + h * 2048, pd = sd + (s == 0 ? 2 : s - 1) * 512;
            pin(acc);
            wg_fence();
#pragma unroll
            for (int kk = 0; kk < 4; kk++) wgmma_ss_n256_tb1(acc, dsc(pd, R3 + kk * 32, 16), dsc(vd, kk * 2048, 8192), 1);
            wg_commit();
            wg_wait<0>();
            pin(acc);
            PL(j, 2);
            if (w0 && elect1()) {
                if (j + 3 < NKV) {
                    mbar_expect_tx(sb + B_KV + s * 8, 32768);
                    tma4(sb + s * 65536 + h * 32768, &mp.xa4, 0, 64 * (j + 3), 4 * h, b, sb + B_KV + s * 8);
                } else if (j < NKV - 1) {
                    const int n0 = (j == NKV - 3 ? 0 : 8) + 4 * h;
#pragma unroll 1
                    for (int n = n0; n < n0 + 4; n++) ring_ld(sb, n * 8, n);
                }
                if (j == NKV - 5 && mode == 0) flag_wait(&g_sync[3], 4);
                if (j >= XPF && j < XPF + 4) {
                    const int t0 = 62 * ti + 32 * h + 8 * (j - XPF), nr = min(8, T_ - t0);
                    if (nr > 0) l2_prefetch(x + ((size_t)b * T_ + t0) * D_, nr * 1024);
                }
                if (KPF && h == 0 && 64 * (j + KPF) + ti < T_) l2_prefetch(g_xa + ((size_t)b * (T_ + 8) + 1 + 64 * (j + KPF) + ti) * D_, 1024);
            }
            uu = pack2(gelu2(blo(uu)), gelu2(bhi(uu)));
            if (j < NKV - 1) asm volatile("st.global.u32 [%0], %1;" ::"l"(cp), "r"(bmul2(uu, bfma2(gc, d2, bfma2(gb, d1, bmul2(ga, d0))))) : "memory");
            ga = gb; gb = gc;
            if (++s == 3) s = 0;
            if (s == 1) ph ^= 1;
        }
        {
            const float i0 = lds_f32(sb + LINV + r0 * 4), i1 = lds_f32(sb + LINV + r0 * 4 + 32);
#pragma unroll
            for (int p = 0; p < 16; p++)
                stsm4(((sb + R0 + h * 32768 + loff) ^ ((p & 3) << 5)) + (p >> 2) * 8192,
                      pack2(acc[8 * p] * i0, acc[8 * p + 1] * i0), pack2(acc[8 * p + 2] * i1, acc[8 * p + 3] * i1),
                      pack2(acc[8 * p + 4] * i0, acc[8 * p + 5] * i0), pack2(acc[8 * p + 6] * i1, acc[8 * p + 7] * i1));
        }
        fence_async();
        fence_async_g();
        bar_sync(2, 256);
        if (lane == 0 && w < 2) ring_ld(sb, 128 + 16 * w + 8 * h, 16 + 2 * w + h);
        PT(7);
        fresh(acc);
        {
            uint32_t slot8 = 8 * h, par = 0, prev8 = 0;
#pragma unroll 1
            for (int kk = 0; kk < 64; kk++) {
                if (kk == 32 || kk == 48) mbar_wait(sb + B_UC + (kk >> 1 & 8), 0);
                mbar_wait(sb + B_R2 + slot8, par);
                wg_fence();
                wgmma_ss_n256_tb1(acc, mkd(sd + (1u << 16) + (R0 >> 4) + (kk >> 2 & 7) * 512 + (kk & 3) * 2), mkd(bd2k + (R1 >> 4) + slot8 * 64), 1);
                wg_commit();
                wg_wait<1>();
                if (kk > 0 && lane == 0) mbar_arrive(sb + B_E2 + prev8);
                if ((kk == 16 || kk == 32) && w0 && elect1() && (atom_inc_s(sb + CNT + 12 + (kk >> 3 & 4)) & 1)) {
                    mbar_expect_tx(sb + B_UC + (kk >> 2 & 8), 32768);
                    tma3(sb + R0 + (kk & 32) * 1024, &mp.uc, 0, 128 * blockIdx.x, kk >> 3 & 4, sb + B_UC + (kk >> 2 & 8));
                }
                prev8 = slot8;
                slot8 += 16;
                if (slot8 >= 160) { slot8 -= 160; par ^= 1; }
            }
        }
        wg_wait<0>();
        pin(acc);
        PT(8);
        mbar_wait(sb + B_X, 0);
        PT(9);
        {
            const uint32_t sr = (lrow + 63) & 63;
            const uint32_t xoff = sr * 128 + ((((lane >> 4) ^ sr) & 7) << 4);
#pragma unroll
            for (int p = 0; p < 16; p++) {
                const uint32_t a = ((sb + R2 + h * 32768 + xoff) ^ ((p & 3) << 5)) + (p >> 2) * 8192;
                uint32_t xv[4];
                ldsm4(a, xv);
#pragma unroll
                for (int e = 0; e < 4; e++)
                    xv[e] = pack2(acc[8 * p + 2 * e] + __uint_as_float(xv[e] << 16), acc[8 * p + 2 * e + 1] + __uint_as_float(xv[e] & 0xffff0000u));
                stsm4(a, xv[0], xv[1], xv[2], xv[3]);
            }
        }
        fence_async();
        bar_sync(3 + h, 128);
        if (el) {
            for (int c = 0; c < 4; c++) tma4_store(&mp.out, sb + R2 + (4 * h + c) * 8192, 0, 62 * ti, 4 * h + c, b);
            asm volatile("cp.async.bulk.commit_group;" ::: "memory");
            PT(10);
            if (h == 0) cta_done(mode);
            asm volatile("cp.async.bulk.wait_group.read 0;" ::: "memory");
        }
        PT(11);
        PG(201);
        PDUMP();
    }
}

typedef CUresult (*PFN_enc)(CUtensorMap*, CUtensorMapDataType, cuuint32_t, void*, const cuuint64_t*, const cuuint64_t*,
                            const cuuint32_t*, const cuuint32_t*, CUtensorMapInterleave, CUtensorMapSwizzle,
                            CUtensorMapL2promotion, CUtensorMapFloatOOBfill);

static void enc(PFN_enc f, CUtensorMap* m, void* base, int rank, const cuuint64_t* dims, const cuuint64_t* strides, const cuuint32_t* box) {
    cuuint32_t es[5] = {1, 1, 1, 1, 1};
    f(m, CU_TENSOR_MAP_DATA_TYPE_BFLOAT16, rank, base, dims, strides, box, es, CU_TENSOR_MAP_INTERLEAVE_NONE,
      CU_TENSOR_MAP_SWIZZLE_128B, CU_TENSOR_MAP_L2_PROMOTION_L2_256B, CU_TENSOR_MAP_FLOAT_OOB_FILL_NONE);
}
static void enc_act(PFN_enc f, CUtensorMap* m, void* base, int rows, int chunks, int trows = T_, int pitch = T_) {
    cuuint64_t dims[4] = {64, (cuuint64_t)trows, 8, (cuuint64_t)NB_};
    cuuint64_t st[3] = {1024, 128, (cuuint64_t)pitch * 1024};
    cuuint32_t box[4] = {64, (cuuint32_t)rows, (cuuint32_t)chunks, 1};
    enc(f, m, base, 4, dims, st, box);
}
static void enc_w(PFN_enc f, CUtensorMap* m, void* base, int krows, int ncols, int bk, int bc) {
    cuuint64_t dims[3] = {64, (cuuint64_t)krows, (cuuint64_t)(ncols / 64)};
    cuuint64_t st[2] = {(cuuint64_t)ncols * 2, 128};
    cuuint32_t box[3] = {64, (cuuint32_t)bk, (cuuint32_t)bc};
    enc(f, m, base, 3, dims, st, box);
}

extern "C" void kernel_launch(void* const* d_in, const int* in_sizes, int n_in, void* d_out, int out_size) {
    const bf16* x = (const bf16*)d_in[0];
    static PFN_enc fenc = nullptr;
    static void *p_xa, *p_mqk, *p_uc, *p_t1;
    static int fused = 0;
    if (!fenc) {
        void* fn = nullptr;
        cudaDriverEntryPointQueryResult qr;
        cudaGetDriverEntryPoint("cuTensorMapEncodeTiled", &fn, cudaEnableDefault, &qr);
        fenc = (PFN_enc)fn;
        cudaGetSymbolAddress(&p_xa, g_xa);
        cudaGetSymbolAddress(&p_mqk, g_mqk);
        cudaGetSymbolAddress(&p_uc, g_uc);
        cudaGetSymbolAddress(&p_t1, g_t1);
        cudaFuncSetAttribute(main_kernel, cudaFuncAttributeMaxDynamicSharedMemorySize, SMEM_BYTES);
        int dev = 0, sms = 0, occ = 0;
        cudaGetDevice(&dev);
        cudaDeviceGetAttribute(&sms, cudaDevAttrMultiProcessorCount, dev);
        cudaOccupancyMaxActiveBlocksPerMultiprocessor(&occ, main_kernel, 384, SMEM_BYTES);
        fused = sms * occ >= NCTA + 2;
    }
    Maps mp;
    enc_act(fenc, &mp.xa, (char*)p_xa + 1024, 64, 8, T_, T_ + 8);
    enc_act(fenc, &mp.xa2, (char*)p_xa + 1024, 64, 2, T_, T_ + 8);
    enc_act(fenc, &mp.xa4, (char*)p_xa + 1024, 64, 4, T_, T_ + 8);
    enc_act(fenc, &mp.xas, p_xa, 64, 1, T_ + 1, T_ + 8);
    enc_act(fenc, &mp.x, (void*)x, 64, 1);
    enc_act(fenc, &mp.out, d_out, 62, 1);
    enc_w(fenc, &mp.wup4, d_in[5], 512, 1024, 16, 4);
    enc_w(fenc, &mp.wup8, d_in[5], 512, 1024, 16, 8);
    enc_w(fenc, &mp.mqa2, p_mqk, 512, 512, 32, 2);
    enc_w(fenc, &mp.mqa4, p_mqk, 512, 512, 32, 4);
    enc_w(fenc, &mp.mqb1, p_mqk, 512, 512, 64, 1);
    enc_w(fenc, &mp.mqb2, p_mqk, 512, 512, 64, 2);
    enc_w(fenc, &mp.uc, p_uc, NCTA * 128, 512, 64, 4);
    enc_w(fenc, &mp.wq, d_in[1], 512, 512, 64, 8);
    enc_w(fenc, &mp.wk, d_in[2], 512, 512, 32, 8);
    enc_w(fenc, &mp.fa[0], d_in[3], 512, 512, 128, 1);
    enc_w(fenc, &mp.fa[1], d_in[7], 512, 512, 128, 1);
    enc_w(fenc, &mp.fa[2], p_t1, 512, 512, 128, 1);
    enc_w(fenc, &mp.fb[0], d_in[4], 512, 512, 64, 4);
    enc_w(fenc, &mp.fb[1], d_in[8], 1024, 512, 64, 4);
    enc_w(fenc, &mp.fc, p_t1, 512, 512, 64, 4);
    cudaStream_t st = cudaStreamPerThread;
    if (fused) {
        main_kernel<<<NCTA + 2, 384, SMEM_BYTES, st>>>(mp, x, (const bf16*)d_in[6], (const bf16*)d_in[5], 0);
    } else {
        main_kernel<<<NCTA + 2, 384, SMEM_BYTES, st>>>(mp, x, (const bf16*)d_in[6], (const bf16*)d_in[5], 1);
        main_kernel<<<NCTA + 2, 384, SMEM_BYTES, st>>>(mp, x, (const bf16*)d_in[6], (const bf16*)d_in[5], 2);
    }
}
```

```cpp
#include <cuda_runtime.h>
#include <cuda_bf16.h>
#include <cuda.h>
#include <stdint.h>

typedef __nv_bfloat16 bf16;

constexpr int T_ = 4000, D_ = 512, NB_ = 2;
constexpr int TPB = 65;
constexpr int NCTA = TPB * NB_;
constexpr int NKV = 63;

__device__ __align__(1024) bf16 g_xa[NB_ * (T_ + 8) * D_];
__device__ __align__(1024) bf16 g_mqk[D_ * D_];
__device__ __align__(1024) bf16 g_t1[D_ * D_];
__device__ __align__(1024) bf16 g_wepi[2 * D_ * D_];
__device__ __align__(1024) bf16 g_uc[NCTA * 128 * D_];
__device__ unsigned g_sync[8];

#define PT(i) do { if (el) asm volatile("st.shared.u32 [%0], %1;" ::"r"(sb + MISC + 2560), "r"((unsigned)clock())); } while (0)
#define PG(i)
#define PE()
#define PLM 15
#define PL(j, q) do { if ((PLM >> ((q) + (wg ? 4 : 0))) & 1) PT(0); } while (0)
#define PDUMP()

#define FENCE_AT 1
#define GO_AT 25
#define LAZY 4294967296.f
#define SU 2
#define XS_GAP 800
#define XPF 50
#define URAW 1
#define LAGA 0
#define LAGB 0
#define DPOS 1
#define KPF 0
#define XEF 0
#define SK0 0
#define MCAST 1
#define PFW 1
constexpr uint32_t R0 = 0, R1 = 65536, R2 = 131072, R3 = 196608, QS = 221184, MISC = 229376;
constexpr uint32_t AT = 147456;
constexpr uint32_t SMEM_BYTES = 232448;
constexpr uint32_t B_R1 = MISC + 1856  , B_MK = MISC + 48, B_LN = MISC + 56, B_MQ = MISC + 64,
                   B_H1 = MISC + 88, B_H2 = MISC + 96, B_H3 = MISC + 104,
                   B_KV = MISC + 112, B_P = MISC + 136, B_GO = MISC + 160, B_UC = MISC + 184  ,
                   B_X = MISC + 200, CNT = MISC + 208  , SCL = MISC + 512  ,
                   LINV = MISC + 1280  , STAT = MISC + 512  ,
                   B_EM = MISC + 1928  , B_R2 = MISC + 1536  , B_E2 = MISC + 1696  ;

__device__ __forceinline__ uint32_t smem_u32(const void* p) { return (uint32_t)__cvta_generic_to_shared(p); }
__device__ __forceinline__ void wg_fence() { asm volatile("wgmma.fence.sync.aligned;" ::: "memory"); }
__device__ __forceinline__ void wg_commit() { asm volatile("wgmma.commit_group.sync.aligned;" ::: "memory"); }
template <int N> __device__ __forceinline__ void wg_wait() { asm volatile("wgmma.wait_group.sync.aligned %0;" ::"n"(N) : "memory"); }
__device__ __forceinline__ uint64_t dsc(uint32_t sd, uint32_t off, uint32_t lbo) {
    uint32_t lo = sd + (off >> 4) + ((lbo >> 4) << 16);
    uint64_t d;
    asm("mov.b64 %0, {%1, %2};" : "=l"(d) : "r"(lo), "r"((1024u >> 4) | (1u << 30)));
    return d;
}
__device__ __forceinline__ bool elect1() {
    uint32_t p;
    asm volatile("{\n.reg .pred p;\nelect.sync _|p, 0xffffffff;\nselp.u32 %0, 1, 0, p;\n}\n" : "=r"(p));
    return p != 0;
}
__device__ __forceinline__ void mbar_init(uint32_t bar, int cnt) { asm volatile("mbarrier.init.shared::cta.b64 [%0], %1;" ::"r"(bar), "r"(cnt) : "memory"); }
__device__ __forceinline__ void mbar_expect_tx(uint32_t bar, uint32_t bytes) { asm volatile("mbarrier.arrive.expect_tx.shared::cta.b64 _, [%0], %1;" ::"r"(bar), "r"(bytes) : "memory"); }
__device__ __forceinline__ void mbar_arrive(uint32_t bar) { asm volatile("mbarrier.arrive.shared::cta.b64 _, [%0];" ::"r"(bar) : "memory"); }
__device__ __forceinline__ void mbar_wait(uint32_t bar, uint32_t parity) {
    uint32_t ok;
#pragma unroll 1
    for (uint32_t it = 0;; ++it) {
        asm volatile("{\n.reg .pred p;\nmbarrier.try_wait.parity.shared::cta.b64 p, [%1], %2;\nselp.u32 %0, 1, 0, p;\n}\n" : "=r"(ok) : "r"(bar), "r"(parity) : "memory");
        if (ok) break;
        if (it > (1u << 20)) __trap();
    }
}
__device__ __forceinline__ bool mbar_test(uint32_t bar, uint32_t parity) {
    uint32_t ok;
    asm volatile("{\n.reg .pred p;\nmbarrier.test_wait.parity.shared::cta.b64 p, [%1], %2;\nselp.u32 %0, 1, 0, p;\n}\n" : "=r"(ok) : "r"(bar), "r"(parity) : "memory");
    return ok != 0;
}
__device__ __forceinline__ void fence_async() { asm volatile("fence.proxy.async.shared::cta;" ::: "memory"); }
__device__ __forceinline__ void fence_async_g() { asm volatile("fence.proxy.async.global;" ::: "memory"); }
__device__ __forceinline__ void bar_sync(int id, int n) { asm volatile("bar.sync %0, %1;" ::"r"(id), "r"(n) : "memory"); }
__device__ __forceinline__ void tma3(uint32_t dst, const CUtensorMap* tm, int c0, int c1, int c2, uint32_t bar) {
    asm volatile("cp.async.bulk.tensor.3d.shared::cluster.global.mbarrier::complete_tx::bytes [%0], [%1, {%3, %4, %5}], [%2];"
                 ::"r"(dst), "l"(tm), "r"(bar), "r"(c0), "r"(c1), "r"(c2) : "memory");
}
__device__ __forceinline__ void tma4(uint32_t dst, const CUtensorMap* tm, int c0, int c1, int c2, int c3, uint32_t bar) {
    asm volatile("cp.async.bulk.tensor.4d.shared::cluster.global.mbarrier::complete_tx::bytes [%0], [%1, {%3, %4, %5, %6}], [%2];"
                 ::"r"(dst), "l"(tm), "r"(bar), "r"(c0), "r"(c1), "r"(c2), "r"(c3) : "memory");
}
__device__ __forceinline__ void tma4_mc(uint32_t dst, const CUtensorMap* tm, int c0, int c1, int c2, int c3, uint32_t bar) {
    asm volatile("cp.async.bulk.tensor.4d.shared::cluster.global.mbarrier::complete_tx::bytes.multicast::cluster [%0], [%1, {%3, %4, %5, %6}], [%2], %7;"
                 ::"r"(dst), "l"(tm), "r"(bar), "r"(c0), "r"(c1), "r"(c2), "r"(c3), "h"((uint16_t)3) : "memory");
}
__device__ __forceinline__ void mbar_arrive_peer(uint32_t bar, uint32_t peer) {
    asm volatile("{\n.reg .b32 a;\nmapa.shared::cluster.u32 a, %0, %1;\nmbarrier.arrive.release.cluster.shared::cluster.b64 _, [a];\n}\n" ::"r"(bar), "r"(peer) : "memory");
}
__device__ __forceinline__ void tma4_store(const CUtensorMap* tm, uint32_t src, int c0, int c1, int c2, int c3) {
    asm volatile("cp.async.bulk.tensor.4d.global.shared::cta.bulk_group [%0, {%2, %3, %4, %5}], [%1];"
                 ::"l"(tm), "r"(src), "r"(c0), "r"(c1), "r"(c2), "r"(c3) : "memory");
}
__device__ __forceinline__ void tma3_store(const CUtensorMap* tm, uint32_t src, int c0, int c1, int c2) {
    asm volatile("cp.async.bulk.tensor.3d.global.shared::cta.bulk_group [%0, {%2, %3, %4}], [%1];"
                 ::"l"(tm), "r"(src), "r"(c0), "r"(c1), "r"(c2) : "memory");
}
__device__ __forceinline__ void stsm4(uint32_t addr, uint32_t a, uint32_t b, uint32_t c, uint32_t d) {
    asm volatile("stmatrix.sync.aligned.m8n8.x4.shared.b16 [%0], {%1, %2, %3, %4};" ::"r"(addr), "r"(a), "r"(b), "r"(c), "r"(d) : "memory");
}
__device__ __forceinline__ void ldsm4(uint32_t addr, uint32_t (&r)[4]) {
    asm volatile("ldmatrix.sync.aligned.m8n8.x4.shared.b16 {%0, %1, %2, %3}, [%4];" : "=r"(r[0]), "=r"(r[1]), "=r"(r[2]), "=r"(r[3]) : "r"(addr) : "memory");
}
__device__ __forceinline__ void ldsm2(uint32_t addr, uint32_t (&r)[2]) {
    asm volatile("ldmatrix.sync.aligned.m8n8.x2.shared.b16 {%0, %1}, [%2];" : "=r"(r[0]), "=r"(r[1]) : "r"(addr) : "memory");
}
__device__ __forceinline__ void stg4(void* p, uint32_t a, uint32_t b, uint32_t c, uint32_t d) {
    asm volatile("st.global.v4.u32 [%0], {%1, %2, %3, %4};" ::"l"(p), "r"(a), "r"(b), "r"(c), "r"(d) : "memory");
}
__device__ __forceinline__ void hmma(float (&c)[4], uint32_t a0, uint32_t a1, uint32_t a2, uint32_t a3, uint32_t b0, uint32_t b1) {
    asm("mma.sync.aligned.m16n8k16.row.col.f32.bf16.bf16.f32 {%0, %1, %2, %3}, {%4, %5, %6, %7}, {%8, %9}, {%0, %1, %2, %3};"
        : "+f"(c[0]), "+f"(c[1]), "+f"(c[2]), "+f"(c[3]) : "r"(a0), "r"(a1), "r"(a2), "r"(a3), "r"(b0), "r"(b1));
}
__device__ __forceinline__ uint32_t pack2(float lo, float hi) {
    uint32_t r;
    asm("cvt.rn.bf16x2.f32 %0, %1, %2;" : "=r"(r) : "f"(hi), "f"(lo));
    return r;
}
__device__ __forceinline__ uint32_t pack2v(float lo, float hi) {
    uint32_t r;
    asm volatile("cvt.rn.bf16x2.f32 %0, %1, %2;" : "=r"(r) : "f"(hi), "f"(lo));
    return r;
}
__device__ __forceinline__ uint32_t bmul2(uint32_t a, uint32_t b) { uint32_t r; asm("mul.rn.bf16x2 %0, %1, %2;" : "=r"(r) : "r"(a), "r"(b)); return r; }
__device__ __forceinline__ uint32_t bfma2(uint32_t a, uint32_t b, uint32_t c) { uint32_t r; asm("fma.rn.bf16x2 %0, %1, %2, %3;" : "=r"(r) : "r"(a), "r"(b), "r"(c)); return r; }
__device__ __forceinline__ float ex2(float x) { float r; asm("ex2.approx.ftz.f32 %0, %1;" : "=f"(r) : "f"(x)); return r; }
__device__ __forceinline__ float rcp(float x) { float r; asm("rcp.approx.ftz.f32 %0, %1;" : "=f"(r) : "f"(x)); return r; }
__device__ __forceinline__ float gelu2(float x) {
    float t = fmaf(x * x, 0.044715f * 0.7978845608028654f, 0.7978845608028654f), th;
    asm("tanh.approx.f32 %0, %1;" : "=f"(th) : "f"(x * t));
    return fmaf(x, th, x);
}
__device__ __forceinline__ uint32_t ldg_v(const uint32_t* p) { uint32_t v; asm volatile("ld.global.nc.u32 %0, [%1];" : "=r"(v) : "l"(p)); return v; }
__device__ __forceinline__ uint32_t ldg_cg(const uint32_t* p) { uint32_t v; asm volatile("ld.global.cg.u32 %0, [%1];" : "=r"(v) : "l"(p) : "memory"); return v; }
__device__ __forceinline__ float lds_f32(uint32_t a) { float v; asm volatile("ld.shared.f32 %0, [%1];" : "=f"(v) : "r"(a) : "memory"); return v; }
__device__ __forceinline__ void sts_f32(uint32_t a, float v) { asm volatile("st.shared.f32 [%0], %1;" ::"r"(a), "f"(v) : "memory"); }
__device__ __forceinline__ uint32_t atom_inc_s(uint32_t a) { uint32_t v; asm volatile("atom.relaxed.cta.shared.add.u32 %0, [%1], 1;" : "=r"(v) : "r"(a) : "memory"); return v; }
__device__ __forceinline__ void lds4(uint32_t a, uint32_t* r) {
    asm volatile("ld.shared.v4.u32 {%0, %1, %2, %3}, [%4];" : "=r"(r[0]), "=r"(r[1]), "=r"(r[2]), "=r"(r[3]) : "r"(a) : "memory");
}
__device__ __forceinline__ void sts4(uint32_t a, uint32_t x, uint32_t y, uint32_t z, uint32_t t) {
    asm volatile("st.shared.v4.u32 [%0], {%1, %2, %3, %4};" ::"r"(a), "r"(x), "r"(y), "r"(z), "r"(t) : "memory");
}
__device__ __forceinline__ uint32_t bsub2(uint32_t a, uint32_t b) { uint32_t r; asm("sub.rn.bf16x2 %0, %1, %2;" : "=r"(r) : "r"(a), "r"(b)); return r; }
__device__ __forceinline__ float blo(uint32_t v) { return __uint_as_float(v << 16); }
__device__ __forceinline__ float bhi(uint32_t v) { return __uint_as_float(v & 0xffff0000u); }
__device__ __forceinline__ float bfr(float x) { return __bfloat162float(__float2bfloat16_rn(x)); }
__device__ __forceinline__ void l2_prefetch(const void* p, uint32_t bytes) { asm volatile("cp.async.bulk.prefetch.L2.global [%0], %1;" ::"l"(p), "r"(bytes) : "memory"); }
__device__ __forceinline__ void flag_add(unsigned* p) { asm volatile("red.release.gpu.global.add.u32 [%0], 1;" ::"l"(p) : "memory"); }
__device__ __forceinline__ void flag_wait(const unsigned* p, unsigned target) {
#pragma unroll 1
    for (uint32_t it = 0;; ++it) {
        unsigned v;
        asm volatile("ld.acquire.gpu.global.u32 %0, [%1];" : "=r"(v) : "l"(p) : "memory");
        if (v >= target) break;
        if (it > (1u << 20)) __trap();
    }
    fence_async_g();
}
template <int N> __device__ __forceinline__ void pin(float (&a)[N]) {
#pragma unroll
    for (int i = 0; i < N; i++) asm volatile("" : "+f"(a[i])::"memory");
}

template <int N> __device__ __forceinline__ void fresh(float (&a)[N]) {
#pragma unroll
    for (int i = 0; i < N; i++) a[i] = 0.f;
    pin(a);
}

__device__ __forceinline__ void wgmma_rs_n64_tb0(float (&d)[32], uint32_t a0, uint32_t a1, uint32_t a2, uint32_t a3, uint64_t db, int scale_d) {
    asm volatile("{\n.reg .pred p;\nsetp.ne.b32 p, %37, 0;\n"
        "wgmma.mma_async.sync.aligned.m64n64k16.f32.bf16.bf16 {%0, %1, %2, %3, %4, %5, %6, %7, %8, %9, %10, %11, %12, %13, %14, %15, %16, %17, %18, %19, %20, %21, %22, %23, %24, %25, %26, %27, %28, %29, %30, %31}, {%32, %33, %34, %35}, %36, p, 1, 1, 0;\n}\n"
        : "+f"(d[0]), "+f"(d[1]), "+f"(d[2]), "+f"(d[3]), "+f"(d[4]), "+f"(d[5]), "+f"(d[6]), "+f"(d[7]), "+f"(d[8]), "+f"(d[9]), "+f"(d[10]), "+f"(d[11]), "+f"(d[12]), "+f"(d[13]), "+f"(d[14]), "+f"(d[15]), "+f"(d[16]), "+f"(d[17]), "+f"(d[18]), "+f"(d[19]), "+f"(d[20]), "+f"(d[21]), "+f"(d[22]), "+f"(d[23]), "+f"(d[24]), "+f"(d[25]), "+f"(d[26]), "+f"(d[27]), "+f"(d[28]), "+f"(d[29]), "+f"(d[30]), "+f"(d[31])
        : "r"(a0), "r"(a1), "r"(a2), "r"(a3), "l"(db), "r"(scale_d));
}

__device__ __forceinline__ void wgmma_ss_n128_tb1(float (&d)[64], uint64_t da, uint64_t db, int scale_d) {
    asm volatile("{\n.reg .pred p;\nsetp.ne.b32 p, %66, 0;\n"
        "wgmma.mma_async.sync.aligned.m64n128k16.f32.bf16.bf16 {%0, %1, %2, %3, %4, %5, %6, %7, %8, %9, %10, %11, %12, %13, %14, %15, %16, %17, %18, %19, %20, %21, %22, %23, %24, %25, %26, %27, %28, %29, %30, %31, %32, %33, %34, %35, %36, %37, %38, %39, %40, %41, %42, %43, %44, %45, %46, %47, %48, %49, %50, %51, %52, %53, %54, %55, %56, %57, %58, %59, %60, %61, %62, %63}, %64, %65, p, 1, 1, 0, 1;\n}\n"
        : "+f"(d[0]), "+f"(d[1]), "+f"(d[2]), "+f"(d[3]), "+f"(d[4]), "+f"(d[5]), "+f"(d[6]), "+f"(d[7]), "+f"(d[8]), "+f"(d[9]), "+f"(d[10]), "+f"(d[11]), "+f"(d[12]), "+f"(d[13]), "+f"(d[14]), "+f"(d[15]), "+f"(d[16]), "+f"(d[17]), "+f"(d[18]), "+f"(d[19]), "+f"(d[20]), "+f"(d[21]), "+f"(d[22]), "+f"(d[23]), "+f"(d[24]), "+f"(d[25]), "+f"(d[26]), "+f"(d[27]), "+f"(d[28]), "+f"(d[29]), "+f"(d[30]), "+f"(d[31]), "+f"(d[32]), "+f"(d[33]), "+f"(d[34]), "+f"(d[35]), "+f"(d[36]), "+f"(d[37]), "+f"(d[38]), "+f"(d[39]), "+f"(d[40]), "+f"(d[41]), "+f"(d[42]), "+f"(d[43]), "+f"(d[44]), "+f"(d[45]), "+f"(d[46]), "+f"(d[47]), "+f"(d[48]), "+f"(d[49]), "+f"(d[50]), "+f"(d[51]), "+f"(d[52]), "+f"(d[53]), "+f"(d[54]), "+f"(d[55]), "+f"(d[56]), "+f"(d[57]), "+f"(d[58]), "+f"(d[59]), "+f"(d[60]), "+f"(d[61]), "+f"(d[62]), "+f"(d[63])
        : "l"(da), "l"(db), "r"(scale_d));
}

__device__ __forceinline__ void wgmma_ss_n256_tb1(float (&d)[128], uint64_t da, uint64_t db, int scale_d) {
    asm volatile("{\n.reg .pred p;\nsetp.ne.b32 p, %130, 0;\n"
        "wgmma.mma_async.sync.aligned.m64n256k16.f32.bf16.bf16 {%0, %1, %2, %3, %4, %5, %6, %7, %8, %9, %10, %11, %12, %13, %14, %15, %16, %17, %18, %19, %20, %21, %22, %23, %24, %25, %26, %27, %28, %29, %30, %31, %32, %33, %34, %35, %36, %37, %38, %39, %40, %41, %42, %43, %44, %45, %46, %47, %48, %49, %50, %51, %52, %53, %54, %55, %56, %57, %58, %59, %60, %61, %62, %63, %64, %65, %66, %67, %68, %69, %70, %71, %72, %73, %74, %75, %76, %77, %78, %79, %80, %81, %82, %83, %84, %85, %86, %87, %88, %89, %90, %91, %92, %93, %94, %95, %96, %97, %98, %99, %100, %101, %102, %103, %104, %105, %106, %107, %108, %109, %110, %111, %112, %113, %114, %115, %116, %117, %118, %119, %120, %121, %122, %123, %124, %125, %126, %127}, %128, %129, p, 1, 1, 0, 1;\n}\n"
        : "+f"(d[0]), "+f"(d[1]), "+f"(d[2]), "+f"(d[3]), "+f"(d[4]), "+f"(d[5]), "+f"(d[6]), "+f"(d[7]), "+f"(d[8]), "+f"(d[9]), "+f"(d[10]), "+f"(d[11]), "+f"(d[12]), "+f"(d[13]), "+f"(d[14]), "+f"(d[15]), "+f"(d[16]), "+f"(d[17]), "+f"(d[18]), "+f"(d[19]), "+f"(d[20]), "+f"(d[21]), "+f"(d[22]), "+f"(d[23]), "+f"(d[24]), "+f"(d[25]), "+f"(d[26]), "+f"(d[27]), "+f"(d[28]), "+f"(d[29]), "+f"(d[30]), "+f"(d[31]), "+f"(d[32]), "+f"(d[33]), "+f"(d[34]), "+f"(d[35]), "+f"(d[36]), "+f"(d[37]), "+f"(d[38]), "+f"(d[39]), "+f"(d[40]), "+f"(d[41]), "+f"(d[42]), "+f"(d[43]), "+f"(d[44]), "+f"(d[45]), "+f"(d[46]), "+f"(d[47]), "+f"(d[48]), "+f"(d[49]), "+f"(d[50]), "+f"(d[51]), "+f"(d[52]), "+f"(d[53]), "+f"(d[54]), "+f"(d[55]), "+f"(d[56]), "+f"(d[57]), "+f"(d[58]), "+f"(d[59]), "+f"(d[60]), "+f"(d[61]), "+f"(d[62]), "+f"(d[63]), "+f"(d[64]), "+f"(d[65]), "+f"(d[66]), "+f"(d[67]), "+f"(d[68]), "+f"(d[69]), "+f"(d[70]), "+f"(d[71]), "+f"(d[72]), "+f"(d[73]), "+f"(d[74]), "+f"(d[75]), "+f"(d[76]), "+f"(d[77]), "+f"(d[78]), "+f"(d[79]), "+f"(d[80]), "+f"(d[81]), "+f"(d[82]), "+f"(d[83]), "+f"(d[84]), "+f"(d[85]), "+f"(d[86]), "+f"(d[87]), "+f"(d[88]), "+f"(d[89]), "+f"(d[90]), "+f"(d[91]), "+f"(d[92]), "+f"(d[93]), "+f"(d[94]), "+f"(d[95]), "+f"(d[96]), "+f"(d[97]), "+f"(d[98]), "+f"(d[99]), "+f"(d[100]), "+f"(d[101]), "+f"(d[102]), "+f"(d[103]), "+f"(d[104]), "+f"(d[105]), "+f"(d[106]), "+f"(d[107]), "+f"(d[108]), "+f"(d[109]), "+f"(d[110]), "+f"(d[111]), "+f"(d[112]), "+f"(d[113]), "+f"(d[114]), "+f"(d[115]), "+f"(d[116]), "+f"(d[117]), "+f"(d[118]), "+f"(d[119]), "+f"(d[120]), "+f"(d[121]), "+f"(d[122]), "+f"(d[123]), "+f"(d[124]), "+f"(d[125]), "+f"(d[126]), "+f"(d[127])
        : "l"(da), "l"(db), "r"(scale_d));
}

__device__ __forceinline__ void wgmma_ss_n32_tb0(float (&d)[16], uint64_t da, uint64_t db, int scale_d) {
    asm volatile("{\n.reg .pred p;\nsetp.ne.b32 p, %18, 0;\n"
        "wgmma.mma_async.sync.aligned.m64n32k16.f32.bf16.bf16 {%0, %1, %2, %3, %4, %5, %6, %7, %8, %9, %10, %11, %12, %13, %14, %15}, %16, %17, p, 1, 1, 0, 0;\n}\n"
        : "+f"(d[0]), "+f"(d[1]), "+f"(d[2]), "+f"(d[3]), "+f"(d[4]), "+f"(d[5]), "+f"(d[6]), "+f"(d[7]), "+f"(d[8]), "+f"(d[9]), "+f"(d[10]), "+f"(d[11]), "+f"(d[12]), "+f"(d[13]), "+f"(d[14]), "+f"(d[15])
        : "l"(da), "l"(db), "r"(scale_d));
}

__device__ __forceinline__ void wgmma_ss_n64_tb0(float (&d)[32], uint64_t da, uint64_t db, int scale_d) {
    asm volatile("{\n.reg .pred p;\nsetp.ne.b32 p, %34, 0;\n"
        "wgmma.mma_async.sync.aligned.m64n64k16.f32.bf16.bf16 {%0, %1, %2, %3, %4, %5, %6, %7, %8, %9, %10, %11, %12, %13, %14, %15, %16, %17, %18, %19, %20, %21, %22, %23, %24, %25, %26, %27, %28, %29, %30, %31}, %32, %33, p, 1, 1, 0, 0;\n}\n"
        : "+f"(d[0]), "+f"(d[1]), "+f"(d[2]), "+f"(d[3]), "+f"(d[4]), "+f"(d[5]), "+f"(d[6]), "+f"(d[7]), "+f"(d[8]), "+f"(d[9]), "+f"(d[10]), "+f"(d[11]), "+f"(d[12]), "+f"(d[13]), "+f"(d[14]), "+f"(d[15]), "+f"(d[16]), "+f"(d[17]), "+f"(d[18]), "+f"(d[19]), "+f"(d[20]), "+f"(d[21]), "+f"(d[22]), "+f"(d[23]), "+f"(d[24]), "+f"(d[25]), "+f"(d[26]), "+f"(d[27]), "+f"(d[28]), "+f"(d[29]), "+f"(d[30]), "+f"(d[31])
        : "l"(da), "l"(db), "r"(scale_d));
}

struct Maps {
    CUtensorMap xa, xa2, xa4, xas, wup4, wup8, mqa2, mqa4, mqb1, mqb2, uc, x, out, wq, wk, fa[3], fb[2], fc;
};

__device__ __forceinline__ uint64_t mkd(uint32_t lo) {
    uint64_t d;
    asm("mov.b64 %0, {%1, %2};" : "=l"(d) : "r"(lo), "r"((1024u >> 4) | (1u << 30)));
    return d;
}
__device__ __forceinline__ void bulk_ld(uint32_t dst, const void* src, uint32_t bytes, uint32_t bar) {
    asm volatile("cp.async.bulk.shared::cluster.global.mbarrier::complete_tx::bytes [%0], [%1], %2, [%3];" ::"r"(dst), "l"(src), "r"(bytes), "r"(bar) : "memory");
}
__device__ __forceinline__ void bulk_st(void* dst, uint32_t src, uint32_t bytes) {
    asm volatile("cp.async.bulk.global.shared::cta.bulk_group [%0], [%1], %2;" ::"l"(dst), "r"(src), "r"(bytes) : "memory");
}
__device__ __forceinline__ void ring_ld(uint32_t sb, uint32_t slot8, int n) {
    mbar_expect_tx(sb + B_R2 + slot8, 8192);
    bulk_ld(sb + R1 + slot8 * 1024, (const char*)g_wepi + n * 8192, 8192, sb + B_R2 + slot8);
}

__device__ __forceinline__ void ring_half(uint32_t sb, uint32_t slot8, uint32_t hoff, const CUtensorMap* tm, int c1, int c2) {
    mbar_expect_tx(sb + B_R1 + slot8, 8192);
    tma3(sb + slot8 * 2048 + hoff, tm, 0, c1, c2, sb + B_R1 + slot8);
}
__device__ __forceinline__ void ring_full(uint32_t sb, uint32_t slot8, const CUtensorMap* tm, int c1, int c2) {
    mbar_expect_tx(sb + B_R1 + slot8, 16384);
    mbar_arrive(sb + B_R1 + slot8);
    tma3(sb + slot8 * 2048, tm, 0, c1, c2, sb + B_R1 + slot8);
}
__device__ __forceinline__ void cta_done(int mode) {
    if (mode == 0 && atomicAdd(&g_sync[4], 1) == NCTA + 1) {
#pragma unroll
        for (int i = 0; i < 5; i++) g_sync[i] = 0;
    }
}

__device__ __forceinline__ void fold_cta(const Maps& mp, uint32_t sb, int mode) {
    constexpr uint32_t F_FULL = MISC, F_EMPTY = MISC + 32, F_T1 = MISC + 64, STG = 49152, FOUT = 3 * STG;
    const int tid = threadIdx.x, f = blockIdx.x - NCTA;
    if (mode == 2) return;
    if (tid == 0) {
        for (int i = 0; i < 3; i++) { mbar_init(sb + F_FULL + 8 * i, 1); mbar_init(sb + F_EMPTY + 8 * i, 2); }
        mbar_init(sb + F_T1, 2);
        asm volatile("fence.mbarrier_init.release.cluster;" ::: "memory");
        fence_async();
    }
    __syncthreads();
    const int wg = __shfl_sync(0xffffffffu, tid >> 7, 0);
    int st = 0, ph = 0;
    if (wg == 0) {
        if (tid == 0) {
#pragma unroll 1
            for (int it = 0; it < 96; it++) {
                const int p = it >> 3, kc = it & 7, job = p >> 2;
                if (it == 64) mbar_wait(sb + F_T1, 0);
                mbar_wait(sb + F_EMPTY + 8 * st, ph ^ 1);
                mbar_expect_tx(sb + F_FULL + 8 * st, STG);
                tma3(sb + st * STG, &mp.fa[job], 0, 256 * f + 128 * ((p >> 1) & 1), kc, sb + F_FULL + 8 * st);
                tma3(sb + st * STG + 16384, &mp.fb[job != 0], 0, 64 * kc + (job == 1 ? 512 : 0), 4 * (p & 1), sb + F_FULL + 8 * st);
                if (++st == 3) { st = 0; ph ^= 1; }
            }
        }
        return;
    }
    const int h = wg - 1, lane = tid & 31, w = (tid >> 5) & 3;
    const uint32_t sd = (sb & 0x3FFFF) >> 4;
    const bool el = (tid & 127) == 0;
#pragma unroll 1
    for (int p = 0; p < 12; p++) {
        float acc[128];
        fresh(acc);
#pragma unroll 1
        for (int kc = 0; kc < 8; kc++) {
            mbar_wait(sb + F_FULL + 8 * st, ph);
            wg_fence();
#pragma unroll
            for (int kk = 0; kk < 4; kk++)
                wgmma_ss_n256_tb1(acc, dsc(sd, st * STG + h * 8192 + kk * 32, 16), dsc(sd, st * STG + 16384 + kk * 2048, 8192), 1);
            wg_commit();
            wg_wait<0>();
            if (el) mbar_arrive(sb + F_EMPTY + 8 * st);
            if (++st == 3) { st = 0; ph ^= 1; }
        }
        pin(acc);
        const int job = p >> 2;
        if (el) {
            asm volatile("cp.async.bulk.wait_group 0;" ::: "memory");
            if (p == 4) { fence_async_g(); mbar_arrive(sb + F_T1); }
        }
        bar_sync(3 + h, 128);
        uint32_t r = 16 * w + (lane & 7) + ((lane >> 3) & 1) * 8;
        const float fs = job == 1 ? 0.5f : 1.f;
        if (job == 1) r = (r & ~31) | (((r >> 1) & 3) << 3) | (((r >> 3) & 3) << 1) | (r & 1);
        const uint32_t oa = sb + FOUT + h * 32768 + r * 128 + ((((lane >> 4) ^ r) & 7) << 4);
#pragma unroll
        for (int i = 0; i < 16; i++)
            stsm4((oa ^ ((i & 3) << 5)) + (i >> 2) * 8192, pack2(acc[8 * i] * fs, acc[8 * i + 1] * fs), pack2(acc[8 * i + 2] * fs, acc[8 * i + 3] * fs),
                  pack2(acc[8 * i + 4] * fs, acc[8 * i + 5] * fs), pack2(acc[8 * i + 6] * fs, acc[8 * i + 7] * fs));
        fence_async();
        bar_sync(3 + h, 128);
        if (el) {
            const int row0 = 256 * f + 128 * ((p >> 1) & 1) + 64 * h + (job == 1 ? 512 : 0);
            if (job == 0) tma3_store(&mp.fc, sb + FOUT + h * 32768, 0, row0, 4 * (p & 1));
            else {
#pragma unroll 1
                for (int i = 0; i < 16; i++)
                    bulk_st((char*)g_wepi + (row0 / 8 + 2 * (i & 3) + (p & 1)) * 8192 + (i >> 2) * 2048, sb + FOUT + h * 32768 + i * 2048, 2048);
            }
            asm volatile("cp.async.bulk.commit_group;" ::: "memory");
        }
    }
    if (el) {
        asm volatile("cp.async.bulk.wait_group 0;" ::: "memory");
        fence_async_g();
        if (mode == 0) flag_add(&g_sync[3]);
    }
    bar_sync(2, 256);
    if (tid == 128) cta_done(mode);
}

__global__ void __launch_bounds__(384, 1) main_kernel(const __grid_constant__ Maps mp, const bf16* __restrict__ x, const bf16* __restrict__ dw, const bf16* wup, const int mode, const int pair) {
    extern __shared__ __align__(1024) uint8_t smem[];
    const uint32_t sb = smem_u32(smem);
    const int tid = threadIdx.x;
    PE();
    if (blockIdx.x >= NCTA) { fold_cta(mp, sb, mode); return; }
    const int b = blockIdx.x / TPB, ti = blockIdx.x % TPB;
    const int piece = blockIdx.x & 127;
    const int wg = __shfl_sync(0xffffffffu, tid >> 7, 0);
    const int lane = tid & 31, w = (tid >> 5) & 3;
    const bool w0 = __shfl_sync(0xffffffffu, w, 0) == 0;
    const uint32_t sd = (sb & 0x3FFFF) >> 4;
    const uint32_t adA = sd + (AT >> 4) + (1u << 16);
    const uint32_t bd0 = sd;
    const uint32_t bd2k = bd0 + ((2048u >> 4) << 16);
    const bool el = (tid & 127) == 0;
    const uint32_t lrow = 16 * w + (lane & 7) + ((lane >> 3) & 1) * 8;
    const uint32_t loff = lrow * 128 + ((((lane >> 4) ^ lrow) & 7) << 4);
    const int r0 = 16 * w + (lane >> 2);

    if (wg == 0) {
        asm volatile("setmaxnreg.inc.sync.aligned.u32 184;");
        uint32_t q[112];
        PG(206);
        if (tid == 0) {
            mbar_init(sb + B_MK, 1);
            for (int i = 0; i < 9; i++) mbar_init(sb + B_R1 + 8 * i, 2);
            for (int i = 0; i < 5; i++) asm volatile("st.shared.u32 [%0], 0;" ::"r"(sb + CNT + 4 * i) : "memory");
        } else if (tid == 32) {
            mbar_init(sb + B_LN, 1); mbar_init(sb + B_MQ, 1);
            mbar_init(sb + B_H1, 2); mbar_init(sb + B_H2, 1); mbar_init(sb + B_H3, 2);
            for (int i = 0; i < 3; i++) { mbar_init(sb + B_KV + 8 * i, 2); mbar_init(sb + B_P + 8 * i, 4); mbar_init(sb + B_GO + 8 * i, 4); }
            mbar_init(sb + B_UC, 1); mbar_init(sb + B_UC + 8, 1); mbar_init(sb + B_X, 8);
        } else if (tid == 64) {
            for (int i = 0; i < 20; i++) mbar_init(sb + B_R2 + 8 * i, 1);
            for (int i = 0; i < 6; i++) mbar_init(sb + B_EM + 8 * i, 1);
        } else if (tid == 96) {
            for (int i = 0; i < 20; i++) mbar_init(sb + B_E2 + 8 * i, 4);
        }
        if (lane == 0) {
            asm volatile("fence.mbarrier_init.release.cluster;" ::: "memory");
            fence_async();
        }
        PG(207);
        __syncwarp();
        if (SU != 2) asm volatile("bar.arrive 5, 384;" ::: "memory");
        if (tid == 0) {
            mbar_expect_tx(sb + B_MK, 65536 + 32768);
            tma3(sb + 16384, &mp.wq, 0, 64 * (piece >> 4), 0, sb + B_MK);
            tma3(sb + 81920, &mp.wk, 0, 32 * (piece & 15), 0, sb + B_MK);
            for (int i = 0; i < 14; i++) mbar_arrive(sb + B_R1 + 8 * (i >> 1));
            if (mode != 1) {
                ring_full(sb, 56, &mp.wup8, 0, 8);
                ring_full(sb, 64, &mp.wup8, 16, 8);
                ring_full(sb, 0, &mp.wup8, 32, 8);
            }
        }
        PG(208);
        bar_sync(1, 128);
        if (SU == 2) asm volatile("bar.arrive 5, 384;" ::: "memory");
        PT(0);
        PG(200);
        {
            float mq[16];
            fresh(mq);
            mbar_wait(sb + B_MK, 0);
            PT(1);
            if (tid == 32) l2_prefetch((const char*)wup + piece * 8192, 8192);
            wg_fence();
#pragma unroll 1
            for (int c = 0; c < 8; c++)
#pragma unroll
                for (int kk = 0; kk < 4; kk++)
                    wgmma_ss_n32_tb0(mq, dsc(sd, 16384 + c * 8192 + kk * 32, 16), dsc(sd, 81920 + c * 4096 + kk * 32, 16), 1);
            wg_commit();
            wg_wait<0>();
            if (mode != 1 && w0 && elect1()) {
#pragma unroll 1
                for (int i = 1; i < 7; i++) ring_full(sb, 8 * i, &mp.wup8, 32 + 16 * i, 8);
            }
            pin(mq);
            uint32_t* c = reinterpret_cast<uint32_t*>(g_mqk + (64 * (piece >> 4) + r0) * D_ + 32 * (piece & 15) + 2 * (lane & 3));
#pragma unroll
            for (int n = 0; n < 4; n++) { c[4 * n] = pack2(mq[4 * n], mq[4 * n + 1]); c[4 * n + 4 * D_] = pack2(mq[4 * n + 2], mq[4 * n + 3]); }
            fence_async_g();
            bar_sync(1, 128);
            if (el) {
                if (mode == 0) flag_add(&g_sync[2]);
                if (mode == 0) flag_wait(&g_sync[2], NCTA);
                mbar_arrive(sb + B_MQ);
                PG(203);
                PT(12);
                mbar_wait(sb + B_LN, 0);
#pragma unroll 1
                for (int c = 0; c < 8; c++) {
                    tma4_store(&mp.xas, sb + AT + c * 8192, 0, 62 * ti, c, b);
                    const unsigned t0 = (unsigned)clock();
                    while (c < 7 && (unsigned)clock() - t0 < XS_GAP) __nanosleep(20);
                }
                asm volatile("cp.async.bulk.commit_group;" ::: "memory");
                if (mode == 1) asm volatile("cp.async.bulk.wait_group 0;" ::: "memory");
            }
            PT(13);
            if (mode == 1) return;
        }
        mbar_wait(sb + B_H1, 0);
        PT(2);
        uint32_t slot8 = 24, par = 0, prev8 = 0, prev2 = 0;
        auto adv = [&]() { prev2 = prev8; prev8 = slot8; slot8 += 8; if (slot8 == 72) { slot8 = 0; par ^= 1; } };
        {
            float acc[128];
            fresh(acc);
            auto step = [&](int i) {
                const uint32_t aa = adA + (i >> 1) * 512 + (i & 1) * 4, bb = bd0 + ((4096u >> 4) << 16) + slot8 * 128;
                wg_fence();
                wgmma_ss_n256_tb1(acc, mkd(aa), mkd(bb), 1);
                wgmma_ss_n256_tb1(acc, mkd(aa + 2), mkd(bb + 128), 1);
                wg_commit();
                wg_wait<1 + LAGA>();
            };
#pragma unroll 1
            for (int i = 0; i < 8 + LAGA; i++) {
                mbar_wait(sb + B_R1 + slot8, par);
                step(i);
                if (i > LAGA && w0 && elect1()) ring_full(sb, LAGA ? prev2 : prev8, &mp.mqa4, 32 * (i - LAGA) + 256, 4);
                adv();
            }
#pragma unroll 1
            for (int i = 8 + LAGA; i < 16; i++) {
                mbar_wait(sb + B_R1 + slot8, par);
                if (i == 15 && el) mbar_arrive(sb + B_H2);
                step(i);
                if (w0 && elect1()) ring_full(sb, LAGA ? prev2 : prev8, &mp.wup8, 16 * (i - LAGA) - 128, 0);
                adv();
            }
            if (LAGA) {
                wg_wait<1>();
                if (w0 && elect1()) ring_full(sb, prev2, &mp.wup8, 112, 0);
            }
            wg_wait<0>();
            if (w0 && elect1()) ring_full(sb, prev8, &mp.wup8, 128, 0);
            pin(acc);
            PT(3);
#pragma unroll
            for (int kk = 0; kk < 4; kk++)
                stsm4((sb + QS + loff) ^ (kk << 5), pack2(acc[96 + 8 * kk], acc[97 + 8 * kk]), pack2(acc[98 + 8 * kk], acc[99 + 8 * kk]),
                      pack2(acc[100 + 8 * kk], acc[101 + 8 * kk]), pack2(acc[102 + 8 * kk], acc[103 + 8 * kk]));
            fence_async();
#pragma unroll
            for (int i = 47; i >= 0; i--) q[64 + i] = pack2v(acc[2 * i], acc[2 * i + 1]);
        }
        if (el) {
            asm volatile("cp.async.bulk.wait_group 0;" ::: "memory");
            if (mode == 0) {
                fence_async_g();
                flag_add(&g_sync[b]);
                flag_wait(&g_sync[b], TPB);
            }
        }
        __syncwarp();
        mbar_wait(sb + B_H3, 0);
        PT(4);
        slot8 = 48; par = 1;
#pragma unroll
        for (int half = 0; half < 2; half++) {
            float acc[64];
            fresh(acc);
            auto step = [&](int m) {
                const uint32_t aa = adA + m * 512, bb = bd0 + ((8192u >> 4) << 16) + slot8 * 128;
                mbar_wait(sb + B_R1 + slot8, par);
                wg_fence();
#pragma unroll
                for (int kk = 0; kk < 4; kk++) wgmma_ss_n128_tb1(acc, mkd(aa + 2 * kk), mkd(bb + 128 * kk), 1);
                wg_commit();
                wg_wait<1 + LAGB>();
            };
#pragma unroll 1
            for (int m = 0; m < 8; m++) {
                step(m);
                if (m > LAGB && w0 && elect1()) {
                    if (half == 0) ring_full(sb, LAGB ? prev2 : prev8, &mp.mqb2, 64 * (m - LAGB), 2);
                    else if (m < 4 + LAGB) tma4(sb + (LAGB ? prev2 : prev8) * 2048, &mp.xa2, 0, 0, 2 * (m - LAGB), b, sb + B_KV + 8);
                }
                adv();
            }
            if (LAGB && half == 0) {
                wg_wait<1>();
                if (w0 && elect1()) ring_full(sb, prev2, &mp.mqb2, 448, 2);
            }
            wg_wait<0>();
            if (w0 && elect1()) {
                if (half == 0) {
                    mbar_expect_tx(sb + B_KV + 8, 65536);
                    for (int i = 0; i < 3; i++) mbar_arrive(sb + B_KV + 8 * i);
                    tma4(sb + prev8 * 2048, &mp.xa2, 0, 0, 0, b, sb + B_KV + 8);
                } else {
                    mbar_expect_tx(sb + B_KV + 16, 65536);
                    tma4(sb + R2, &mp.xa, 0, 64, 0, b, sb + B_KV + 16);
                    mbar_expect_tx(sb + B_KV, 65536);
                    tma4(sb + R0, &mp.xa, 0, 128, 0, b, sb + B_KV);
                }
            }
            pin(acc);
#pragma unroll
            for (int i = 31; i >= 0; i--) q[32 * half + i] = pack2v(acc[2 * i], acc[2 * i + 1]);
        }
        bar_sync(1, 128);
        PT(5);

        const float CS = 0.04419417382415922f * 1.4426950408889634f;
        float m0 = -INFINITY, m1 = -INFINITY, l0 = 0.f, l1 = 0.f;
        int s = 0, sn = 1, ph = 0;
        float S[32];
        const bool l0w = lane == 0, q0 = (lane & 3) == 0;
#pragma unroll 1
        for (int j = -1;; j++) {
            if (j >= 0) {
                PL(j, 1);
                if (j == NKV - 1) {
#pragma unroll
                    for (int i = (T_ - 64 * (NKV - 1)) / 2; i < 32; i++) asm volatile("mov.b32 %0, 0xff800000;" : "=f"(S[i]));
                }
                const bool kv = mbar_test(sb + B_KV + sn * 8, ph);
                const uint32_t pb = sb + R3 + (s == 0 ? 2 : s - 1) * 8192;
                float a0 = 0.f, a1 = 0.f, sc0 = 1.f, sc1 = 1.f;
                auto expo = [&]() {
                    const float n0 = -m0 * CS, n1 = -m1 * CS;
                    a0 = 0.f; a1 = 0.f;
#pragma unroll
                    for (int kk = 0; kk < 4; kk++) {
                        float p[8];
#pragma unroll
                        for (int e = 0; e < 8; e++) p[e] = ex2(fmaf(S[8 * kk + e], CS, (e & 2) ? n1 : n0));
                        a0 += (p[0] + p[1]) + (p[4] + p[5]);
                        a1 += (p[2] + p[3]) + (p[6] + p[7]);
                        stsm4((pb + loff) ^ (kk << 5), pack2(p[0], p[1]), pack2(p[2], p[3]), pack2(p[4], p[5]), pack2(p[6], p[7]));
                    }
                };
                if (j > 0 || !SK0) expo();
                if ((SK0 && j == 0) || __any_sync(0xffffffffu, !(a0 <= LAZY) || !(a1 <= LAZY))) {
                    float x0 = m0, x1 = m1;
#pragma unroll
                    for (int n = 0; n < 8; n++) { x0 = fmaxf(x0, fmaxf(S[4 * n], S[4 * n + 1])); x1 = fmaxf(x1, fmaxf(S[4 * n + 2], S[4 * n + 3])); }
                    x0 = fmaxf(x0, __shfl_xor_sync(0xffffffffu, x0, 1));
                    x1 = fmaxf(x1, __shfl_xor_sync(0xffffffffu, x1, 1));
                    x0 = fmaxf(x0, __shfl_xor_sync(0xffffffffu, x0, 2));
                    x1 = fmaxf(x1, __shfl_xor_sync(0xffffffffu, x1, 2));
                    sc0 = ex2((m0 - x0) * CS); sc1 = ex2((m1 - x1) * CS);
                    m0 = x0; m1 = x1;
                    expo();
                }
                if (q0) { sts_f32(sb + SCL + s * 256 + r0 * 4, sc0); sts_f32(sb + SCL + s * 256 + r0 * 4 + 32, sc1); }
                __syncwarp();
                if (l0w) mbar_arrive(sb + B_P + s * 8);
                l0 = fmaf(l0, sc0, a0); l1 = fmaf(l1, sc1, a1);
                PL(j, 2);
                if (j == NKV - 1) break;
                if (!kv) mbar_wait(sb + B_KV + sn * 8, ph);
            } else {
                mbar_wait(sb + B_KV + 8, 0);
            }
            float Sn[32];
            const uint32_t kd = sd + sn * 4096;
            wg_fence();
#pragma unroll
            for (int kk = 0; kk < 28; kk++) {
                wgmma_rs_n64_tb0(Sn, q[4 * kk], q[4 * kk + 1], q[4 * kk + 2], q[4 * kk + 3], dsc(kd, (kk >> 2) * 8192 + (kk & 3) * 32, 16), kk > 0);
                if (kk == FENCE_AT) { fence_async(); __syncwarp(); }
                if (kk == GO_AT) { PL(j, 3); if (j >= 0 && l0w) mbar_arrive(sb + B_GO + s * 8); }
            }
#pragma unroll
            for (int kk = 0; kk < 4; kk++)
                wgmma_ss_n64_tb0(Sn, dsc(sd, QS + kk * 32, 16), dsc(kd, 7 * 8192 + kk * 32, 16), 1);
            wg_commit();
            PL(j, 0);
            wg_wait<0>();
            pin(Sn);
#pragma unroll
            for (int i = 0; i < 32; i++) S[i] = Sn[i];
            s = sn;
            if (++sn == 3) sn = 0;
            if (sn == 1) ph ^= 1;
        }
        l0 += __shfl_xor_sync(0xffffffffu, l0, 1); l1 += __shfl_xor_sync(0xffffffffu, l1, 1);
        l0 += __shfl_xor_sync(0xffffffffu, l0, 2); l1 += __shfl_xor_sync(0xffffffffu, l1, 2);
        if (q0) { sts_f32(sb + LINV + r0 * 4, rcp(l0)); sts_f32(sb + LINV + r0 * 4 + 32, rcp(l1)); }
        fence_async();
        __syncwarp();
        if (l0w) {
            mbar_arrive(sb + B_GO + s * 8);
            uint32_t slot8 = 8 * w, par = 0;
#pragma unroll 1
            for (int n = 20 + w; n < 136; n += 4) {
                mbar_wait(sb + B_E2 + slot8, par);
                if (n < 128) ring_ld(sb, slot8, n);
                else {
                    mbar_expect_tx(sb + B_X, 8192);
                    tma4(sb + R1 + slot8 * 1024, &mp.x, 0, 62 * ti, n - 128, b, sb + B_X);
                }
                slot8 += 32;
                if (slot8 >= 160) { slot8 -= 160; par ^= 1; }
            }
        }
        PDUMP();
    } else {
        asm volatile("setmaxnreg.dec.sync.aligned.u32 160;");
        const int h = wg - 1;
        uint32_t v[4][8], v2[4][8];
        if (SU != 0) bar_sync(5, 384);
        PG(206);
#pragma unroll
        for (int i = 0; i < 8; i++) {
            const int t = 62 * ti - 1 + 32 * (i >> 2) + 16 * h + 4 * w + (i & 3);
            const uint4* p = reinterpret_cast<const uint4*>(x + ((size_t)b * T_ + t) * D_) + lane;
            uint32_t* d = i < 4 ? v[i & 3] : v2[i & 3];
#pragma unroll
            for (int c = 0; c < 2; c++)
                asm volatile("{\n.reg .pred p;\nsetp.lt.u32 p, %5, %6;\nmov.b32 %0, 0;\nmov.b32 %1, 0;\nmov.b32 %2, 0;\nmov.b32 %3, 0;\n"
                             "@p ld.global.nc.v4.u32 {%0, %1, %2, %3}, [%4];\n}\n"
                             : "=r"(d[4 * c]), "=r"(d[4 * c + 1]), "=r"(d[4 * c + 2]), "=r"(d[4 * c + 3]) : "l"(p + 32 * c), "r"(t), "n"(T_));
        }
#pragma unroll 1
        for (int bt = 0; bt < 2; bt++) {
            PT(bt ? 13 : 0);
            float a[8];
            const uint32_t la = sb + AT + (lane >> 3) * 8192 + (32 * bt + 16 * h + 4 * w) * 128 + (((lane & 7) ^ ((w & 1) * 4)) << 4);
            const bool b4 = lane & 16, b3 = lane & 8, b2 = lane & 4;
#pragma unroll
            for (int r = 0; r < 4; r++) {
                float c[4] = {0.f, 0.f, 0.f, 0.f};
#pragma unroll
                for (int i = 0; i < 8; i += 2) hmma(c, v[r][i], v[r][i], v[r][i + 1], v[r][i + 1], v[r][i], v[r][i + 1]);
                a[4 + r] = (lane & 3) == (lane >> 3) ? (b2 ? c[1] : c[0]) : 0.f;
                if (r & 1) {
                    float e[4] = {0.f, 0.f, 0.f, 0.f};
#pragma unroll
                    for (int i = 0; i < 8; i += 2) hmma(e, v[r - 1][i], v[r][i], v[r - 1][i + 1], v[r][i + 1], 0x3f803f80u, 0x3f803f80u);
                    a[r - 1] = e[0]; a[r] = e[2];
                }
            }
            float k[4];
#pragma unroll
            for (int i = 0; i < 4; i++) {
                const int lo = (i & 1) + 4 * (i >> 1);
                k[i] = (b4 ? a[lo + 2] : a[lo]) + __shfl_xor_sync(0xffffffffu, b4 ? a[lo] : a[lo + 2], 16);
            }
            const float k0 = (b3 ? k[1] : k[0]) + __shfl_xor_sync(0xffffffffu, b3 ? k[0] : k[1], 8);
            const float k1 = (b3 ? k[3] : k[2]) + __shfl_xor_sync(0xffffffffu, b3 ? k[2] : k[3], 8);
            float z = (b2 ? k1 : k0) + __shfl_xor_sync(0xffffffffu, b2 ? k0 : k1, 4);
            z += __shfl_xor_sync(0xffffffffu, z, 2);
            z += __shfl_xor_sync(0xffffffffu, z, 1);
            const float zo = __shfl_xor_sync(0xffffffffu, z, 4);
            PG(204 + bt);
            const float mu = (b2 ? zo : z) * (0.25f / D_);
            float sd_ = bfr(bfr(fmaxf(fmaf(b2 ? z : zo, 1.f / D_, -mu * mu), 0.f)) + 1e-5f);
            asm("sqrt.approx.f32 %0, %0;" : "+f"(sd_));
            const float ri = rcp(bfr(sd_));
            const uint32_t w1 = pack2(mu, ri), w2 = pack2(ri - bhi(w1), ri - bhi(w1));
#pragma unroll
            for (int r = 0; r < 4; r++) {
                const uint32_t s1 = __shfl_sync(0xffffffffu, w1, 8 * r), rl = __shfl_sync(0xffffffffu, w2, 8 * r);
                const uint32_t m2 = __byte_perm(s1, 0, 0x1010), rh = __byte_perm(s1, 0, 0x3232);
#pragma unroll
                for (int i = 0; i < 8; i++) { const uint32_t d = bsub2(v[r][i], m2); v[r][i] = bfma2(d, rh, bmul2(d, rl)); }
                sts4((la ^ (r << 4)) + r * 128, v[r][0], v[r][1], v[r][2], v[r][3]);
                sts4((la ^ (r << 4)) + r * 128 + 32768, v[r][4], v[r][5], v[r][6], v[r][7]);
#pragma unroll
                for (int i = 0; i < 8; i++) v[r][i] = v2[r][i];
            }
        }
        fence_async();
        if (SU == 0) bar_sync(5, 384); else bar_sync(2, 256);
        if (tid == 128) mbar_arrive(sb + B_LN);
        PG(202);
        if (mode == 1) return;
        float acc[128];
#pragma unroll
        for (int pass = 0; pass < 2; pass++) {
            if (pass == 1) mbar_wait(sb + B_H2, 0);
            PT(1 + 3 * pass);
            fresh(acc);
            uint32_t slot8 = pass ? 8 : 56, par = 0, prev8 = 0;
            auto adv = [&]() { prev8 = slot8; slot8 += 8; if (slot8 == 72) { slot8 = 0; par ^= 1; } };
            auto step = [&](int kk) {
                wg_fence();
                wgmma_ss_n256_tb1(acc, mkd(adA + (kk >> 2) * 512 + (kk & 3) * 2), mkd(bd2k + h * 512 + slot8 * 128), 1);
                wg_commit();
                wg_wait<1>();
            };
#pragma unroll 1
            for (int kk = 0; kk < 24; kk++) {
                mbar_wait(sb + B_R1 + slot8, par);
                step(kk);
                if (kk > 0 && w0 && elect1()) ring_half(sb, prev8, h * 8192, &mp.wup4, 16 * kk + 128, (pass ? 0 : 8) + 4 * h);
                adv();
            }
            if (pass == 0 && w0) mbar_wait(sb + B_MQ, 0);
#pragma unroll 1
            for (int kk = 24; kk < 32; kk++) {
                mbar_wait(sb + B_R1 + slot8, par);
                if (kk == 31 && el) mbar_arrive(sb + (pass ? B_H3 : B_H1));
                step(kk);
                if (w0 && elect1()) ring_half(sb, prev8, h * 8192, pass ? &mp.mqb1 : &mp.mqa2, (pass ? 64 : 32) * (kk - 24), pass ? h : 4 + 2 * h);
                adv();
            }
            wg_wait<0>();
            if (w0 && elect1()) ring_half(sb, prev8, h * 8192, pass ? &mp.mqb1 : &mp.mqa2, pass ? 0 : 256, pass ? 2 + h : 4 + 2 * h);
            pin(acc);
            PT(2 + 3 * pass);
            bf16* ucp = g_uc + ((size_t)blockIdx.x * 128 + r0) * D_ + 256 * h + 8 * (lane & 3);
            if (pass == 0) {
                float s0 = 0.f, s1 = 0.f, v0 = 0.f, v1 = 0.f;
#pragma unroll
                for (int n = 0; n < 32; n++) {
#pragma unroll
                    for (int e = 0; e < 4; e++) acc[4 * n + e] = gelu2(acc[4 * n + e]);
                    s0 += acc[4 * n] + acc[4 * n + 1]; s1 += acc[4 * n + 2] + acc[4 * n + 3];
                    v0 = fmaf(acc[4 * n], acc[4 * n], v0); v0 = fmaf(acc[4 * n + 1], acc[4 * n + 1], v0);
                    v1 = fmaf(acc[4 * n + 2], acc[4 * n + 2], v1); v1 = fmaf(acc[4 * n + 3], acc[4 * n + 3], v1);
                }
#pragma unroll
                for (int o = 1; o < 4; o <<= 1) {
                    s0 += __shfl_xor_sync(0xffffffffu, s0, o); s1 += __shfl_xor_sync(0xffffffffu, s1, o);
                    v0 += __shfl_xor_sync(0xffffffffu, v0, o); v1 += __shfl_xor_sync(0xffffffffu, v1, o);
                }
                if ((lane & 3) == 0) {
                    uint32_t a = sb + STAT + h * 512 + r0 * 8;
                    sts_f32(a, s0); sts_f32(a + 4, v0); sts_f32(a + 64, s1); sts_f32(a + 68, v1);
                }
                bar_sync(2, 256);
                {
                    uint32_t a = sb + STAT + (h ^ 1) * 512 + r0 * 8;
                    s0 = (s0 + lds_f32(a)) * (1.f / 512.f); v0 = (v0 + lds_f32(a + 4)) * (1.f / 512.f);
                    s1 = (s1 + lds_f32(a + 64)) * (1.f / 512.f); v1 = (v1 + lds_f32(a + 68)) * (1.f / 512.f);
                }
                v0 = rsqrtf(fmaxf(fmaf(-s0, s0, v0), 0.f) + 4e-5f); v1 = rsqrtf(fmaxf(fmaf(-s1, s1, v1), 0.f) + 4e-5f);
                s0 = -s0 * v0; s1 = -s1 * v1;
#pragma unroll
                for (int m = 0; m < 8; m++) {
                    const float* a_ = acc + 16 * m;
                    stg4(ucp + 64 * D_ + 32 * m, pack2(fmaf(a_[0], v0, s0), fmaf(a_[1], v0, s0)), pack2(fmaf(a_[4], v0, s0), fmaf(a_[5], v0, s0)),
                         pack2(fmaf(a_[8], v0, s0), fmaf(a_[9], v0, s0)), pack2(fmaf(a_[12], v0, s0), fmaf(a_[13], v0, s0)));
                    stg4(ucp + 72 * D_ + 32 * m, pack2(fmaf(a_[2], v1, s1), fmaf(a_[3], v1, s1)), pack2(fmaf(a_[6], v1, s1), fmaf(a_[7], v1, s1)),
                         pack2(fmaf(a_[10], v1, s1), fmaf(a_[11], v1, s1)), pack2(fmaf(a_[14], v1, s1), fmaf(a_[15], v1, s1)));
                }
            } else {
#pragma unroll
                for (int m = 0; m < 8; m++) {
                    const float* a_ = acc + 16 * m;
                    stg4(ucp + 32 * m, pack2(a_[0], a_[1]), pack2(a_[4], a_[5]), pack2(a_[8], a_[9]), pack2(a_[12], a_[13]));
                    stg4(ucp + 8 * D_ + 32 * m, pack2(a_[2], a_[3]), pack2(a_[6], a_[7]), pack2(a_[10], a_[11]), pack2(a_[14], a_[15]));
                }
                bar_sync(3 + h, 128);
            }
            PT(3 + 3 * pass);
        }
        const bool mc = pair && (blockIdx.x | 1) != TPB;
        int s = 1, ph = 0;
        uint32_t* cp = reinterpret_cast<uint32_t*>(g_uc + (size_t)blockIdx.x * 128 * D_) + (tid - 128);
        const uint32_t* dp = reinterpret_cast<const uint32_t*>(dw) + (((tid - 128) & ~15) | ((lane & 3) << 2) | ((lane >> 2) & 3));
        const uint32_t d0 = ldg_v(dp), d1 = ldg_v(dp + D_ / 2), d2 = ldg_v(dp + D_);
        uint32_t ga = ldg_cg(cp + 64 * (D_ / 2)), gb = ldg_cg(cp + 65 * (D_ / 2));
        fresh(acc);
#pragma unroll 1
        for (int j = 0; j < NKV; j++) {
            cp += D_ / 2;
            uint32_t gc = 0, uu = 0;
            if (j < NKV - 1) { gc = ldg_cg(cp + 65 * (D_ / 2)); uu = ldg_cg(cp); }
            mbar_wait(sb + B_P + s * 8, ph);
            PL(j, 0);
            if (j > 0) {
                const float sc0 = lds_f32(sb + SCL + s * 256 + r0 * 4), sc1 = lds_f32(sb + SCL + s * 256 + r0 * 4 + 32);
                if (__any_sync(0xffffffffu, sc0 != 1.f || sc1 != 1.f)) {
#pragma unroll
                    for (int n = 0; n < 32; n++) { acc[4 * n] *= sc0; acc[4 * n + 1] *= sc0; acc[4 * n + 2] *= sc1; acc[4 * n + 3] *= sc1; }
                }
            }
            mbar_wait(sb + B_GO + s * 8, ph);
            PL(j, 1);
            const uint32_t vd = sd + s * 4096 + h * 2048, pd = sd + (s == 0 ? 2 : s - 1) * 512;
            pin(acc);
            wg_fence();
#pragma unroll
            for (int kk = 0; kk < 4; kk++) wgmma_ss_n256_tb1(acc, dsc(pd, R3 + kk * 32, 16), dsc(vd, kk * 2048, 8192), 1);
            wg_commit();
            wg_wait<0>();
            pin(acc);
            PL(j, 2);
            if (w0 && elect1()) {
                if (j + 3 < NKV) {
                    mbar_expect_tx(sb + B_KV + s * 8, 32768);
                    if (mc) {
                        mbar_arrive_peer(sb + B_EM + s * 16 + h * 8, (blockIdx.x & 1) ^ 1);
                        mbar_wait(sb + B_EM + s * 16 + h * 8, ph);
                        const int c = 4 * h + 2 * (blockIdx.x & 1);
                        tma4_mc(sb + s * 65536 + c * 8192, &mp.xa2, 0, 64 * (j + 3), c, b, sb + B_KV + s * 8);
                    } else
                        tma4(sb + s * 65536 + h * 32768, &mp.xa4, 0, 64 * (j + 3), 4 * h, b, sb + B_KV + s * 8);
                } else if (j < NKV - 1) {
                    const int n0 = (j == NKV - 3 ? 0 : 8) + 4 * h;
#pragma unroll 1
                    for (int n = n0; n < n0 + 4; n++) ring_ld(sb, n * 8, n);
                }
                if (j == NKV - 5 && mode == 0) flag_wait(&g_sync[3], 4);
                if (j >= XPF && j < XPF + 4) {
                    const int t0 = 62 * ti + 32 * h + 8 * (j - XPF), nr = min(8, T_ - t0);
                    if (nr > 0) l2_prefetch(x + ((size_t)b * T_ + t0) * D_, nr * 1024);
                }
                if (KPF && h == 0 && 64 * (j + KPF) + ti < T_) l2_prefetch(g_xa + ((size_t)b * (T_ + 8) + 1 + 64 * (j + KPF) + ti) * D_, 1024);
            }
            uu = pack2(gelu2(blo(uu)), gelu2(bhi(uu)));
            if (j < NKV - 1) asm volatile("st.global.u32 [%0], %1;" ::"l"(cp), "r"(bmul2(uu, bfma2(gc, d2, bfma2(gb, d1, bmul2(ga, d0))))) : "memory");
            ga = gb; gb = gc;
            if (++s == 3) s = 0;
            if (s == 1) ph ^= 1;
        }
        {
            const float i0 = lds_f32(sb + LINV + r0 * 4), i1 = lds_f32(sb + LINV + r0 * 4 + 32);
#pragma unroll
            for (int p = 0; p < 16; p++)
                stsm4(((sb + R0 + h * 32768 + loff) ^ ((p & 3) << 5)) + (p >> 2) * 8192,
                      pack2(acc[8 * p] * i0, acc[8 * p + 1] * i0), pack2(acc[8 * p + 2] * i1, acc[8 * p + 3] * i1),
                      pack2(acc[8 * p + 4] * i0, acc[8 * p + 5] * i0), pack2(acc[8 * p + 6] * i1, acc[8 * p + 7] * i1));
        }
        fence_async();
        fence_async_g();
        bar_sync(2, 256);
        if (lane == 0 && w < 2) ring_ld(sb, 128 + 16 * w + 8 * h, 16 + 2 * w + h);
        PT(7);
        fresh(acc);
        {
            uint32_t slot8 = 8 * h, par = 0, prev8 = 0;
#pragma unroll 1
            for (int kk = 0; kk < 64; kk++) {
                if (kk == 32 || kk == 48) mbar_wait(sb + B_UC + (kk >> 1 & 8), 0);
                mbar_wait(sb + B_R2 + slot8, par);
                wg_fence();
                wgmma_ss_n256_tb1(acc, mkd(sd + (1u << 16) + (R0 >> 4) + (kk >> 2 & 7) * 512 + (kk & 3) * 2), mkd(bd2k + (R1 >> 4) + slot8 * 64), 1);
                wg_commit();
                wg_wait<1>();
                if (kk > 0 && lane == 0) mbar_arrive(sb + B_E2 + prev8);
                if ((kk == 16 || kk == 32) && w0 && elect1() && (atom_inc_s(sb + CNT + 12 + (kk >> 3 & 4)) & 1)) {
                    mbar_expect_tx(sb + B_UC + (kk >> 2 & 8), 32768);
                    tma3(sb + R0 + (kk & 32) * 1024, &mp.uc, 0, 128 * blockIdx.x, kk >> 3 & 4, sb + B_UC + (kk >> 2 & 8));
                }
                prev8 = slot8;
                slot8 += 16;
                if (slot8 >= 160) { slot8 -= 160; par ^= 1; }
            }
        }
        wg_wait<0>();
        pin(acc);
        PT(8);
        mbar_wait(sb + B_X, 0);
        PT(9);
        {
            const uint32_t sr = (lrow + 63) & 63;
            const uint32_t xoff = sr * 128 + ((((lane >> 4) ^ sr) & 7) << 4);
#pragma unroll
            for (int p = 0; p < 16; p++) {
                const uint32_t a = ((sb + R2 + h * 32768 + xoff) ^ ((p & 3) << 5)) + (p >> 2) * 8192;
                uint32_t xv[4];
                ldsm4(a, xv);
#pragma unroll
                for (int e = 0; e < 4; e++)
                    xv[e] = pack2(acc[8 * p + 2 * e] + __uint_as_float(xv[e] << 16), acc[8 * p + 2 * e + 1] + __uint_as_float(xv[e] & 0xffff0000u));
                stsm4(a, xv[0], xv[1], xv[2], xv[3]);
            }
        }
        fence_async();
        bar_sync(3 + h, 128);
        if (el) {
            for (int c = 0; c < 4; c++) tma4_store(&mp.out, sb + R2 + (4 * h + c) * 8192, 0, 62 * ti, 4 * h + c, b);
            asm volatile("cp.async.bulk.commit_group;" ::: "memory");
            PT(10);
            if (h == 0) cta_done(mode);
            asm volatile("cp.async.bulk.wait_group.read 0;" ::: "memory");
        }
        PT(11);
        PG(201);
        PDUMP();
    }
}

typedef CUresult (*PFN_enc)(CUtensorMap*, CUtensorMapDataType, cuuint32_t, void*, const cuuint64_t*, const cuuint64_t*,
                            const cuuint32_t*, const cuuint32_t*, CUtensorMapInterleave, CUtensorMapSwizzle,
                            CUtensorMapL2promotion, CUtensorMapFloatOOBfill);

static void enc(PFN_enc f, CUtensorMap* m, void* base, int rank, const cuuint64_t* dims, const cuuint64_t* strides, const cuuint32_t* box) {
    cuuint32_t es[5] = {1, 1, 1, 1, 1};
    f(m, CU_TENSOR_MAP_DATA_TYPE_BFLOAT16, rank, base, dims, strides, box, es, CU_TENSOR_MAP_INTERLEAVE_NONE,
      CU_TENSOR_MAP_SWIZZLE_128B, CU_TENSOR_MAP_L2_PROMOTION_L2_256B, CU_TENSOR_MAP_FLOAT_OOB_FILL_NONE);
}
static void enc_act(PFN_enc f, CUtensorMap* m, void* base, int rows, int chunks, int trows = T_, int pitch = T_) {
    cuuint64_t dims[4] = {64, (cuuint64_t)trows, 8, (cuuint64_t)NB_};
    cuuint64_t st[3] = {1024, 128, (cuuint64_t)pitch * 1024};
    cuuint32_t box[4] = {64, (cuuint32_t)rows, (cuuint32_t)chunks, 1};
    enc(f, m, base, 4, dims, st, box);
}
static void enc_w(PFN_enc f, CUtensorMap* m, void* base, int krows, int ncols, int bk, int bc) {
    cuuint64_t dims[3] = {64, (cuuint64_t)krows, (cuuint64_t)(ncols / 64)};
    cuuint64_t st[2] = {(cuuint64_t)ncols * 2, 128};
    cuuint32_t box[3] = {64, (cuuint32_t)bk, (cuuint32_t)bc};
    enc(f, m, base, 3, dims, st, box);
}

extern "C" void kernel_launch(void* const* d_in, const int* in_sizes, int n_in, void* d_out, int out_size) {
    const bf16* x = (const bf16*)d_in[0];
    static PFN_enc fenc = nullptr;
    static void *p_xa, *p_mqk, *p_uc, *p_t1;
    static int fused = 0, paired = 0;
    cudaLaunchAttribute at[1];
    at[0].id = cudaLaunchAttributeClusterDimension;
    at[0].val.clusterDim.x = 2; at[0].val.clusterDim.y = 1; at[0].val.clusterDim.z = 1;
    if (!fenc) {
        void* fn = nullptr;
        cudaDriverEntryPointQueryResult qr;
        cudaGetDriverEntryPoint("cuTensorMapEncodeTiled", &fn, cudaEnableDefault, &qr);
        fenc = (PFN_enc)fn;
        cudaGetSymbolAddress(&p_xa, g_xa);
        cudaGetSymbolAddress(&p_mqk, g_mqk);
        cudaGetSymbolAddress(&p_uc, g_uc);
        cudaGetSymbolAddress(&p_t1, g_t1);
        cudaFuncSetAttribute(main_kernel, cudaFuncAttributeMaxDynamicSharedMemorySize, SMEM_BYTES);
        int dev = 0, sms = 0, occ = 0;
        cudaGetDevice(&dev);
        cudaDeviceGetAttribute(&sms, cudaDevAttrMultiProcessorCount, dev);
        cudaOccupancyMaxActiveBlocksPerMultiprocessor(&occ, main_kernel, 384, SMEM_BYTES);
        fused = sms * occ >= NCTA + 2;
        int ncl = 0;
        cudaLaunchConfig_t qc = {};
        qc.gridDim = dim3(NCTA + 2); qc.blockDim = dim3(384); qc.dynamicSmemBytes = SMEM_BYTES; qc.attrs = at; qc.numAttrs = 1;
        paired = MCAST && fused && cudaOccupancyMaxActiveClusters(&ncl, main_kernel, &qc) == cudaSuccess && 2 * ncl >= NCTA + 2;
        cudaGetLastError();
    }
    Maps mp;
    enc_act(fenc, &mp.xa, (char*)p_xa + 1024, 64, 8, T_, T_ + 8);
    enc_act(fenc, &mp.xa2, (char*)p_xa + 1024, 64, 2, T_, T_ + 8);
    enc_act(fenc, &mp.xa4, (char*)p_xa + 1024, 64, 4, T_, T_ + 8);
    enc_act(fenc, &mp.xas, p_xa, 64, 1, T_ + 1, T_ + 8);
    enc_act(fenc, &mp.x, (void*)x, 64, 1);
    enc_act(fenc, &mp.out, d_out, 62, 1);
    enc_w(fenc, &mp.wup4, d_in[5], 512, 1024, 16, 4);
    enc_w(fenc, &mp.wup8, d_in[5], 512, 1024, 16, 8);
    enc_w(fenc, &mp.mqa2, p_mqk, 512, 512, 32, 2);
    enc_w(fenc, &mp.mqa4, p_mqk, 512, 512, 32, 4);
    enc_w(fenc, &mp.mqb1, p_mqk, 512, 512, 64, 1);
    enc_w(fenc, &mp.mqb2, p_mqk, 512, 512, 64, 2);
    enc_w(fenc, &mp.uc, p_uc, NCTA * 128, 512, 64, 4);
    enc_w(fenc, &mp.wq, d_in[1], 512, 512, 64, 8);
    enc_w(fenc, &mp.wk, d_in[2], 512, 512, 32, 8);
    enc_w(fenc, &mp.fa[0], d_in[3], 512, 512, 128, 1);
    enc_w(fenc, &mp.fa[1], d_in[7], 512, 512, 128, 1);
    enc_w(fenc, &mp.fa[2], p_t1, 512, 512, 128, 1);
    enc_w(fenc, &mp.fb[0], d_in[4], 512, 512, 64, 4);
    enc_w(fenc, &mp.fb[1], d_in[8], 1024, 512, 64, 4);
    enc_w(fenc, &mp.fc, p_t1, 512, 512, 64, 4);
    cudaStream_t st = cudaStreamPerThread;
    if (paired) {
        cudaLaunchConfig_t lc = {};
        lc.gridDim = dim3(NCTA + 2); lc.blockDim = dim3(384); lc.dynamicSmemBytes = SMEM_BYTES; lc.stream = st; lc.attrs = at; lc.numAttrs = 1;
        cudaLaunchKernelEx(&lc, main_kernel, mp, x, (const bf16*)d_in[6], (const bf16*)d_in[5], 0, MCAST == 1 ? 1 : 0);
    } else if (fused) {
        main_kernel<<<NCTA + 2, 384, SMEM_BYTES, st>>>(mp, x, (const bf16*)d_in[6], (const bf16*)d_in[5], 0, 0);
    } else {
        main_kernel<<<NCTA + 2, 384, SMEM_BYTES, st>>>(mp, x, (const bf16*)d_in[6], (const bf16*)d_in[5], 1, 0);
        main_kernel<<<NCTA + 2, 384, SMEM_BYTES, st>>>(mp, x, (const bf16*)d_in[6], (const bf16*)d_in[5], 2, 0);
    }
}
```

```cpp
#include <cuda_runtime.h>
#include <cuda_bf16.h>
#include <cuda.h>
#include <stdint.h>

typedef __nv_bfloat16 bf16;

constexpr int T_ = 4000, D_ = 512, NB_ = 2;
constexpr int TPB = 65;
constexpr int NCTA = TPB * NB_;
constexpr int NKV = 63;

__device__ __align__(1024) bf16 g_xa[NB_ * (T_ + 8) * D_];
__device__ __align__(1024) bf16 g_mqk[D_ * D_];
__device__ __align__(1024) bf16 g_t1[D_ * D_];
__device__ __align__(1024) bf16 g_wepi[2 * D_ * D_];
__device__ __align__(1024) bf16 g_uc[NCTA * 128 * D_];
__device__ unsigned g_sync[8];

#define PT(i) do { if (el) asm volatile("st.shared.u32 [%0], %1;" ::"r"(sb + MISC + 2560), "r"((unsigned)clock())); } while (0)
#define PG(i)
#define PE()
#define PLM 15
#define PL(j, q) do { if ((PLM >> ((q) + (wg ? 4 : 0))) & 1) PT(0); } while (0)
#define PDUMP()

#define FENCE_AT 1
#define GO_AT 25
#define LAZY 4294967296.f
#define SU 2
#define XS_GAP 800
#define XPF 50
#define URAW 1
#define LAGA 0
#define LAGB 0
#define DPOS 1
#define KPF 0
#define XEF 0
#define SK0 0
#define MCAST 1
#define PFW 1
constexpr uint32_t R0 = 0, R1 = 65536, R2 = 131072, R3 = 196608, QS = 221184, MISC = 229376;
constexpr uint32_t AT = 147456;
constexpr uint32_t SMEM_BYTES = 232448;
constexpr uint32_t B_R1 = MISC + 1856  , B_MK = MISC + 48, B_LN = MISC + 56, B_MQ = MISC + 64,
                   B_H1 = MISC + 88, B_H2 = MISC + 96, B_H3 = MISC + 104,
                   B_KV = MISC + 112, B_P = MISC + 136, B_GO = MISC + 160, B_UC = MISC + 184  ,
                   B_X = MISC + 200, CNT = MISC + 208  , SCL = MISC + 512  ,
                   LINV = MISC + 1280  , STAT = MISC + 512  ,
                   B_EM = MISC + 1928  , B_R2 = MISC + 1536  , B_E2 = MISC + 1696  ;

__device__ __forceinline__ uint32_t smem_u32(const void* p) { return (uint32_t)__cvta_generic_to_shared(p); }
__device__ __forceinline__ void wg_fence() { asm volatile("wgmma.fence.sync.aligned;" ::: "memory"); }
__device__ __forceinline__ void wg_commit() { asm volatile("wgmma.commit_group.sync.aligned;" ::: "memory"); }
template <int N> __device__ __forceinline__ void wg_wait() { asm volatile("wgmma.wait_group.sync.aligned %0;" ::"n"(N) : "memory"); }
__device__ __forceinline__ uint64_t dsc(uint32_t sd, uint32_t off, uint32_t lbo) {
    uint32_t lo = sd + (off >> 4) + ((lbo >> 4) << 16);
    uint64_t d;
    asm("mov.b64 %0, {%1, %2};" : "=l"(d) : "r"(lo), "r"((1024u >> 4) | (1u << 30)));
    return d;
}
__device__ __forceinline__ bool elect1() {
    uint32_t p;
    asm volatile("{\n.reg .pred p;\nelect.sync _|p, 0xffffffff;\nselp.u32 %0, 1, 0, p;\n}\n" : "=r"(p));
    return p != 0;
}
__device__ __forceinline__ void mbar_init(uint32_t bar, int cnt) { asm volatile("mbarrier.init.shared::cta.b64 [%0], %1;" ::"r"(bar), "r"(cnt) : "memory"); }
__device__ __forceinline__ void mbar_expect_tx(uint32_t bar, uint32_t bytes) { asm volatile("mbarrier.arrive.expect_tx.shared::cta.b64 _, [%0], %1;" ::"r"(bar), "r"(bytes) : "memory"); }
__device__ __forceinline__ void mbar_arrive(uint32_t bar) { asm volatile("mbarrier.arrive.shared::cta.b64 _, [%0];" ::"r"(bar) : "memory"); }
__device__ __forceinline__ void mbar_wait(uint32_t bar, uint32_t parity) {
    uint32_t ok;
#pragma unroll 1
    for (uint32_t it = 0;; ++it) {
        asm volatile("{\n.reg .pred p;\nmbarrier.try_wait.parity.shared::cta.b64 p, [%1], %2;\nselp.u32 %0, 1, 0, p;\n}\n" : "=r"(ok) : "r"(bar), "r"(parity) : "memory");
        if (ok) break;
        if (it > (1u << 20)) __trap();
    }
}
__device__ __forceinline__ bool mbar_test(uint32_t bar, uint32_t parity) {
    uint32_t ok;
    asm volatile("{\n.reg .pred p;\nmbarrier.test_wait.parity.shared::cta.b64 p, [%1], %2;\nselp.u32 %0, 1, 0, p;\n}\n" : "=r"(ok) : "r"(bar), "r"(parity) : "memory");
    return ok != 0;
}
__device__ __forceinline__ void fence_async() { asm volatile("fence.proxy.async.shared::cta;" ::: "memory"); }
__device__ __forceinline__ void fence_async_g() { asm volatile("fence.proxy.async.global;" ::: "memory"); }
__device__ __forceinline__ void bar_sync(int id, int n) { asm volatile("bar.sync %0, %1;" ::"r"(id), "r"(n) : "memory"); }
__device__ __forceinline__ void tma3(uint32_t dst, const CUtensorMap* tm, int c0, int c1, int c2, uint32_t bar) {
    asm volatile("cp.async.bulk.tensor.3d.shared::cluster.global.mbarrier::complete_tx::bytes [%0], [%1, {%3, %4, %5}], [%2];"
                 ::"r"(dst), "l"(tm), "r"(bar), "r"(c0), "r"(c1), "r"(c2) : "memory");
}
__device__ __forceinline__ void tma4(uint32_t dst, const CUtensorMap* tm, int c0, int c1, int c2, int c3, uint32_t bar) {
    asm volatile("cp.async.bulk.tensor.4d.shared::cluster.global.mbarrier::complete_tx::bytes [%0], [%1, {%3, %4, %5, %6}], [%2];"
                 ::"r"(dst), "l"(tm), "r"(bar), "r"(c0), "r"(c1), "r"(c2), "r"(c3) : "memory");
}
__device__ __forceinline__ void tma4_mc(uint32_t dst, const CUtensorMap* tm, int c0, int c1, int c2, int c3, uint32_t bar) {
    asm volatile("cp.async.bulk.tensor.4d.shared::cluster.global.mbarrier::complete_tx::bytes.multicast::cluster [%0], [%1, {%3, %4, %5, %6}], [%2], %7;"
                 ::"r"(dst), "l"(tm), "r"(bar), "r"(c0), "r"(c1), "r"(c2), "r"(c3), "h"((uint16_t)3) : "memory");
}
__device__ __forceinline__ void mbar_arrive_peer(uint32_t bar, uint32_t peer) {
    asm volatile("{\n.reg .b32 a;\nmapa.shared::cluster.u32 a, %0, %1;\nmbarrier.arrive.shared::cluster.b64 _, [a];\n}\n" ::"r"(bar), "r"(peer) : "memory");
}
__device__ __forceinline__ void tma4_store(const CUtensorMap* tm, uint32_t src, int c0, int c1, int c2, int c3) {
    asm volatile("cp.async.bulk.tensor.4d.global.shared::cta.bulk_group [%0, {%2, %3, %4, %5}], [%1];"
                 ::"l"(tm), "r"(src), "r"(c0), "r"(c1), "r"(c2), "r"(c3) : "memory");
}
__device__ __forceinline__ void tma3_store(const CUtensorMap* tm, uint32_t src, int c0, int c1, int c2) {
    asm volatile("cp.async.bulk.tensor.3d.global.shared::cta.bulk_group [%0, {%2, %3, %4}], [%1];"
                 ::"l"(tm), "r"(src), "r"(c0), "r"(c1), "r"(c2) : "memory");
}
__device__ __forceinline__ void stsm4(uint32_t addr, uint32_t a, uint32_t b, uint32_t c, uint32_t d) {
    asm volatile("stmatrix.sync.aligned.m8n8.x4.shared.b16 [%0], {%1, %2, %3, %4};" ::"r"(addr), "r"(a), "r"(b), "r"(c), "r"(d) : "memory");
}
__device__ __forceinline__ void ldsm4(uint32_t addr, uint32_t (&r)[4]) {
    asm volatile("ldmatrix.sync.aligned.m8n8.x4.shared.b16 {%0, %1, %2, %3}, [%4];" : "=r"(r[0]), "=r"(r[1]), "=r"(r[2]), "=r"(r[3]) : "r"(addr) : "memory");
}
__device__ __forceinline__ void ldsm2(uint32_t addr, uint32_t (&r)[2]) {
    asm volatile("ldmatrix.sync.aligned.m8n8.x2.shared.b16 {%0, %1}, [%2];" : "=r"(r[0]), "=r"(r[1]) : "r"(addr) : "memory");
}
__device__ __forceinline__ void stg4(void* p, uint32_t a, uint32_t b, uint32_t c, uint32_t d) {
    asm volatile("st.global.v4.u32 [%0], {%1, %2, %3, %4};" ::"l"(p), "r"(a), "r"(b), "r"(c), "r"(d) : "memory");
}
__device__ __forceinline__ void hmma(float (&c)[4], uint32_t a0, uint32_t a1, uint32_t a2, uint32_t a3, uint32_t b0, uint32_t b1) {
    asm("mma.sync.aligned.m16n8k16.row.col.f32.bf16.bf16.f32 {%0, %1, %2, %3}, {%4, %5, %6, %7}, {%8, %9}, {%0, %1, %2, %3};"
        : "+f"(c[0]), "+f"(c[1]), "+f"(c[2]), "+f"(c[3]) : "r"(a0), "r"(a1), "r"(a2), "r"(a3), "r"(b0), "r"(b1));
}
__device__ __forceinline__ uint32_t pack2(float lo, float hi) {
    uint32_t r;
    asm("cvt.rn.bf16x2.f32 %0, %1, %2;" : "=r"(r) : "f"(hi), "f"(lo));
    return r;
}
__device__ __forceinline__ uint32_t pack2v(float lo, float hi) {
    uint32_t r;
    asm volatile("cvt.rn.bf16x2.f32 %0, %1, %2;" : "=r"(r) : "f"(hi), "f"(lo));
    return r;
}
__device__ __forceinline__ uint32_t bmul2(uint32_t a, uint32_t b) { uint32_t r; asm("mul.rn.bf16x2 %0, %1, %2;" : "=r"(r) : "r"(a), "r"(b)); return r; }
__device__ __forceinline__ uint32_t bfma2(uint32_t a, uint32_t b, uint32_t c) { uint32_t r; asm("fma.rn.bf16x2 %0, %1, %2, %3;" : "=r"(r) : "r"(a), "r"(b), "r"(c)); return r; }
__device__ __forceinline__ float ex2(float x) { float r; asm("ex2.approx.ftz.f32 %0, %1;" : "=f"(r) : "f"(x)); return r; }
__device__ __forceinline__ float rcp(float x) { float r; asm("rcp.approx.ftz.f32 %0, %1;" : "=f"(r) : "f"(x)); return r; }
__device__ __forceinline__ float gelu2(float x) {
    float t = fmaf(x * x, 0.044715f * 0.7978845608028654f, 0.7978845608028654f), th;
    asm("tanh.approx.f32 %0, %1;" : "=f"(th) : "f"(x * t));
    return fmaf(x, th, x);
}
__device__ __forceinline__ uint32_t ldg_v(const uint32_t* p) { uint32_t v; asm volatile("ld.global.nc.u32 %0, [%1];" : "=r"(v) : "l"(p)); return v; }
__device__ __forceinline__ uint32_t ldg_cg(const uint32_t* p) { uint32_t v; asm volatile("ld.global.cg.u32 %0, [%1];" : "=r"(v) : "l"(p) : "memory"); return v; }
__device__ __forceinline__ float lds_f32(uint32_t a) { float v; asm volatile("ld.shared.f32 %0, [%1];" : "=f"(v) : "r"(a) : "memory"); return v; }
__device__ __forceinline__ void sts_f32(uint32_t a, float v) { asm volatile("st.shared.f32 [%0], %1;" ::"r"(a), "f"(v) : "memory"); }
__device__ __forceinline__ uint32_t atom_inc_s(uint32_t a) { uint32_t v; asm volatile("atom.relaxed.cta.shared.add.u32 %0, [%1], 1;" : "=r"(v) : "r"(a) : "memory"); return v; }
__device__ __forceinline__ void lds4(uint32_t a, uint32_t* r) {
    asm volatile("ld.shared.v4.u32 {%0, %1, %2, %3}, [%4];" : "=r"(r[0]), "=r"(r[1]), "=r"(r[2]), "=r"(r[3]) : "r"(a) : "memory");
}
__device__ __forceinline__ void sts4(uint32_t a, uint32_t x, uint32_t y, uint32_t z, uint32_t t) {
    asm volatile("st.shared.v4.u32 [%0], {%1, %2, %3, %4};" ::"r"(a), "r"(x), "r"(y), "r"(z), "r"(t) : "memory");
}
__device__ __forceinline__ uint32_t bsub2(uint32_t a, uint32_t b) { uint32_t r; asm("sub.rn.bf16x2 %0, %1, %2;" : "=r"(r) : "r"(a), "r"(b)); return r; }
__device__ __forceinline__ float blo(uint32_t v) { return __uint_as_float(v << 16); }
__device__ __forceinline__ float bhi(uint32_t v) { return __uint_as_float(v & 0xffff0000u); }
__device__ __forceinline__ float bfr(float x) { return __bfloat162float(__float2bfloat16_rn(x)); }
__device__ __forceinline__ void l2_prefetch(const void* p, uint32_t bytes) { asm volatile("cp.async.bulk.prefetch.L2.global [%0], %1;" ::"l"(p), "r"(bytes) : "memory"); }
__device__ __forceinline__ void flag_add(unsigned* p) { asm volatile("red.release.gpu.global.add.u32 [%0], 1;" ::"l"(p) : "memory"); }
__device__ __forceinline__ void flag_wait(const unsigned* p, unsigned target) {
#pragma unroll 1
    for (uint32_t it = 0;; ++it) {
        unsigned v;
        asm volatile("ld.acquire.gpu.global.u32 %0, [%1];" : "=r"(v) : "l"(p) : "memory");
        if (v >= target) break;
        if (it > (1u << 20)) __trap();
    }
    fence_async_g();
}
template <int N> __device__ __forceinline__ void pin(float (&a)[N]) {
#pragma unroll
    for (int i = 0; i < N; i++) asm volatile("" : "+f"(a[i])::"memory");
}

template <int N> __device__ __forceinline__ void fresh(float (&a)[N]) {
#pragma unroll
    for (int i = 0; i < N; i++) a[i] = 0.f;
    pin(a);
}

__device__ __forceinline__ void wgmma_rs_n64_tb0(float (&d)[32], uint32_t a0, uint32_t a1, uint32_t a2, uint32_t a3, uint64_t db, int scale_d) {
    asm volatile("{\n.reg .pred p;\nsetp.ne.b32 p, %37, 0;\n"
        "wgmma.mma_async.sync.aligned.m64n64k16.f32.bf16.bf16 {%0, %1, %2, %3, %4, %5, %6, %7, %8, %9, %10, %11, %12, %13, %14, %15, %16, %17, %18, %19, %20, %21, %22, %23, %24, %25, %26, %27, %28, %29, %30, %31}, {%32, %33, %34, %35}, %36, p, 1, 1, 0;\n}\n"
        : "+f"(d[0]), "+f"(d[1]), "+f"(d[2]), "+f"(d[3]), "+f"(d[4]), "+f"(d[5]), "+f"(d[6]), "+f"(d[7]), "+f"(d[8]), "+f"(d[9]), "+f"(d[10]), "+f"(d[11]), "+f"(d[12]), "+f"(d[13]), "+f"(d[14]), "+f"(d[15]), "+f"(d[16]), "+f"(d[17]), "+f"(d[18]), "+f"(d[19]), "+f"(d[20]), "+f"(d[21]), "+f"(d[22]), "+f"(d[23]), "+f"(d[24]), "+f"(d[25]), "+f"(d[26]), "+f"(d[27]), "+f"(d[28]), "+f"(d[29]), "+f"(d[30]), "+f"(d[31])
        : "r"(a0), "r"(a1), "r"(a2), "r"(a3), "l"(db), "r"(scale_d));
}

__device__ __forceinline__ void wgmma_ss_n128_tb1(float (&d)[64], uint64_t da, uint64_t db, int scale_d) {
    asm volatile("{\n.reg .pred p;\nsetp.ne.b32 p, %66, 0;\n"
        "wgmma.mma_async.sync.aligned.m64n128k16.f32.bf16.bf16 {%0, %1, %2, %3, %4, %5, %6, %7, %8, %9, %10, %11, %12, %13, %14, %15, %16, %17, %18, %19, %20, %21, %22, %23, %24, %25, %26, %27, %28, %29, %30, %31, %32, %33, %34, %35, %36, %37, %38, %39, %40, %41, %42, %43, %44, %45, %46, %47, %48, %49, %50, %51, %52, %53, %54, %55, %56, %57, %58, %59, %60, %61, %62, %63}, %64, %65, p, 1, 1, 0, 1;\n}\n"
        : "+f"(d[0]), "+f"(d[1]), "+f"(d[2]), "+f"(d[3]), "+f"(d[4]), "+f"(d[5]), "+f"(d[6]), "+f"(d[7]), "+f"(d[8]), "+f"(d[9]), "+f"(d[10]), "+f"(d[11]), "+f"(d[12]), "+f"(d[13]), "+f"(d[14]), "+f"(d[15]), "+f"(d[16]), "+f"(d[17]), "+f"(d[18]), "+f"(d[19]), "+f"(d[20]), "+f"(d[21]), "+f"(d[22]), "+f"(d[23]), "+f"(d[24]), "+f"(d[25]), "+f"(d[26]), "+f"(d[27]), "+f"(d[28]), "+f"(d[29]), "+f"(d[30]), "+f"(d[31]), "+f"(d[32]), "+f"(d[33]), "+f"(d[34]), "+f"(d[35]), "+f"(d[36]), "+f"(d[37]), "+f"(d[38]), "+f"(d[39]), "+f"(d[40]), "+f"(d[41]), "+f"(d[42]), "+f"(d[43]), "+f"(d[44]), "+f"(d[45]), "+f"(d[46]), "+f"(d[47]), "+f"(d[48]), "+f"(d[49]), "+f"(d[50]), "+f"(d[51]), "+f"(d[52]), "+f"(d[53]), "+f"(d[54]), "+f"(d[55]), "+f"(d[56]), "+f"(d[57]), "+f"(d[58]), "+f"(d[59]), "+f"(d[60]), "+f"(d[61]), "+f"(d[62]), "+f"(d[63])
        : "l"(da), "l"(db), "r"(scale_d));
}

__device__ __forceinline__ void wgmma_ss_n256_tb1(float (&d)[128], uint64_t da, uint64_t db, int scale_d) {
    asm volatile("{\n.reg .pred p;\nsetp.ne.b32 p, %130, 0;\n"
        "wgmma.mma_async.sync.aligned.m64n256k16.f32.bf16.bf16 {%0, %1, %2, %3, %4, %5, %6, %7, %8, %9, %10, %11, %12, %13, %14, %15, %16, %17, %18, %19, %20, %21, %22, %23, %24, %25, %26, %27, %28, %29, %30, %31, %32, %33, %34, %35, %36, %37, %38, %39, %40, %41, %42, %43, %44, %45, %46, %47, %48, %49, %50, %51, %52, %53, %54, %55, %56, %57, %58, %59, %60, %61, %62, %63, %64, %65, %66, %67, %68, %69, %70, %71, %72, %73, %74, %75, %76, %77, %78, %79, %80, %81, %82, %83, %84, %85, %86, %87, %88, %89, %90, %91, %92, %93, %94, %95, %96, %97, %98, %99, %100, %101, %102, %103, %104, %105, %106, %107, %108, %109, %110, %111, %112, %113, %114, %115, %116, %117, %118, %119, %120, %121, %122, %123, %124, %125, %126, %127}, %128, %129, p, 1, 1, 0, 1;\n}\n"
        : "+f"(d[0]), "+f"(d[1]), "+f"(d[2]), "+f"(d[3]), "+f"(d[4]), "+f"(d[5]), "+f"(d[6]), "+f"(d[7]), "+f"(d[8]), "+f"(d[9]), "+f"(d[10]), "+f"(d[11]), "+f"(d[12]), "+f"(d[13]), "+f"(d[14]), "+f"(d[15]), "+f"(d[16]), "+f"(d[17]), "+f"(d[18]), "+f"(d[19]), "+f"(d[20]), "+f"(d[21]), "+f"(d[22]), "+f"(d[23]), "+f"(d[24]), "+f"(d[25]), "+f"(d[26]), "+f"(d[27]), "+f"(d[28]), "+f"(d[29]), "+f"(d[30]), "+f"(d[31]), "+f"(d[32]), "+f"(d[33]), "+f"(d[34]), "+f"(d[35]), "+f"(d[36]), "+f"(d[37]), "+f"(d[38]), "+f"(d[39]), "+f"(d[40]), "+f"(d[41]), "+f"(d[42]), "+f"(d[43]), "+f"(d[44]), "+f"(d[45]), "+f"(d[46]), "+f"(d[47]), "+f"(d[48]), "+f"(d[49]), "+f"(d[50]), "+f"(d[51]), "+f"(d[52]), "+f"(d[53]), "+f"(d[54]), "+f"(d[55]), "+f"(d[56]), "+f"(d[57]), "+f"(d[58]), "+f"(d[59]), "+f"(d[60]), "+f"(d[61]), "+f"(d[62]), "+f"(d[63]), "+f"(d[64]), "+f"(d[65]), "+f"(d[66]), "+f"(d[67]), "+f"(d[68]), "+f"(d[69]), "+f"(d[70]), "+f"(d[71]), "+f"(d[72]), "+f"(d[73]), "+f"(d[74]), "+f"(d[75]), "+f"(d[76]), "+f"(d[77]), "+f"(d[78]), "+f"(d[79]), "+f"(d[80]), "+f"(d[81]), "+f"(d[82]), "+f"(d[83]), "+f"(d[84]), "+f"(d[85]), "+f"(d[86]), "+f"(d[87]), "+f"(d[88]), "+f"(d[89]), "+f"(d[90]), "+f"(d[91]), "+f"(d[92]), "+f"(d[93]), "+f"(d[94]), "+f"(d[95]), "+f"(d[96]), "+f"(d[97]), "+f"(d[98]), "+f"(d[99]), "+f"(d[100]), "+f"(d[101]), "+f"(d[102]), "+f"(d[103]), "+f"(d[104]), "+f"(d[105]), "+f"(d[106]), "+f"(d[107]), "+f"(d[108]), "+f"(d[109]), "+f"(d[110]), "+f"(d[111]), "+f"(d[112]), "+f"(d[113]), "+f"(d[114]), "+f"(d[115]), "+f"(d[116]), "+f"(d[117]), "+f"(d[118]), "+f"(d[119]), "+f"(d[120]), "+f"(d[121]), "+f"(d[122]), "+f"(d[123]), "+f"(d[124]), "+f"(d[125]), "+f"(d[126]), "+f"(d[127])
        : "l"(da), "l"(db), "r"(scale_d));
}

__device__ __forceinline__ void wgmma_ss_n32_tb0(float (&d)[16], uint64_t da, uint64_t db, int scale_d) {
    asm volatile("{\n.reg .pred p;\nsetp.ne.b32 p, %18, 0;\n"
        "wgmma.mma_async.sync.aligned.m64n32k16.f32.bf16.bf16 {%0, %1, %2, %3, %4, %5, %6, %7, %8, %9, %10, %11, %12, %13, %14, %15}, %16, %17, p, 1, 1, 0, 0;\n}\n"
        : "+f"(d[0]), "+f"(d[1]), "+f"(d[2]), "+f"(d[3]), "+f"(d[4]), "+f"(d[5]), "+f"(d[6]), "+f"(d[7]), "+f"(d[8]), "+f"(d[9]), "+f"(d[10]), "+f"(d[11]), "+f"(d[12]), "+f"(d[13]), "+f"(d[14]), "+f"(d[15])
        : "l"(da), "l"(db), "r"(scale_d));
}

__device__ __forceinline__ void wgmma_ss_n64_tb0(float (&d)[32], uint64_t da, uint64_t db, int scale_d) {
    asm volatile("{\n.reg .pred p;\nsetp.ne.b32 p, %34, 0;\n"
        "wgmma.mma_async.sync.aligned.m64n64k16.f32.bf16.bf16 {%0, %1, %2, %3, %4, %5, %6, %7, %8, %9, %10, %11, %12, %13, %14, %15, %16, %17, %18, %19, %20, %21, %22, %23, %24, %25, %26, %27, %28, %29, %30, %31}, %32, %33, p, 1, 1, 0, 0;\n}\n"
        : "+f"(d[0]), "+f"(d[1]), "+f"(d[2]), "+f"(d[3]), "+f"(d[4]), "+f"(d[5]), "+f"(d[6]), "+f"(d[7]), "+f"(d[8]), "+f"(d[9]), "+f"(d[10]), "+f"(d[11]), "+f"(d[12]), "+f"(d[13]), "+f"(d[14]), "+f"(d[15]), "+f"(d[16]), "+f"(d[17]), "+f"(d[18]), "+f"(d[19]), "+f"(d[20]), "+f"(d[21]), "+f"(d[22]), "+f"(d[23]), "+f"(d[24]), "+f"(d[25]), "+f"(d[26]), "+f"(d[27]), "+f"(d[28]), "+f"(d[29]), "+f"(d[30]), "+f"(d[31])
        : "l"(da), "l"(db), "r"(scale_d));
}

struct Maps {
    CUtensorMap xa, xa2, xa4, xas, wup4, wup8, mqa2, mqa4, mqb1, mqb2, uc, x, out, wq, wk, fa[3], fb[2], fc;
};

__device__ __forceinline__ uint64_t mkd(uint32_t lo) {
    uint64_t d;
    asm("mov.b64 %0, {%1, %2};" : "=l"(d) : "r"(lo), "r"((1024u >> 4) | (1u << 30)));
    return d;
}
__device__ __forceinline__ void bulk_ld(uint32_t dst, const void* src, uint32_t bytes, uint32_t bar) {
    asm volatile("cp.async.bulk.shared::cluster.global.mbarrier::complete_tx::bytes [%0], [%1], %2, [%3];" ::"r"(dst), "l"(src), "r"(bytes), "r"(bar) : "memory");
}
__device__ __forceinline__ void bulk_st(void* dst, uint32_t src, uint32_t bytes) {
    asm volatile("cp.async.bulk.global.shared::cta.bulk_group [%0], [%1], %2;" ::"l"(dst), "r"(src), "r"(bytes) : "memory");
}
__device__ __forceinline__ void ring_ld(uint32_t sb, uint32_t slot8, int n) {
    mbar_expect_tx(sb + B_R2 + slot8, 8192);
    bulk_ld(sb + R1 + slot8 * 1024, (const char*)g_wepi + n * 8192, 8192, sb + B_R2 + slot8);
}

__device__ __forceinline__ void ring_half(uint32_t sb, uint32_t slot8, uint32_t hoff, const CUtensorMap* tm, int c1, int c2) {
    mbar_expect_tx(sb + B_R1 + slot8, 8192);
    tma3(sb + slot8 * 2048 + hoff, tm, 0, c1, c2, sb + B_R1 + slot8);
}
__device__ __forceinline__ void ring_full(uint32_t sb, uint32_t slot8, const CUtensorMap* tm, int c1, int c2) {
    mbar_expect_tx(sb + B_R1 + slot8, 16384);
    mbar_arrive(sb + B_R1 + slot8);
    tma3(sb + slot8 * 2048, tm, 0, c1, c2, sb + B_R1 + slot8);
}
__device__ __forceinline__ void cta_done(int mode) {
    if (mode == 0 && atomicAdd(&g_sync[4], 1) == NCTA + 1) {
#pragma unroll
        for (int i = 0; i < 5; i++) g_sync[i] = 0;
    }
}

__device__ __forceinline__ void fold_cta(const Maps& mp, uint32_t sb, int mode) {
    constexpr uint32_t F_FULL = MISC, F_EMPTY = MISC + 32, F_T1 = MISC + 64, STG = 49152, FOUT = 3 * STG;
    const int tid = threadIdx.x, f = blockIdx.x - NCTA;
    if (mode == 2) return;
    if (tid == 0) {
        for (int i = 0; i < 3; i++) { mbar_init(sb + F_FULL + 8 * i, 1); mbar_init(sb + F_EMPTY + 8 * i, 2); }
        mbar_init(sb + F_T1, 2);
        asm volatile("fence.mbarrier_init.release.cluster;" ::: "memory");
        fence_async();
    }
    __syncthreads();
    const int wg = __shfl_sync(0xffffffffu, tid >> 7, 0);
    int st = 0, ph = 0;
    if (wg == 0) {
        if (tid == 0) {
#pragma unroll 1
            for (int it = 0; it < 96; it++) {
                const int p = it >> 3, kc = it & 7, job = p >> 2;
                if (it == 64) mbar_wait(sb + F_T1, 0);
                mbar_wait(sb + F_EMPTY + 8 * st, ph ^ 1);
                mbar_expect_tx(sb + F_FULL + 8 * st, STG);
                tma3(sb + st * STG, &mp.fa[job], 0, 256 * f + 128 * ((p >> 1) & 1), kc, sb + F_FULL + 8 * st);
                tma3(sb + st * STG + 16384, &mp.fb[job != 0], 0, 64 * kc + (job == 1 ? 512 : 0), 4 * (p & 1), sb + F_FULL + 8 * st);
                if (++st == 3) { st = 0; ph ^= 1; }
            }
        }
        return;
    }
    const int h = wg - 1, lane = tid & 31, w = (tid >> 5) & 3;
    const uint32_t sd = (sb & 0x3FFFF) >> 4;
    const bool el = (tid & 127) == 0;
#pragma unroll 1
    for (int p = 0; p < 12; p++) {
        float acc[128];
        fresh(acc);
#pragma unroll 1
        for (int kc = 0; kc < 8; kc++) {
            mbar_wait(sb + F_FULL + 8 * st, ph);
            wg_fence();
#pragma unroll
            for (int kk = 0; kk < 4; kk++)
                wgmma_ss_n256_tb1(acc, dsc(sd, st * STG + h * 8192 + kk * 32, 16), dsc(sd, st * STG + 16384 + kk * 2048, 8192), 1);
            wg_commit();
            wg_wait<0>();
            if (el) mbar_arrive(sb + F_EMPTY + 8 * st);
            if (++st == 3) { st = 0; ph ^= 1; }
        }
        pin(acc);
        const int job = p >> 2;
        if (el) {
            asm volatile("cp.async.bulk.wait_group 0;" ::: "memory");
            if (p == 4) { fence_async_g(); mbar_arrive(sb + F_T1); }
        }
        bar_sync(3 + h, 128);
        uint32_t r = 16 * w + (lane & 7) + ((lane >> 3) & 1) * 8;
        const float fs = job == 1 ? 0.5f : 1.f;
        if (job == 1) r = (r & ~31) | (((r >> 1) & 3) << 3) | (((r >> 3) & 3) << 1) | (r & 1);
        const uint32_t oa = sb + FOUT + h * 32768 + r * 128 + ((((lane >> 4) ^ r) & 7) << 4);
#pragma unroll
        for (int i = 0; i < 16; i++)
            stsm4((oa ^ ((i & 3) << 5)) + (i >> 2) * 8192, pack2(acc[8 * i] * fs, acc[8 * i + 1] * fs), pack2(acc[8 * i + 2] * fs, acc[8 * i + 3] * fs),
                  pack2(acc[8 * i + 4] * fs, acc[8 * i + 5] * fs), pack2(acc[8 * i + 6] * fs, acc[8 * i + 7] * fs));
        fence_async();
        bar_sync(3 + h, 128);
        if (el) {
            const int row0 = 256 * f + 128 * ((p >> 1) & 1) + 64 * h + (job == 1 ? 512 : 0);
            if (job == 0) tma3_store(&mp.fc, sb + FOUT + h * 32768, 0, row0, 4 * (p & 1));
            else {
#pragma unroll 1
                for (int i = 0; i < 16; i++)
                    bulk_st((char*)g_wepi + (row0 / 8 + 2 * (i & 3) + (p & 1)) * 8192 + (i >> 2) * 2048, sb + FOUT + h * 32768 + i * 2048, 2048);
            }
            asm volatile("cp.async.bulk.commit_group;" ::: "memory");
        }
    }
    if (el) {
        asm volatile("cp.async.bulk.wait_group 0;" ::: "memory");
        fence_async_g();
        if (mode == 0) flag_add(&g_sync[3]);
    }
    bar_sync(2, 256);
    if (tid == 128) cta_done(mode);
}

__global__ void __launch_bounds__(384, 1) main_kernel(const __grid_constant__ Maps mp, const bf16* __restrict__ x, const bf16* __restrict__ dw, const bf16* wup, const int mode, const int pair) {
    extern __shared__ __align__(1024) uint8_t smem[];
    const uint32_t sb = smem_u32(smem);
    const int tid = threadIdx.x;
    PE();
    if (blockIdx.x >= NCTA) { fold_cta(mp, sb, mode); return; }
    const int b = blockIdx.x / TPB, ti = blockIdx.x % TPB;
    const int piece = blockIdx.x & 127;
    const int wg = __shfl_sync(0xffffffffu, tid >> 7, 0);
    const int lane = tid & 31, w = (tid >> 5) & 3;
    const bool w0 = __shfl_sync(0xffffffffu, w, 0) == 0;
    const uint32_t sd = (sb & 0x3FFFF) >> 4;
    const uint32_t adA = sd + (AT >> 4) + (1u << 16);
    const uint32_t bd0 = sd;
    const uint32_t bd2k = bd0 + ((2048u >> 4) << 16);
    const bool el = (tid & 127) == 0;
    const uint32_t lrow = 16 * w + (lane & 7) + ((lane >> 3) & 1) * 8;
    const uint32_t loff = lrow * 128 + ((((lane >> 4) ^ lrow) & 7) << 4);
    const int r0 = 16 * w + (lane >> 2);

    if (wg == 0) {
        asm volatile("setmaxnreg.inc.sync.aligned.u32 184;");
        uint32_t q[112];
        PG(206);
        if (tid == 0) {
            mbar_init(sb + B_MK, 1);
            for (int i = 0; i < 9; i++) mbar_init(sb + B_R1 + 8 * i, 2);
            for (int i = 0; i < 5; i++) asm volatile("st.shared.u32 [%0], 0;" ::"r"(sb + CNT + 4 * i) : "memory");
        } else if (tid == 32) {
            mbar_init(sb + B_LN, 1); mbar_init(sb + B_MQ, 1);
            mbar_init(sb + B_H1, 2); mbar_init(sb + B_H2, 1); mbar_init(sb + B_H3, 2);
            for (int i = 0; i < 3; i++) { mbar_init(sb + B_KV + 8 * i, 2); mbar_init(sb + B_P + 8 * i, 4); mbar_init(sb + B_GO + 8 * i, 4); }
            mbar_init(sb + B_UC, 1); mbar_init(sb + B_UC + 8, 1); mbar_init(sb + B_X, 8);
        } else if (tid == 64) {
            for (int i = 0; i < 20; i++) mbar_init(sb + B_R2 + 8 * i, 1);
            for (int i = 0; i < 6; i++) mbar_init(sb + B_EM + 8 * i, 1);
        } else if (tid == 96) {
            for (int i = 0; i < 20; i++) mbar_init(sb + B_E2 + 8 * i, 4);
        }
        if (lane == 0) {
            asm volatile("fence.mbarrier_init.release.cluster;" ::: "memory");
            fence_async();
        }
        PG(207);
        __syncwarp();
        if (SU != 2) asm volatile("bar.arrive 5, 384;" ::: "memory");
        if (tid == 0) {
            mbar_expect_tx(sb + B_MK, 65536 + 32768);
            tma3(sb + 16384, &mp.wq, 0, 64 * (piece >> 4), 0, sb + B_MK);
            tma3(sb + 81920, &mp.wk, 0, 32 * (piece & 15), 0, sb + B_MK);
            for (int i = 0; i < 14; i++) mbar_arrive(sb + B_R1 + 8 * (i >> 1));
            if (mode != 1) {
                ring_full(sb, 56, &mp.wup8, 0, 8);
                ring_full(sb, 64, &mp.wup8, 16, 8);
                ring_full(sb, 0, &mp.wup8, 32, 8);
            }
        }
        PG(208);
        bar_sync(1, 128);
        if (SU == 2) asm volatile("bar.arrive 5, 384;" ::: "memory");
        PT(0);
        PG(200);
        {
            float mq[16];
            fresh(mq);
            mbar_wait(sb + B_MK, 0);
            PT(1);
            if (tid == 32) l2_prefetch((const char*)wup + piece * 8192, 8192);
            wg_fence();
#pragma unroll 1
            for (int c = 0; c < 8; c++)
#pragma unroll
                for (int kk = 0; kk < 4; kk++)
                    wgmma_ss_n32_tb0(mq, dsc(sd, 16384 + c * 8192 + kk * 32, 16), dsc(sd, 81920 + c * 4096 + kk * 32, 16), 1);
            wg_commit();
            wg_wait<0>();
            if (mode != 1 && w0 && elect1()) {
#pragma unroll 1
                for (int i = 1; i < 7; i++) ring_full(sb, 8 * i, &mp.wup8, 32 + 16 * i, 8);
            }
            pin(mq);
            uint32_t* c = reinterpret_cast<uint32_t*>(g_mqk + (64 * (piece >> 4) + r0) * D_ + 32 * (piece & 15) + 2 * (lane & 3));
#pragma unroll
            for (int n = 0; n < 4; n++) { c[4 * n] = pack2(mq[4 * n], mq[4 * n + 1]); c[4 * n + 4 * D_] = pack2(mq[4 * n + 2], mq[4 * n + 3]); }
            fence_async_g();
            bar_sync(1, 128);
            if (el) {
                if (mode == 0) flag_add(&g_sync[2]);
                if (mode == 0) flag_wait(&g_sync[2], NCTA);
                mbar_arrive(sb + B_MQ);
                PG(203);
                PT(12);
                mbar_wait(sb + B_LN, 0);
#pragma unroll 1
                for (int c = 0; c < 8; c++) {
                    tma4_store(&mp.xas, sb + AT + c * 8192, 0, 62 * ti, c, b);
                    const unsigned t0 = (unsigned)clock();
                    while (c < 7 && (unsigned)clock() - t0 < XS_GAP) __nanosleep(20);
                }
                asm volatile("cp.async.bulk.commit_group;" ::: "memory");
                if (mode == 1) asm volatile("cp.async.bulk.wait_group 0;" ::: "memory");
            }
            PT(13);
            if (mode == 1) return;
        }
        mbar_wait(sb + B_H1, 0);
        PT(2);
        uint32_t slot8 = 24, par = 0, prev8 = 0, prev2 = 0;
        auto adv = [&]() { prev2 = prev8; prev8 = slot8; slot8 += 8; if (slot8 == 72) { slot8 = 0; par ^= 1; } };
        {
            float acc[128];
            fresh(acc);
            auto step = [&](int i) {
                const uint32_t aa = adA + (i >> 1) * 512 + (i & 1) * 4, bb = bd0 + ((4096u >> 4) << 16) + slot8 * 128;
                wg_fence();
                wgmma_ss_n256_tb1(acc, mkd(aa), mkd(bb), 1);
                wgmma_ss_n256_tb1(acc, mkd(aa + 2), mkd(bb + 128), 1);
                wg_commit();
                wg_wait<1 + LAGA>();
            };
#pragma unroll 1
            for (int i = 0; i < 8 + LAGA; i++) {
                mbar_wait(sb + B_R1 + slot8, par);
                step(i);
                if (i > LAGA && w0 && elect1()) ring_full(sb, LAGA ? prev2 : prev8, &mp.mqa4, 32 * (i - LAGA) + 256, 4);
                adv();
            }
#pragma unroll 1
            for (int i = 8 + LAGA; i < 16; i++) {
                mbar_wait(sb + B_R1 + slot8, par);
                if (i == 15 && el) mbar_arrive(sb + B_H2);
                step(i);
                if (w0 && elect1()) ring_full(sb, LAGA ? prev2 : prev8, &mp.wup8, 16 * (i - LAGA) - 128, 0);
                adv();
            }
            if (LAGA) {
                wg_wait<1>();
                if (w0 && elect1()) ring_full(sb, prev2, &mp.wup8, 112, 0);
            }
            wg_wait<0>();
            if (w0 && elect1()) ring_full(sb, prev8, &mp.wup8, 128, 0);
            pin(acc);
            PT(3);
#pragma unroll
            for (int kk = 0; kk < 4; kk++)
                stsm4((sb + QS + loff) ^ (kk << 5), pack2(acc[96 + 8 * kk], acc[97 + 8 * kk]), pack2(acc[98 + 8 * kk], acc[99 + 8 * kk]),
                      pack2(acc[100 + 8 * kk], acc[101 + 8 * kk]), pack2(acc[102 + 8 * kk], acc[103 + 8 * kk]));
            fence_async();
#pragma unroll
            for (int i = 47; i >= 0; i--) q[64 + i] = pack2v(acc[2 * i], acc[2 * i + 1]);
        }
        if (el) {
            asm volatile("cp.async.bulk.wait_group 0;" ::: "memory");
            if (mode == 0) {
                fence_async_g();
                flag_add(&g_sync[b]);
                flag_wait(&g_sync[b], TPB);
            }
        }
        __syncwarp();
        mbar_wait(sb + B_H3, 0);
        PT(4);
        slot8 = 48; par = 1;
#pragma unroll
        for (int half = 0; half < 2; half++) {
            float acc[64];
            fresh(acc);
            auto step = [&](int m) {
                const uint32_t aa = adA + m * 512, bb = bd0 + ((8192u >> 4) << 16) + slot8 * 128;
                mbar_wait(sb + B_R1 + slot8, par);
                wg_fence();
#pragma unroll
                for (int kk = 0; kk < 4; kk++) wgmma_ss_n128_tb1(acc, mkd(aa + 2 * kk), mkd(bb + 128 * kk), 1);
                wg_commit();
                wg_wait<1 + LAGB>();
            };
#pragma unroll 1
            for (int m = 0; m < 8; m++) {
                step(m);
                if (m > LAGB && w0 && elect1()) {
                    if (half == 0) ring_full(sb, LAGB ? prev2 : prev8, &mp.mqb2, 64 * (m - LAGB), 2);
                    else if (m < 4 + LAGB) tma4(sb + (LAGB ? prev2 : prev8) * 2048, &mp.xa2, 0, 0, 2 * (m - LAGB), b, sb + B_KV + 8);
                }
                adv();
            }
            if (LAGB && half == 0) {
                wg_wait<1>();
                if (w0 && elect1()) ring_full(sb, prev2, &mp.mqb2, 448, 2);
            }
            wg_wait<0>();
            if (w0 && elect1()) {
                if (half == 0) {
                    mbar_expect_tx(sb + B_KV + 8, 65536);
                    for (int i = 0; i < 3; i++) mbar_arrive(sb + B_KV + 8 * i);
                    tma4(sb + prev8 * 2048, &mp.xa2, 0, 0, 0, b, sb + B_KV + 8);
                } else {
                    mbar_expect_tx(sb + B_KV + 16, 65536);
                    tma4(sb + R2, &mp.xa, 0, 64, 0, b, sb + B_KV + 16);
                    mbar_expect_tx(sb + B_KV, 65536);
                    tma4(sb + R0, &mp.xa, 0, 128, 0, b, sb + B_KV);
                }
            }
            pin(acc);
#pragma unroll
            for (int i = 31; i >= 0; i--) q[32 * half + i] = pack2v(acc[2 * i], acc[2 * i + 1]);
        }
        bar_sync(1, 128);
        PT(5);

        const float CS = 0.04419417382415922f * 1.4426950408889634f;
        float m0 = -INFINITY, m1 = -INFINITY, l0 = 0.f, l1 = 0.f;
        int s = 0, sn = 1, ph = 0;
        float S[32];
        const bool l0w = lane == 0, q0 = (lane & 3) == 0;
#pragma unroll 1
        for (int j = -1;; j++) {
            if (j >= 0) {
                PL(j, 1);
                if (j == NKV - 1) {
#pragma unroll
                    for (int i = (T_ - 64 * (NKV - 1)) / 2; i < 32; i++) asm volatile("mov.b32 %0, 0xff800000;" : "=f"(S[i]));
                }
                const bool kv = mbar_test(sb + B_KV + sn * 8, ph);
                const uint32_t pb = sb + R3 + (s == 0 ? 2 : s - 1) * 8192;
                float a0 = 0.f, a1 = 0.f, sc0 = 1.f, sc1 = 1.f;
                auto expo = [&]() {
                    const float n0 = -m0 * CS, n1 = -m1 * CS;
                    a0 = 0.f; a1 = 0.f;
#pragma unroll
                    for (int kk = 0; kk < 4; kk++) {
                        float p[8];
#pragma unroll
                        for (int e = 0; e < 8; e++) p[e] = ex2(fmaf(S[8 * kk + e], CS, (e & 2) ? n1 : n0));
                        a0 += (p[0] + p[1]) + (p[4] + p[5]);
                        a1 += (p[2] + p[3]) + (p[6] + p[7]);
                        stsm4((pb + loff) ^ (kk << 5), pack2(p[0], p[1]), pack2(p[2], p[3]), pack2(p[4], p[5]), pack2(p[6], p[7]));
                    }
                };
                if (j > 0 || !SK0) expo();
                if ((SK0 && j == 0) || __any_sync(0xffffffffu, !(a0 <= LAZY) || !(a1 <= LAZY))) {
                    float x0 = m0, x1 = m1;
#pragma unroll
                    for (int n = 0; n < 8; n++) { x0 = fmaxf(x0, fmaxf(S[4 * n], S[4 * n + 1])); x1 = fmaxf(x1, fmaxf(S[4 * n + 2], S[4 * n + 3])); }
                    x0 = fmaxf(x0, __shfl_xor_sync(0xffffffffu, x0, 1));
                    x1 = fmaxf(x1, __shfl_xor_sync(0xffffffffu, x1, 1));
                    x0 = fmaxf(x0, __shfl_xor_sync(0xffffffffu, x0, 2));
                    x1 = fmaxf(x1, __shfl_xor_sync(0xffffffffu, x1, 2));
                    sc0 = ex2((m0 - x0) * CS); sc1 = ex2((m1 - x1) * CS);
                    m0 = x0; m1 = x1;
                    expo();
                }
                if (q0) { sts_f32(sb + SCL + s * 256 + r0 * 4, sc0); sts_f32(sb + SCL + s * 256 + r0 * 4 + 32, sc1); }
                __syncwarp();
                if (l0w) mbar_arrive(sb + B_P + s * 8);
                l0 = fmaf(l0, sc0, a0); l1 = fmaf(l1, sc1, a1);
                PL(j, 2);
                if (j == NKV - 1) break;
                if (!kv) mbar_wait(sb + B_KV + sn * 8, ph);
            } else {
                mbar_wait(sb + B_KV + 8, 0);
            }
            float Sn[32];
            const uint32_t kd = sd + sn * 4096;
            wg_fence();
#pragma unroll
            for (int kk = 0; kk < 28; kk++) {
                wgmma_rs_n64_tb0(Sn, q[4 * kk], q[4 * kk + 1], q[4 * kk + 2], q[4 * kk + 3], dsc(kd, (kk >> 2) * 8192 + (kk & 3) * 32, 16), kk > 0);
                if (kk == FENCE_AT) { fence_async(); __syncwarp(); }
                if (kk == GO_AT) { PL(j, 3); if (j >= 0 && l0w) mbar_arrive(sb + B_GO + s * 8); }
            }
#pragma unroll
            for (int kk = 0; kk < 4; kk++)
                wgmma_ss_n64_tb0(Sn, dsc(sd, QS + kk * 32, 16), dsc(kd, 7 * 8192 + kk * 32, 16), 1);
            wg_commit();
            PL(j, 0);
            wg_wait<0>();
            pin(Sn);
#pragma unroll
            for (int i = 0; i < 32; i++) S[i] = Sn[i];
            s = sn;
            if (++sn == 3) sn = 0;
            if (sn == 1) ph ^= 1;
        }
        l0 += __shfl_xor_sync(0xffffffffu, l0, 1); l1 += __shfl_xor_sync(0xffffffffu, l1, 1);
        l0 += __shfl_xor_sync(0xffffffffu, l0, 2); l1 += __shfl_xor_sync(0xffffffffu, l1, 2);
        if (q0) { sts_f32(sb + LINV + r0 * 4, rcp(l0)); sts_f32(sb + LINV + r0 * 4 + 32, rcp(l1)); }
        fence_async();
        __syncwarp();
        if (l0w) {
            mbar_arrive(sb + B_GO + s * 8);
            uint32_t slot8 = 8 * w, par = 0;
#pragma unroll 1
            for (int n = 20 + w; n < 136; n += 4) {
                mbar_wait(sb + B_E2 + slot8, par);
                if (n < 128) ring_ld(sb, slot8, n);
                else {
                    mbar_expect_tx(sb + B_X, 8192);
                    tma4(sb + R1 + slot8 * 1024, &mp.x, 0, 62 * ti, n - 128, b, sb + B_X);
                }
                slot8 += 32;
                if (slot8 >= 160) { slot8 -= 160; par ^= 1; }
            }
        }
        PDUMP();
    } else {
        asm volatile("setmaxnreg.dec.sync.aligned.u32 160;");
        const int h = wg - 1;
        uint32_t v[4][8], v2[4][8];
        if (SU != 0) bar_sync(5, 384);
        PG(206);
#pragma unroll
        for (int i = 0; i < 8; i++) {
            const int t = 62 * ti - 1 + 32 * (i >> 2) + 16 * h + 4 * w + (i & 3);
            const uint4* p = reinterpret_cast<const uint4*>(x + ((size_t)b * T_ + t) * D_) + lane;
            uint32_t* d = i < 4 ? v[i & 3] : v2[i & 3];
#pragma unroll
            for (int c = 0; c < 2; c++)
                asm volatile("{\n.reg .pred p;\nsetp.lt.u32 p, %5, %6;\nmov.b32 %0, 0;\nmov.b32 %1, 0;\nmov.b32 %2, 0;\nmov.b32 %3, 0;\n"
                             "@p ld.global.nc.v4.u32 {%0, %1, %2, %3}, [%4];\n}\n"
                             : "=r"(d[4 * c]), "=r"(d[4 * c + 1]), "=r"(d[4 * c + 2]), "=r"(d[4 * c + 3]) : "l"(p + 32 * c), "r"(t), "n"(T_));
        }
#pragma unroll 1
        for (int bt = 0; bt < 2; bt++) {
            PT(bt ? 13 : 0);
            float a[8];
            const uint32_t la = sb + AT + (lane >> 3) * 8192 + (32 * bt + 16 * h + 4 * w) * 128 + (((lane & 7) ^ ((w & 1) * 4)) << 4);
            const bool b4 = lane & 16, b3 = lane & 8, b2 = lane & 4;
#pragma unroll
            for (int r = 0; r < 4; r++) {
                float c[4] = {0.f, 0.f, 0.f, 0.f};
#pragma unroll
                for (int i = 0; i < 8; i += 2) hmma(c, v[r][i], v[r][i], v[r][i + 1], v[r][i + 1], v[r][i], v[r][i + 1]);
                a[4 + r] = (lane & 3) == (lane >> 3) ? (b2 ? c[1] : c[0]) : 0.f;
                if (r & 1) {
                    float e[4] = {0.f, 0.f, 0.f, 0.f};
#pragma unroll
                    for (int i = 0; i < 8; i += 2) hmma(e, v[r - 1][i], v[r][i], v[r - 1][i + 1], v[r][i + 1], 0x3f803f80u, 0x3f803f80u);
                    a[r - 1] = e[0]; a[r] = e[2];
                }
            }
            float k[4];
#pragma unroll
            for (int i = 0; i < 4; i++) {
                const int lo = (i & 1) + 4 * (i >> 1);
                k[i] = (b4 ? a[lo + 2] : a[lo]) + __shfl_xor_sync(0xffffffffu, b4 ? a[lo] : a[lo + 2], 16);
            }
            const float k0 = (b3 ? k[1] : k[0]) + __shfl_xor_sync(0xffffffffu, b3 ? k[0] : k[1], 8);
            const float k1 = (b3 ? k[3] : k[2]) + __shfl_xor_sync(0xffffffffu, b3 ? k[2] : k[3], 8);
            float z = (b2 ? k1 : k0) + __shfl_xor_sync(0xffffffffu, b2 ? k0 : k1, 4);
            z += __shfl_xor_sync(0xffffffffu, z, 2);
            z += __shfl_xor_sync(0xffffffffu, z, 1);
            const float zo = __shfl_xor_sync(0xffffffffu, z, 4);
            PG(204 + bt);
            const float mu = (b2 ? zo : z) * (0.25f / D_);
            float sd_ = bfr(bfr(fmaxf(fmaf(b2 ? z : zo, 1.f / D_, -mu * mu), 0.f)) + 1e-5f);
            asm("sqrt.approx.f32 %0, %0;" : "+f"(sd_));
            const float ri = rcp(bfr(sd_));
            const uint32_t w1 = pack2(mu, ri), w2 = pack2(ri - bhi(w1), ri - bhi(w1));
#pragma unroll
            for (int r = 0; r < 4; r++) {
                const uint32_t s1 = __shfl_sync(0xffffffffu, w1, 8 * r), rl = __shfl_sync(0xffffffffu, w2, 8 * r);
                const uint32_t m2 = __byte_perm(s1, 0, 0x1010), rh = __byte_perm(s1, 0, 0x3232);
#pragma unroll
                for (int i = 0; i < 8; i++) { const uint32_t d = bsub2(v[r][i], m2); v[r][i] = bfma2(d, rh, bmul2(d, rl)); }
                sts4((la ^ (r << 4)) + r * 128, v[r][0], v[r][1], v[r][2], v[r][3]);
                sts4((la ^ (r << 4)) + r * 128 + 32768, v[r][4], v[r][5], v[r][6], v[r][7]);
#pragma unroll
                for (int i = 0; i < 8; i++) v[r][i] = v2[r][i];
            }
        }
        fence_async();
        if (SU == 0) bar_sync(5, 384); else bar_sync(2, 256);
        if (tid == 128) mbar_arrive(sb + B_LN);
        PG(202);
        if (mode == 1) return;
        float acc[128];
#pragma unroll
        for (int pass = 0; pass < 2; pass++) {
            if (pass == 1) mbar_wait(sb + B_H2, 0);
            PT(1 + 3 * pass);
            fresh(acc);
            uint32_t slot8 = pass ? 8 : 56, par = 0, prev8 = 0;
            auto adv = [&]() { prev8 = slot8; slot8 += 8; if (slot8 == 72) { slot8 = 0; par ^= 1; } };
            auto step = [&](int kk) {
                wg_fence();
                wgmma_ss_n256_tb1(acc, mkd(adA + (kk >> 2) * 512 + (kk & 3) * 2), mkd(bd2k + h * 512 + slot8 * 128), 1);
                wg_commit();
                wg_wait<1>();
            };
#pragma unroll 1
            for (int kk = 0; kk < 24; kk++) {
                mbar_wait(sb + B_R1 + slot8, par);
                step(kk);
                if (kk > 0 && w0 && elect1()) ring_half(sb, prev8, h * 8192, &mp.wup4, 16 * kk + 128, (pass ? 0 : 8) + 4 * h);
                adv();
            }
            if (pass == 0 && w0) mbar_wait(sb + B_MQ, 0);
#pragma unroll 1
            for (int kk = 24; kk < 32; kk++) {
                mbar_wait(sb + B_R1 + slot8, par);
                if (kk == 31 && el) mbar_arrive(sb + (pass ? B_H3 : B_H1));
                step(kk);
                if (w0 && elect1()) ring_half(sb, prev8, h * 8192, pass ? &mp.mqb1 : &mp.mqa2, (pass ? 64 : 32) * (kk - 24), pass ? h : 4 + 2 * h);
                adv();
            }
            wg_wait<0>();
            if (w0 && elect1()) ring_half(sb, prev8, h * 8192, pass ? &mp.mqb1 : &mp.mqa2, pass ? 0 : 256, pass ? 2 + h : 4 + 2 * h);
            pin(acc);
            PT(2 + 3 * pass);
            bf16* ucp = g_uc + ((size_t)blockIdx.x * 128 + r0) * D_ + 256 * h + 8 * (lane & 3);
            if (pass == 0) {
                float s0 = 0.f, s1 = 0.f, v0 = 0.f, v1 = 0.f;
#pragma unroll
                for (int n = 0; n < 32; n++) {
#pragma unroll
                    for (int e = 0; e < 4; e++) acc[4 * n + e] = gelu2(acc[4 * n + e]);
                    s0 += acc[4 * n] + acc[4 * n + 1]; s1 += acc[4 * n + 2] + acc[4 * n + 3];
                    v0 = fmaf(acc[4 * n], acc[4 * n], v0); v0 = fmaf(acc[4 * n + 1], acc[4 * n + 1], v0);
                    v1 = fmaf(acc[4 * n + 2], acc[4 * n + 2], v1); v1 = fmaf(acc[4 * n + 3], acc[4 * n + 3], v1);
                }
#pragma unroll
                for (int o = 1; o < 4; o <<= 1) {
                    s0 += __shfl_xor_sync(0xffffffffu, s0, o); s1 += __shfl_xor_sync(0xffffffffu, s1, o);
                    v0 += __shfl_xor_sync(0xffffffffu, v0, o); v1 += __shfl_xor_sync(0xffffffffu, v1, o);
                }
                if ((lane & 3) == 0) {
                    uint32_t a = sb + STAT + h * 512 + r0 * 8;
                    sts_f32(a, s0); sts_f32(a + 4, v0); sts_f32(a + 64, s1); sts_f32(a + 68, v1);
                }
                bar_sync(2, 256);
                {
                    uint32_t a = sb + STAT + (h ^ 1) * 512 + r0 * 8;
                    s0 = (s0 + lds_f32(a)) * (1.f / 512.f); v0 = (v0 + lds_f32(a + 4)) * (1.f / 512.f);
                    s1 = (s1 + lds_f32(a + 64)) * (1.f / 512.f); v1 = (v1 + lds_f32(a + 68)) * (1.f / 512.f);
                }
                v0 = rsqrtf(fmaxf(fmaf(-s0, s0, v0), 0.f) + 4e-5f); v1 = rsqrtf(fmaxf(fmaf(-s1, s1, v1), 0.f) + 4e-5f);
                s0 = -s0 * v0; s1 = -s1 * v1;
#pragma unroll
                for (int m = 0; m < 8; m++) {
                    const float* a_ = acc + 16 * m;
                    stg4(ucp + 64 * D_ + 32 * m, pack2(fmaf(a_[0], v0, s0), fmaf(a_[1], v0, s0)), pack2(fmaf(a_[4], v0, s0), fmaf(a_[5], v0, s0)),
                         pack2(fmaf(a_[8], v0, s0), fmaf(a_[9], v0, s0)), pack2(fmaf(a_[12], v0, s0), fmaf(a_[13], v0, s0)));
                    stg4(ucp + 72 * D_ + 32 * m, pack2(fmaf(a_[2], v1, s1), fmaf(a_[3], v1, s1)), pack2(fmaf(a_[6], v1, s1), fmaf(a_[7], v1, s1)),
                         pack2(fmaf(a_[10], v1, s1), fmaf(a_[11], v1, s1)), pack2(fmaf(a_[14], v1, s1), fmaf(a_[15], v1, s1)));
                }
            } else {
#pragma unroll
                for (int m = 0; m < 8; m++) {
                    const float* a_ = acc + 16 * m;
                    stg4(ucp + 32 * m, pack2(a_[0], a_[1]), pack2(a_[4], a_[5]), pack2(a_[8], a_[9]), pack2(a_[12], a_[13]));
                    stg4(ucp + 8 * D_ + 32 * m, pack2(a_[2], a_[3]), pack2(a_[6], a_[7]), pack2(a_[10], a_[11]), pack2(a_[14], a_[15]));
                }
                bar_sync(3 + h, 128);
            }
            PT(3 + 3 * pass);
        }
        const bool mc = pair && (blockIdx.x | 1) != TPB;
        const int mcc = 4 * h + 2 * (blockIdx.x & 1);
        bool pend = false;
        int s = 1, ph = 0;
        uint32_t* cp = reinterpret_cast<uint32_t*>(g_uc + (size_t)blockIdx.x * 128 * D_) + (tid - 128);
        const uint32_t* dp = reinterpret_cast<const uint32_t*>(dw) + (((tid - 128) & ~15) | ((lane & 3) << 2) | ((lane >> 2) & 3));
        const uint32_t d0 = ldg_v(dp), d1 = ldg_v(dp + D_ / 2), d2 = ldg_v(dp + D_);
        uint32_t ga = ldg_cg(cp + 64 * (D_ / 2)), gb = ldg_cg(cp + 65 * (D_ / 2));
        fresh(acc);
#pragma unroll 1
        for (int j = 0; j < NKV; j++) {
            cp += D_ / 2;
            uint32_t gc = 0, uu = 0;
            if (j < NKV - 1) { gc = ldg_cg(cp + 65 * (D_ / 2)); uu = ldg_cg(cp); }
            mbar_wait(sb + B_P + s * 8, ph);
            PL(j, 0);
            if (j > 0) {
                const float sc0 = lds_f32(sb + SCL + s * 256 + r0 * 4), sc1 = lds_f32(sb + SCL + s * 256 + r0 * 4 + 32);
                if (__any_sync(0xffffffffu, sc0 != 1.f || sc1 != 1.f)) {
#pragma unroll
                    for (int n = 0; n < 32; n++) { acc[4 * n] *= sc0; acc[4 * n + 1] *= sc0; acc[4 * n + 2] *= sc1; acc[4 * n + 3] *= sc1; }
                }
            }
            if (pend) {
                const int sp = s == 0 ? 2 : s - 1;
                mbar_wait(sb + B_EM + sp * 16 + h * 8, s == 1 ? ph ^ 1 : ph);
                tma4_mc(sb + sp * 65536 + mcc * 8192, &mp.xa2, 0, 64 * (j + 2), mcc, b, sb + B_KV + sp * 8);
                pend = false;
            }
            __syncwarp();
            mbar_wait(sb + B_GO + s * 8, ph);
            PL(j, 1);
            const uint32_t vd = sd + s * 4096 + h * 2048, pd = sd + (s == 0 ? 2 : s - 1) * 512;
            pin(acc);
            wg_fence();
#pragma unroll
            for (int kk = 0; kk < 4; kk++) wgmma_ss_n256_tb1(acc, dsc(pd, R3 + kk * 32, 16), dsc(vd, kk * 2048, 8192), 1);
            wg_commit();
            wg_wait<0>();
            pin(acc);
            PL(j, 2);
            if (el) {
                if (j + 3 < NKV) {
                    mbar_expect_tx(sb + B_KV + s * 8, 32768);
                    if (mc) {
                        mbar_arrive_peer(sb + B_EM + s * 16 + h * 8, (blockIdx.x & 1) ^ 1);
                        pend = !mbar_test(sb + B_EM + s * 16 + h * 8, ph);
                        if (!pend) tma4_mc(sb + s * 65536 + mcc * 8192, &mp.xa2, 0, 64 * (j + 3), mcc, b, sb + B_KV + s * 8);
                    } else
                        tma4(sb + s * 65536 + h * 32768, &mp.xa4, 0, 64 * (j + 3), 4 * h, b, sb + B_KV + s * 8);
                } else if (j < NKV - 1) {
                    const int n0 = (j == NKV - 3 ? 0 : 8) + 4 * h;
#pragma unroll 1
                    for (int n = n0; n < n0 + 4; n++) ring_ld(sb, n * 8, n);
                }
                if (j == NKV - 5 && mode == 0) flag_wait(&g_sync[3], 4);
                if (j >= XPF && j < XPF + 4) {
                    const int t0 = 62 * ti + 32 * h + 8 * (j - XPF), nr = min(8, T_ - t0);
                    if (nr > 0) l2_prefetch(x + ((size_t)b * T_ + t0) * D_, nr * 1024);
                }
                if (KPF && h == 0 && 64 * (j + KPF) + ti < T_) l2_prefetch(g_xa + ((size_t)b * (T_ + 8) + 1 + 64 * (j + KPF) + ti) * D_, 1024);
            }
            uu = pack2(gelu2(blo(uu)), gelu2(bhi(uu)));
            if (j < NKV - 1) asm volatile("st.global.u32 [%0], %1;" ::"l"(cp), "r"(bmul2(uu, bfma2(gc, d2, bfma2(gb, d1, bmul2(ga, d0))))) : "memory");
            ga = gb; gb = gc;
            if (++s == 3) s = 0;
            if (s == 1) ph ^= 1;
        }
        {
            const float i0 = lds_f32(sb + LINV + r0 * 4), i1 = lds_f32(sb + LINV + r0 * 4 + 32);
#pragma unroll
            for (int p = 0; p < 16; p++)
                stsm4(((sb + R0 + h * 32768 + loff) ^ ((p & 3) << 5)) + (p >> 2) * 8192,
                      pack2(acc[8 * p] * i0, acc[8 * p + 1] * i0), pack2(acc[8 * p + 2] * i1, acc[8 * p + 3] * i1),
                      pack2(acc[8 * p + 4] * i0, acc[8 * p + 5] * i0), pack2(acc[8 * p + 6] * i1, acc[8 * p + 7] * i1));
        }
        fence_async();
        fence_async_g();
        bar_sync(2, 256);
        if (lane == 0 && w < 2) ring_ld(sb, 128 + 16 * w + 8 * h, 16 + 2 * w + h);
        PT(7);
        fresh(acc);
        {
            uint32_t slot8 = 8 * h, par = 0, prev8 = 0;
#pragma unroll 1
            for (int kk = 0; kk < 64; kk++) {
                if (kk == 32 || kk == 48) mbar_wait(sb + B_UC + (kk >> 1 & 8), 0);
                mbar_wait(sb + B_R2 + slot8, par);
                wg_fence();
                wgmma_ss_n256_tb1(acc, mkd(sd + (1u << 16) + (R0 >> 4) + (kk >> 2 & 7) * 512 + (kk & 3) * 2), mkd(bd2k + (R1 >> 4) + slot8 * 64), 1);
                wg_commit();
                wg_wait<1>();
                if (kk > 0 && lane == 0) mbar_arrive(sb + B_E2 + prev8);
                if ((kk == 16 || kk == 32) && w0 && elect1() && (atom_inc_s(sb + CNT + 12 + (kk >> 3 & 4)) & 1)) {
                    mbar_expect_tx(sb + B_UC + (kk >> 2 & 8), 32768);
                    tma3(sb + R0 + (kk & 32) * 1024, &mp.uc, 0, 128 * blockIdx.x, kk >> 3 & 4, sb + B_UC + (kk >> 2 & 8));
                }
                prev8 = slot8;
                slot8 += 16;
                if (slot8 >= 160) { slot8 -= 160; par ^= 1; }
            }
        }
        wg_wait<0>();
        pin(acc);
        PT(8);
        mbar_wait(sb + B_X, 0);
        PT(9);
        {
            const uint32_t sr = (lrow + 63) & 63;
            const uint32_t xoff = sr * 128 + ((((lane >> 4) ^ sr) & 7) << 4);
#pragma unroll
            for (int p = 0; p < 16; p++) {
                const uint32_t a = ((sb + R2 + h * 32768 + xoff) ^ ((p & 3) << 5)) + (p >> 2) * 8192;
                uint32_t xv[4];
                ldsm4(a, xv);
#pragma unroll
                for (int e = 0; e < 4; e++)
                    xv[e] = pack2(acc[8 * p + 2 * e] + __uint_as_float(xv[e] << 16), acc[8 * p + 2 * e + 1] + __uint_as_float(xv[e] & 0xffff0000u));
                stsm4(a, xv[0], xv[1], xv[2], xv[3]);
            }
        }
        fence_async();
        bar_sync(3 + h, 128);
        if (el) {
            for (int c = 0; c < 4; c++) tma4_store(&mp.out, sb + R2 + (4 * h + c) * 8192, 0, 62 * ti, 4 * h + c, b);
            asm volatile("cp.async.bulk.commit_group;" ::: "memory");
            PT(10);
            if (h == 0) cta_done(mode);
            asm volatile("cp.async.bulk.wait_group.read 0;" ::: "memory");
        }
        PT(11);
        PG(201);
        PDUMP();
    }
}

typedef CUresult (*PFN_enc)(CUtensorMap*, CUtensorMapDataType, cuuint32_t, void*, const cuuint64_t*, const cuuint64_t*,
                            const cuuint32_t*, const cuuint32_t*, CUtensorMapInterleave, CUtensorMapSwizzle,
                            CUtensorMapL2promotion, CUtensorMapFloatOOBfill);

static void enc(PFN_enc f, CUtensorMap* m, void* base, int rank, const cuuint64_t* dims, const cuuint64_t* strides, const cuuint32_t* box) {
    cuuint32_t es[5] = {1, 1, 1, 1, 1};
    f(m, CU_TENSOR_MAP_DATA_TYPE_BFLOAT16, rank, base, dims, strides, box, es, CU_TENSOR_MAP_INTERLEAVE_NONE,
      CU_TENSOR_MAP_SWIZZLE_128B, CU_TENSOR_MAP_L2_PROMOTION_L2_256B, CU_TENSOR_MAP_FLOAT_OOB_FILL_NONE);
}
static void enc_act(PFN_enc f, CUtensorMap* m, void* base, int rows, int chunks, int trows = T_, int pitch = T_) {
    cuuint64_t dims[4] = {64, (cuuint64_t)trows, 8, (cuuint64_t)NB_};
    cuuint64_t st[3] = {1024, 128, (cuuint64_t)pitch * 1024};
    cuuint32_t box[4] = {64, (cuuint32_t)rows, (cuuint32_t)chunks, 1};
    enc(f, m, base, 4, dims, st, box);
}
static void enc_w(PFN_enc f, CUtensorMap* m, void* base, int krows, int ncols, int bk, int bc) {
    cuuint64_t dims[3] = {64, (cuuint64_t)krows, (cuuint64_t)(ncols / 64)};
    cuuint64_t st[2] = {(cuuint64_t)ncols * 2, 128};
    cuuint32_t box[3] = {64, (cuuint32_t)bk, (cuuint32_t)bc};
    enc(f, m, base, 3, dims, st, box);
}

extern "C" void kernel_launch(void* const* d_in, const int* in_sizes, int n_in, void* d_out, int out_size) {
    const bf16* x = (const bf16*)d_in[0];
    static PFN_enc fenc = nullptr;
    static void *p_xa, *p_mqk, *p_uc, *p_t1;
    static int fused = 0, paired = 0;
    cudaLaunchAttribute at[1];
    at[0].id = cudaLaunchAttributeClusterDimension;
    at[0].val.clusterDim.x = 2; at[0].val.clusterDim.y = 1; at[0].val.clusterDim.z = 1;
    if (!fenc) {
        void* fn = nullptr;
        cudaDriverEntryPointQueryResult qr;
        cudaGetDriverEntryPoint("cuTensorMapEncodeTiled", &fn, cudaEnableDefault, &qr);
        fenc = (PFN_enc)fn;
        cudaGetSymbolAddress(&p_xa, g_xa);
        cudaGetSymbolAddress(&p_mqk, g_mqk);
        cudaGetSymbolAddress(&p_uc, g_uc);
        cudaGetSymbolAddress(&p_t1, g_t1);
        cudaFuncSetAttribute(main_kernel, cudaFuncAttributeMaxDynamicSharedMemorySize, SMEM_BYTES);
        int dev = 0, sms = 0, occ = 0;
        cudaGetDevice(&dev);
        cudaDeviceGetAttribute(&sms, cudaDevAttrMultiProcessorCount, dev);
        cudaOccupancyMaxActiveBlocksPerMultiprocessor(&occ, main_kernel, 384, SMEM_BYTES);
        fused = sms * occ >= NCTA + 2;
        int ncl = 0;
        cudaLaunchConfig_t qc = {};
        qc.gridDim = dim3(NCTA + 2); qc.blockDim = dim3(384); qc.dynamicSmemBytes = SMEM_BYTES; qc.attrs = at; qc.numAttrs = 1;
        paired = MCAST && fused && cudaOccupancyMaxActiveClusters(&ncl, main_kernel, &qc) == cudaSuccess && 2 * ncl >= NCTA + 2;
        cudaGetLastError();
    }
    Maps mp;
    enc_act(fenc, &mp.xa, (char*)p_xa + 1024, 64, 8, T_, T_ + 8);
    enc_act(fenc, &mp.xa2, (char*)p_xa + 1024, 64, 2, T_, T_ + 8);
    enc_act(fenc, &mp.xa4, (char*)p_xa + 1024, 64, 4, T_, T_ + 8);
    enc_act(fenc, &mp.xas, p_xa, 64, 1, T_ + 1, T_ + 8);
    enc_act(fenc, &mp.x, (void*)x, 64, 1);
    enc_act(fenc, &mp.out, d_out, 62, 1);
    enc_w(fenc, &mp.wup4, d_in[5], 512, 1024, 16, 4);
    enc_w(fenc, &mp.wup8, d_in[5], 512, 1024, 16, 8);
    enc_w(fenc, &mp.mqa2, p_mqk, 512, 512, 32, 2);
    enc_w(fenc, &mp.mqa4, p_mqk, 512, 512, 32, 4);
    enc_w(fenc, &mp.mqb1, p_mqk, 512, 512, 64, 1);
    enc_w(fenc, &mp.mqb2, p_mqk, 512, 512, 64, 2);
    enc_w(fenc, &mp.uc, p_uc, NCTA * 128, 512, 64, 4);
    enc_w(fenc, &mp.wq, d_in[1], 512, 512, 64, 8);
    enc_w(fenc, &mp.wk, d_in[2], 512, 512, 32, 8);
    enc_w(fenc, &mp.fa[0], d_in[3], 512, 512, 128, 1);
    enc_w(fenc, &mp.fa[1], d_in[7], 512, 512, 128, 1);
    enc_w(fenc, &mp.fa[2], p_t1, 512, 512, 128, 1);
    enc_w(fenc, &mp.fb[0], d_in[4], 512, 512, 64, 4);
    enc_w(fenc, &mp.fb[1], d_in[8], 1024, 512, 64, 4);
    enc_w(fenc, &mp.fc, p_t1, 512, 512, 64, 4);
    cudaStream_t st = cudaStreamPerThread;
    if (paired) {
        cudaLaunchConfig_t lc = {};
        lc.gridDim = dim3(NCTA + 2); lc.blockDim = dim3(384); lc.dynamicSmemBytes = SMEM_BYTES; lc.stream = st; lc.attrs = at; lc.numAttrs = 1;
        cudaLaunchKernelEx(&lc, main_kernel, mp, x, (const bf16*)d_in[6], (const bf16*)d_in[5], 0, MCAST == 1 ? 1 : 0);
    } else if (fused) {
        main_kernel<<<NCTA + 2, 384, SMEM_BYTES, st>>>(mp, x, (const bf16*)d_in[6], (const bf16*)d_in[5], 0, 0);
    } else {
        main_kernel<<<NCTA + 2, 384, SMEM_BYTES, st>>>(mp, x, (const bf16*)d_in[6], (const bf16*)d_in[5], 1, 0);
        main_kernel<<<NCTA + 2, 384, SMEM_BYTES, st>>>(mp, x, (const bf16*)d_in[6], (const bf16*)d_in[5], 2, 0);
    }
}
```

```cpp
#include <cuda_runtime.h>
#include <cuda_bf16.h>
#include <cuda.h>
#include <stdint.h>

typedef __nv_bfloat16 bf16;

constexpr int T_ = 4000, D_ = 512, NB_ = 2;
constexpr int TPB = 65;
constexpr int NCTA = TPB * NB_;
constexpr int NKV = 63;

__device__ __align__(1024) bf16 g_xa[NB_ * (T_ + 8) * D_];
__device__ __align__(1024) bf16 g_mqk[D_ * D_];
__device__ __align__(1024) bf16 g_t1[D_ * D_];
__device__ __align__(1024) bf16 g_wepi[2 * D_ * D_];
__device__ __align__(1024) bf16 g_uc[NCTA * 128 * D_];
__device__ unsigned g_sync[8];

#define PT(i) do { if (el) asm volatile("st.shared.u32 [%0], %1;" ::"r"(sb + MISC + 2560), "r"((unsigned)clock())); } while (0)
#define PG(i)
#define PE()
#define PLM 15
#define PL(j, q) do { if ((PLM >> ((q) + (wg ? 4 : 0))) & 1) PT(0); } while (0)
#define PDUMP()

#define FENCE_AT 1
#define GO_AT 25
#define LAZY 4294967296.f
#define SU 2
#define XS_GAP 800
#define XPF 50
#define URAW 1
#define LAGA 0
#define LAGB 0
#define DPOS 1
#define KPF 0
#define XEF 0
#define SK0 0
#define TRIM 1
#define CHS 1
#define PFW 1
constexpr uint32_t R0 = 0, R1 = 65536, R2 = 131072, R3 = 196608, QS = 221184, MISC = 229376;
constexpr uint32_t AT = 147456;
constexpr uint32_t SMEM_BYTES = 232448;
constexpr uint32_t B_R1 = MISC + 1856  , B_MK = MISC + 48, B_LN = MISC + 56, B_MQ = MISC + 64,
                   B_H1 = MISC + 88, B_H2 = MISC + 96, B_H3 = MISC + 104,
                   B_KV = MISC + 112, B_P = MISC + 136, B_GO = MISC + 160, B_UC = MISC + 184  ,
                   B_X = MISC + 200, CNT = MISC + 208  , SCL = MISC + 512  ,
                   LINV = MISC + 1280  , STAT = MISC + 512  ,
                   B_R2 = MISC + 1536  , B_E2 = MISC + 1696  ;

__device__ __forceinline__ uint32_t smem_u32(const void* p) { return (uint32_t)__cvta_generic_to_shared(p); }
__device__ __forceinline__ void wg_fence() { asm volatile("wgmma.fence.sync.aligned;" ::: "memory"); }
__device__ __forceinline__ void wg_commit() { asm volatile("wgmma.commit_group.sync.aligned;" ::: "memory"); }
template <int N> __device__ __forceinline__ void wg_wait() { asm volatile("wgmma.wait_group.sync.aligned %0;" ::"n"(N) : "memory"); }
__device__ __forceinline__ uint64_t dsc(uint32_t sd, uint32_t off, uint32_t lbo) {
    uint32_t lo = sd + (off >> 4) + ((lbo >> 4) << 16);
    uint64_t d;
    asm("mov.b64 %0, {%1, %2};" : "=l"(d) : "r"(lo), "r"((1024u >> 4) | (1u << 30)));
    return d;
}
__device__ __forceinline__ bool elect1() {
    uint32_t p;
    asm volatile("{\n.reg .pred p;\nelect.sync _|p, 0xffffffff;\nselp.u32 %0, 1, 0, p;\n}\n" : "=r"(p));
    return p != 0;
}
__device__ __forceinline__ void mbar_init(uint32_t bar, int cnt) { asm volatile("mbarrier.init.shared::cta.b64 [%0], %1;" ::"r"(bar), "r"(cnt) : "memory"); }
__device__ __forceinline__ void mbar_expect_tx(uint32_t bar, uint32_t bytes) { asm volatile("mbarrier.arrive.expect_tx.shared::cta.b64 _, [%0], %1;" ::"r"(bar), "r"(bytes) : "memory"); }
__device__ __forceinline__ void mbar_arrive(uint32_t bar) { asm volatile("mbarrier.arrive.shared::cta.b64 _, [%0];" ::"r"(bar) : "memory"); }
__device__ __forceinline__ void mbar_wait(uint32_t bar, uint32_t parity) {
    uint32_t ok;
#pragma unroll 1
    for (uint32_t it = 0;; ++it) {
        asm volatile("{\n.reg .pred p;\nmbarrier.try_wait.parity.shared::cta.b64 p, [%1], %2;\nselp.u32 %0, 1, 0, p;\n}\n" : "=r"(ok) : "r"(bar), "r"(parity) : "memory");
        if (ok) break;
        if (it > (1u << 20)) __trap();
    }
}
__device__ __forceinline__ bool mbar_test(uint32_t bar, uint32_t parity) {
    uint32_t ok;
    asm volatile("{\n.reg .pred p;\nmbarrier.test_wait.parity.shared::cta.b64 p, [%1], %2;\nselp.u32 %0, 1, 0, p;\n}\n" : "=r"(ok) : "r"(bar), "r"(parity) : "memory");
    return ok != 0;
}
__device__ __forceinline__ void fence_async() { asm volatile("fence.proxy.async.shared::cta;" ::: "memory"); }
__device__ __forceinline__ void fence_async_g() { asm volatile("fence.proxy.async.global;" ::: "memory"); }
__device__ __forceinline__ void bar_sync(int id, int n) { asm volatile("bar.sync %0, %1;" ::"r"(id), "r"(n) : "memory"); }
__device__ __forceinline__ void tma3(uint32_t dst, const CUtensorMap* tm, int c0, int c1, int c2, uint32_t bar) {
    asm volatile("cp.async.bulk.tensor.3d.shared::cluster.global.mbarrier::complete_tx::bytes [%0], [%1, {%3, %4, %5}], [%2];"
                 ::"r"(dst), "l"(tm), "r"(bar), "r"(c0), "r"(c1), "r"(c2) : "memory");
}
__device__ __forceinline__ void tma4(uint32_t dst, const CUtensorMap* tm, int c0, int c1, int c2, int c3, uint32_t bar) {
    asm volatile("cp.async.bulk.tensor.4d.shared::cluster.global.mbarrier::complete_tx::bytes [%0], [%1, {%3, %4, %5, %6}], [%2];"
                 ::"r"(dst), "l"(tm), "r"(bar), "r"(c0), "r"(c1), "r"(c2), "r"(c3) : "memory");
}
__device__ __forceinline__ void tma4_store(const CUtensorMap* tm, uint32_t src, int c0, int c1, int c2, int c3) {
    asm volatile("cp.async.bulk.tensor.4d.global.shared::cta.bulk_group [%0, {%2, %3, %4, %5}], [%1];"
                 ::"l"(tm), "r"(src), "r"(c0), "r"(c1), "r"(c2), "r"(c3) : "memory");
}
__device__ __forceinline__ void tma3_store(const CUtensorMap* tm, uint32_t src, int c0, int c1, int c2) {
    asm volatile("cp.async.bulk.tensor.3d.global.shared::cta.bulk_group [%0, {%2, %3, %4}], [%1];"
                 ::"l"(tm), "r"(src), "r"(c0), "r"(c1), "r"(c2) : "memory");
}
__device__ __forceinline__ void stsm4(uint32_t addr, uint32_t a, uint32_t b, uint32_t c, uint32_t d) {
    asm volatile("stmatrix.sync.aligned.m8n8.x4.shared.b16 [%0], {%1, %2, %3, %4};" ::"r"(addr), "r"(a), "r"(b), "r"(c), "r"(d) : "memory");
}
__device__ __forceinline__ void ldsm4(uint32_t addr, uint32_t (&r)[4]) {
    asm volatile("ldmatrix.sync.aligned.m8n8.x4.shared.b16 {%0, %1, %2, %3}, [%4];" : "=r"(r[0]), "=r"(r[1]), "=r"(r[2]), "=r"(r[3]) : "r"(addr) : "memory");
}
__device__ __forceinline__ void ldsm2(uint32_t addr, uint32_t (&r)[2]) {
    asm volatile("ldmatrix.sync.aligned.m8n8.x2.shared.b16 {%0, %1}, [%2];" : "=r"(r[0]), "=r"(r[1]) : "r"(addr) : "memory");
}
__device__ __forceinline__ void stg4(void* p, uint32_t a, uint32_t b, uint32_t c, uint32_t d) {
    asm volatile("st.global.v4.u32 [%0], {%1, %2, %3, %4};" ::"l"(p), "r"(a), "r"(b), "r"(c), "r"(d) : "memory");
}
__device__ __forceinline__ void hmma(float (&c)[4], uint32_t a0, uint32_t a1, uint32_t a2, uint32_t a3, uint32_t b0, uint32_t b1) {
    asm("mma.sync.aligned.m16n8k16.row.col.f32.bf16.bf16.f32 {%0, %1, %2, %3}, {%4, %5, %6, %7}, {%8, %9}, {%0, %1, %2, %3};"
        : "+f"(c[0]), "+f"(c[1]), "+f"(c[2]), "+f"(c[3]) : "r"(a0), "r"(a1), "r"(a2), "r"(a3), "r"(b0), "r"(b1));
}
__device__ __forceinline__ uint32_t pack2(float lo, float hi) {
    uint32_t r;
    asm("cvt.rn.bf16x2.f32 %0, %1, %2;" : "=r"(r) : "f"(hi), "f"(lo));
    return r;
}
__device__ __forceinline__ uint32_t pack2v(float lo, float hi) {
    uint32_t r;
    asm volatile("cvt.rn.bf16x2.f32 %0, %1, %2;" : "=r"(r) : "f"(hi), "f"(lo));
    return r;
}
__device__ __forceinline__ uint32_t bmul2(uint32_t a, uint32_t b) { uint32_t r; asm("mul.rn.bf16x2 %0, %1, %2;" : "=r"(r) : "r"(a), "r"(b)); return r; }
__device__ __forceinline__ uint32_t bfma2(uint32_t a, uint32_t b, uint32_t c) { uint32_t r; asm("fma.rn.bf16x2 %0, %1, %2, %3;" : "=r"(r) : "r"(a), "r"(b), "r"(c)); return r; }
__device__ __forceinline__ float ex2(float x) { float r; asm("ex2.approx.ftz.f32 %0, %1;" : "=f"(r) : "f"(x)); return r; }
__device__ __forceinline__ float rcp(float x) { float r; asm("rcp.approx.ftz.f32 %0, %1;" : "=f"(r) : "f"(x)); return r; }
__device__ __forceinline__ float gelu2(float x) {
    float t = fmaf(x * x, 0.044715f * 0.7978845608028654f, 0.7978845608028654f), th;
    asm("tanh.approx.f32 %0, %1;" : "=f"(th) : "f"(x * t));
    return fmaf(x, th, x);
}
__device__ __forceinline__ uint32_t ldg_v(const uint32_t* p) { uint32_t v; asm volatile("ld.global.nc.u32 %0, [%1];" : "=r"(v) : "l"(p)); return v; }
__device__ __forceinline__ uint32_t ldg_cg(const uint32_t* p) { uint32_t v; asm volatile("ld.global.cg.u32 %0, [%1];" : "=r"(v) : "l"(p) : "memory"); return v; }
__device__ __forceinline__ float lds_f32(uint32_t a) { float v; asm volatile("ld.shared.f32 %0, [%1];" : "=f"(v) : "r"(a) : "memory"); return v; }
__device__ __forceinline__ void sts_f32(uint32_t a, float v) { asm volatile("st.shared.f32 [%0], %1;" ::"r"(a), "f"(v) : "memory"); }
__device__ __forceinline__ uint32_t atom_inc_s(uint32_t a) { uint32_t v; asm volatile("atom.relaxed.cta.shared.add.u32 %0, [%1], 1;" : "=r"(v) : "r"(a) : "memory"); return v; }
__device__ __forceinline__ void lds4(uint32_t a, uint32_t* r) {
    asm volatile("ld.shared.v4.u32 {%0, %1, %2, %3}, [%4];" : "=r"(r[0]), "=r"(r[1]), "=r"(r[2]), "=r"(r[3]) : "r"(a) : "memory");
}
__device__ __forceinline__ void sts4(uint32_t a, uint32_t x, uint32_t y, uint32_t z, uint32_t t) {
    asm volatile("st.shared.v4.u32 [%0], {%1, %2, %3, %4};" ::"r"(a), "r"(x), "r"(y), "r"(z), "r"(t) : "memory");
}
__device__ __forceinline__ uint32_t bsub2(uint32_t a, uint32_t b) { uint32_t r; asm("sub.rn.bf16x2 %0, %1, %2;" : "=r"(r) : "r"(a), "r"(b)); return r; }
__device__ __forceinline__ float blo(uint32_t v) { return __uint_as_float(v << 16); }
__device__ __forceinline__ float bhi(uint32_t v) { return __uint_as_float(v & 0xffff0000u); }
__device__ __forceinline__ float bfr(float x) { return __bfloat162float(__float2bfloat16_rn(x)); }
__device__ __forceinline__ void l2_prefetch(const void* p, uint32_t bytes) { asm volatile("cp.async.bulk.prefetch.L2.global [%0], %1;" ::"l"(p), "r"(bytes) : "memory"); }
__device__ __forceinline__ void flag_add(unsigned* p) { asm volatile("red.release.gpu.global.add.u32 [%0], 1;" ::"l"(p) : "memory"); }
__device__ __forceinline__ void flag_wait(const unsigned* p, unsigned target) {
#pragma unroll 1
    for (uint32_t it = 0;; ++it) {
        unsigned v;
        asm volatile("ld.acquire.gpu.global.u32 %0, [%1];" : "=r"(v) : "l"(p) : "memory");
        if (v >= target) break;
        if (it > (1u << 20)) __trap();
    }
    fence_async_g();
}
template <int N> __device__ __forceinline__ void pin(float (&a)[N]) {
#pragma unroll
    for (int i = 0; i < N; i++) asm volatile("" : "+f"(a[i])::"memory");
}

template <int N> __device__ __forceinline__ void fresh(float (&a)[N]) {
#pragma unroll
    for (int i = 0; i < N; i++) a[i] = 0.f;
    pin(a);
}

__device__ __forceinline__ void wgmma_rs_n64_tb0(float (&d)[32], uint32_t a0, uint32_t a1, uint32_t a2, uint32_t a3, uint64_t db, int scale_d) {
    asm volatile("{\n.reg .pred p;\nsetp.ne.b32 p, %37, 0;\n"
        "wgmma.mma_async.sync.aligned.m64n64k16.f32.bf16.bf16 {%0, %1, %2, %3, %4, %5, %6, %7, %8, %9, %10, %11, %12, %13, %14, %15, %16, %17, %18, %19, %20, %21, %22, %23, %24, %25, %26, %27, %28, %29, %30, %31}, {%32, %33, %34, %35}, %36, p, 1, 1, 0;\n}\n"
        : "+f"(d[0]), "+f"(d[1]), "+f"(d[2]), "+f"(d[3]), "+f"(d[4]), "+f"(d[5]), "+f"(d[6]), "+f"(d[7]), "+f"(d[8]), "+f"(d[9]), "+f"(d[10]), "+f"(d[11]), "+f"(d[12]), "+f"(d[13]), "+f"(d[14]), "+f"(d[15]), "+f"(d[16]), "+f"(d[17]), "+f"(d[18]), "+f"(d[19]), "+f"(d[20]), "+f"(d[21]), "+f"(d[22]), "+f"(d[23]), "+f"(d[24]), "+f"(d[25]), "+f"(d[26]), "+f"(d[27]), "+f"(d[28]), "+f"(d[29]), "+f"(d[30]), "+f"(d[31])
        : "r"(a0), "r"(a1), "r"(a2), "r"(a3), "l"(db), "r"(scale_d));
}

__device__ __forceinline__ void wgmma_ss_n128_tb1(float (&d)[64], uint64_t da, uint64_t db, int scale_d) {
    asm volatile("{\n.reg .pred p;\nsetp.ne.b32 p, %66, 0;\n"
        "wgmma.mma_async.sync.aligned.m64n128k16.f32.bf16.bf16 {%0, %1, %2, %3, %4, %5, %6, %7, %8, %9, %10, %11, %12, %13, %14, %15, %16, %17, %18, %19, %20, %21, %22, %23, %24, %25, %26, %27, %28, %29, %30, %31, %32, %33, %34, %35, %36, %37, %38, %39, %40, %41, %42, %43, %44, %45, %46, %47, %48, %49, %50, %51, %52, %53, %54, %55, %56, %57, %58, %59, %60, %61, %62, %63}, %64, %65, p, 1, 1, 0, 1;\n}\n"
        : "+f"(d[0]), "+f"(d[1]), "+f"(d[2]), "+f"(d[3]), "+f"(d[4]), "+f"(d[5]), "+f"(d[6]), "+f"(d[7]), "+f"(d[8]), "+f"(d[9]), "+f"(d[10]), "+f"(d[11]), "+f"(d[12]), "+f"(d[13]), "+f"(d[14]), "+f"(d[15]), "+f"(d[16]), "+f"(d[17]), "+f"(d[18]), "+f"(d[19]), "+f"(d[20]), "+f"(d[21]), "+f"(d[22]), "+f"(d[23]), "+f"(d[24]), "+f"(d[25]), "+f"(d[26]), "+f"(d[27]), "+f"(d[28]), "+f"(d[29]), "+f"(d[30]), "+f"(d[31]), "+f"(d[32]), "+f"(d[33]), "+f"(d[34]), "+f"(d[35]), "+f"(d[36]), "+f"(d[37]), "+f"(d[38]), "+f"(d[39]), "+f"(d[40]), "+f"(d[41]), "+f"(d[42]), "+f"(d[43]), "+f"(d[44]), "+f"(d[45]), "+f"(d[46]), "+f"(d[47]), "+f"(d[48]), "+f"(d[49]), "+f"(d[50]), "+f"(d[51]), "+f"(d[52]), "+f"(d[53]), "+f"(d[54]), "+f"(d[55]), "+f"(d[56]), "+f"(d[57]), "+f"(d[58]), "+f"(d[59]), "+f"(d[60]), "+f"(d[61]), "+f"(d[62]), "+f"(d[63])
        : "l"(da), "l"(db), "r"(scale_d));
}

__device__ __forceinline__ void wgmma_ss_n256_tb1(float (&d)[128], uint64_t da, uint64_t db, int scale_d) {
    asm volatile("{\n.reg .pred p;\nsetp.ne.b32 p, %130, 0;\n"
        "wgmma.mma_async.sync.aligned.m64n256k16.f32.bf16.bf16 {%0, %1, %2, %3, %4, %5, %6, %7, %8, %9, %10, %11, %12, %13, %14, %15, %16, %17, %18, %19, %20, %21, %22, %23, %24, %25, %26, %27, %28, %29, %30, %31, %32, %33, %34, %35, %36, %37, %38, %39, %40, %41, %42, %43, %44, %45, %46, %47, %48, %49, %50, %51, %52, %53, %54, %55, %56, %57, %58, %59, %60, %61, %62, %63, %64, %65, %66, %67, %68, %69, %70, %71, %72, %73, %74, %75, %76, %77, %78, %79, %80, %81, %82, %83, %84, %85, %86, %87, %88, %89, %90, %91, %92, %93, %94, %95, %96, %97, %98, %99, %100, %101, %102, %103, %104, %105, %106, %107, %108, %109, %110, %111, %112, %113, %114, %115, %116, %117, %118, %119, %120, %121, %122, %123, %124, %125, %126, %127}, %128, %129, p, 1, 1, 0, 1;\n}\n"
        : "+f"(d[0]), "+f"(d[1]), "+f"(d[2]), "+f"(d[3]), "+f"(d[4]), "+f"(d[5]), "+f"(d[6]), "+f"(d[7]), "+f"(d[8]), "+f"(d[9]), "+f"(d[10]), "+f"(d[11]), "+f"(d[12]), "+f"(d[13]), "+f"(d[14]), "+f"(d[15]), "+f"(d[16]), "+f"(d[17]), "+f"(d[18]), "+f"(d[19]), "+f"(d[20]), "+f"(d[21]), "+f"(d[22]), "+f"(d[23]), "+f"(d[24]), "+f"(d[25]), "+f"(d[26]), "+f"(d[27]), "+f"(d[28]), "+f"(d[29]), "+f"(d[30]), "+f"(d[31]), "+f"(d[32]), "+f"(d[33]), "+f"(d[34]), "+f"(d[35]), "+f"(d[36]), "+f"(d[37]), "+f"(d[38]), "+f"(d[39]), "+f"(d[40]), "+f"(d[41]), "+f"(d[42]), "+f"(d[43]), "+f"(d[44]), "+f"(d[45]), "+f"(d[46]), "+f"(d[47]), "+f"(d[48]), "+f"(d[49]), "+f"(d[50]), "+f"(d[51]), "+f"(d[52]), "+f"(d[53]), "+f"(d[54]), "+f"(d[55]), "+f"(d[56]), "+f"(d[57]), "+f"(d[58]), "+f"(d[59]), "+f"(d[60]), "+f"(d[61]), "+f"(d[62]), "+f"(d[63]), "+f"(d[64]), "+f"(d[65]), "+f"(d[66]), "+f"(d[67]), "+f"(d[68]), "+f"(d[69]), "+f"(d[70]), "+f"(d[71]), "+f"(d[72]), "+f"(d[73]), "+f"(d[74]), "+f"(d[75]), "+f"(d[76]), "+f"(d[77]), "+f"(d[78]), "+f"(d[79]), "+f"(d[80]), "+f"(d[81]), "+f"(d[82]), "+f"(d[83]), "+f"(d[84]), "+f"(d[85]), "+f"(d[86]), "+f"(d[87]), "+f"(d[88]), "+f"(d[89]), "+f"(d[90]), "+f"(d[91]), "+f"(d[92]), "+f"(d[93]), "+f"(d[94]), "+f"(d[95]), "+f"(d[96]), "+f"(d[97]), "+f"(d[98]), "+f"(d[99]), "+f"(d[100]), "+f"(d[101]), "+f"(d[102]), "+f"(d[103]), "+f"(d[104]), "+f"(d[105]), "+f"(d[106]), "+f"(d[107]), "+f"(d[108]), "+f"(d[109]), "+f"(d[110]), "+f"(d[111]), "+f"(d[112]), "+f"(d[113]), "+f"(d[114]), "+f"(d[115]), "+f"(d[116]), "+f"(d[117]), "+f"(d[118]), "+f"(d[119]), "+f"(d[120]), "+f"(d[121]), "+f"(d[122]), "+f"(d[123]), "+f"(d[124]), "+f"(d[125]), "+f"(d[126]), "+f"(d[127])
        : "l"(da), "l"(db), "r"(scale_d));
}

__device__ __forceinline__ void wgmma_ss_n32_tb0(float (&d)[16], uint64_t da, uint64_t db, int scale_d) {
    asm volatile("{\n.reg .pred p;\nsetp.ne.b32 p, %18, 0;\n"
        "wgmma.mma_async.sync.aligned.m64n32k16.f32.bf16.bf16 {%0, %1, %2, %3, %4, %5, %6, %7, %8, %9, %10, %11, %12, %13, %14, %15}, %16, %17, p, 1, 1, 0, 0;\n}\n"
        : "+f"(d[0]), "+f"(d[1]), "+f"(d[2]), "+f"(d[3]), "+f"(d[4]), "+f"(d[5]), "+f"(d[6]), "+f"(d[7]), "+f"(d[8]), "+f"(d[9]), "+f"(d[10]), "+f"(d[11]), "+f"(d[12]), "+f"(d[13]), "+f"(d[14]), "+f"(d[15])
        : "l"(da), "l"(db), "r"(scale_d));
}

__device__ __forceinline__ void wgmma_ss_n64_tb0(float (&d)[32], uint64_t da, uint64_t db, int scale_d) {
    asm volatile("{\n.reg .pred p;\nsetp.ne.b32 p, %34, 0;\n"
        "wgmma.mma_async.sync.aligned.m64n64k16.f32.bf16.bf16 {%0, %1, %2, %3, %4, %5, %6, %7, %8, %9, %10, %11, %12, %13, %14, %15, %16, %17, %18, %19, %20, %21, %22, %23, %24, %25, %26, %27, %28, %29, %30, %31}, %32, %33, p, 1, 1, 0, 0;\n}\n"
        : "+f"(d[0]), "+f"(d[1]), "+f"(d[2]), "+f"(d[3]), "+f"(d[4]), "+f"(d[5]), "+f"(d[6]), "+f"(d[7]), "+f"(d[8]), "+f"(d[9]), "+f"(d[10]), "+f"(d[11]), "+f"(d[12]), "+f"(d[13]), "+f"(d[14]), "+f"(d[15]), "+f"(d[16]), "+f"(d[17]), "+f"(d[18]), "+f"(d[19]), "+f"(d[20]), "+f"(d[21]), "+f"(d[22]), "+f"(d[23]), "+f"(d[24]), "+f"(d[25]), "+f"(d[26]), "+f"(d[27]), "+f"(d[28]), "+f"(d[29]), "+f"(d[30]), "+f"(d[31])
        : "l"(da), "l"(db), "r"(scale_d));
}

struct Maps {
    CUtensorMap xa, xa2, xa4, xas, wup4, wup8, mqa2, mqa4, mqb1, mqb2, uc, x, out, wq, wk, fa[3], fb[2], fc;
};

__device__ __forceinline__ uint64_t mkd(uint32_t lo) {
    uint64_t d;
    asm("mov.b64 %0, {%1, %2};" : "=l"(d) : "r"(lo), "r"((1024u >> 4) | (1u << 30)));
    return d;
}
__device__ __forceinline__ void bulk_ld(uint32_t dst, const void* src, uint32_t bytes, uint32_t bar) {
    asm volatile("cp.async.bulk.shared::cluster.global.mbarrier::complete_tx::bytes [%0], [%1], %2, [%3];" ::"r"(dst), "l"(src), "r"(bytes), "r"(bar) : "memory");
}
__device__ __forceinline__ void bulk_st(void* dst, uint32_t src, uint32_t bytes) {
    asm volatile("cp.async.bulk.global.shared::cta.bulk_group [%0], [%1], %2;" ::"l"(dst), "r"(src), "r"(bytes) : "memory");
}
__device__ __forceinline__ void ring_ld(uint32_t sb, uint32_t slot8, int n) {
    mbar_expect_tx(sb + B_R2 + slot8, 8192);
    bulk_ld(sb + R1 + slot8 * 1024, (const char*)g_wepi + n * 8192, 8192, sb + B_R2 + slot8);
}

__device__ __forceinline__ void ring_half(uint32_t sb, uint32_t slot8, uint32_t hoff, const CUtensorMap* tm, int c1, int c2) {
    mbar_expect_tx(sb + B_R1 + slot8, 8192);
    tma3(sb + slot8 * 2048 + hoff, tm, 0, c1, c2, sb + B_R1 + slot8);
}
__device__ __forceinline__ void ring_full(uint32_t sb, uint32_t slot8, const CUtensorMap* tm, int c1, int c2) {
    mbar_expect_tx(sb + B_R1 + slot8, 16384);
    mbar_arrive(sb + B_R1 + slot8);
    tma3(sb + slot8 * 2048, tm, 0, c1, c2, sb + B_R1 + slot8);
}
__device__ __forceinline__ void cta_done(int mode) {
    if (mode == 0 && atomicAdd(&g_sync[4], 1) == NCTA + 1) {
#pragma unroll
        for (int i = 0; i < 5; i++) g_sync[i] = 0;
    }
}

__device__ __forceinline__ void fold_cta(const Maps& mp, uint32_t sb, int mode) {
    constexpr uint32_t F_FULL = MISC, F_EMPTY = MISC + 32, F_T1 = MISC + 64, STG = 49152, FOUT = 3 * STG;
    const int tid = threadIdx.x, f = blockIdx.x - NCTA;
    if (mode == 2) return;
    if (tid == 0) {
        for (int i = 0; i < 3; i++) { mbar_init(sb + F_FULL + 8 * i, 1); mbar_init(sb + F_EMPTY + 8 * i, 2); }
        mbar_init(sb + F_T1, 2);
        asm volatile("fence.mbarrier_init.release.cluster;" ::: "memory");
        fence_async();
    }
    __syncthreads();
    const int wg = __shfl_sync(0xffffffffu, tid >> 7, 0);
    int st = 0, ph = 0;
    if (wg == 0) {
        if (tid == 0) {
#pragma unroll 1
            for (int it = 0; it < 96; it++) {
                const int p = it >> 3, kc = it & 7, job = p >> 2;
                if (it == 64) mbar_wait(sb + F_T1, 0);
                mbar_wait(sb + F_EMPTY + 8 * st, ph ^ 1);
                mbar_expect_tx(sb + F_FULL + 8 * st, STG);
                tma3(sb + st * STG, &mp.fa[job], 0, 256 * f + 128 * ((p >> 1) & 1), kc, sb + F_FULL + 8 * st);
                tma3(sb + st * STG + 16384, &mp.fb[job != 0], 0, 64 * kc + (job == 1 ? 512 : 0), 4 * (p & 1), sb + F_FULL + 8 * st);
                if (++st == 3) { st = 0; ph ^= 1; }
            }
        }
        return;
    }
    const int h = wg - 1, lane = tid & 31, w = (tid >> 5) & 3;
    const uint32_t sd = (sb & 0x3FFFF) >> 4;
    const bool el = (tid & 127) == 0;
#pragma unroll 1
    for (int p = 0; p < 12; p++) {
        float acc[128];
        fresh(acc);
#pragma unroll 1
        for (int kc = 0; kc < 8; kc++) {
            mbar_wait(sb + F_FULL + 8 * st, ph);
            wg_fence();
#pragma unroll
            for (int kk = 0; kk < 4; kk++)
                wgmma_ss_n256_tb1(acc, dsc(sd, st * STG + h * 8192 + kk * 32, 16), dsc(sd, st * STG + 16384 + kk * 2048, 8192), 1);
            wg_commit();
            wg_wait<0>();
            if (el) mbar_arrive(sb + F_EMPTY + 8 * st);
            if (++st == 3) { st = 0; ph ^= 1; }
        }
        pin(acc);
        const int job = p >> 2;
        if (el) {
            asm volatile("cp.async.bulk.wait_group 0;" ::: "memory");
            if (p == 4) { fence_async_g(); mbar_arrive(sb + F_T1); }
        }
        bar_sync(3 + h, 128);
        uint32_t r = 16 * w + (lane & 7) + ((lane >> 3) & 1) * 8;
        const float fs = job == 1 ? 0.5f : 1.f;
        if (job == 1) r = (r & ~31) | (((r >> 1) & 3) << 3) | (((r >> 3) & 3) << 1) | (r & 1);
        const uint32_t oa = sb + FOUT + h * 32768 + r * 128 + ((((lane >> 4) ^ r) & 7) << 4);
#pragma unroll
        for (int i = 0; i < 16; i++)
            stsm4((oa ^ ((i & 3) << 5)) + (i >> 2) * 8192, pack2(acc[8 * i] * fs, acc[8 * i + 1] * fs), pack2(acc[8 * i + 2] * fs, acc[8 * i + 3] * fs),
                  pack2(acc[8 * i + 4] * fs, acc[8 * i + 5] * fs), pack2(acc[8 * i + 6] * fs, acc[8 * i + 7] * fs));
        fence_async();
        bar_sync(3 + h, 128);
        if (el) {
            const int row0 = 256 * f + 128 * ((p >> 1) & 1) + 64 * h + (job == 1 ? 512 : 0);
            if (job == 0) tma3_store(&mp.fc, sb + FOUT + h * 32768, 0, row0, 4 * (p & 1));
            else {
#pragma unroll 1
                for (int i = 0; i < 16; i++)
                    bulk_st((char*)g_wepi + (row0 / 8 + 2 * (i & 3) + (p & 1)) * 8192 + (i >> 2) * 2048, sb + FOUT + h * 32768 + i * 2048, 2048);
            }
            asm volatile("cp.async.bulk.commit_group;" ::: "memory");
        }
    }
    if (el) {
        asm volatile("cp.async.bulk.wait_group 0;" ::: "memory");
        fence_async_g();
        if (mode == 0) flag_add(&g_sync[3]);
    }
    bar_sync(2, 256);
    if (tid == 128) cta_done(mode);
}

__global__ void __launch_bounds__(384, 1) main_kernel(const __grid_constant__ Maps mp, const bf16* __restrict__ x, const bf16* __restrict__ dw, const bf16* wup, const int mode) {
    extern __shared__ __align__(1024) uint8_t smem[];
    const uint32_t sb = smem_u32(smem);
    const int tid = threadIdx.x;
    PE();
    if (blockIdx.x >= NCTA) { fold_cta(mp, sb, mode); return; }
    const int b = blockIdx.x / TPB, ti = blockIdx.x % TPB;
    const int piece = blockIdx.x & 127;
    const int wg = __shfl_sync(0xffffffffu, tid >> 7, 0);
    const int lane = tid & 31, w = (tid >> 5) & 3;
    const bool w0 = __shfl_sync(0xffffffffu, w, 0) == 0;
    const uint32_t sd = (sb & 0x3FFFF) >> 4;
    const uint32_t adA = sd + (AT >> 4) + (1u << 16);
    const uint32_t bd0 = sd;
    const uint32_t bd2k = bd0 + ((2048u >> 4) << 16);
    const bool el = (tid & 127) == 0;
    const uint32_t lrow = 16 * w + (lane & 7) + ((lane >> 3) & 1) * 8;
    const uint32_t loff = lrow * 128 + ((((lane >> 4) ^ lrow) & 7) << 4);
    const int r0 = 16 * w + (lane >> 2);

    if (wg == 0) {
        asm volatile("setmaxnreg.inc.sync.aligned.u32 184;");
        uint32_t q[112];
        PG(206);
        if (tid == 0) {
            mbar_init(sb + B_MK, 1);
            for (int i = 0; i < 9; i++) mbar_init(sb + B_R1 + 8 * i, 2);
            for (int i = 0; i < 5; i++) asm volatile("st.shared.u32 [%0], 0;" ::"r"(sb + CNT + 4 * i) : "memory");
        } else if (tid == 32) {
            mbar_init(sb + B_LN, 1); mbar_init(sb + B_MQ, 1);
            mbar_init(sb + B_H1, 2); mbar_init(sb + B_H2, 1); mbar_init(sb + B_H3, 2);
            for (int i = 0; i < 3; i++) { mbar_init(sb + B_KV + 8 * i, 2); mbar_init(sb + B_P + 8 * i, 4); mbar_init(sb + B_GO + 8 * i, 4); }
            mbar_init(sb + B_UC, 1); mbar_init(sb + B_UC + 8, 1); mbar_init(sb + B_X, 8);
        } else if (tid == 64) {
            for (int i = 0; i < 20; i++) mbar_init(sb + B_R2 + 8 * i, 1);
        } else if (tid == 96) {
            for (int i = 0; i < 20; i++) mbar_init(sb + B_E2 + 8 * i, 4);
        }
        if (lane == 0) {
            asm volatile("fence.mbarrier_init.release.cluster;" ::: "memory");
            fence_async();
        }
        PG(207);
        __syncwarp();
        if (SU != 2) asm volatile("bar.arrive 5, 384;" ::: "memory");
        if (tid == 0) {
            mbar_expect_tx(sb + B_MK, 65536 + 32768);
            tma3(sb + 16384, &mp.wq, 0, 64 * (piece >> 4), 0, sb + B_MK);
            tma3(sb + 81920, &mp.wk, 0, 32 * (piece & 15), 0, sb + B_MK);
            for (int i = 0; i < 14; i++) mbar_arrive(sb + B_R1 + 8 * (i >> 1));
            if (mode != 1) {
                ring_full(sb, 56, &mp.wup8, 0, 8);
                ring_full(sb, 64, &mp.wup8, 16, 8);
                ring_full(sb, 0, &mp.wup8, 32, 8);
            }
        }
        PG(208);
        bar_sync(1, 128);
        if (SU == 2) asm volatile("bar.arrive 5, 384;" ::: "memory");
        PT(0);
        PG(200);
        {
            float mq[16];
            fresh(mq);
            mbar_wait(sb + B_MK, 0);
            PT(1);
            if (tid == 32) l2_prefetch((const char*)wup + piece * 8192, 8192);
            wg_fence();
#pragma unroll 1
            for (int c = 0; c < 8; c++)
#pragma unroll
                for (int kk = 0; kk < 4; kk++)
                    wgmma_ss_n32_tb0(mq, dsc(sd, 16384 + c * 8192 + kk * 32, 16), dsc(sd, 81920 + c * 4096 + kk * 32, 16), 1);
            wg_commit();
            wg_wait<0>();
            if (mode != 1 && w0 && elect1()) {
#pragma unroll 1
                for (int i = 1; i < 7; i++) ring_full(sb, 8 * i, &mp.wup8, 32 + 16 * i, 8);
            }
            pin(mq);
            uint32_t* c = reinterpret_cast<uint32_t*>(g_mqk + (64 * (piece >> 4) + r0) * D_ + 32 * (piece & 15) + 2 * (lane & 3));
#pragma unroll
            for (int n = 0; n < 4; n++) { c[4 * n] = pack2(mq[4 * n], mq[4 * n + 1]); c[4 * n + 4 * D_] = pack2(mq[4 * n + 2], mq[4 * n + 3]); }
            fence_async_g();
            bar_sync(1, 128);
            if (el) {
                if (mode == 0) flag_add(&g_sync[2]);
                if (mode == 0) flag_wait(&g_sync[2], NCTA);
                mbar_arrive(sb + B_MQ);
                PG(203);
                PT(12);
                mbar_wait(sb + B_LN, 0);
#pragma unroll 1
                for (int c = 0; c < 8; c++) {
                    tma4_store(&mp.xas, sb + AT + c * 8192, 0, 62 * ti, c, b);
                    const unsigned t0 = (unsigned)clock();
                    while (c < 7 && (unsigned)clock() - t0 < XS_GAP) __nanosleep(20);
                }
                asm volatile("cp.async.bulk.commit_group;" ::: "memory");
                if (mode == 1) asm volatile("cp.async.bulk.wait_group 0;" ::: "memory");
            }
            PT(13);
            if (mode == 1) return;
        }
        mbar_wait(sb + B_H1, 0);
        PT(2);
        uint32_t slot8 = 24, par = 0, prev8 = 0, prev2 = 0;
        auto adv = [&]() { prev2 = prev8; prev8 = slot8; slot8 += 8; if (slot8 == 72) { slot8 = 0; par ^= 1; } };
        {
            float acc[128];
            fresh(acc);
            auto step = [&](int i) {
                const uint32_t aa = adA + (i >> 1) * 512 + (i & 1) * 4, bb = bd0 + ((4096u >> 4) << 16) + slot8 * 128;
                wg_fence();
                wgmma_ss_n256_tb1(acc, mkd(aa), mkd(bb), 1);
                wgmma_ss_n256_tb1(acc, mkd(aa + 2), mkd(bb + 128), 1);
                wg_commit();
                wg_wait<1 + LAGA>();
            };
#pragma unroll 1
            for (int i = 0; i < 8 + LAGA; i++) {
                mbar_wait(sb + B_R1 + slot8, par);
                step(i);
                if (i > LAGA && w0 && elect1()) ring_full(sb, LAGA ? prev2 : prev8, &mp.mqa4, 32 * (i - LAGA) + 256, 4);
                adv();
            }
#pragma unroll 1
            for (int i = 8 + LAGA; i < 16; i++) {
                mbar_wait(sb + B_R1 + slot8, par);
                if (i == 15 && el) mbar_arrive(sb + B_H2);
                step(i);
                if (w0 && elect1()) ring_full(sb, LAGA ? prev2 : prev8, &mp.wup8, 16 * (i - LAGA) - 128, 0);
                adv();
            }
            if (LAGA) {
                wg_wait<1>();
                if (w0 && elect1()) ring_full(sb, prev2, &mp.wup8, 112, 0);
            }
            wg_wait<0>();
            if (w0 && elect1()) ring_full(sb, prev8, &mp.wup8, 128, 0);
            pin(acc);
            PT(3);
#pragma unroll
            for (int kk = 0; kk < 4; kk++)
                stsm4((sb + QS + loff) ^ (kk << 5), pack2(acc[96 + 8 * kk], acc[97 + 8 * kk]), pack2(acc[98 + 8 * kk], acc[99 + 8 * kk]),
                      pack2(acc[100 + 8 * kk], acc[101 + 8 * kk]), pack2(acc[102 + 8 * kk], acc[103 + 8 * kk]));
            fence_async();
#pragma unroll
            for (int i = 47; i >= 0; i--) q[64 + i] = pack2v(acc[2 * i], acc[2 * i + 1]);
        }
        if (el) {
            asm volatile("cp.async.bulk.wait_group 0;" ::: "memory");
            if (mode == 0) {
                fence_async_g();
                flag_add(&g_sync[b]);
                flag_wait(&g_sync[b], TPB);
            }
        }
        __syncwarp();
        mbar_wait(sb + B_H3, 0);
        PT(4);
        slot8 = 48; par = 1;
#pragma unroll
        for (int half = 0; half < 2; half++) {
            float acc[64];
            fresh(acc);
            auto step = [&](int m) {
                const uint32_t aa = adA + m * 512, bb = bd0 + ((8192u >> 4) << 16) + slot8 * 128;
                mbar_wait(sb + B_R1 + slot8, par);
                wg_fence();
#pragma unroll
                for (int kk = 0; kk < 4; kk++) wgmma_ss_n128_tb1(acc, mkd(aa + 2 * kk), mkd(bb + 128 * kk), 1);
                wg_commit();
                wg_wait<1 + LAGB>();
            };
#pragma unroll 1
            for (int m = 0; m < 8; m++) {
                step(m);
                if (m > LAGB && w0 && elect1()) {
                    if (half == 0) ring_full(sb, LAGB ? prev2 : prev8, &mp.mqb2, 64 * (m - LAGB), 2);
                    else if (m < 4 + LAGB) tma4(sb + (LAGB ? prev2 : prev8) * 2048, &mp.xa2, 0, 0, 2 * (m - LAGB), b, sb + B_KV + 8);
                }
                adv();
            }
            if (LAGB && half == 0) {
                wg_wait<1>();
                if (w0 && elect1()) ring_full(sb, prev2, &mp.mqb2, 448, 2);
            }
            wg_wait<0>();
            if (w0 && elect1()) {
                if (half == 0) {
                    mbar_expect_tx(sb + B_KV + 8, 65536);
                    for (int i = 0; i < 3; i++) mbar_arrive(sb + B_KV + 8 * i);
                    tma4(sb + prev8 * 2048, &mp.xa2, 0, 0, 0, b, sb + B_KV + 8);
                } else {
                    mbar_expect_tx(sb + B_KV + 16, 65536);
                    tma4(sb + R2, &mp.xa, 0, 64, 0, b, sb + B_KV + 16);
                    mbar_expect_tx(sb + B_KV, 65536);
                    tma4(sb + R0, &mp.xa, 0, 128, 0, b, sb + B_KV);
                }
            }
            pin(acc);
#pragma unroll
            for (int i = 31; i >= 0; i--) q[32 * half + i] = pack2v(acc[2 * i], acc[2 * i + 1]);
        }
        bar_sync(1, 128);
        PT(5);

        const float CS = 0.04419417382415922f * 1.4426950408889634f;
        float m0 = -INFINITY, m1 = -INFINITY, l0 = 0.f, l1 = 0.f;
        int s = 0, sn = 1, ph = 0;
        float S[32];
        const bool l0w = lane == 0, q0 = (lane & 3) == 0;
#pragma unroll 1
        for (int j = -1;; j++) {
            if (j >= 0) {
                PL(j, 1);
                if (j == NKV - 1) {
#pragma unroll
                    for (int i = (T_ - 64 * (NKV - 1)) / 2; i < 32; i++) asm volatile("mov.b32 %0, 0xff800000;" : "=f"(S[i]));
                }
                const bool kv = mbar_test(sb + B_KV + sn * 8, ph);
                const uint32_t pb = sb + R3 + (s == 0 ? 2 : s - 1) * 8192;
                float a0 = 0.f, a1 = 0.f, sc0 = 1.f, sc1 = 1.f;
                auto expo = [&]() {
                    const float n0 = -m0 * CS, n1 = -m1 * CS;
                    a0 = 0.f; a1 = 0.f;
#pragma unroll
                    for (int kk = 0; kk < 4; kk++) {
                        float p[8];
#pragma unroll
                        for (int e = 0; e < 8; e++) p[e] = ex2(fmaf(S[8 * kk + e], CS, (e & 2) ? n1 : n0));
                        a0 += (p[0] + p[1]) + (p[4] + p[5]);
                        a1 += (p[2] + p[3]) + (p[6] + p[7]);
                        stsm4((pb + loff) ^ (kk << 5), pack2(p[0], p[1]), pack2(p[2], p[3]), pack2(p[4], p[5]), pack2(p[6], p[7]));
                    }
                };
                if (j > 0 || !SK0) expo();
                if ((SK0 && j == 0) || __any_sync(0xffffffffu, !(a0 <= LAZY) || !(a1 <= LAZY))) {
                    float x0 = m0, x1 = m1;
#pragma unroll
                    for (int n = 0; n < 8; n++) { x0 = fmaxf(x0, fmaxf(S[4 * n], S[4 * n + 1])); x1 = fmaxf(x1, fmaxf(S[4 * n + 2], S[4 * n + 3])); }
                    x0 = fmaxf(x0, __shfl_xor_sync(0xffffffffu, x0, 1));
                    x1 = fmaxf(x1, __shfl_xor_sync(0xffffffffu, x1, 1));
                    x0 = fmaxf(x0, __shfl_xor_sync(0xffffffffu, x0, 2));
                    x1 = fmaxf(x1, __shfl_xor_sync(0xffffffffu, x1, 2));
                    sc0 = ex2((m0 - x0) * CS); sc1 = ex2((m1 - x1) * CS);
                    m0 = x0; m1 = x1;
                    expo();
                }
                if (q0) { sts_f32(sb + SCL + s * 256 + r0 * 4, sc0); sts_f32(sb + SCL + s * 256 + r0 * 4 + 32, sc1); }
                __syncwarp();
                if (l0w) mbar_arrive(sb + B_P + s * 8);
                l0 = fmaf(l0, sc0, a0); l1 = fmaf(l1, sc1, a1);
                PL(j, 2);
                if (j == NKV - 1) break;
                if (!kv) mbar_wait(sb + B_KV + sn * 8, ph);
            } else {
                mbar_wait(sb + B_KV + 8, 0);
            }
            float Sn[32];
            const uint32_t kd = sd + sn * 4096;
            wg_fence();
#pragma unroll
            for (int kk = 0; kk < 28; kk++) {
                wgmma_rs_n64_tb0(Sn, q[4 * kk], q[4 * kk + 1], q[4 * kk + 2], q[4 * kk + 3], dsc(kd, (kk >> 2) * 8192 + (kk & 3) * 32, 16), kk > 0);
                if (kk == FENCE_AT) { fence_async(); __syncwarp(); }
                if (kk == GO_AT) { PL(j, 3); if (j >= 0 && l0w) mbar_arrive(sb + B_GO + s * 8); }
            }
#pragma unroll
            for (int kk = 0; kk < 4; kk++)
                wgmma_ss_n64_tb0(Sn, dsc(sd, QS + kk * 32, 16), dsc(kd, 7 * 8192 + kk * 32, 16), 1);
            wg_commit();
            PL(j, 0);
            wg_wait<0>();
            pin(Sn);
#pragma unroll
            for (int i = 0; i < 32; i++) S[i] = Sn[i];
            s = sn;
            if (++sn == 3) sn = 0;
            if (sn == 1) ph ^= 1;
        }
        l0 += __shfl_xor_sync(0xffffffffu, l0, 1); l1 += __shfl_xor_sync(0xffffffffu, l1, 1);
        l0 += __shfl_xor_sync(0xffffffffu, l0, 2); l1 += __shfl_xor_sync(0xffffffffu, l1, 2);
        if (q0) { sts_f32(sb + LINV + r0 * 4, rcp(l0)); sts_f32(sb + LINV + r0 * 4 + 32, rcp(l1)); }
        fence_async();
        __syncwarp();
        if (l0w) {
            mbar_arrive(sb + B_GO + s * 8);
            uint32_t slot8 = 8 * w, par = 0;
#pragma unroll 1
            for (int n = 20 + w; n < 136; n += 4) {
                mbar_wait(sb + B_E2 + slot8, par);
                if (n < 128) ring_ld(sb, slot8, n);
                else {
                    mbar_expect_tx(sb + B_X, 8192);
                    tma4(sb + R1 + slot8 * 1024, &mp.x, 0, 62 * ti, n - 128, b, sb + B_X);
                }
                slot8 += 32;
                if (slot8 >= 160) { slot8 -= 160; par ^= 1; }
            }
        }
        PDUMP();
    } else {
        asm volatile("setmaxnreg.dec.sync.aligned.u32 160;");
        const int h = wg - 1;
        uint32_t v[4][8], v2[4][8];
        if (SU != 0) bar_sync(5, 384);
        PG(206);
#pragma unroll
        for (int i = 0; i < 8; i++) {
            const int t = 62 * ti - 1 + 32 * (i >> 2) + 16 * h + 4 * w + (i & 3);
            const uint4* p = reinterpret_cast<const uint4*>(x + ((size_t)b * T_ + t) * D_) + lane;
            uint32_t* d = i < 4 ? v[i & 3] : v2[i & 3];
#pragma unroll
            for (int c = 0; c < 2; c++)
                asm volatile("{\n.reg .pred p;\nsetp.lt.u32 p, %5, %6;\nmov.b32 %0, 0;\nmov.b32 %1, 0;\nmov.b32 %2, 0;\nmov.b32 %3, 0;\n"
                             "@p ld.global.nc.v4.u32 {%0, %1, %2, %3}, [%4];\n}\n"
                             : "=r"(d[4 * c]), "=r"(d[4 * c + 1]), "=r"(d[4 * c + 2]), "=r"(d[4 * c + 3]) : "l"(p + 32 * c), "r"(t), "n"(T_));
        }
#pragma unroll 1
        for (int bt = 0; bt < 2; bt++) {
            PT(bt ? 13 : 0);
            float a[8];
            const uint32_t la = sb + AT + (lane >> 3) * 8192 + (32 * bt + 16 * h + 4 * w) * 128 + (((lane & 7) ^ ((w & 1) * 4)) << 4);
            const bool b4 = lane & 16, b3 = lane & 8, b2 = lane & 4;
#pragma unroll
            for (int r = 0; r < 4; r++) {
                float c[4] = {0.f, 0.f, 0.f, 0.f};
#pragma unroll
                for (int i = 0; i < 8; i += 2) hmma(c, v[r][i], v[r][i], v[r][i + 1], v[r][i + 1], v[r][i], v[r][i + 1]);
                a[4 + r] = (lane & 3) == (lane >> 3) ? (b2 ? c[1] : c[0]) : 0.f;
                if (r & 1) {
                    float e[4] = {0.f, 0.f, 0.f, 0.f};
#pragma unroll
                    for (int i = 0; i < 8; i += 2) hmma(e, v[r - 1][i], v[r][i], v[r - 1][i + 1], v[r][i + 1], 0x3f803f80u, 0x3f803f80u);
                    a[r - 1] = e[0]; a[r] = e[2];
                }
            }
            float k[4];
#pragma unroll
            for (int i = 0; i < 4; i++) {
                const int lo = (i & 1) + 4 * (i >> 1);
                k[i] = (b4 ? a[lo + 2] : a[lo]) + __shfl_xor_sync(0xffffffffu, b4 ? a[lo] : a[lo + 2], 16);
            }
            const float k0 = (b3 ? k[1] : k[0]) + __shfl_xor_sync(0xffffffffu, b3 ? k[0] : k[1], 8);
            const float k1 = (b3 ? k[3] : k[2]) + __shfl_xor_sync(0xffffffffu, b3 ? k[2] : k[3], 8);
            float z = (b2 ? k1 : k0) + __shfl_xor_sync(0xffffffffu, b2 ? k0 : k1, 4);
            z += __shfl_xor_sync(0xffffffffu, z, 2);
            z += __shfl_xor_sync(0xffffffffu, z, 1);
            const float zo = __shfl_xor_sync(0xffffffffu, z, 4);
            PG(204 + bt);
            const float mu = (b2 ? zo : z) * (0.25f / D_);
            float sd_ = bfr(bfr(fmaxf(fmaf(b2 ? z : zo, 1.f / D_, -mu * mu), 0.f)) + 1e-5f);
            asm("sqrt.approx.f32 %0, %0;" : "+f"(sd_));
            const float ri = rcp(bfr(sd_));
            const uint32_t w1 = pack2(mu, ri), w2 = pack2(ri - bhi(w1), ri - bhi(w1));
#pragma unroll
            for (int r = 0; r < 4; r++) {
                const uint32_t s1 = __shfl_sync(0xffffffffu, w1, 8 * r), rl = __shfl_sync(0xffffffffu, w2, 8 * r);
                const uint32_t m2 = __byte_perm(s1, 0, 0x1010), rh = __byte_perm(s1, 0, 0x3232);
#pragma unroll
                for (int i = 0; i < 8; i++) { const uint32_t d = bsub2(v[r][i], m2); v[r][i] = bfma2(d, rh, bmul2(d, rl)); }
                sts4((la ^ (r << 4)) + r * 128, v[r][0], v[r][1], v[r][2], v[r][3]);
                sts4((la ^ (r << 4)) + r * 128 + 32768, v[r][4], v[r][5], v[r][6], v[r][7]);
#pragma unroll
                for (int i = 0; i < 8; i++) v[r][i] = v2[r][i];
            }
        }
        fence_async();
        if (SU == 0) bar_sync(5, 384); else bar_sync(2, 256);
        if (tid == 128) mbar_arrive(sb + B_LN);
        PG(202);
        if (mode == 1) return;
        float acc[128];
#pragma unroll
        for (int pass = 0; pass < 2; pass++) {
            if (pass == 1) mbar_wait(sb + B_H2, 0);
            PT(1 + 3 * pass);
            fresh(acc);
            uint32_t slot8 = pass ? 8 : 56, par = 0, prev8 = 0;
            auto adv = [&]() { prev8 = slot8; slot8 += 8; if (slot8 == 72) { slot8 = 0; par ^= 1; } };
            auto step = [&](int kk) {
                wg_fence();
                wgmma_ss_n256_tb1(acc, mkd(adA + (kk >> 2) * 512 + (kk & 3) * 2), mkd(bd2k + h * 512 + slot8 * 128), 1);
                wg_commit();
                wg_wait<1>();
            };
#pragma unroll 1
            for (int kk = 0; kk < 24; kk++) {
                mbar_wait(sb + B_R1 + slot8, par);
                step(kk);
                if (kk > 0 && w0 && elect1()) ring_half(sb, prev8, h * 8192, &mp.wup4, 16 * kk + 128, (pass ? 0 : 8) + 4 * h);
                adv();
            }
            if (pass == 0 && w0) mbar_wait(sb + B_MQ, 0);
#pragma unroll 1
            for (int kk = 24; kk < 32; kk++) {
                mbar_wait(sb + B_R1 + slot8, par);
                if (kk == 31 && el) mbar_arrive(sb + (pass ? B_H3 : B_H1));
                step(kk);
                if (w0 && elect1()) ring_half(sb, prev8, h * 8192, pass ? &mp.mqb1 : &mp.mqa2, (pass ? 64 : 32) * (kk - 24), pass ? h : 4 + 2 * h);
                adv();
            }
            wg_wait<0>();
            if (w0 && elect1()) ring_half(sb, prev8, h * 8192, pass ? &mp.mqb1 : &mp.mqa2, pass ? 0 : 256, pass ? 2 + h : 4 + 2 * h);
            pin(acc);
            PT(2 + 3 * pass);
            bf16* ucp = g_uc + ((size_t)blockIdx.x * 128 + r0) * D_ + 256 * h + 8 * (lane & 3);
            if (pass == 0) {
                float s0 = 0.f, s1 = 0.f, v0 = 0.f, v1 = 0.f;
#pragma unroll
                for (int n = 0; n < 32; n++) {
#pragma unroll
                    for (int e = 0; e < 4; e++) acc[4 * n + e] = gelu2(acc[4 * n + e]);
                    s0 += acc[4 * n] + acc[4 * n + 1]; s1 += acc[4 * n + 2] + acc[4 * n + 3];
                    v0 = fmaf(acc[4 * n], acc[4 * n], v0); v0 = fmaf(acc[4 * n + 1], acc[4 * n + 1], v0);
                    v1 = fmaf(acc[4 * n + 2], acc[4 * n + 2], v1); v1 = fmaf(acc[4 * n + 3], acc[4 * n + 3], v1);
                }
#pragma unroll
                for (int o = 1; o < 4; o <<= 1) {
                    s0 += __shfl_xor_sync(0xffffffffu, s0, o); s1 += __shfl_xor_sync(0xffffffffu, s1, o);
                    v0 += __shfl_xor_sync(0xffffffffu, v0, o); v1 += __shfl_xor_sync(0xffffffffu, v1, o);
                }
                if ((lane & 3) == 0) {
                    uint32_t a = sb + STAT + h * 512 + r0 * 8;
                    sts_f32(a, s0); sts_f32(a + 4, v0); sts_f32(a + 64, s1); sts_f32(a + 68, v1);
                }
                bar_sync(2, 256);
                {
                    uint32_t a = sb + STAT + (h ^ 1) * 512 + r0 * 8;
                    s0 = (s0 + lds_f32(a)) * (1.f / 512.f); v0 = (v0 + lds_f32(a + 4)) * (1.f / 512.f);
                    s1 = (s1 + lds_f32(a + 64)) * (1.f / 512.f); v1 = (v1 + lds_f32(a + 68)) * (1.f / 512.f);
                }
                v0 = rsqrtf(fmaxf(fmaf(-s0, s0, v0), 0.f) + 4e-5f); v1 = rsqrtf(fmaxf(fmaf(-s1, s1, v1), 0.f) + 4e-5f);
                s0 = -s0 * v0; s1 = -s1 * v1;
#pragma unroll
                for (int m = 0; m < 8; m++) {
                    const float* a_ = acc + 16 * m;
                    stg4(ucp + 64 * D_ + 32 * m, pack2(fmaf(a_[0], v0, s0), fmaf(a_[1], v0, s0)), pack2(fmaf(a_[4], v0, s0), fmaf(a_[5], v0, s0)),
                         pack2(fmaf(a_[8], v0, s0), fmaf(a_[9], v0, s0)), pack2(fmaf(a_[12], v0, s0), fmaf(a_[13], v0, s0)));
                    stg4(ucp + 72 * D_ + 32 * m, pack2(fmaf(a_[2], v1, s1), fmaf(a_[3], v1, s1)), pack2(fmaf(a_[6], v1, s1), fmaf(a_[7], v1, s1)),
                         pack2(fmaf(a_[10], v1, s1), fmaf(a_[11], v1, s1)), pack2(fmaf(a_[14], v1, s1), fmaf(a_[15], v1, s1)));
                }
            } else {
#pragma unroll
                for (int m = 0; m < 8; m++) {
                    const float* a_ = acc + 16 * m;
                    stg4(ucp + 32 * m, pack2(a_[0], a_[1]), pack2(a_[4], a_[5]), pack2(a_[8], a_[9]), pack2(a_[12], a_[13]));
                    stg4(ucp + 8 * D_ + 32 * m, pack2(a_[2], a_[3]), pack2(a_[6], a_[7]), pack2(a_[10], a_[11]), pack2(a_[14], a_[15]));
                }
                bar_sync(3 + h, 128);
            }
            PT(3 + 3 * pass);
        }
        int s = 1, ph = 0;
        uint32_t* cp = reinterpret_cast<uint32_t*>(g_uc + (size_t)blockIdx.x * 128 * D_) + (tid - 128);
        const uint32_t* dp = reinterpret_cast<const uint32_t*>(dw) + (((tid - 128) & ~15) | ((lane & 3) << 2) | ((lane >> 2) & 3));
        const uint32_t d0 = ldg_v(dp), d1 = ldg_v(dp + D_ / 2), d2 = ldg_v(dp + D_);
        uint32_t ga = ldg_cg(cp + 64 * (D_ / 2)), gb = ldg_cg(cp + 65 * (D_ / 2));
        fresh(acc);
#pragma unroll 1
        for (int j = 0; j < NKV; j++) {
            cp += D_ / 2;
            uint32_t gc = 0, uu = 0;
            if (j < NKV - 1) { gc = ldg_cg(cp + 65 * (D_ / 2)); uu = ldg_cg(cp); }
            mbar_wait(sb + B_P + s * 8, ph);
            PL(j, 0);
            if (j > 0) {
                const float sc0 = lds_f32(sb + SCL + s * 256 + r0 * 4), sc1 = lds_f32(sb + SCL + s * 256 + r0 * 4 + 32);
                if (__any_sync(0xffffffffu, sc0 != 1.f || sc1 != 1.f)) {
#pragma unroll
                    for (int n = 0; n < 32; n++) { acc[4 * n] *= sc0; acc[4 * n + 1] *= sc0; acc[4 * n + 2] *= sc1; acc[4 * n + 3] *= sc1; }
                }
            }
            mbar_wait(sb + B_GO + s * 8, ph);
            PL(j, 1);
            const uint32_t vd = sd + s * 4096 + h * 2048, pd = sd + (s == 0 ? 2 : s - 1) * 512;
            pin(acc);
            wg_fence();
#pragma unroll
            for (int kk = 0; kk < 2; kk++) wgmma_ss_n256_tb1(acc, dsc(pd, R3 + kk * 32, 16), dsc(vd, kk * 2048, 8192), 1);
            if (!TRIM || j < NKV - 1) {
#pragma unroll
                for (int kk = 2; kk < 4; kk++) wgmma_ss_n256_tb1(acc, dsc(pd, R3 + kk * 32, 16), dsc(vd, kk * 2048, 8192), 1);
            }
            wg_commit();
            wg_wait<0>();
            pin(acc);
            PL(j, 2);
            if (w0 && elect1()) {
                if (j + 3 < NKV) {
                    mbar_expect_tx(sb + B_KV + s * 8, 32768);
                    tma4(sb + s * 65536 + h * 32768, &mp.xa4, 0, 64 * (j + 3), 4 * h, b, sb + B_KV + s * 8);
                } else if (j < NKV - 1) {
                    const int n0 = (j == NKV - 3 ? 0 : 8) + 4 * h;
#pragma unroll 1
                    for (int n = n0; n < n0 + 4; n++) ring_ld(sb, n * 8, n);
                }
                if (j == NKV - 5 && mode == 0) flag_wait(&g_sync[3], 4);
                if (j >= XPF && j < XPF + 4) {
                    const int t0 = 62 * ti + 32 * h + 8 * (j - XPF), nr = min(8, T_ - t0);
                    if (nr > 0) l2_prefetch(x + ((size_t)b * T_ + t0) * D_, nr * 1024);
                }
                if (KPF && h == 0 && 64 * (j + KPF) + ti < T_) l2_prefetch(g_xa + ((size_t)b * (T_ + 8) + 1 + 64 * (j + KPF) + ti) * D_, 1024);
            }
            uu = pack2(gelu2(blo(uu)), gelu2(bhi(uu)));
            if (j < NKV - 1) asm volatile("st.global.u32 [%0], %1;" ::"l"(cp), "r"(bmul2(uu, bfma2(gc, d2, bfma2(gb, d1, bmul2(ga, d0))))) : "memory");
            ga = gb; gb = gc;
            if (++s == 3) s = 0;
            if (s == 1) ph ^= 1;
        }
        {
            const float i0 = lds_f32(sb + LINV + r0 * 4), i1 = lds_f32(sb + LINV + r0 * 4 + 32);
#pragma unroll
            for (int p = 0; p < 16; p++)
                stsm4(((sb + R0 + h * 32768 + loff) ^ ((p & 3) << 5)) + (p >> 2) * 8192,
                      pack2(acc[8 * p] * i0, acc[8 * p + 1] * i0), pack2(acc[8 * p + 2] * i1, acc[8 * p + 3] * i1),
                      pack2(acc[8 * p + 4] * i0, acc[8 * p + 5] * i0), pack2(acc[8 * p + 6] * i1, acc[8 * p + 7] * i1));
        }
        fence_async();
        fence_async_g();
        bar_sync(2, 256);
        if (lane == 0 && w < 2) ring_ld(sb, 128 + 16 * w + 8 * h, 16 + 2 * w + h);
        PT(7);
        fresh(acc);
        {
            uint32_t slot8 = 8 * h, par = 0, prev8 = 0;
#pragma unroll 1
            for (int kk = 0; kk < 64; kk++) {
                if (kk == 32 || kk == 48) mbar_wait(sb + B_UC + (kk >> 1 & 8), 0);
                mbar_wait(sb + B_R2 + slot8, par);
                wg_fence();
                wgmma_ss_n256_tb1(acc, mkd(sd + (1u << 16) + (R0 >> 4) + (kk >> 2 & 7) * 512 + (kk & 3) * 2), mkd(bd2k + (R1 >> 4) + slot8 * 64), 1);
                wg_commit();
                wg_wait<1>();
                if (kk > 0 && lane == 0) mbar_arrive(sb + B_E2 + prev8);
                if ((kk == 16 || kk == 32) && w0 && elect1() && (atom_inc_s(sb + CNT + 12 + (kk >> 3 & 4)) & 1)) {
                    mbar_expect_tx(sb + B_UC + (kk >> 2 & 8), 32768);
                    tma3(sb + R0 + (kk & 32) * 1024, &mp.uc, 0, 128 * blockIdx.x, kk >> 3 & 4, sb + B_UC + (kk >> 2 & 8));
                }
                prev8 = slot8;
                slot8 += 16;
                if (slot8 >= 160) { slot8 -= 160; par ^= 1; }
            }
        }
        wg_wait<0>();
        pin(acc);
        PT(8);
        mbar_wait(sb + B_X, 0);
        PT(9);
        {
            const uint32_t sr = (lrow + 63) & 63;
            const uint32_t xoff = sr * 128 + ((((lane >> 4) ^ sr) & 7) << 4);
#pragma unroll
            for (int p = 0; p < 16; p++) {
                const uint32_t a = ((sb + R2 + h * 32768 + xoff) ^ ((p & 3) << 5)) + (p >> 2) * 8192;
                uint32_t xv[4];
                ldsm4(a, xv);
#pragma unroll
                for (int e = 0; e < 4; e++)
                    xv[e] = pack2(acc[8 * p + 2 * e] + __uint_as_float(xv[e] << 16), acc[8 * p + 2 * e + 1] + __uint_as_float(xv[e] & 0xffff0000u));
                stsm4(a, xv[0], xv[1], xv[2], xv[3]);
                if (CHS ? (p & 3) == 3 : p == 15) {
                    fence_async();
                    bar_sync(3 + h, 128);
                    if (el)
                        for (int c = CHS ? p >> 2 : 0; c <= (p >> 2); c++) tma4_store(&mp.out, sb + R2 + (4 * h + c) * 8192, 0, 62 * ti, 4 * h + c, b);
                }
            }
        }
        if (el) {
            asm volatile("cp.async.bulk.commit_group;" ::: "memory");
            PT(10);
            if (h == 0) cta_done(mode);
            asm volatile("cp.async.bulk.wait_group.read 0;" ::: "memory");
        }
        PT(11);
        PG(201);
        PDUMP();
    }
}

typedef CUresult (*PFN_enc)(CUtensorMap*, CUtensorMapDataType, cuuint32_t, void*, const cuuint64_t*, const cuuint64_t*,
                            const cuuint32_t*, const cuuint32_t*, CUtensorMapInterleave, CUtensorMapSwizzle,
                            CUtensorMapL2promotion, CUtensorMapFloatOOBfill);

static void enc(PFN_enc f, CUtensorMap* m, void* base, int rank, const cuuint64_t* dims, const cuuint64_t* strides, const cuuint32_t* box) {
    cuuint32_t es[5] = {1, 1, 1, 1, 1};
    f(m, CU_TENSOR_MAP_DATA_TYPE_BFLOAT16, rank, base, dims, strides, box, es, CU_TENSOR_MAP_INTERLEAVE_NONE,
      CU_TENSOR_MAP_SWIZZLE_128B, CU_TENSOR_MAP_L2_PROMOTION_L2_256B, CU_TENSOR_MAP_FLOAT_OOB_FILL_NONE);
}
static void enc_act(PFN_enc f, CUtensorMap* m, void* base, int rows, int chunks, int trows = T_, int pitch = T_) {
    cuuint64_t dims[4] = {64, (cuuint64_t)trows, 8, (cuuint64_t)NB_};
    cuuint64_t st[3] = {1024, 128, (cuuint64_t)pitch * 1024};
    cuuint32_t box[4] = {64, (cuuint32_t)rows, (cuuint32_t)chunks, 1};
    enc(f, m, base, 4, dims, st, box);
}
static void enc_w(PFN_enc f, CUtensorMap* m, void* base, int krows, int ncols, int bk, int bc) {
    cuuint64_t dims[3] = {64, (cuuint64_t)krows, (cuuint64_t)(ncols / 64)};
    cuuint64_t st[2] = {(cuuint64_t)ncols * 2, 128};
    cuuint32_t box[3] = {64, (cuuint32_t)bk, (cuuint32_t)bc};
    enc(f, m, base, 3, dims, st, box);
}

extern "C" void kernel_launch(void* const* d_in, const int* in_sizes, int n_in, void* d_out, int out_size) {
    const bf16* x = (const bf16*)d_in[0];
    static PFN_enc fenc = nullptr;
    static void *p_xa, *p_mqk, *p_uc, *p_t1;
    static int fused = 0;
    if (!fenc) {
        void* fn = nullptr;
        cudaDriverEntryPointQueryResult qr;
        cudaGetDriverEntryPoint("cuTensorMapEncodeTiled", &fn, cudaEnableDefault, &qr);
        fenc = (PFN_enc)fn;
        cudaGetSymbolAddress(&p_xa, g_xa);
        cudaGetSymbolAddress(&p_mqk, g_mqk);
        cudaGetSymbolAddress(&p_uc, g_uc);
        cudaGetSymbolAddress(&p_t1, g_t1);
        cudaFuncSetAttribute(main_kernel, cudaFuncAttributeMaxDynamicSharedMemorySize, SMEM_BYTES);
        int dev = 0, sms = 0, occ = 0;
        cudaGetDevice(&dev);
        cudaDeviceGetAttribute(&sms, cudaDevAttrMultiProcessorCount, dev);
        cudaOccupancyMaxActiveBlocksPerMultiprocessor(&occ, main_kernel, 384, SMEM_BYTES);
        fused = sms * occ >= NCTA + 2;
    }
    Maps mp;
    enc_act(fenc, &mp.xa, (char*)p_xa + 1024, 64, 8, T_, T_ + 8);
    enc_act(fenc, &mp.xa2, (char*)p_xa + 1024, 64, 2, T_, T_ + 8);
    enc_act(fenc, &mp.xa4, (char*)p_xa + 1024, 64, 4, T_, T_ + 8);
    enc_act(fenc, &mp.xas, p_xa, 64, 1, T_ + 1, T_ + 8);
    enc_act(fenc, &mp.x, (void*)x, 64, 1);
    enc_act(fenc, &mp.out, d_out, 62, 1);
    enc_w(fenc, &mp.wup4, d_in[5], 512, 1024, 16, 4);
    enc_w(fenc, &mp.wup8, d_in[5], 512, 1024, 16, 8);
    enc_w(fenc, &mp.mqa2, p_mqk, 512, 512, 32, 2);
    enc_w(fenc, &mp.mqa4, p_mqk, 512, 512, 32, 4);
    enc_w(fenc, &mp.mqb1, p_mqk, 512, 512, 64, 1);
    enc_w(fenc, &mp.mqb2, p_mqk, 512, 512, 64, 2);
    enc_w(fenc, &mp.uc, p_uc, NCTA * 128, 512, 64, 4);
    enc_w(fenc, &mp.wq, d_in[1], 512, 512, 64, 8);
    enc_w(fenc, &mp.wk, d_in[2], 512, 512, 32, 8);
    enc_w(fenc, &mp.fa[0], d_in[3], 512, 512, 128, 1);
    enc_w(fenc, &mp.fa[1], d_in[7], 512, 512, 128, 1);
    enc_w(fenc, &mp.fa[2], p_t1, 512, 512, 128, 1);
    enc_w(fenc, &mp.fb[0], d_in[4], 512, 512, 64, 4);
    enc_w(fenc, &mp.fb[1], d_in[8], 1024, 512, 64, 4);
    enc_w(fenc, &mp.fc, p_t1, 512, 512, 64, 4);
    cudaStream_t st = cudaStreamPerThread;
    if (fused) {
        main_kernel<<<NCTA + 2, 384, SMEM_BYTES, st>>>(mp, x, (const bf16*)d_in[6], (const bf16*)d_in[5], 0);
    } else {
        main_kernel<<<NCTA + 2, 384, SMEM_BYTES, st>>>(mp, x, (const bf16*)d_in[6], (const bf16*)d_in[5], 1);
        main_kernel<<<NCTA + 2, 384, SMEM_BYTES, st>>>(mp, x, (const bf16*)d_in[6], (const bf16*)d_in[5], 2);
    }
}
```

```cpp
#include <cuda_runtime.h>
#include <cuda_bf16.h>
#include <cuda.h>
#include <stdint.h>

typedef __nv_bfloat16 bf16;

constexpr int T_ = 4000, D_ = 512, NB_ = 2;
constexpr int TPB = 65;
constexpr int NCTA = TPB * NB_;
constexpr int NKV = 63;

__device__ __align__(1024) bf16 g_xa[NB_ * (T_ + 8) * D_];
__device__ __align__(1024) bf16 g_mqk[D_ * D_];
__device__ __align__(1024) bf16 g_t1[D_ * D_];
__device__ __align__(1024) bf16 g_wepi[2 * D_ * D_];
__device__ __align__(1024) bf16 g_uc[NCTA * 128 * D_];
__device__ unsigned g_sync[8];

#define PT(i) do { if (el) asm volatile("st.shared.u32 [%0], %1;" ::"r"(sb + MISC + 2560), "r"((unsigned)clock())); } while (0)
#define PG(i)
#define PE()
#define PLM 15
#define PL(j, q) do { if ((PLM >> ((q) + (wg ? 4 : 0))) & 1) PT(0); } while (0)
#define PDUMP()

#define FENCE_AT 1
#define GO_AT 25
#define LAZY 4294967296.f
#define SU 2
#define XS_GAP 800
#define XPF 50
#define URAW 1
#define LAGA 0
#define LAGB 0
#define DPOS 1
#define KPF 0
#define XEF 0
#define SK0 0
#define TRIM 3
#define GO_LAST 20
#define PFW 1
constexpr uint32_t R0 = 0, R1 = 65536, R2 = 131072, R3 = 196608, QS = 221184, MISC = 229376;
constexpr uint32_t AT = 147456;
constexpr uint32_t SMEM_BYTES = 232448;
constexpr uint32_t B_R1 = MISC + 1856  , B_MK = MISC + 48, B_LN = MISC + 56, B_MQ = MISC + 64,
                   B_H1 = MISC + 88, B_H2 = MISC + 96, B_H3 = MISC + 104,
                   B_KV = MISC + 112, B_P = MISC + 136, B_GO = MISC + 160, B_UC = MISC + 184  ,
                   B_X = MISC + 200, CNT = MISC + 208  , SCL = MISC + 512  ,
                   LINV = MISC + 1280  , STAT = MISC + 512  ,
                   B_R2 = MISC + 1536  , B_E2 = MISC + 1696  ;

__device__ __forceinline__ uint32_t smem_u32(const void* p) { return (uint32_t)__cvta_generic_to_shared(p); }
__device__ __forceinline__ void wg_fence() { asm volatile("wgmma.fence.sync.aligned;" ::: "memory"); }
__device__ __forceinline__ void wg_commit() { asm volatile("wgmma.commit_group.sync.aligned;" ::: "memory"); }
template <int N> __device__ __forceinline__ void wg_wait() { asm volatile("wgmma.wait_group.sync.aligned %0;" ::"n"(N) : "memory"); }
__device__ __forceinline__ uint64_t dsc(uint32_t sd, uint32_t off, uint32_t lbo) {
    uint32_t lo = sd + (off >> 4) + ((lbo >> 4) << 16);
    uint64_t d;
    asm("mov.b64 %0, {%1, %2};" : "=l"(d) : "r"(lo), "r"((1024u >> 4) | (1u << 30)));
    return d;
}
__device__ __forceinline__ bool elect1() {
    uint32_t p;
    asm volatile("{\n.reg .pred p;\nelect.sync _|p, 0xffffffff;\nselp.u32 %0, 1, 0, p;\n}\n" : "=r"(p));
    return p != 0;
}
__device__ __forceinline__ void mbar_init(uint32_t bar, int cnt) { asm volatile("mbarrier.init.shared::cta.b64 [%0], %1;" ::"r"(bar), "r"(cnt) : "memory"); }
__device__ __forceinline__ void mbar_expect_tx(uint32_t bar, uint32_t bytes) { asm volatile("mbarrier.arrive.expect_tx.shared::cta.b64 _, [%0], %1;" ::"r"(bar), "r"(bytes) : "memory"); }
__device__ __forceinline__ void mbar_arrive(uint32_t bar) { asm volatile("mbarrier.arrive.shared::cta.b64 _, [%0];" ::"r"(bar) : "memory"); }
__device__ __forceinline__ void mbar_wait(uint32_t bar, uint32_t parity) {
    uint32_t ok;
#pragma unroll 1
    for (uint32_t it = 0;; ++it) {
        asm volatile("{\n.reg .pred p;\nmbarrier.try_wait.parity.shared::cta.b64 p, [%1], %2;\nselp.u32 %0, 1, 0, p;\n}\n" : "=r"(ok) : "r"(bar), "r"(parity) : "memory");
        if (ok) break;
        if (it > (1u << 20)) __trap();
    }
}
__device__ __forceinline__ bool mbar_test(uint32_t bar, uint32_t parity) {
    uint32_t ok;
    asm volatile("{\n.reg .pred p;\nmbarrier.test_wait.parity.shared::cta.b64 p, [%1], %2;\nselp.u32 %0, 1, 0, p;\n}\n" : "=r"(ok) : "r"(bar), "r"(parity) : "memory");
    return ok != 0;
}
__device__ __forceinline__ void fence_async() { asm volatile("fence.proxy.async.shared::cta;" ::: "memory"); }
__device__ __forceinline__ void fence_async_g() { asm volatile("fence.proxy.async.global;" ::: "memory"); }
__device__ __forceinline__ void bar_sync(int id, int n) { asm volatile("bar.sync %0, %1;" ::"r"(id), "r"(n) : "memory"); }
__device__ __forceinline__ void tma3(uint32_t dst, const CUtensorMap* tm, int c0, int c1, int c2, uint32_t bar) {
    asm volatile("cp.async.bulk.tensor.3d.shared::cluster.global.mbarrier::complete_tx::bytes [%0], [%1, {%3, %4, %5}], [%2];"
                 ::"r"(dst), "l"(tm), "r"(bar), "r"(c0), "r"(c1), "r"(c2) : "memory");
}
__device__ __forceinline__ void tma4(uint32_t dst, const CUtensorMap* tm, int c0, int c1, int c2, int c3, uint32_t bar) {
    asm volatile("cp.async.bulk.tensor.4d.shared::cluster.global.mbarrier::complete_tx::bytes [%0], [%1, {%3, %4, %5, %6}], [%2];"
                 ::"r"(dst), "l"(tm), "r"(bar), "r"(c0), "r"(c1), "r"(c2), "r"(c3) : "memory");
}
__device__ __forceinline__ void tma4_store(const CUtensorMap* tm, uint32_t src, int c0, int c1, int c2, int c3) {
    asm volatile("cp.async.bulk.tensor.4d.global.shared::cta.bulk_group [%0, {%2, %3, %4, %5}], [%1];"
                 ::"l"(tm), "r"(src), "r"(c0), "r"(c1), "r"(c2), "r"(c3) : "memory");
}
__device__ __forceinline__ void tma3_store(const CUtensorMap* tm, uint32_t src, int c0, int c1, int c2) {
    asm volatile("cp.async.bulk.tensor.3d.global.shared::cta.bulk_group [%0, {%2, %3, %4}], [%1];"
                 ::"l"(tm), "r"(src), "r"(c0), "r"(c1), "r"(c2) : "memory");
}
__device__ __forceinline__ void stsm4(uint32_t addr, uint32_t a, uint32_t b, uint32_t c, uint32_t d) {
    asm volatile("stmatrix.sync.aligned.m8n8.x4.shared.b16 [%0], {%1, %2, %3, %4};" ::"r"(addr), "r"(a), "r"(b), "r"(c), "r"(d) : "memory");
}
__device__ __forceinline__ void ldsm4(uint32_t addr, uint32_t (&r)[4]) {
    asm volatile("ldmatrix.sync.aligned.m8n8.x4.shared.b16 {%0, %1, %2, %3}, [%4];" : "=r"(r[0]), "=r"(r[1]), "=r"(r[2]), "=r"(r[3]) : "r"(addr) : "memory");
}
__device__ __forceinline__ void ldsm2(uint32_t addr, uint32_t (&r)[2]) {
    asm volatile("ldmatrix.sync.aligned.m8n8.x2.shared.b16 {%0, %1}, [%2];" : "=r"(r[0]), "=r"(r[1]) : "r"(addr) : "memory");
}
__device__ __forceinline__ void stg4(void* p, uint32_t a, uint32_t b, uint32_t c, uint32_t d) {
    asm volatile("st.global.v4.u32 [%0], {%1, %2, %3, %4};" ::"l"(p), "r"(a), "r"(b), "r"(c), "r"(d) : "memory");
}
__device__ __forceinline__ void hmma(float (&c)[4], uint32_t a0, uint32_t a1, uint32_t a2, uint32_t a3, uint32_t b0, uint32_t b1) {
    asm("mma.sync.aligned.m16n8k16.row.col.f32.bf16.bf16.f32 {%0, %1, %2, %3}, {%4, %5, %6, %7}, {%8, %9}, {%0, %1, %2, %3};"
        : "+f"(c[0]), "+f"(c[1]), "+f"(c[2]), "+f"(c[3]) : "r"(a0), "r"(a1), "r"(a2), "r"(a3), "r"(b0), "r"(b1));
}
__device__ __forceinline__ uint32_t pack2(float lo, float hi) {
    uint32_t r;
    asm("cvt.rn.bf16x2.f32 %0, %1, %2;" : "=r"(r) : "f"(hi), "f"(lo));
    return r;
}
__device__ __forceinline__ uint32_t pack2v(float lo, float hi) {
    uint32_t r;
    asm volatile("cvt.rn.bf16x2.f32 %0, %1, %2;" : "=r"(r) : "f"(hi), "f"(lo));
    return r;
}
__device__ __forceinline__ uint32_t bmul2(uint32_t a, uint32_t b) { uint32_t r; asm("mul.rn.bf16x2 %0, %1, %2;" : "=r"(r) : "r"(a), "r"(b)); return r; }
__device__ __forceinline__ uint32_t bfma2(uint32_t a, uint32_t b, uint32_t c) { uint32_t r; asm("fma.rn.bf16x2 %0, %1, %2, %3;" : "=r"(r) : "r"(a), "r"(b), "r"(c)); return r; }
__device__ __forceinline__ float ex2(float x) { float r; asm("ex2.approx.ftz.f32 %0, %1;" : "=f"(r) : "f"(x)); return r; }
__device__ __forceinline__ float rcp(float x) { float r; asm("rcp.approx.ftz.f32 %0, %1;" : "=f"(r) : "f"(x)); return r; }
__device__ __forceinline__ float gelu2(float x) {
    float t = fmaf(x * x, 0.044715f * 0.7978845608028654f, 0.7978845608028654f), th;
    asm("tanh.approx.f32 %0, %1;" : "=f"(th) : "f"(x * t));
    return fmaf(x, th, x);
}
__device__ __forceinline__ uint32_t ldg_v(const uint32_t* p) { uint32_t v; asm volatile("ld.global.nc.u32 %0, [%1];" : "=r"(v) : "l"(p)); return v; }
__device__ __forceinline__ uint32_t ldg_cg(const uint32_t* p) { uint32_t v; asm volatile("ld.global.cg.u32 %0, [%1];" : "=r"(v) : "l"(p) : "memory"); return v; }
__device__ __forceinline__ float lds_f32(uint32_t a) { float v; asm volatile("ld.shared.f32 %0, [%1];" : "=f"(v) : "r"(a) : "memory"); return v; }
__device__ __forceinline__ void sts_f32(uint32_t a, float v) { asm volatile("st.shared.f32 [%0], %1;" ::"r"(a), "f"(v) : "memory"); }
__device__ __forceinline__ uint32_t atom_inc_s(uint32_t a) { uint32_t v; asm volatile("atom.relaxed.cta.shared.add.u32 %0, [%1], 1;" : "=r"(v) : "r"(a) : "memory"); return v; }
__device__ __forceinline__ void lds4(uint32_t a, uint32_t* r) {
    asm volatile("ld.shared.v4.u32 {%0, %1, %2, %3}, [%4];" : "=r"(r[0]), "=r"(r[1]), "=r"(r[2]), "=r"(r[3]) : "r"(a) : "memory");
}
__device__ __forceinline__ void sts4(uint32_t a, uint32_t x, uint32_t y, uint32_t z, uint32_t t) {
    asm volatile("st.shared.v4.u32 [%0], {%1, %2, %3, %4};" ::"r"(a), "r"(x), "r"(y), "r"(z), "r"(t) : "memory");
}
__device__ __forceinline__ uint32_t bsub2(uint32_t a, uint32_t b) { uint32_t r; asm("sub.rn.bf16x2 %0, %1, %2;" : "=r"(r) : "r"(a), "r"(b)); return r; }
__device__ __forceinline__ float blo(uint32_t v) { return __uint_as_float(v << 16); }
__device__ __forceinline__ float bhi(uint32_t v) { return __uint_as_float(v & 0xffff0000u); }
__device__ __forceinline__ float bfr(float x) { return __bfloat162float(__float2bfloat16_rn(x)); }
__device__ __forceinline__ void l2_prefetch(const void* p, uint32_t bytes) { asm volatile("cp.async.bulk.prefetch.L2.global [%0], %1;" ::"l"(p), "r"(bytes) : "memory"); }
__device__ __forceinline__ void flag_add(unsigned* p) { asm volatile("red.release.gpu.global.add.u32 [%0], 1;" ::"l"(p) : "memory"); }
__device__ __forceinline__ void flag_wait(const unsigned* p, unsigned target) {
#pragma unroll 1
    for (uint32_t it = 0;; ++it) {
        unsigned v;
        asm volatile("ld.acquire.gpu.global.u32 %0, [%1];" : "=r"(v) : "l"(p) : "memory");
        if (v >= target) break;
        if (it > (1u << 20)) __trap();
    }
    fence_async_g();
}
template <int N> __device__ __forceinline__ void pin(float (&a)[N]) {
#pragma unroll
    for (int i = 0; i < N; i++) asm volatile("" : "+f"(a[i])::"memory");
}

template <int N> __device__ __forceinline__ void fresh(float (&a)[N]) {
#pragma unroll
    for (int i = 0; i < N; i++) a[i] = 0.f;
    pin(a);
}

__device__ __forceinline__ void wgmma_rs_n32_tb0(float (&d)[16], uint32_t a0, uint32_t a1, uint32_t a2, uint32_t a3, uint64_t db, int scale_d) {
    asm volatile("{\n.reg .pred p;\nsetp.ne.b32 p, %21, 0;\n"
        "wgmma.mma_async.sync.aligned.m64n32k16.f32.bf16.bf16 {%0, %1, %2, %3, %4, %5, %6, %7, %8, %9, %10, %11, %12, %13, %14, %15}, {%16, %17, %18, %19}, %20, p, 1, 1, 0;\n}\n"
        : "+f"(d[0]), "+f"(d[1]), "+f"(d[2]), "+f"(d[3]), "+f"(d[4]), "+f"(d[5]), "+f"(d[6]), "+f"(d[7]), "+f"(d[8]), "+f"(d[9]), "+f"(d[10]), "+f"(d[11]), "+f"(d[12]), "+f"(d[13]), "+f"(d[14]), "+f"(d[15])
        : "r"(a0), "r"(a1), "r"(a2), "r"(a3), "l"(db), "r"(scale_d));
}

__device__ __forceinline__ void wgmma_rs_n64_tb0(float (&d)[32], uint32_t a0, uint32_t a1, uint32_t a2, uint32_t a3, uint64_t db, int scale_d) {
    asm volatile("{\n.reg .pred p;\nsetp.ne.b32 p, %37, 0;\n"
        "wgmma.mma_async.sync.aligned.m64n64k16.f32.bf16.bf16 {%0, %1, %2, %3, %4, %5, %6, %7, %8, %9, %10, %11, %12, %13, %14, %15, %16, %17, %18, %19, %20, %21, %22, %23, %24, %25, %26, %27, %28, %29, %30, %31}, {%32, %33, %34, %35}, %36, p, 1, 1, 0;\n}\n"
        : "+f"(d[0]), "+f"(d[1]), "+f"(d[2]), "+f"(d[3]), "+f"(d[4]), "+f"(d[5]), "+f"(d[6]), "+f"(d[7]), "+f"(d[8]), "+f"(d[9]), "+f"(d[10]), "+f"(d[11]), "+f"(d[12]), "+f"(d[13]), "+f"(d[14]), "+f"(d[15]), "+f"(d[16]), "+f"(d[17]), "+f"(d[18]), "+f"(d[19]), "+f"(d[20]), "+f"(d[21]), "+f"(d[22]), "+f"(d[23]), "+f"(d[24]), "+f"(d[25]), "+f"(d[26]), "+f"(d[27]), "+f"(d[28]), "+f"(d[29]), "+f"(d[30]), "+f"(d[31])
        : "r"(a0), "r"(a1), "r"(a2), "r"(a3), "l"(db), "r"(scale_d));
}

__device__ __forceinline__ void wgmma_ss_n128_tb1(float (&d)[64], uint64_t da, uint64_t db, int scale_d) {
    asm volatile("{\n.reg .pred p;\nsetp.ne.b32 p, %66, 0;\n"
        "wgmma.mma_async.sync.aligned.m64n128k16.f32.bf16.bf16 {%0, %1, %2, %3, %4, %5, %6, %7, %8, %9, %10, %11, %12, %13, %14, %15, %16, %17, %18, %19, %20, %21, %22, %23, %24, %25, %26, %27, %28, %29, %30, %31, %32, %33, %34, %35, %36, %37, %38, %39, %40, %41, %42, %43, %44, %45, %46, %47, %48, %49, %50, %51, %52, %53, %54, %55, %56, %57, %58, %59, %60, %61, %62, %63}, %64, %65, p, 1, 1, 0, 1;\n}\n"
        : "+f"(d[0]), "+f"(d[1]), "+f"(d[2]), "+f"(d[3]), "+f"(d[4]), "+f"(d[5]), "+f"(d[6]), "+f"(d[7]), "+f"(d[8]), "+f"(d[9]), "+f"(d[10]), "+f"(d[11]), "+f"(d[12]), "+f"(d[13]), "+f"(d[14]), "+f"(d[15]), "+f"(d[16]), "+f"(d[17]), "+f"(d[18]), "+f"(d[19]), "+f"(d[20]), "+f"(d[21]), "+f"(d[22]), "+f"(d[23]), "+f"(d[24]), "+f"(d[25]), "+f"(d[26]), "+f"(d[27]), "+f"(d[28]), "+f"(d[29]), "+f"(d[30]), "+f"(d[31]), "+f"(d[32]), "+f"(d[33]), "+f"(d[34]), "+f"(d[35]), "+f"(d[36]), "+f"(d[37]), "+f"(d[38]), "+f"(d[39]), "+f"(d[40]), "+f"(d[41]), "+f"(d[42]), "+f"(d[43]), "+f"(d[44]), "+f"(d[45]), "+f"(d[46]), "+f"(d[47]), "+f"(d[48]), "+f"(d[49]), "+f"(d[50]), "+f"(d[51]), "+f"(d[52]), "+f"(d[53]), "+f"(d[54]), "+f"(d[55]), "+f"(d[56]), "+f"(d[57]), "+f"(d[58]), "+f"(d[59]), "+f"(d[60]), "+f"(d[61]), "+f"(d[62]), "+f"(d[63])
        : "l"(da), "l"(db), "r"(scale_d));
}

__device__ __forceinline__ void wgmma_ss_n256_tb1(float (&d)[128], uint64_t da, uint64_t db, int scale_d) {
    asm volatile("{\n.reg .pred p;\nsetp.ne.b32 p, %130, 0;\n"
        "wgmma.mma_async.sync.aligned.m64n256k16.f32.bf16.bf16 {%0, %1, %2, %3, %4, %5, %6, %7, %8, %9, %10, %11, %12, %13, %14, %15, %16, %17, %18, %19, %20, %21, %22, %23, %24, %25, %26, %27, %28, %29, %30, %31, %32, %33, %34, %35, %36, %37, %38, %39, %40, %41, %42, %43, %44, %45, %46, %47, %48, %49, %50, %51, %52, %53, %54, %55, %56, %57, %58, %59, %60, %61, %62, %63, %64, %65, %66, %67, %68, %69, %70, %71, %72, %73, %74, %75, %76, %77, %78, %79, %80, %81, %82, %83, %84, %85, %86, %87, %88, %89, %90, %91, %92, %93, %94, %95, %96, %97, %98, %99, %100, %101, %102, %103, %104, %105, %106, %107, %108, %109, %110, %111, %112, %113, %114, %115, %116, %117, %118, %119, %120, %121, %122, %123, %124, %125, %126, %127}, %128, %129, p, 1, 1, 0, 1;\n}\n"
        : "+f"(d[0]), "+f"(d[1]), "+f"(d[2]), "+f"(d[3]), "+f"(d[4]), "+f"(d[5]), "+f"(d[6]), "+f"(d[7]), "+f"(d[8]), "+f"(d[9]), "+f"(d[10]), "+f"(d[11]), "+f"(d[12]), "+f"(d[13]), "+f"(d[14]), "+f"(d[15]), "+f"(d[16]), "+f"(d[17]), "+f"(d[18]), "+f"(d[19]), "+f"(d[20]), "+f"(d[21]), "+f"(d[22]), "+f"(d[23]), "+f"(d[24]), "+f"(d[25]), "+f"(d[26]), "+f"(d[27]), "+f"(d[28]), "+f"(d[29]), "+f"(d[30]), "+f"(d[31]), "+f"(d[32]), "+f"(d[33]), "+f"(d[34]), "+f"(d[35]), "+f"(d[36]), "+f"(d[37]), "+f"(d[38]), "+f"(d[39]), "+f"(d[40]), "+f"(d[41]), "+f"(d[42]), "+f"(d[43]), "+f"(d[44]), "+f"(d[45]), "+f"(d[46]), "+f"(d[47]), "+f"(d[48]), "+f"(d[49]), "+f"(d[50]), "+f"(d[51]), "+f"(d[52]), "+f"(d[53]), "+f"(d[54]), "+f"(d[55]), "+f"(d[56]), "+f"(d[57]), "+f"(d[58]), "+f"(d[59]), "+f"(d[60]), "+f"(d[61]), "+f"(d[62]), "+f"(d[63]), "+f"(d[64]), "+f"(d[65]), "+f"(d[66]), "+f"(d[67]), "+f"(d[68]), "+f"(d[69]), "+f"(d[70]), "+f"(d[71]), "+f"(d[72]), "+f"(d[73]), "+f"(d[74]), "+f"(d[75]), "+f"(d[76]), "+f"(d[77]), "+f"(d[78]), "+f"(d[79]), "+f"(d[80]), "+f"(d[81]), "+f"(d[82]), "+f"(d[83]), "+f"(d[84]), "+f"(d[85]), "+f"(d[86]), "+f"(d[87]), "+f"(d[88]), "+f"(d[89]), "+f"(d[90]), "+f"(d[91]), "+f"(d[92]), "+f"(d[93]), "+f"(d[94]), "+f"(d[95]), "+f"(d[96]), "+f"(d[97]), "+f"(d[98]), "+f"(d[99]), "+f"(d[100]), "+f"(d[101]), "+f"(d[102]), "+f"(d[103]), "+f"(d[104]), "+f"(d[105]), "+f"(d[106]), "+f"(d[107]), "+f"(d[108]), "+f"(d[109]), "+f"(d[110]), "+f"(d[111]), "+f"(d[112]), "+f"(d[113]), "+f"(d[114]), "+f"(d[115]), "+f"(d[116]), "+f"(d[117]), "+f"(d[118]), "+f"(d[119]), "+f"(d[120]), "+f"(d[121]), "+f"(d[122]), "+f"(d[123]), "+f"(d[124]), "+f"(d[125]), "+f"(d[126]), "+f"(d[127])
        : "l"(da), "l"(db), "r"(scale_d));
}

__device__ __forceinline__ void wgmma_ss_n32_tb0(float (&d)[16], uint64_t da, uint64_t db, int scale_d) {
    asm volatile("{\n.reg .pred p;\nsetp.ne.b32 p, %18, 0;\n"
        "wgmma.mma_async.sync.aligned.m64n32k16.f32.bf16.bf16 {%0, %1, %2, %3, %4, %5, %6, %7, %8, %9, %10, %11, %12, %13, %14, %15}, %16, %17, p, 1, 1, 0, 0;\n}\n"
        : "+f"(d[0]), "+f"(d[1]), "+f"(d[2]), "+f"(d[3]), "+f"(d[4]), "+f"(d[5]), "+f"(d[6]), "+f"(d[7]), "+f"(d[8]), "+f"(d[9]), "+f"(d[10]), "+f"(d[11]), "+f"(d[12]), "+f"(d[13]), "+f"(d[14]), "+f"(d[15])
        : "l"(da), "l"(db), "r"(scale_d));
}

__device__ __forceinline__ void wgmma_ss_n64_tb0(float (&d)[32], uint64_t da, uint64_t db, int scale_d) {
    asm volatile("{\n.reg .pred p;\nsetp.ne.b32 p, %34, 0;\n"
        "wgmma.mma_async.sync.aligned.m64n64k16.f32.bf16.bf16 {%0, %1, %2, %3, %4, %5, %6, %7, %8, %9, %10, %11, %12, %13, %14, %15, %16, %17, %18, %19, %20, %21, %22, %23, %24, %25, %26, %27, %28, %29, %30, %31}, %32, %33, p, 1, 1, 0, 0;\n}\n"
        : "+f"(d[0]), "+f"(d[1]), "+f"(d[2]), "+f"(d[3]), "+f"(d[4]), "+f"(d[5]), "+f"(d[6]), "+f"(d[7]), "+f"(d[8]), "+f"(d[9]), "+f"(d[10]), "+f"(d[11]), "+f"(d[12]), "+f"(d[13]), "+f"(d[14]), "+f"(d[15]), "+f"(d[16]), "+f"(d[17]), "+f"(d[18]), "+f"(d[19]), "+f"(d[20]), "+f"(d[21]), "+f"(d[22]), "+f"(d[23]), "+f"(d[24]), "+f"(d[25]), "+f"(d[26]), "+f"(d[27]), "+f"(d[28]), "+f"(d[29]), "+f"(d[30]), "+f"(d[31])
        : "l"(da), "l"(db), "r"(scale_d));
}

struct Maps {
    CUtensorMap xa, xa2, xa4, xas, wup4, wup8, mqa2, mqa4, mqb1, mqb2, uc, x, out, wq, wk, fa[3], fb[2], fc;
};

__device__ __forceinline__ uint64_t mkd(uint32_t lo) {
    uint64_t d;
    asm("mov.b64 %0, {%1, %2};" : "=l"(d) : "r"(lo), "r"((1024u >> 4) | (1u << 30)));
    return d;
}
__device__ __forceinline__ void bulk_ld(uint32_t dst, const void* src, uint32_t bytes, uint32_t bar) {
    asm volatile("cp.async.bulk.shared::cluster.global.mbarrier::complete_tx::bytes [%0], [%1], %2, [%3];" ::"r"(dst), "l"(src), "r"(bytes), "r"(bar) : "memory");
}
__device__ __forceinline__ void bulk_st(void* dst, uint32_t src, uint32_t bytes) {
    asm volatile("cp.async.bulk.global.shared::cta.bulk_group [%0], [%1], %2;" ::"l"(dst), "r"(src), "r"(bytes) : "memory");
}
__device__ __forceinline__ void ring_ld(uint32_t sb, uint32_t slot8, int n) {
    mbar_expect_tx(sb + B_R2 + slot8, 8192);
    bulk_ld(sb + R1 + slot8 * 1024, (const char*)g_wepi + n * 8192, 8192, sb + B_R2 + slot8);
}

__device__ __forceinline__ void ring_half(uint32_t sb, uint32_t slot8, uint32_t hoff, const CUtensorMap* tm, int c1, int c2) {
    mbar_expect_tx(sb + B_R1 + slot8, 8192);
    tma3(sb + slot8 * 2048 + hoff, tm, 0, c1, c2, sb + B_R1 + slot8);
}
__device__ __forceinline__ void ring_full(uint32_t sb, uint32_t slot8, const CUtensorMap* tm, int c1, int c2) {
    mbar_expect_tx(sb + B_R1 + slot8, 16384);
    mbar_arrive(sb + B_R1 + slot8);
    tma3(sb + slot8 * 2048, tm, 0, c1, c2, sb + B_R1 + slot8);
}
__device__ __forceinline__ void cta_done(int mode) {
    if (mode == 0 && atomicAdd(&g_sync[4], 1) == NCTA + 1) {
#pragma unroll
        for (int i = 0; i < 5; i++) g_sync[i] = 0;
    }
}

__device__ __forceinline__ void fold_cta(const Maps& mp, uint32_t sb, int mode) {
    constexpr uint32_t F_FULL = MISC, F_EMPTY = MISC + 32, F_T1 = MISC + 64, STG = 49152, FOUT = 3 * STG;
    const int tid = threadIdx.x, f = blockIdx.x - NCTA;
    if (mode == 2) return;
    if (tid == 0) {
        for (int i = 0; i < 3; i++) { mbar_init(sb + F_FULL + 8 * i, 1); mbar_init(sb + F_EMPTY + 8 * i, 2); }
        mbar_init(sb + F_T1, 2);
        asm volatile("fence.mbarrier_init.release.cluster;" ::: "memory");
        fence_async();
    }
    __syncthreads();
    const int wg = __shfl_sync(0xffffffffu, tid >> 7, 0);
    int st = 0, ph = 0;
    if (wg == 0) {
        if (tid == 0) {
#pragma unroll 1
            for (int it = 0; it < 96; it++) {
                const int p = it >> 3, kc = it & 7, job = p >> 2;
                if (it == 64) mbar_wait(sb + F_T1, 0);
                mbar_wait(sb + F_EMPTY + 8 * st, ph ^ 1);
                mbar_expect_tx(sb + F_FULL + 8 * st, STG);
                tma3(sb + st * STG, &mp.fa[job], 0, 256 * f + 128 * ((p >> 1) & 1), kc, sb + F_FULL + 8 * st);
                tma3(sb + st * STG + 16384, &mp.fb[job != 0], 0, 64 * kc + (job == 1 ? 512 : 0), 4 * (p & 1), sb + F_FULL + 8 * st);
                if (++st == 3) { st = 0; ph ^= 1; }
            }
        }
        return;
    }
    const int h = wg - 1, lane = tid & 31, w = (tid >> 5) & 3;
    const uint32_t sd = (sb & 0x3FFFF) >> 4;
    const bool el = (tid & 127) == 0;
#pragma unroll 1
    for (int p = 0; p < 12; p++) {
        float acc[128];
        fresh(acc);
#pragma unroll 1
        for (int kc = 0; kc < 8; kc++) {
            mbar_wait(sb + F_FULL + 8 * st, ph);
            wg_fence();
#pragma unroll
            for (int kk = 0; kk < 4; kk++)
                wgmma_ss_n256_tb1(acc, dsc(sd, st * STG + h * 8192 + kk * 32, 16), dsc(sd, st * STG + 16384 + kk * 2048, 8192), 1);
            wg_commit();
            wg_wait<0>();
            if (el) mbar_arrive(sb + F_EMPTY + 8 * st);
            if (++st == 3) { st = 0; ph ^= 1; }
        }
        pin(acc);
        const int job = p >> 2;
        if (el) {
            asm volatile("cp.async.bulk.wait_group 0;" ::: "memory");
            if (p == 4) { fence_async_g(); mbar_arrive(sb + F_T1); }
        }
        bar_sync(3 + h, 128);
        uint32_t r = 16 * w + (lane & 7) + ((lane >> 3) & 1) * 8;
        const float fs = job == 1 ? 0.5f : 1.f;
        if (job == 1) r = (r & ~31) | (((r >> 1) & 3) << 3) | (((r >> 3) & 3) << 1) | (r & 1);
        const uint32_t oa = sb + FOUT + h * 32768 + r * 128 + ((((lane >> 4) ^ r) & 7) << 4);
#pragma unroll
        for (int i = 0; i < 16; i++)
            stsm4((oa ^ ((i & 3) << 5)) + (i >> 2) * 8192, pack2(acc[8 * i] * fs, acc[8 * i + 1] * fs), pack2(acc[8 * i + 2] * fs, acc[8 * i + 3] * fs),
                  pack2(acc[8 * i + 4] * fs, acc[8 * i + 5] * fs), pack2(acc[8 * i + 6] * fs, acc[8 * i + 7] * fs));
        fence_async();
        bar_sync(3 + h, 128);
        if (el) {
            const int row0 = 256 * f + 128 * ((p >> 1) & 1) + 64 * h + (job == 1 ? 512 : 0);
            if (job == 0) tma3_store(&mp.fc, sb + FOUT + h * 32768, 0, row0, 4 * (p & 1));
            else {
#pragma unroll 1
                for (int i = 0; i < 16; i++)
                    bulk_st((char*)g_wepi + (row0 / 8 + 2 * (i & 3) + (p & 1)) * 8192 + (i >> 2) * 2048, sb + FOUT + h * 32768 + i * 2048, 2048);
            }
            asm volatile("cp.async.bulk.commit_group;" ::: "memory");
        }
    }
    if (el) {
        asm volatile("cp.async.bulk.wait_group 0;" ::: "memory");
        fence_async_g();
        if (mode == 0) flag_add(&g_sync[3]);
    }
    bar_sync(2, 256);
    if (tid == 128) cta_done(mode);
}

__global__ void __launch_bounds__(384, 1) main_kernel(const __grid_constant__ Maps mp, const bf16* __restrict__ x, const bf16* __restrict__ dw, const bf16* wup, const int mode) {
    extern __shared__ __align__(1024) uint8_t smem[];
    const uint32_t sb = smem_u32(smem);
    const int tid = threadIdx.x;
    PE();
    if (blockIdx.x >= NCTA) { fold_cta(mp, sb, mode); return; }
    const int b = blockIdx.x / TPB, ti = blockIdx.x % TPB;
    const int piece = blockIdx.x & 127;
    const int wg = __shfl_sync(0xffffffffu, tid >> 7, 0);
    const int lane = tid & 31, w = (tid >> 5) & 3;
    const bool w0 = __shfl_sync(0xffffffffu, w, 0) == 0;
    const uint32_t sd = (sb & 0x3FFFF) >> 4;
    const uint32_t adA = sd + (AT >> 4) + (1u << 16);
    const uint32_t bd0 = sd;
    const uint32_t bd2k = bd0 + ((2048u >> 4) << 16);
    const bool el = (tid & 127) == 0;
    const uint32_t lrow = 16 * w + (lane & 7) + ((lane >> 3) & 1) * 8;
    const uint32_t loff = lrow * 128 + ((((lane >> 4) ^ lrow) & 7) << 4);
    const int r0 = 16 * w + (lane >> 2);

    if (wg == 0) {
        asm volatile("setmaxnreg.inc.sync.aligned.u32 184;");
        uint32_t q[112];
        PG(206);
        if (tid == 0) {
            mbar_init(sb + B_MK, 1);
            for (int i = 0; i < 9; i++) mbar_init(sb + B_R1 + 8 * i, 2);
            for (int i = 0; i < 5; i++) asm volatile("st.shared.u32 [%0], 0;" ::"r"(sb + CNT + 4 * i) : "memory");
        } else if (tid == 32) {
            mbar_init(sb + B_LN, 1); mbar_init(sb + B_MQ, 1);
            mbar_init(sb + B_H1, 2); mbar_init(sb + B_H2, 1); mbar_init(sb + B_H3, 2);
            for (int i = 0; i < 3; i++) { mbar_init(sb + B_KV + 8 * i, 2); mbar_init(sb + B_P + 8 * i, 4); mbar_init(sb + B_GO + 8 * i, 4); }
            mbar_init(sb + B_UC, 1); mbar_init(sb + B_UC + 8, 1); mbar_init(sb + B_X, 8);
        } else if (tid == 64) {
            for (int i = 0; i < 20; i++) mbar_init(sb + B_R2 + 8 * i, 1);
        } else if (tid == 96) {
            for (int i = 0; i < 20; i++) mbar_init(sb + B_E2 + 8 * i, 4);
        }
        if (lane == 0) {
            asm volatile("fence.mbarrier_init.release.cluster;" ::: "memory");
            fence_async();
        }
        PG(207);
        __syncwarp();
        if (SU != 2) asm volatile("bar.arrive 5, 384;" ::: "memory");
        if (tid == 0) {
            mbar_expect_tx(sb + B_MK, 65536 + 32768);
            tma3(sb + 16384, &mp.wq, 0, 64 * (piece >> 4), 0, sb + B_MK);
            tma3(sb + 81920, &mp.wk, 0, 32 * (piece & 15), 0, sb + B_MK);
            for (int i = 0; i < 14; i++) mbar_arrive(sb + B_R1 + 8 * (i >> 1));
            if (mode != 1) {
                ring_full(sb, 56, &mp.wup8, 0, 8);
                ring_full(sb, 64, &mp.wup8, 16, 8);
                ring_full(sb, 0, &mp.wup8, 32, 8);
            }
        }
        PG(208);
        bar_sync(1, 128);
        if (SU == 2) asm volatile("bar.arrive 5, 384;" ::: "memory");
        PT(0);
        PG(200);
        {
            float mq[16];
            fresh(mq);
            mbar_wait(sb + B_MK, 0);
            PT(1);
            if (tid == 32) l2_prefetch((const char*)wup + piece * 8192, 8192);
            wg_fence();
#pragma unroll 1
            for (int c = 0; c < 8; c++)
#pragma unroll
                for (int kk = 0; kk < 4; kk++)
                    wgmma_ss_n32_tb0(mq, dsc(sd, 16384 + c * 8192 + kk * 32, 16), dsc(sd, 81920 + c * 4096 + kk * 32, 16), 1);
            wg_commit();
            wg_wait<0>();
            if (mode != 1 && w0 && elect1()) {
#pragma unroll 1
                for (int i = 1; i < 7; i++) ring_full(sb, 8 * i, &mp.wup8, 32 + 16 * i, 8);
            }
            pin(mq);
            uint32_t* c = reinterpret_cast<uint32_t*>(g_mqk + (64 * (piece >> 4) + r0) * D_ + 32 * (piece & 15) + 2 * (lane & 3));
#pragma unroll
            for (int n = 0; n < 4; n++) { c[4 * n] = pack2(mq[4 * n], mq[4 * n + 1]); c[4 * n + 4 * D_] = pack2(mq[4 * n + 2], mq[4 * n + 3]); }
            fence_async_g();
            bar_sync(1, 128);
            if (el) {
                if (mode == 0) flag_add(&g_sync[2]);
                if (mode == 0) flag_wait(&g_sync[2], NCTA);
                mbar_arrive(sb + B_MQ);
                PG(203);
                PT(12);
                mbar_wait(sb + B_LN, 0);
#pragma unroll 1
                for (int c = 0; c < 8; c++) {
                    tma4_store(&mp.xas, sb + AT + c * 8192, 0, 62 * ti, c, b);
                    const unsigned t0 = (unsigned)clock();
                    while (c < 7 && (unsigned)clock() - t0 < XS_GAP) __nanosleep(20);
                }
                asm volatile("cp.async.bulk.commit_group;" ::: "memory");
                if (mode == 1) asm volatile("cp.async.bulk.wait_group 0;" ::: "memory");
            }
            PT(13);
            if (mode == 1) return;
        }
        mbar_wait(sb + B_H1, 0);
        PT(2);
        uint32_t slot8 = 24, par = 0, prev8 = 0, prev2 = 0;
        auto adv = [&]() { prev2 = prev8; prev8 = slot8; slot8 += 8; if (slot8 == 72) { slot8 = 0; par ^= 1; } };
        {
            float acc[128];
            fresh(acc);
            auto step = [&](int i) {
                const uint32_t aa = adA + (i >> 1) * 512 + (i & 1) * 4, bb = bd0 + ((4096u >> 4) << 16) + slot8 * 128;
                wg_fence();
                wgmma_ss_n256_tb1(acc, mkd(aa), mkd(bb), 1);
                wgmma_ss_n256_tb1(acc, mkd(aa + 2), mkd(bb + 128), 1);
                wg_commit();
                wg_wait<1 + LAGA>();
            };
#pragma unroll 1
            for (int i = 0; i < 8 + LAGA; i++) {
                mbar_wait(sb + B_R1 + slot8, par);
                step(i);
                if (i > LAGA && w0 && elect1()) ring_full(sb, LAGA ? prev2 : prev8, &mp.mqa4, 32 * (i - LAGA) + 256, 4);
                adv();
            }
#pragma unroll 1
            for (int i = 8 + LAGA; i < 16; i++) {
                mbar_wait(sb + B_R1 + slot8, par);
                if (i == 15 && el) mbar_arrive(sb + B_H2);
                step(i);
                if (w0 && elect1()) ring_full(sb, LAGA ? prev2 : prev8, &mp.wup8, 16 * (i - LAGA) - 128, 0);
                adv();
            }
            if (LAGA) {
                wg_wait<1>();
                if (w0 && elect1()) ring_full(sb, prev2, &mp.wup8, 112, 0);
            }
            wg_wait<0>();
            if (w0 && elect1()) ring_full(sb, prev8, &mp.wup8, 128, 0);
            pin(acc);
            PT(3);
#pragma unroll
            for (int kk = 0; kk < 4; kk++)
                stsm4((sb + QS + loff) ^ (kk << 5), pack2(acc[96 + 8 * kk], acc[97 + 8 * kk]), pack2(acc[98 + 8 * kk], acc[99 + 8 * kk]),
                      pack2(acc[100 + 8 * kk], acc[101 + 8 * kk]), pack2(acc[102 + 8 * kk], acc[103 + 8 * kk]));
            fence_async();
#pragma unroll
            for (int i = 47; i >= 0; i--) q[64 + i] = pack2v(acc[2 * i], acc[2 * i + 1]);
        }
        if (el) {
            asm volatile("cp.async.bulk.wait_group 0;" ::: "memory");
            if (mode == 0) {
                fence_async_g();
                flag_add(&g_sync[b]);
                flag_wait(&g_sync[b], TPB);
            }
        }
        __syncwarp();
        mbar_wait(sb + B_H3, 0);
        PT(4);
        slot8 = 48; par = 1;
#pragma unroll
        for (int half = 0; half < 2; half++) {
            float acc[64];
            fresh(acc);
            auto step = [&](int m) {
                const uint32_t aa = adA + m * 512, bb = bd0 + ((8192u >> 4) << 16) + slot8 * 128;
                mbar_wait(sb + B_R1 + slot8, par);
                wg_fence();
#pragma unroll
                for (int kk = 0; kk < 4; kk++) wgmma_ss_n128_tb1(acc, mkd(aa + 2 * kk), mkd(bb + 128 * kk), 1);
                wg_commit();
                wg_wait<1 + LAGB>();
            };
#pragma unroll 1
            for (int m = 0; m < 8; m++) {
                step(m);
                if (m > LAGB && w0 && elect1()) {
                    if (half == 0) ring_full(sb, LAGB ? prev2 : prev8, &mp.mqb2, 64 * (m - LAGB), 2);
                    else if (m < 4 + LAGB) tma4(sb + (LAGB ? prev2 : prev8) * 2048, &mp.xa2, 0, 0, 2 * (m - LAGB), b, sb + B_KV + 8);
                }
                adv();
            }
            if (LAGB && half == 0) {
                wg_wait<1>();
                if (w0 && elect1()) ring_full(sb, prev2, &mp.mqb2, 448, 2);
            }
            wg_wait<0>();
            if (w0 && elect1()) {
                if (half == 0) {
                    mbar_expect_tx(sb + B_KV + 8, 65536);
                    for (int i = 0; i < 3; i++) mbar_arrive(sb + B_KV + 8 * i);
                    tma4(sb + prev8 * 2048, &mp.xa2, 0, 0, 0, b, sb + B_KV + 8);
                } else {
                    mbar_expect_tx(sb + B_KV + 16, 65536);
                    tma4(sb + R2, &mp.xa, 0, 64, 0, b, sb + B_KV + 16);
                    mbar_expect_tx(sb + B_KV, 65536);
                    tma4(sb + R0, &mp.xa, 0, 128, 0, b, sb + B_KV);
                }
            }
            pin(acc);
#pragma unroll
            for (int i = 31; i >= 0; i--) q[32 * half + i] = pack2v(acc[2 * i], acc[2 * i + 1]);
        }
        bar_sync(1, 128);
        PT(5);

        const float CS = 0.04419417382415922f * 1.4426950408889634f;
        float m0 = -INFINITY, m1 = -INFINITY, l0 = 0.f, l1 = 0.f;
        int s = 0, sn = 1, ph = 0;
        float S[32];
        const bool l0w = lane == 0, q0 = (lane & 3) == 0;
#pragma unroll 1
        for (int j = -1;; j++) {
            if (j >= 0) {
                PL(j, 1);
                if (j == NKV - 1) {
#pragma unroll
                    for (int i = (T_ - 64 * (NKV - 1)) / 2; i < 32; i++) asm volatile("mov.b32 %0, 0xff800000;" : "=f"(S[i]));
                }
                const bool kv = mbar_test(sb + B_KV + sn * 8, ph);
                const uint32_t pb = sb + R3 + (s == 0 ? 2 : s - 1) * 8192;
                float a0 = 0.f, a1 = 0.f, sc0 = 1.f, sc1 = 1.f;
                auto expo = [&]() {
                    const float n0 = -m0 * CS, n1 = -m1 * CS;
                    a0 = 0.f; a1 = 0.f;
#pragma unroll
                    for (int kk = 0; kk < 4; kk++) {
                        float p[8];
#pragma unroll
                        for (int e = 0; e < 8; e++) p[e] = ex2(fmaf(S[8 * kk + e], CS, (e & 2) ? n1 : n0));
                        a0 += (p[0] + p[1]) + (p[4] + p[5]);
                        a1 += (p[2] + p[3]) + (p[6] + p[7]);
                        stsm4((pb + loff) ^ (kk << 5), pack2(p[0], p[1]), pack2(p[2], p[3]), pack2(p[4], p[5]), pack2(p[6], p[7]));
                    }
                };
                if (j > 0 || !SK0) expo();
                if ((SK0 && j == 0) || __any_sync(0xffffffffu, !(a0 <= LAZY) || !(a1 <= LAZY))) {
                    float x0 = m0, x1 = m1;
#pragma unroll
                    for (int n = 0; n < 8; n++) { x0 = fmaxf(x0, fmaxf(S[4 * n], S[4 * n + 1])); x1 = fmaxf(x1, fmaxf(S[4 * n + 2], S[4 * n + 3])); }
                    x0 = fmaxf(x0, __shfl_xor_sync(0xffffffffu, x0, 1));
                    x1 = fmaxf(x1, __shfl_xor_sync(0xffffffffu, x1, 1));
                    x0 = fmaxf(x0, __shfl_xor_sync(0xffffffffu, x0, 2));
                    x1 = fmaxf(x1, __shfl_xor_sync(0xffffffffu, x1, 2));
                    sc0 = ex2((m0 - x0) * CS); sc1 = ex2((m1 - x1) * CS);
                    m0 = x0; m1 = x1;
                    expo();
                }
                if (q0) { sts_f32(sb + SCL + s * 256 + r0 * 4, sc0); sts_f32(sb + SCL + s * 256 + r0 * 4 + 32, sc1); }
                __syncwarp();
                if (l0w) mbar_arrive(sb + B_P + s * 8);
                l0 = fmaf(l0, sc0, a0); l1 = fmaf(l1, sc1, a1);
                PL(j, 2);
                if (j == NKV - 1) break;
                if (!kv) mbar_wait(sb + B_KV + sn * 8, ph);
            } else {
                mbar_wait(sb + B_KV + 8, 0);
            }
            const uint32_t kd = sd + sn * 4096;
            if (TRIM & 2 && j == NKV - 2) {
                float Sn[16];
                wg_fence();
#pragma unroll
                for (int kk = 0; kk < 28; kk++) {
                    wgmma_rs_n32_tb0(Sn, q[4 * kk], q[4 * kk + 1], q[4 * kk + 2], q[4 * kk + 3], dsc(kd, (kk >> 2) * 8192 + (kk & 3) * 32, 16), kk > 0);
                    if (kk == FENCE_AT) { fence_async(); __syncwarp(); }
                    if (kk == GO_LAST && l0w) mbar_arrive(sb + B_GO + s * 8);
                }
#pragma unroll
                for (int kk = 0; kk < 4; kk++)
                    wgmma_ss_n32_tb0(Sn, dsc(sd, QS + kk * 32, 16), dsc(kd, 7 * 8192 + kk * 32, 16), 1);
                wg_commit();
                wg_wait<0>();
                pin(Sn);
#pragma unroll
                for (int i = 0; i < 16; i++) S[i] = Sn[i];
            } else {
            float Sn[32];
            wg_fence();
#pragma unroll
            for (int kk = 0; kk < 28; kk++) {
                wgmma_rs_n64_tb0(Sn, q[4 * kk], q[4 * kk + 1], q[4 * kk + 2], q[4 * kk + 3], dsc(kd, (kk >> 2) * 8192 + (kk & 3) * 32, 16), kk > 0);
                if (kk == FENCE_AT) { fence_async(); __syncwarp(); }
                if (kk == GO_AT) { PL(j, 3); if (j >= 0 && l0w) mbar_arrive(sb + B_GO + s * 8); }
            }
#pragma unroll
            for (int kk = 0; kk < 4; kk++)
                wgmma_ss_n64_tb0(Sn, dsc(sd, QS + kk * 32, 16), dsc(kd, 7 * 8192 + kk * 32, 16), 1);
            wg_commit();
            PL(j, 0);
            wg_wait<0>();
            pin(Sn);
#pragma unroll
            for (int i = 0; i < 32; i++) S[i] = Sn[i];
            }
            s = sn;
            if (++sn == 3) sn = 0;
            if (sn == 1) ph ^= 1;
        }
        l0 += __shfl_xor_sync(0xffffffffu, l0, 1); l1 += __shfl_xor_sync(0xffffffffu, l1, 1);
        l0 += __shfl_xor_sync(0xffffffffu, l0, 2); l1 += __shfl_xor_sync(0xffffffffu, l1, 2);
        if (q0) { sts_f32(sb + LINV + r0 * 4, rcp(l0)); sts_f32(sb + LINV + r0 * 4 + 32, rcp(l1)); }
        fence_async();
        __syncwarp();
        if (l0w) {
            mbar_arrive(sb + B_GO + s * 8);
            uint32_t slot8 = 8 * w, par = 0;
#pragma unroll 1
            for (int n = 20 + w; n < 136; n += 4) {
                mbar_wait(sb + B_E2 + slot8, par);
                if (n < 128) ring_ld(sb, slot8, n);
                else {
                    mbar_expect_tx(sb + B_X, 8192);
                    tma4(sb + R1 + slot8 * 1024, &mp.x, 0, 62 * ti, n - 128, b, sb + B_X);
                }
                slot8 += 32;
                if (slot8 >= 160) { slot8 -= 160; par ^= 1; }
            }
        }
        PDUMP();
    } else {
        asm volatile("setmaxnreg.dec.sync.aligned.u32 160;");
        const int h = wg - 1;
        uint32_t v[4][8], v2[4][8];
        if (SU != 0) bar_sync(5, 384);
        PG(206);
#pragma unroll
        for (int i = 0; i < 8; i++) {
            const int t = 62 * ti - 1 + 32 * (i >> 2) + 16 * h + 4 * w + (i & 3);
            const uint4* p = reinterpret_cast<const uint4*>(x + ((size_t)b * T_ + t) * D_) + lane;
            uint32_t* d = i < 4 ? v[i & 3] : v2[i & 3];
#pragma unroll
            for (int c = 0; c < 2; c++)
                asm volatile("{\n.reg .pred p;\nsetp.lt.u32 p, %5, %6;\nmov.b32 %0, 0;\nmov.b32 %1, 0;\nmov.b32 %2, 0;\nmov.b32 %3, 0;\n"
                             "@p ld.global.nc.v4.u32 {%0, %1, %2, %3}, [%4];\n}\n"
                             : "=r"(d[4 * c]), "=r"(d[4 * c + 1]), "=r"(d[4 * c + 2]), "=r"(d[4 * c + 3]) : "l"(p + 32 * c), "r"(t), "n"(T_));
        }
#pragma unroll 1
        for (int bt = 0; bt < 2; bt++) {
            PT(bt ? 13 : 0);
            float a[8];
            const uint32_t la = sb + AT + (lane >> 3) * 8192 + (32 * bt + 16 * h + 4 * w) * 128 + (((lane & 7) ^ ((w & 1) * 4)) << 4);
            const bool b4 = lane & 16, b3 = lane & 8, b2 = lane & 4;
#pragma unroll
            for (int r = 0; r < 4; r++) {
                float c[4] = {0.f, 0.f, 0.f, 0.f};
#pragma unroll
                for (int i = 0; i < 8; i += 2) hmma(c, v[r][i], v[r][i], v[r][i + 1], v[r][i + 1], v[r][i], v[r][i + 1]);
                a[4 + r] = (lane & 3) == (lane >> 3) ? (b2 ? c[1] : c[0]) : 0.f;
                if (r & 1) {
                    float e[4] = {0.f, 0.f, 0.f, 0.f};
#pragma unroll
                    for (int i = 0; i < 8; i += 2) hmma(e, v[r - 1][i], v[r][i], v[r - 1][i + 1], v[r][i + 1], 0x3f803f80u, 0x3f803f80u);
                    a[r - 1] = e[0]; a[r] = e[2];
                }
            }
            float k[4];
#pragma unroll
            for (int i = 0; i < 4; i++) {
                const int lo = (i & 1) + 4 * (i >> 1);
                k[i] = (b4 ? a[lo + 2] : a[lo]) + __shfl_xor_sync(0xffffffffu, b4 ? a[lo] : a[lo + 2], 16);
            }
            const float k0 = (b3 ? k[1] : k[0]) + __shfl_xor_sync(0xffffffffu, b3 ? k[0] : k[1], 8);
            const float k1 = (b3 ? k[3] : k[2]) + __shfl_xor_sync(0xffffffffu, b3 ? k[2] : k[3], 8);
            float z = (b2 ? k1 : k0) + __shfl_xor_sync(0xffffffffu, b2 ? k0 : k1, 4);
            z += __shfl_xor_sync(0xffffffffu, z, 2);
            z += __shfl_xor_sync(0xffffffffu, z, 1);
            const float zo = __shfl_xor_sync(0xffffffffu, z, 4);
            PG(204 + bt);
            const float mu = (b2 ? zo : z) * (0.25f / D_);
            float sd_ = bfr(bfr(fmaxf(fmaf(b2 ? z : zo, 1.f / D_, -mu * mu), 0.f)) + 1e-5f);
            asm("sqrt.approx.f32 %0, %0;" : "+f"(sd_));
            const float ri = rcp(bfr(sd_));
            const uint32_t w1 = pack2(mu, ri), w2 = pack2(ri - bhi(w1), ri - bhi(w1));
#pragma unroll
            for (int r = 0; r < 4; r++) {
                const uint32_t s1 = __shfl_sync(0xffffffffu, w1, 8 * r), rl = __shfl_sync(0xffffffffu, w2, 8 * r);
                const uint32_t m2 = __byte_perm(s1, 0, 0x1010), rh = __byte_perm(s1, 0, 0x3232);
#pragma unroll
                for (int i = 0; i < 8; i++) { const uint32_t d = bsub2(v[r][i], m2); v[r][i] = bfma2(d, rh, bmul2(d, rl)); }
                sts4((la ^ (r << 4)) + r * 128, v[r][0], v[r][1], v[r][2], v[r][3]);
                sts4((la ^ (r << 4)) + r * 128 + 32768, v[r][4], v[r][5], v[r][6], v[r][7]);
#pragma unroll
                for (int i = 0; i < 8; i++) v[r][i] = v2[r][i];
            }
        }
        fence_async();
        if (SU == 0) bar_sync(5, 384); else bar_sync(2, 256);
        if (tid == 128) mbar_arrive(sb + B_LN);
        PG(202);
        if (mode == 1) return;
        float acc[128];
#pragma unroll
        for (int pass = 0; pass < 2; pass++) {
            if (pass == 1) mbar_wait(sb + B_H2, 0);
            PT(1 + 3 * pass);
            fresh(acc);
            uint32_t slot8 = pass ? 8 : 56, par = 0, prev8 = 0;
            auto adv = [&]() { prev8 = slot8; slot8 += 8; if (slot8 == 72) { slot8 = 0; par ^= 1; } };
            auto step = [&](int kk) {
                wg_fence();
                wgmma_ss_n256_tb1(acc, mkd(adA + (kk >> 2) * 512 + (kk & 3) * 2), mkd(bd2k + h * 512 + slot8 * 128), 1);
                wg_commit();
                wg_wait<1>();
            };
#pragma unroll 1
            for (int kk = 0; kk < 24; kk++) {
                mbar_wait(sb + B_R1 + slot8, par);
                step(kk);
                if (kk > 0 && w0 && elect1()) ring_half(sb, prev8, h * 8192, &mp.wup4, 16 * kk + 128, (pass ? 0 : 8) + 4 * h);
                adv();
            }
            if (pass == 0 && w0) mbar_wait(sb + B_MQ, 0);
#pragma unroll 1
            for (int kk = 24; kk < 32; kk++) {
                mbar_wait(sb + B_R1 + slot8, par);
                if (kk == 31 && el) mbar_arrive(sb + (pass ? B_H3 : B_H1));
                step(kk);
                if (w0 && elect1()) ring_half(sb, prev8, h * 8192, pass ? &mp.mqb1 : &mp.mqa2, (pass ? 64 : 32) * (kk - 24), pass ? h : 4 + 2 * h);
                adv();
            }
            wg_wait<0>();
            if (w0 && elect1()) ring_half(sb, prev8, h * 8192, pass ? &mp.mqb1 : &mp.mqa2, pass ? 0 : 256, pass ? 2 + h : 4 + 2 * h);
            pin(acc);
            PT(2 + 3 * pass);
            bf16* ucp = g_uc + ((size_t)blockIdx.x * 128 + r0) * D_ + 256 * h + 8 * (lane & 3);
            if (pass == 0) {
                float s0 = 0.f, s1 = 0.f, v0 = 0.f, v1 = 0.f;
#pragma unroll
                for (int n = 0; n < 32; n++) {
#pragma unroll
                    for (int e = 0; e < 4; e++) acc[4 * n + e] = gelu2(acc[4 * n + e]);
                    s0 += acc[4 * n] + acc[4 * n + 1]; s1 += acc[4 * n + 2] + acc[4 * n + 3];
                    v0 = fmaf(acc[4 * n], acc[4 * n], v0); v0 = fmaf(acc[4 * n + 1], acc[4 * n + 1], v0);
                    v1 = fmaf(acc[4 * n + 2], acc[4 * n + 2], v1); v1 = fmaf(acc[4 * n + 3], acc[4 * n + 3], v1);
                }
#pragma unroll
                for (int o = 1; o < 4; o <<= 1) {
                    s0 += __shfl_xor_sync(0xffffffffu, s0, o); s1 += __shfl_xor_sync(0xffffffffu, s1, o);
                    v0 += __shfl_xor_sync(0xffffffffu, v0, o); v1 += __shfl_xor_sync(0xffffffffu, v1, o);
                }
                if ((lane & 3) == 0) {
                    uint32_t a = sb + STAT + h * 512 + r0 * 8;
                    sts_f32(a, s0); sts_f32(a + 4, v0); sts_f32(a + 64, s1); sts_f32(a + 68, v1);
                }
                bar_sync(2, 256);
                {
                    uint32_t a = sb + STAT + (h ^ 1) * 512 + r0 * 8;
                    s0 = (s0 + lds_f32(a)) * (1.f / 512.f); v0 = (v0 + lds_f32(a + 4)) * (1.f / 512.f);
                    s1 = (s1 + lds_f32(a + 64)) * (1.f / 512.f); v1 = (v1 + lds_f32(a + 68)) * (1.f / 512.f);
                }
                v0 = rsqrtf(fmaxf(fmaf(-s0, s0, v0), 0.f) + 4e-5f); v1 = rsqrtf(fmaxf(fmaf(-s1, s1, v1), 0.f) + 4e-5f);
                s0 = -s0 * v0; s1 = -s1 * v1;
#pragma unroll
                for (int m = 0; m < 8; m++) {
                    const float* a_ = acc + 16 * m;
                    stg4(ucp + 64 * D_ + 32 * m, pack2(fmaf(a_[0], v0, s0), fmaf(a_[1], v0, s0)), pack2(fmaf(a_[4], v0, s0), fmaf(a_[5], v0, s0)),
                         pack2(fmaf(a_[8], v0, s0), fmaf(a_[9], v0, s0)), pack2(fmaf(a_[12], v0, s0), fmaf(a_[13], v0, s0)));
                    stg4(ucp + 72 * D_ + 32 * m, pack2(fmaf(a_[2], v1, s1), fmaf(a_[3], v1, s1)), pack2(fmaf(a_[6], v1, s1), fmaf(a_[7], v1, s1)),
                         pack2(fmaf(a_[10], v1, s1), fmaf(a_[11], v1, s1)), pack2(fmaf(a_[14], v1, s1), fmaf(a_[15], v1, s1)));
                }
            } else {
#pragma unroll
                for (int m = 0; m < 8; m++) {
                    const float* a_ = acc + 16 * m;
                    stg4(ucp + 32 * m, pack2(a_[0], a_[1]), pack2(a_[4], a_[5]), pack2(a_[8], a_[9]), pack2(a_[12], a_[13]));
                    stg4(ucp + 8 * D_ + 32 * m, pack2(a_[2], a_[3]), pack2(a_[6], a_[7]), pack2(a_[10], a_[11]), pack2(a_[14], a_[15]));
                }
                bar_sync(3 + h, 128);
            }
            PT(3 + 3 * pass);
        }
        int s = 1, ph = 0;
        uint32_t* cp = reinterpret_cast<uint32_t*>(g_uc + (size_t)blockIdx.x * 128 * D_) + (tid - 128);
        const uint32_t* dp = reinterpret_cast<const uint32_t*>(dw) + (((tid - 128) & ~15) | ((lane & 3) << 2) | ((lane >> 2) & 3));
        const uint32_t d0 = ldg_v(dp), d1 = ldg_v(dp + D_ / 2), d2 = ldg_v(dp + D_);
        uint32_t ga = ldg_cg(cp + 64 * (D_ / 2)), gb = ldg_cg(cp + 65 * (D_ / 2));
        fresh(acc);
#pragma unroll 1
        for (int j = 0; j < NKV; j++) {
            cp += D_ / 2;
            uint32_t gc = 0, uu = 0;
            if (j < NKV - 1) { gc = ldg_cg(cp + 65 * (D_ / 2)); uu = ldg_cg(cp); }
            mbar_wait(sb + B_P + s * 8, ph);
            PL(j, 0);
            if (j > 0) {
                const float sc0 = lds_f32(sb + SCL + s * 256 + r0 * 4), sc1 = lds_f32(sb + SCL + s * 256 + r0 * 4 + 32);
                if (__any_sync(0xffffffffu, sc0 != 1.f || sc1 != 1.f)) {
#pragma unroll
                    for (int n = 0; n < 32; n++) { acc[4 * n] *= sc0; acc[4 * n + 1] *= sc0; acc[4 * n + 2] *= sc1; acc[4 * n + 3] *= sc1; }
                }
            }
            mbar_wait(sb + B_GO + s * 8, ph);
            PL(j, 1);
            const uint32_t vd = sd + s * 4096 + h * 2048, pd = sd + (s == 0 ? 2 : s - 1) * 512;
            pin(acc);
            if (TRIM & 1 && j == NKV - 1) {
                wg_fence();
#pragma unroll
                for (int kk = 0; kk < 2; kk++) wgmma_ss_n256_tb1(acc, dsc(pd, R3 + kk * 32, 16), dsc(vd, kk * 2048, 8192), 1);
                wg_commit();
                wg_wait<0>();
                pin(acc);
                break;
            }
            wg_fence();
#pragma unroll
            for (int kk = 0; kk < 4; kk++) wgmma_ss_n256_tb1(acc, dsc(pd, R3 + kk * 32, 16), dsc(vd, kk * 2048, 8192), 1);
            wg_commit();
            wg_wait<0>();
            pin(acc);
            PL(j, 2);
            if (w0 && elect1()) {
                if (j + 3 < NKV) {
                    mbar_expect_tx(sb + B_KV + s * 8, 32768);
                    tma4(sb + s * 65536 + h * 32768, &mp.xa4, 0, 64 * (j + 3), 4 * h, b, sb + B_KV + s * 8);
                } else if (j < NKV - 1) {
                    const int n0 = (j == NKV - 3 ? 0 : 8) + 4 * h;
#pragma unroll 1
                    for (int n = n0; n < n0 + 4; n++) ring_ld(sb, n * 8, n);
                }
                if (j == NKV - 5 && mode == 0) flag_wait(&g_sync[3], 4);
                if (j >= XPF && j < XPF + 4) {
                    const int t0 = 62 * ti + 32 * h + 8 * (j - XPF), nr = min(8, T_ - t0);
                    if (nr > 0) l2_prefetch(x + ((size_t)b * T_ + t0) * D_, nr * 1024);
                }
                if (KPF && h == 0 && 64 * (j + KPF) + ti < T_) l2_prefetch(g_xa + ((size_t)b * (T_ + 8) + 1 + 64 * (j + KPF) + ti) * D_, 1024);
            }
            uu = pack2(gelu2(blo(uu)), gelu2(bhi(uu)));
            if (j < NKV - 1) asm volatile("st.global.u32 [%0], %1;" ::"l"(cp), "r"(bmul2(uu, bfma2(gc, d2, bfma2(gb, d1, bmul2(ga, d0))))) : "memory");
            ga = gb; gb = gc;
            if (++s == 3) s = 0;
            if (s == 1) ph ^= 1;
        }
        {
            const float i0 = lds_f32(sb + LINV + r0 * 4), i1 = lds_f32(sb + LINV + r0 * 4 + 32);
#pragma unroll
            for (int p = 0; p < 16; p++)
                stsm4(((sb + R0 + h * 32768 + loff) ^ ((p & 3) << 5)) + (p >> 2) * 8192,
                      pack2(acc[8 * p] * i0, acc[8 * p + 1] * i0), pack2(acc[8 * p + 2] * i1, acc[8 * p + 3] * i1),
                      pack2(acc[8 * p + 4] * i0, acc[8 * p + 5] * i0), pack2(acc[8 * p + 6] * i1, acc[8 * p + 7] * i1));
        }
        fence_async();
        fence_async_g();
        bar_sync(2, 256);
        if (lane == 0 && w < 2) ring_ld(sb, 128 + 16 * w + 8 * h, 16 + 2 * w + h);
        PT(7);
        fresh(acc);
        {
            uint32_t slot8 = 8 * h, par = 0, prev8 = 0;
#pragma unroll 1
            for (int kk = 0; kk < 64; kk++) {
                if (kk == 32 || kk == 48) mbar_wait(sb + B_UC + (kk >> 1 & 8), 0);
                mbar_wait(sb + B_R2 + slot8, par);
                wg_fence();
                wgmma_ss_n256_tb1(acc, mkd(sd + (1u << 16) + (R0 >> 4) + (kk >> 2 & 7) * 512 + (kk & 3) * 2), mkd(bd2k + (R1 >> 4) + slot8 * 64), 1);
                wg_commit();
                wg_wait<1>();
                if (kk > 0 && lane == 0) mbar_arrive(sb + B_E2 + prev8);
                if ((kk == 16 || kk == 32) && w0 && elect1() && (atom_inc_s(sb + CNT + 12 + (kk >> 3 & 4)) & 1)) {
                    mbar_expect_tx(sb + B_UC + (kk >> 2 & 8), 32768);
                    tma3(sb + R0 + (kk & 32) * 1024, &mp.uc, 0, 128 * blockIdx.x, kk >> 3 & 4, sb + B_UC + (kk >> 2 & 8));
                }
                prev8 = slot8;
                slot8 += 16;
                if (slot8 >= 160) { slot8 -= 160; par ^= 1; }
            }
        }
        wg_wait<0>();
        pin(acc);
        PT(8);
        mbar_wait(sb + B_X, 0);
        PT(9);
        {
            const uint32_t sr = (lrow + 63) & 63;
            const uint32_t xoff = sr * 128 + ((((lane >> 4) ^ sr) & 7) << 4);
#pragma unroll
            for (int p = 0; p < 16; p++) {
                const uint32_t a = ((sb + R2 + h * 32768 + xoff) ^ ((p & 3) << 5)) + (p >> 2) * 8192;
                uint32_t xv[4];
                ldsm4(a, xv);
#pragma unroll
                for (int e = 0; e < 4; e++)
                    xv[e] = pack2(acc[8 * p + 2 * e] + __uint_as_float(xv[e] << 16), acc[8 * p + 2 * e + 1] + __uint_as_float(xv[e] & 0xffff0000u));
                stsm4(a, xv[0], xv[1], xv[2], xv[3]);
            }
        }
        fence_async();
        bar_sync(3 + h, 128);
        if (el) {
            for (int c = 0; c < 4; c++) tma4_store(&mp.out, sb + R2 + (4 * h + c) * 8192, 0, 62 * ti, 4 * h + c, b);
            asm volatile("cp.async.bulk.commit_group;" ::: "memory");
            PT(10);
            if (h == 0) cta_done(mode);
            asm volatile("cp.async.bulk.wait_group.read 0;" ::: "memory");
        }
        PT(11);
        PG(201);
        PDUMP();
    }
}

typedef CUresult (*PFN_enc)(CUtensorMap*, CUtensorMapDataType, cuuint32_t, void*, const cuuint64_t*, const cuuint64_t*,
                            const cuuint32_t*, const cuuint32_t*, CUtensorMapInterleave, CUtensorMapSwizzle,
                            CUtensorMapL2promotion, CUtensorMapFloatOOBfill);

static void enc(PFN_enc f, CUtensorMap* m, void* base, int rank, const cuuint64_t* dims, const cuuint64_t* strides, const cuuint32_t* box) {
    cuuint32_t es[5] = {1, 1, 1, 1, 1};
    f(m, CU_TENSOR_MAP_DATA_TYPE_BFLOAT16, rank, base, dims, strides, box, es, CU_TENSOR_MAP_INTERLEAVE_NONE,
      CU_TENSOR_MAP_SWIZZLE_128B, CU_TENSOR_MAP_L2_PROMOTION_L2_256B, CU_TENSOR_MAP_FLOAT_OOB_FILL_NONE);
}
static void enc_act(PFN_enc f, CUtensorMap* m, void* base, int rows, int chunks, int trows = T_, int pitch = T_) {
    cuuint64_t dims[4] = {64, (cuuint64_t)trows, 8, (cuuint64_t)NB_};
    cuuint64_t st[3] = {1024, 128, (cuuint64_t)pitch * 1024};
    cuuint32_t box[4] = {64, (cuuint32_t)rows, (cuuint32_t)chunks, 1};
    enc(f, m, base, 4, dims, st, box);
}
static void enc_w(PFN_enc f, CUtensorMap* m, void* base, int krows, int ncols, int bk, int bc) {
    cuuint64_t dims[3] = {64, (cuuint64_t)krows, (cuuint64_t)(ncols / 64)};
    cuuint64_t st[2] = {(cuuint64_t)ncols * 2, 128};
    cuuint32_t box[3] = {64, (cuuint32_t)bk, (cuuint32_t)bc};
    enc(f, m, base, 3, dims, st, box);
}

extern "C" void kernel_launch(void* const* d_in, const int* in_sizes, int n_in, void* d_out, int out_size) {
    const bf16* x = (const bf16*)d_in[0];
    static PFN_enc fenc = nullptr;
    static void *p_xa, *p_mqk, *p_uc, *p_t1;
    static int fused = 0;
    if (!fenc) {
        void* fn = nullptr;
        cudaDriverEntryPointQueryResult qr;
        cudaGetDriverEntryPoint("cuTensorMapEncodeTiled", &fn, cudaEnableDefault, &qr);
        fenc = (PFN_enc)fn;
        cudaGetSymbolAddress(&p_xa, g_xa);
        cudaGetSymbolAddress(&p_mqk, g_mqk);
        cudaGetSymbolAddress(&p_uc, g_uc);
        cudaGetSymbolAddress(&p_t1, g_t1);
        cudaFuncSetAttribute(main_kernel, cudaFuncAttributeMaxDynamicSharedMemorySize, SMEM_BYTES);
        int dev = 0, sms = 0, occ = 0;
        cudaGetDevice(&dev);
        cudaDeviceGetAttribute(&sms, cudaDevAttrMultiProcessorCount, dev);
        cudaOccupancyMaxActiveBlocksPerMultiprocessor(&occ, main_kernel, 384, SMEM_BYTES);
        fused = sms * occ >= NCTA + 2;
    }
    Maps mp;
    enc_act(fenc, &mp.xa, (char*)p_xa + 1024, 64, 8, T_, T_ + 8);
    enc_act(fenc, &mp.xa2, (char*)p_xa + 1024, 64, 2, T_, T_ + 8);
    enc_act(fenc, &mp.xa4, (char*)p_xa + 1024, 64, 4, T_, T_ + 8);
    enc_act(fenc, &mp.xas, p_xa, 64, 1, T_ + 1, T_ + 8);
    enc_act(fenc, &mp.x, (void*)x, 64, 1);
    enc_act(fenc, &mp.out, d_out, 62, 1);
    enc_w(fenc, &mp.wup4, d_in[5], 512, 1024, 16, 4);
    enc_w(fenc, &mp.wup8, d_in[5], 512, 1024, 16, 8);
    enc_w(fenc, &mp.mqa2, p_mqk, 512, 512, 32, 2);
    enc_w(fenc, &mp.mqa4, p_mqk, 512, 512, 32, 4);
    enc_w(fenc, &mp.mqb1, p_mqk, 512, 512, 64, 1);
    enc_w(fenc, &mp.mqb2, p_mqk, 512, 512, 64, 2);
    enc_w(fenc, &mp.uc, p_uc, NCTA * 128, 512, 64, 4);
    enc_w(fenc, &mp.wq, d_in[1], 512, 512, 64, 8);
    enc_w(fenc, &mp.wk, d_in[2], 512, 512, 32, 8);
    enc_w(fenc, &mp.fa[0], d_in[3], 512, 512, 128, 1);
    enc_w(fenc, &mp.fa[1], d_in[7], 512, 512, 128, 1);
    enc_w(fenc, &mp.fa[2], p_t1, 512, 512, 128, 1);
    enc_w(fenc, &mp.fb[0], d_in[4], 512, 512, 64, 4);
    enc_w(fenc, &mp.fb[1], d_in[8], 1024, 512, 64, 4);
    enc_w(fenc, &mp.fc, p_t1, 512, 512, 64, 4);
    cudaStream_t st = cudaStreamPerThread;
    if (fused) {
        main_kernel<<<NCTA + 2, 384, SMEM_BYTES, st>>>(mp, x, (const bf16*)d_in[6], (const bf16*)d_in[5], 0);
    } else {
        main_kernel<<<NCTA + 2, 384, SMEM_BYTES, st>>>(mp, x, (const bf16*)d_in[6], (const bf16*)d_in[5], 1);
        main_kernel<<<NCTA + 2, 384, SMEM_BYTES, st>>>(mp, x, (const bf16*)d_in[6], (const bf16*)d_in[5], 2);
    }
}
```

```cpp
#include <cuda_runtime.h>
#include <cuda_bf16.h>
#include <cuda.h>
#include <stdint.h>

typedef __nv_bfloat16 bf16;

constexpr int T_ = 4000, D_ = 512, NB_ = 2;
constexpr int TPB = 65;
constexpr int NCTA = TPB * NB_;
constexpr int NKV = 63;

__device__ __align__(1024) bf16 g_xa[NB_ * (T_ + 8) * D_];
__device__ __align__(1024) bf16 g_mqk[D_ * D_];
__device__ __align__(1024) bf16 g_t1[D_ * D_];
__device__ __align__(1024) bf16 g_wepi[2 * D_ * D_];
__device__ __align__(1024) bf16 g_uc[NCTA * 128 * D_];
__device__ unsigned g_sync[8];

#define PT(i) do { if (el) asm volatile("st.shared.u32 [%0], %1;" ::"r"(sb + MISC + 2560), "r"((unsigned)clock())); } while (0)
#define PG(i)
#define PE()
#define PLM 15
#define PL(j, q) do { if ((PLM >> ((q) + (wg ? 4 : 0))) & 1) PT(0); } while (0)
#define PDUMP()

#define FENCE_AT 1
#define GO_AT 25
#define LAZY 4294967296.f
#define SU 2
#define XS_GAP 800
#define XPF 50
#define URAW 1
#define LAGA 0
#define LAGB 0
#define DPOS 1
#define KPF 0
#define XEF 0
#define SK0 0
#define TRIM 3
#define GO_LAST 20
#define GST 8
#define PFW 1
constexpr uint32_t R0 = 0, R1 = 65536, R2 = 131072, R3 = 196608, QS = 221184, MISC = 229376;
constexpr uint32_t AT = 147456;
constexpr uint32_t SMEM_BYTES = 232448;
constexpr uint32_t B_R1 = MISC + 1856  , B_MK = MISC + 48, B_LN = MISC + 56, B_MQ = MISC + 64,
                   B_H1 = MISC + 88, B_H2 = MISC + 96, B_H3 = MISC + 104,
                   B_KV = MISC + 112, B_P = MISC + 136, B_GO = MISC + 160, B_UC = MISC + 184  ,
                   B_X = MISC + 200, CNT = MISC + 208  , SCL = MISC + 512  ,
                   LINV = MISC + 1280  , STAT = MISC + 2048  ,
                   B_R2 = MISC + 1536  , B_E2 = MISC + 1696  ;

__device__ __forceinline__ uint32_t smem_u32(const void* p) { return (uint32_t)__cvta_generic_to_shared(p); }
__device__ __forceinline__ void wg_fence() { asm volatile("wgmma.fence.sync.aligned;" ::: "memory"); }
__device__ __forceinline__ void wg_commit() { asm volatile("wgmma.commit_group.sync.aligned;" ::: "memory"); }
template <int N> __device__ __forceinline__ void wg_wait() { asm volatile("wgmma.wait_group.sync.aligned %0;" ::"n"(N) : "memory"); }
__device__ __forceinline__ uint64_t dsc(uint32_t sd, uint32_t off, uint32_t lbo) {
    uint32_t lo = sd + (off >> 4) + ((lbo >> 4) << 16);
    uint64_t d;
    asm("mov.b64 %0, {%1, %2};" : "=l"(d) : "r"(lo), "r"((1024u >> 4) | (1u << 30)));
    return d;
}
__device__ __forceinline__ bool elect1() {
    uint32_t p;
    asm volatile("{\n.reg .pred p;\nelect.sync _|p, 0xffffffff;\nselp.u32 %0, 1, 0, p;\n}\n" : "=r"(p));
    return p != 0;
}
__device__ __forceinline__ void mbar_init(uint32_t bar, int cnt) { asm volatile("mbarrier.init.shared::cta.b64 [%0], %1;" ::"r"(bar), "r"(cnt) : "memory"); }
__device__ __forceinline__ void mbar_expect_tx(uint32_t bar, uint32_t bytes) { asm volatile("mbarrier.arrive.expect_tx.shared::cta.b64 _, [%0], %1;" ::"r"(bar), "r"(bytes) : "memory"); }
__device__ __forceinline__ void mbar_arrive(uint32_t bar) { asm volatile("mbarrier.arrive.shared::cta.b64 _, [%0];" ::"r"(bar) : "memory"); }
__device__ __forceinline__ void mbar_wait(uint32_t bar, uint32_t parity) {
    uint32_t ok;
#pragma unroll 1
    for (uint32_t it = 0;; ++it) {
        asm volatile("{\n.reg .pred p;\nmbarrier.try_wait.parity.shared::cta.b64 p, [%1], %2;\nselp.u32 %0, 1, 0, p;\n}\n" : "=r"(ok) : "r"(bar), "r"(parity) : "memory");
        if (ok) break;
        if (it > (1u << 20)) __trap();
    }
}
__device__ __forceinline__ bool mbar_test(uint32_t bar, uint32_t parity) {
    uint32_t ok;
    asm volatile("{\n.reg .pred p;\nmbarrier.test_wait.parity.shared::cta.b64 p, [%1], %2;\nselp.u32 %0, 1, 0, p;\n}\n" : "=r"(ok) : "r"(bar), "r"(parity) : "memory");
    return ok != 0;
}
__device__ __forceinline__ void fence_async() { asm volatile("fence.proxy.async.shared::cta;" ::: "memory"); }
__device__ __forceinline__ void fence_async_g() { asm volatile("fence.proxy.async.global;" ::: "memory"); }
__device__ __forceinline__ void bar_sync(int id, int n) { asm volatile("bar.sync %0, %1;" ::"r"(id), "r"(n) : "memory"); }
__device__ __forceinline__ void tma3(uint32_t dst, const CUtensorMap* tm, int c0, int c1, int c2, uint32_t bar) {
    asm volatile("cp.async.bulk.tensor.3d.shared::cluster.global.mbarrier::complete_tx::bytes [%0], [%1, {%3, %4, %5}], [%2];"
                 ::"r"(dst), "l"(tm), "r"(bar), "r"(c0), "r"(c1), "r"(c2) : "memory");
}
__device__ __forceinline__ void tma4(uint32_t dst, const CUtensorMap* tm, int c0, int c1, int c2, int c3, uint32_t bar) {
    asm volatile("cp.async.bulk.tensor.4d.shared::cluster.global.mbarrier::complete_tx::bytes [%0], [%1, {%3, %4, %5, %6}], [%2];"
                 ::"r"(dst), "l"(tm), "r"(bar), "r"(c0), "r"(c1), "r"(c2), "r"(c3) : "memory");
}
__device__ __forceinline__ void tma4_store(const CUtensorMap* tm, uint32_t src, int c0, int c1, int c2, int c3) {
    asm volatile("cp.async.bulk.tensor.4d.global.shared::cta.bulk_group [%0, {%2, %3, %4, %5}], [%1];"
                 ::"l"(tm), "r"(src), "r"(c0), "r"(c1), "r"(c2), "r"(c3) : "memory");
}
__device__ __forceinline__ void tma3_store(const CUtensorMap* tm, uint32_t src, int c0, int c1, int c2) {
    asm volatile("cp.async.bulk.tensor.3d.global.shared::cta.bulk_group [%0, {%2, %3, %4}], [%1];"
                 ::"l"(tm), "r"(src), "r"(c0), "r"(c1), "r"(c2) : "memory");
}
__device__ __forceinline__ void stsm4(uint32_t addr, uint32_t a, uint32_t b, uint32_t c, uint32_t d) {
    asm volatile("stmatrix.sync.aligned.m8n8.x4.shared.b16 [%0], {%1, %2, %3, %4};" ::"r"(addr), "r"(a), "r"(b), "r"(c), "r"(d) : "memory");
}
__device__ __forceinline__ void ldsm4(uint32_t addr, uint32_t (&r)[4]) {
    asm volatile("ldmatrix.sync.aligned.m8n8.x4.shared.b16 {%0, %1, %2, %3}, [%4];" : "=r"(r[0]), "=r"(r[1]), "=r"(r[2]), "=r"(r[3]) : "r"(addr) : "memory");
}
__device__ __forceinline__ void ldsm2(uint32_t addr, uint32_t (&r)[2]) {
    asm volatile("ldmatrix.sync.aligned.m8n8.x2.shared.b16 {%0, %1}, [%2];" : "=r"(r[0]), "=r"(r[1]) : "r"(addr) : "memory");
}
__device__ __forceinline__ void stg4(void* p, uint32_t a, uint32_t b, uint32_t c, uint32_t d) {
    asm volatile("st.global.v4.u32 [%0], {%1, %2, %3, %4};" ::"l"(p), "r"(a), "r"(b), "r"(c), "r"(d) : "memory");
}
__device__ __forceinline__ void hmma(float (&c)[4], uint32_t a0, uint32_t a1, uint32_t a2, uint32_t a3, uint32_t b0, uint32_t b1) {
    asm("mma.sync.aligned.m16n8k16.row.col.f32.bf16.bf16.f32 {%0, %1, %2, %3}, {%4, %5, %6, %7}, {%8, %9}, {%0, %1, %2, %3};"
        : "+f"(c[0]), "+f"(c[1]), "+f"(c[2]), "+f"(c[3]) : "r"(a0), "r"(a1), "r"(a2), "r"(a3), "r"(b0), "r"(b1));
}
__device__ __forceinline__ uint32_t pack2(float lo, float hi) {
    uint32_t r;
    asm("cvt.rn.bf16x2.f32 %0, %1, %2;" : "=r"(r) : "f"(hi), "f"(lo));
    return r;
}
__device__ __forceinline__ uint32_t pack2v(float lo, float hi) {
    uint32_t r;
    asm volatile("cvt.rn.bf16x2.f32 %0, %1, %2;" : "=r"(r) : "f"(hi), "f"(lo));
    return r;
}
__device__ __forceinline__ uint32_t bmul2(uint32_t a, uint32_t b) { uint32_t r; asm("mul.rn.bf16x2 %0, %1, %2;" : "=r"(r) : "r"(a), "r"(b)); return r; }
__device__ __forceinline__ uint32_t bfma2(uint32_t a, uint32_t b, uint32_t c) { uint32_t r; asm("fma.rn.bf16x2 %0, %1, %2, %3;" : "=r"(r) : "r"(a), "r"(b), "r"(c)); return r; }
__device__ __forceinline__ float ex2(float x) { float r; asm("ex2.approx.ftz.f32 %0, %1;" : "=f"(r) : "f"(x)); return r; }
__device__ __forceinline__ float rcp(float x) { float r; asm("rcp.approx.ftz.f32 %0, %1;" : "=f"(r) : "f"(x)); return r; }
__device__ __forceinline__ float gelu2(float x) {
    float t = fmaf(x * x, 0.044715f * 0.7978845608028654f, 0.7978845608028654f), th;
    asm("tanh.approx.f32 %0, %1;" : "=f"(th) : "f"(x * t));
    return fmaf(x, th, x);
}
__device__ __forceinline__ uint32_t ldg_v(const uint32_t* p) { uint32_t v; asm volatile("ld.global.nc.u32 %0, [%1];" : "=r"(v) : "l"(p)); return v; }
__device__ __forceinline__ uint32_t ldg_cg(const uint32_t* p) { uint32_t v; asm volatile("ld.global.cg.u32 %0, [%1];" : "=r"(v) : "l"(p) : "memory"); return v; }
__device__ __forceinline__ float lds_f32(uint32_t a) { float v; asm volatile("ld.shared.f32 %0, [%1];" : "=f"(v) : "r"(a) : "memory"); return v; }
__device__ __forceinline__ void sts_f32(uint32_t a, float v) { asm volatile("st.shared.f32 [%0], %1;" ::"r"(a), "f"(v) : "memory"); }
__device__ __forceinline__ void red_f32(uint32_t a, float v) { asm volatile("red.shared.add.f32 [%0], %1;" ::"r"(a), "f"(v) : "memory"); }
__device__ __forceinline__ uint32_t atom_inc_s(uint32_t a) { uint32_t v; asm volatile("atom.relaxed.cta.shared.add.u32 %0, [%1], 1;" : "=r"(v) : "r"(a) : "memory"); return v; }
__device__ __forceinline__ void lds4(uint32_t a, uint32_t* r) {
    asm volatile("ld.shared.v4.u32 {%0, %1, %2, %3}, [%4];" : "=r"(r[0]), "=r"(r[1]), "=r"(r[2]), "=r"(r[3]) : "r"(a) : "memory");
}
__device__ __forceinline__ void sts4(uint32_t a, uint32_t x, uint32_t y, uint32_t z, uint32_t t) {
    asm volatile("st.shared.v4.u32 [%0], {%1, %2, %3, %4};" ::"r"(a), "r"(x), "r"(y), "r"(z), "r"(t) : "memory");
}
__device__ __forceinline__ uint32_t bsub2(uint32_t a, uint32_t b) { uint32_t r; asm("sub.rn.bf16x2 %0, %1, %2;" : "=r"(r) : "r"(a), "r"(b)); return r; }
__device__ __forceinline__ float blo(uint32_t v) { return __uint_as_float(v << 16); }
__device__ __forceinline__ float bhi(uint32_t v) { return __uint_as_float(v & 0xffff0000u); }
__device__ __forceinline__ float bfr(float x) { return __bfloat162float(__float2bfloat16_rn(x)); }
__device__ __forceinline__ void l2_prefetch(const void* p, uint32_t bytes) { asm volatile("cp.async.bulk.prefetch.L2.global [%0], %1;" ::"l"(p), "r"(bytes) : "memory"); }
__device__ __forceinline__ void flag_add(unsigned* p) { asm volatile("red.release.gpu.global.add.u32 [%0], 1;" ::"l"(p) : "memory"); }
__device__ __forceinline__ void flag_wait(const unsigned* p, unsigned target) {
#pragma unroll 1
    for (uint32_t it = 0;; ++it) {
        unsigned v;
        asm volatile("ld.acquire.gpu.global.u32 %0, [%1];" : "=r"(v) : "l"(p) : "memory");
        if (v >= target) break;
        if (it > (1u << 20)) __trap();
    }
    fence_async_g();
}
template <int N> __device__ __forceinline__ void pin(float (&a)[N]) {
#pragma unroll
    for (int i = 0; i < N; i++) asm volatile("" : "+f"(a[i])::"memory");
}

template <int N> __device__ __forceinline__ void fresh(float (&a)[N]) {
#pragma unroll
    for (int i = 0; i < N; i++) a[i] = 0.f;
    pin(a);
}

__device__ __forceinline__ void wgmma_rs_n32_tb0(float (&d)[16], uint32_t a0, uint32_t a1, uint32_t a2, uint32_t a3, uint64_t db, int scale_d) {
    asm volatile("{\n.reg .pred p;\nsetp.ne.b32 p, %21, 0;\n"
        "wgmma.mma_async.sync.aligned.m64n32k16.f32.bf16.bf16 {%0, %1, %2, %3, %4, %5, %6, %7, %8, %9, %10, %11, %12, %13, %14, %15}, {%16, %17, %18, %19}, %20, p, 1, 1, 0;\n}\n"
        : "+f"(d[0]), "+f"(d[1]), "+f"(d[2]), "+f"(d[3]), "+f"(d[4]), "+f"(d[5]), "+f"(d[6]), "+f"(d[7]), "+f"(d[8]), "+f"(d[9]), "+f"(d[10]), "+f"(d[11]), "+f"(d[12]), "+f"(d[13]), "+f"(d[14]), "+f"(d[15])
        : "r"(a0), "r"(a1), "r"(a2), "r"(a3), "l"(db), "r"(scale_d));
}

__device__ __forceinline__ void wgmma_rs_n64_tb0(float (&d)[32], uint32_t a0, uint32_t a1, uint32_t a2, uint32_t a3, uint64_t db, int scale_d) {
    asm volatile("{\n.reg .pred p;\nsetp.ne.b32 p, %37, 0;\n"
        "wgmma.mma_async.sync.aligned.m64n64k16.f32.bf16.bf16 {%0, %1, %2, %3, %4, %5, %6, %7, %8, %9, %10, %11, %12, %13, %14, %15, %16, %17, %18, %19, %20, %21, %22, %23, %24, %25, %26, %27, %28, %29, %30, %31}, {%32, %33, %34, %35}, %36, p, 1, 1, 0;\n}\n"
        : "+f"(d[0]), "+f"(d[1]), "+f"(d[2]), "+f"(d[3]), "+f"(d[4]), "+f"(d[5]), "+f"(d[6]), "+f"(d[7]), "+f"(d[8]), "+f"(d[9]), "+f"(d[10]), "+f"(d[11]), "+f"(d[12]), "+f"(d[13]), "+f"(d[14]), "+f"(d[15]), "+f"(d[16]), "+f"(d[17]), "+f"(d[18]), "+f"(d[19]), "+f"(d[20]), "+f"(d[21]), "+f"(d[22]), "+f"(d[23]), "+f"(d[24]), "+f"(d[25]), "+f"(d[26]), "+f"(d[27]), "+f"(d[28]), "+f"(d[29]), "+f"(d[30]), "+f"(d[31])
        : "r"(a0), "r"(a1), "r"(a2), "r"(a3), "l"(db), "r"(scale_d));
}

__device__ __forceinline__ void wgmma_ss_n128_tb1(float (&d)[64], uint64_t da, uint64_t db, int scale_d) {
    asm volatile("{\n.reg .pred p;\nsetp.ne.b32 p, %66, 0;\n"
        "wgmma.mma_async.sync.aligned.m64n128k16.f32.bf16.bf16 {%0, %1, %2, %3, %4, %5, %6, %7, %8, %9, %10, %11, %12, %13, %14, %15, %16, %17, %18, %19, %20, %21, %22, %23, %24, %25, %26, %27, %28, %29, %30, %31, %32, %33, %34, %35, %36, %37, %38, %39, %40, %41, %42, %43, %44, %45, %46, %47, %48, %49, %50, %51, %52, %53, %54, %55, %56, %57, %58, %59, %60, %61, %62, %63}, %64, %65, p, 1, 1, 0, 1;\n}\n"
        : "+f"(d[0]), "+f"(d[1]), "+f"(d[2]), "+f"(d[3]), "+f"(d[4]), "+f"(d[5]), "+f"(d[6]), "+f"(d[7]), "+f"(d[8]), "+f"(d[9]), "+f"(d[10]), "+f"(d[11]), "+f"(d[12]), "+f"(d[13]), "+f"(d[14]), "+f"(d[15]), "+f"(d[16]), "+f"(d[17]), "+f"(d[18]), "+f"(d[19]), "+f"(d[20]), "+f"(d[21]), "+f"(d[22]), "+f"(d[23]), "+f"(d[24]), "+f"(d[25]), "+f"(d[26]), "+f"(d[27]), "+f"(d[28]), "+f"(d[29]), "+f"(d[30]), "+f"(d[31]), "+f"(d[32]), "+f"(d[33]), "+f"(d[34]), "+f"(d[35]), "+f"(d[36]), "+f"(d[37]), "+f"(d[38]), "+f"(d[39]), "+f"(d[40]), "+f"(d[41]), "+f"(d[42]), "+f"(d[43]), "+f"(d[44]), "+f"(d[45]), "+f"(d[46]), "+f"(d[47]), "+f"(d[48]), "+f"(d[49]), "+f"(d[50]), "+f"(d[51]), "+f"(d[52]), "+f"(d[53]), "+f"(d[54]), "+f"(d[55]), "+f"(d[56]), "+f"(d[57]), "+f"(d[58]), "+f"(d[59]), "+f"(d[60]), "+f"(d[61]), "+f"(d[62]), "+f"(d[63])
        : "l"(da), "l"(db), "r"(scale_d));
}

__device__ __forceinline__ void wgmma_ss_n256_tb1(float (&d)[128], uint64_t da, uint64_t db, int scale_d) {
    asm volatile("{\n.reg .pred p;\nsetp.ne.b32 p, %130, 0;\n"
        "wgmma.mma_async.sync.aligned.m64n256k16.f32.bf16.bf16 {%0, %1, %2, %3, %4, %5, %6, %7, %8, %9, %10, %11, %12, %13, %14, %15, %16, %17, %18, %19, %20, %21, %22, %23, %24, %25, %26, %27, %28, %29, %30, %31, %32, %33, %34, %35, %36, %37, %38, %39, %40, %41, %42, %43, %44, %45, %46, %47, %48, %49, %50, %51, %52, %53, %54, %55, %56, %57, %58, %59, %60, %61, %62, %63, %64, %65, %66, %67, %68, %69, %70, %71, %72, %73, %74, %75, %76, %77, %78, %79, %80, %81, %82, %83, %84, %85, %86, %87, %88, %89, %90, %91, %92, %93, %94, %95, %96, %97, %98, %99, %100, %101, %102, %103, %104, %105, %106, %107, %108, %109, %110, %111, %112, %113, %114, %115, %116, %117, %118, %119, %120, %121, %122, %123, %124, %125, %126, %127}, %128, %129, p, 1, 1, 0, 1;\n}\n"
        : "+f"(d[0]), "+f"(d[1]), "+f"(d[2]), "+f"(d[3]), "+f"(d[4]), "+f"(d[5]), "+f"(d[6]), "+f"(d[7]), "+f"(d[8]), "+f"(d[9]), "+f"(d[10]), "+f"(d[11]), "+f"(d[12]), "+f"(d[13]), "+f"(d[14]), "+f"(d[15]), "+f"(d[16]), "+f"(d[17]), "+f"(d[18]), "+f"(d[19]), "+f"(d[20]), "+f"(d[21]), "+f"(d[22]), "+f"(d[23]), "+f"(d[24]), "+f"(d[25]), "+f"(d[26]), "+f"(d[27]), "+f"(d[28]), "+f"(d[29]), "+f"(d[30]), "+f"(d[31]), "+f"(d[32]), "+f"(d[33]), "+f"(d[34]), "+f"(d[35]), "+f"(d[36]), "+f"(d[37]), "+f"(d[38]), "+f"(d[39]), "+f"(d[40]), "+f"(d[41]), "+f"(d[42]), "+f"(d[43]), "+f"(d[44]), "+f"(d[45]), "+f"(d[46]), "+f"(d[47]), "+f"(d[48]), "+f"(d[49]), "+f"(d[50]), "+f"(d[51]), "+f"(d[52]), "+f"(d[53]), "+f"(d[54]), "+f"(d[55]), "+f"(d[56]), "+f"(d[57]), "+f"(d[58]), "+f"(d[59]), "+f"(d[60]), "+f"(d[61]), "+f"(d[62]), "+f"(d[63]), "+f"(d[64]), "+f"(d[65]), "+f"(d[66]), "+f"(d[67]), "+f"(d[68]), "+f"(d[69]), "+f"(d[70]), "+f"(d[71]), "+f"(d[72]), "+f"(d[73]), "+f"(d[74]), "+f"(d[75]), "+f"(d[76]), "+f"(d[77]), "+f"(d[78]), "+f"(d[79]), "+f"(d[80]), "+f"(d[81]), "+f"(d[82]), "+f"(d[83]), "+f"(d[84]), "+f"(d[85]), "+f"(d[86]), "+f"(d[87]), "+f"(d[88]), "+f"(d[89]), "+f"(d[90]), "+f"(d[91]), "+f"(d[92]), "+f"(d[93]), "+f"(d[94]), "+f"(d[95]), "+f"(d[96]), "+f"(d[97]), "+f"(d[98]), "+f"(d[99]), "+f"(d[100]), "+f"(d[101]), "+f"(d[102]), "+f"(d[103]), "+f"(d[104]), "+f"(d[105]), "+f"(d[106]), "+f"(d[107]), "+f"(d[108]), "+f"(d[109]), "+f"(d[110]), "+f"(d[111]), "+f"(d[112]), "+f"(d[113]), "+f"(d[114]), "+f"(d[115]), "+f"(d[116]), "+f"(d[117]), "+f"(d[118]), "+f"(d[119]), "+f"(d[120]), "+f"(d[121]), "+f"(d[122]), "+f"(d[123]), "+f"(d[124]), "+f"(d[125]), "+f"(d[126]), "+f"(d[127])
        : "l"(da), "l"(db), "r"(scale_d));
}

__device__ __forceinline__ void wgmma_ss_n32_tb0(float (&d)[16], uint64_t da, uint64_t db, int scale_d) {
    asm volatile("{\n.reg .pred p;\nsetp.ne.b32 p, %18, 0;\n"
        "wgmma.mma_async.sync.aligned.m64n32k16.f32.bf16.bf16 {%0, %1, %2, %3, %4, %5, %6, %7, %8, %9, %10, %11, %12, %13, %14, %15}, %16, %17, p, 1, 1, 0, 0;\n}\n"
        : "+f"(d[0]), "+f"(d[1]), "+f"(d[2]), "+f"(d[3]), "+f"(d[4]), "+f"(d[5]), "+f"(d[6]), "+f"(d[7]), "+f"(d[8]), "+f"(d[9]), "+f"(d[10]), "+f"(d[11]), "+f"(d[12]), "+f"(d[13]), "+f"(d[14]), "+f"(d[15])
        : "l"(da), "l"(db), "r"(scale_d));
}

__device__ __forceinline__ void wgmma_ss_n64_tb0(float (&d)[32], uint64_t da, uint64_t db, int scale_d) {
    asm volatile("{\n.reg .pred p;\nsetp.ne.b32 p, %34, 0;\n"
        "wgmma.mma_async.sync.aligned.m64n64k16.f32.bf16.bf16 {%0, %1, %2, %3, %4, %5, %6, %7, %8, %9, %10, %11, %12, %13, %14, %15, %16, %17, %18, %19, %20, %21, %22, %23, %24, %25, %26, %27, %28, %29, %30, %31}, %32, %33, p, 1, 1, 0, 0;\n}\n"
        : "+f"(d[0]), "+f"(d[1]), "+f"(d[2]), "+f"(d[3]), "+f"(d[4]), "+f"(d[5]), "+f"(d[6]), "+f"(d[7]), "+f"(d[8]), "+f"(d[9]), "+f"(d[10]), "+f"(d[11]), "+f"(d[12]), "+f"(d[13]), "+f"(d[14]), "+f"(d[15]), "+f"(d[16]), "+f"(d[17]), "+f"(d[18]), "+f"(d[19]), "+f"(d[20]), "+f"(d[21]), "+f"(d[22]), "+f"(d[23]), "+f"(d[24]), "+f"(d[25]), "+f"(d[26]), "+f"(d[27]), "+f"(d[28]), "+f"(d[29]), "+f"(d[30]), "+f"(d[31])
        : "l"(da), "l"(db), "r"(scale_d));
}

struct Maps {
    CUtensorMap xa, xa2, xa4, xas, wup4, wup8, mqa2, mqa4, mqb1, mqb2, uc, x, out, wq, wk, fa[3], fb[2], fc;
};

__device__ __forceinline__ uint64_t mkd(uint32_t lo) {
    uint64_t d;
    asm("mov.b64 %0, {%1, %2};" : "=l"(d) : "r"(lo), "r"((1024u >> 4) | (1u << 30)));
    return d;
}
__device__ __forceinline__ void bulk_ld(uint32_t dst, const void* src, uint32_t bytes, uint32_t bar) {
    asm volatile("cp.async.bulk.shared::cluster.global.mbarrier::complete_tx::bytes [%0], [%1], %2, [%3];" ::"r"(dst), "l"(src), "r"(bytes), "r"(bar) : "memory");
}
__device__ __forceinline__ void bulk_st(void* dst, uint32_t src, uint32_t bytes) {
    asm volatile("cp.async.bulk.global.shared::cta.bulk_group [%0], [%1], %2;" ::"l"(dst), "r"(src), "r"(bytes) : "memory");
}
__device__ __forceinline__ void ring_ld(uint32_t sb, uint32_t slot8, int n) {
    mbar_expect_tx(sb + B_R2 + slot8, 8192);
    bulk_ld(sb + R1 + slot8 * 1024, (const char*)g_wepi + n * 8192, 8192, sb + B_R2 + slot8);
}

__device__ __forceinline__ void ring_half(uint32_t sb, uint32_t slot8, uint32_t hoff, const CUtensorMap* tm, int c1, int c2) {
    mbar_expect_tx(sb + B_R1 + slot8, 8192);
    tma3(sb + slot8 * 2048 + hoff, tm, 0, c1, c2, sb + B_R1 + slot8);
}
__device__ __forceinline__ void ring_full(uint32_t sb, uint32_t slot8, const CUtensorMap* tm, int c1, int c2) {
    mbar_expect_tx(sb + B_R1 + slot8, 16384);
    mbar_arrive(sb + B_R1 + slot8);
    tma3(sb + slot8 * 2048, tm, 0, c1, c2, sb + B_R1 + slot8);
}
__device__ __forceinline__ void cta_done(int mode) {
    if (mode == 0 && atomicAdd(&g_sync[4], 1) == NCTA + 1) {
#pragma unroll
        for (int i = 0; i < 5; i++) g_sync[i] = 0;
    }
}

__device__ __forceinline__ void fold_cta(const Maps& mp, uint32_t sb, int mode) {
    constexpr uint32_t F_FULL = MISC, F_EMPTY = MISC + 32, F_T1 = MISC + 64, STG = 49152, FOUT = 3 * STG;
    const int tid = threadIdx.x, f = blockIdx.x - NCTA;
    if (mode == 2) return;
    if (tid == 0) {
        for (int i = 0; i < 3; i++) { mbar_init(sb + F_FULL + 8 * i, 1); mbar_init(sb + F_EMPTY + 8 * i, 2); }
        mbar_init(sb + F_T1, 2);
        asm volatile("fence.mbarrier_init.release.cluster;" ::: "memory");
        fence_async();
    }
    __syncthreads();
    const int wg = __shfl_sync(0xffffffffu, tid >> 7, 0);
    int st = 0, ph = 0;
    if (wg == 0) {
        if (tid == 0) {
#pragma unroll 1
            for (int it = 0; it < 96; it++) {
                const int p = it >> 3, kc = it & 7, job = p >> 2;
                if (it == 64) mbar_wait(sb + F_T1, 0);
                mbar_wait(sb + F_EMPTY + 8 * st, ph ^ 1);
                mbar_expect_tx(sb + F_FULL + 8 * st, STG);
                tma3(sb + st * STG, &mp.fa[job], 0, 256 * f + 128 * ((p >> 1) & 1), kc, sb + F_FULL + 8 * st);
                tma3(sb + st * STG + 16384, &mp.fb[job != 0], 0, 64 * kc + (job == 1 ? 512 : 0), 4 * (p & 1), sb + F_FULL + 8 * st);
                if (++st == 3) { st = 0; ph ^= 1; }
            }
        }
        return;
    }
    const int h = wg - 1, lane = tid & 31, w = (tid >> 5) & 3;
    const uint32_t sd = (sb & 0x3FFFF) >> 4;
    const bool el = (tid & 127) == 0;
#pragma unroll 1
    for (int p = 0; p < 12; p++) {
        float acc[128];
        fresh(acc);
#pragma unroll 1
        for (int kc = 0; kc < 8; kc++) {
            mbar_wait(sb + F_FULL + 8 * st, ph);
            wg_fence();
#pragma unroll
            for (int kk = 0; kk < 4; kk++)
                wgmma_ss_n256_tb1(acc, dsc(sd, st * STG + h * 8192 + kk * 32, 16), dsc(sd, st * STG + 16384 + kk * 2048, 8192), 1);
            wg_commit();
            wg_wait<0>();
            if (el) mbar_arrive(sb + F_EMPTY + 8 * st);
            if (++st == 3) { st = 0; ph ^= 1; }
        }
        pin(acc);
        const int job = p >> 2;
        if (el) {
            asm volatile("cp.async.bulk.wait_group 0;" ::: "memory");
            if (p == 4) { fence_async_g(); mbar_arrive(sb + F_T1); }
        }
        bar_sync(3 + h, 128);
        uint32_t r = 16 * w + (lane & 7) + ((lane >> 3) & 1) * 8;
        const float fs = job == 1 ? 0.5f : 1.f;
        if (job == 1) r = (r & ~31) | (((r >> 1) & 3) << 3) | (((r >> 3) & 3) << 1) | (r & 1);
        const uint32_t oa = sb + FOUT + h * 32768 + r * 128 + ((((lane >> 4) ^ r) & 7) << 4);
#pragma unroll
        for (int i = 0; i < 16; i++)
            stsm4((oa ^ ((i & 3) << 5)) + (i >> 2) * 8192, pack2(acc[8 * i] * fs, acc[8 * i + 1] * fs), pack2(acc[8 * i + 2] * fs, acc[8 * i + 3] * fs),
                  pack2(acc[8 * i + 4] * fs, acc[8 * i + 5] * fs), pack2(acc[8 * i + 6] * fs, acc[8 * i + 7] * fs));
        fence_async();
        bar_sync(3 + h, 128);
        if (el) {
            const int row0 = 256 * f + 128 * ((p >> 1) & 1) + 64 * h + (job == 1 ? 512 : 0);
            if (job == 0) tma3_store(&mp.fc, sb + FOUT + h * 32768, 0, row0, 4 * (p & 1));
            else {
#pragma unroll 1
                for (int i = 0; i < 16; i++)
                    bulk_st((char*)g_wepi + (row0 / 8 + 2 * (i & 3) + (p & 1)) * 8192 + (i >> 2) * 2048, sb + FOUT + h * 32768 + i * 2048, 2048);
            }
            asm volatile("cp.async.bulk.commit_group;" ::: "memory");
        }
    }
    if (el) {
        asm volatile("cp.async.bulk.wait_group 0;" ::: "memory");
        fence_async_g();
        if (mode == 0) flag_add(&g_sync[3]);
    }
    bar_sync(2, 256);
    if (tid == 128) cta_done(mode);
}

__global__ void __launch_bounds__(384, 1) main_kernel(const __grid_constant__ Maps mp, const bf16* __restrict__ x, const bf16* __restrict__ dw, const bf16* wup, const int mode) {
    extern __shared__ __align__(1024) uint8_t smem[];
    const uint32_t sb = smem_u32(smem);
    const int tid = threadIdx.x;
    PE();
    if (blockIdx.x >= NCTA) { fold_cta(mp, sb, mode); return; }
    const int b = blockIdx.x / TPB, ti = blockIdx.x % TPB;
    const int piece = blockIdx.x & 127;
    const int wg = __shfl_sync(0xffffffffu, tid >> 7, 0);
    const int lane = tid & 31, w = (tid >> 5) & 3;
    const bool w0 = __shfl_sync(0xffffffffu, w, 0) == 0;
    const uint32_t sd = (sb & 0x3FFFF) >> 4;
    const uint32_t adA = sd + (AT >> 4) + (1u << 16);
    const uint32_t bd0 = sd;
    const uint32_t bd2k = bd0 + ((2048u >> 4) << 16);
    const bool el = (tid & 127) == 0;
    const uint32_t lrow = 16 * w + (lane & 7) + ((lane >> 3) & 1) * 8;
    const uint32_t loff = lrow * 128 + ((((lane >> 4) ^ lrow) & 7) << 4);
    const int r0 = 16 * w + (lane >> 2);

    if (wg == 0) {
        asm volatile("setmaxnreg.inc.sync.aligned.u32 184;");
        uint32_t q[112];
        PG(206);
        if (tid == 0) {
            mbar_init(sb + B_MK, 1);
            for (int i = 0; i < 9; i++) mbar_init(sb + B_R1 + 8 * i, 2);
            for (int i = 0; i < 5; i++) asm volatile("st.shared.u32 [%0], 0;" ::"r"(sb + CNT + 4 * i) : "memory");
        } else if (tid == 32) {
            mbar_init(sb + B_LN, 1); mbar_init(sb + B_MQ, 1);
            mbar_init(sb + B_H1, 2); mbar_init(sb + B_H2, 1); mbar_init(sb + B_H3, 2);
            for (int i = 0; i < 3; i++) { mbar_init(sb + B_KV + 8 * i, 2); mbar_init(sb + B_P + 8 * i, 4); mbar_init(sb + B_GO + 8 * i, 4); }
            mbar_init(sb + B_UC, 1); mbar_init(sb + B_UC + 8, 1); mbar_init(sb + B_X, 8);
        } else if (tid == 64) {
            for (int i = 0; i < 20; i++) mbar_init(sb + B_R2 + 8 * i, 1);
        } else if (tid == 96) {
            for (int i = 0; i < 20; i++) mbar_init(sb + B_E2 + 8 * i, 4);
        }
        sts_f32(sb + STAT + 4 * tid, 0.f);
        if (lane == 0) {
            asm volatile("fence.mbarrier_init.release.cluster;" ::: "memory");
            fence_async();
        }
        PG(207);
        __syncwarp();
        if (SU != 2) asm volatile("bar.arrive 5, 384;" ::: "memory");
        if (tid == 0) {
            mbar_expect_tx(sb + B_MK, 65536 + 32768);
            tma3(sb + 16384, &mp.wq, 0, 64 * (piece >> 4), 0, sb + B_MK);
            tma3(sb + 81920, &mp.wk, 0, 32 * (piece & 15), 0, sb + B_MK);
            for (int i = 0; i < 14; i++) mbar_arrive(sb + B_R1 + 8 * (i >> 1));
            if (mode != 1) {
                ring_full(sb, 56, &mp.wup8, 0, 0);
                ring_full(sb, 64, &mp.wup8, 16, 0);
                ring_full(sb, 0, &mp.wup8, 32, 0);
            }
        }
        PG(208);
        bar_sync(1, 128);
        if (SU == 2) asm volatile("bar.arrive 5, 384;" ::: "memory");
        PT(0);
        PG(200);
        {
            float mq[16];
            fresh(mq);
            mbar_wait(sb + B_MK, 0);
            PT(1);
            if (tid == 32) l2_prefetch((const char*)wup + piece * 8192, 8192);
            wg_fence();
#pragma unroll 1
            for (int c = 0; c < 8; c++)
#pragma unroll
                for (int kk = 0; kk < 4; kk++)
                    wgmma_ss_n32_tb0(mq, dsc(sd, 16384 + c * 8192 + kk * 32, 16), dsc(sd, 81920 + c * 4096 + kk * 32, 16), 1);
            wg_commit();
            wg_wait<0>();
            if (mode != 1 && w0 && elect1()) {
#pragma unroll 1
                for (int i = 1; i < 7; i++) ring_full(sb, 8 * i, &mp.wup8, 32 + 16 * i, 0);
            }
            pin(mq);
            uint32_t* c = reinterpret_cast<uint32_t*>(g_mqk + (64 * (piece >> 4) + r0) * D_ + 32 * (piece & 15) + 2 * (lane & 3));
#pragma unroll
            for (int n = 0; n < 4; n++) { c[4 * n] = pack2(mq[4 * n], mq[4 * n + 1]); c[4 * n + 4 * D_] = pack2(mq[4 * n + 2], mq[4 * n + 3]); }
            fence_async_g();
            bar_sync(1, 128);
            if (el) {
                if (mode == 0) flag_add(&g_sync[2]);
                if (mode == 0) flag_wait(&g_sync[2], NCTA);
                mbar_arrive(sb + B_MQ);
                PG(203);
                mbar_wait(sb + B_LN, 0);
#pragma unroll 1
                for (int c = 0; c < 8; c++) {
                    tma4_store(&mp.xas, sb + AT + c * 8192, 0, 62 * ti, c, b);
                    const unsigned t0 = (unsigned)clock();
                    while (c < 7 && (unsigned)clock() - t0 < XS_GAP) __nanosleep(20);
                }
                asm volatile("cp.async.bulk.commit_group;" ::: "memory");
                if (mode == 1) asm volatile("cp.async.bulk.wait_group 0;" ::: "memory");
            }
            PT(13);
            if (mode == 1) return;
        }
        mbar_wait(sb + B_H1, 0);
        PT(2);
        uint32_t slot8 = 24, par = 0, prev8 = 0, prev2 = 0;
        auto adv = [&]() { prev2 = prev8; prev8 = slot8; slot8 += 8; if (slot8 == 72) { slot8 = 0; par ^= 1; } };
        {
            float acc[128];
            fresh(acc);
            auto step = [&](int i) {
                const uint32_t aa = adA + (i >> 1) * 512 + (i & 1) * 4, bb = bd0 + ((4096u >> 4) << 16) + slot8 * 128;
                wg_fence();
                wgmma_ss_n256_tb1(acc, mkd(aa), mkd(bb), 1);
                wgmma_ss_n256_tb1(acc, mkd(aa + 2), mkd(bb + 128), 1);
                wg_commit();
                wg_wait<1 + LAGA>();
            };
#pragma unroll 1
            for (int i = 0; i < 8 + LAGA; i++) {
                mbar_wait(sb + B_R1 + slot8, par);
                step(i);
                if (i > LAGA && w0 && elect1()) ring_full(sb, LAGA ? prev2 : prev8, &mp.mqa4, 32 * (i - LAGA) + 256, 4);
                adv();
            }
#pragma unroll 1
            for (int i = 8 + LAGA; i < 16; i++) {
                mbar_wait(sb + B_R1 + slot8, par);
                if (i == 15 && el) mbar_arrive(sb + B_H2);
                step(i);
                if (w0 && elect1()) ring_full(sb, LAGA ? prev2 : prev8, &mp.wup8, 16 * (i - LAGA) - 128, 8);
                adv();
            }
            if (LAGA) {
                wg_wait<1>();
                if (w0 && elect1()) ring_full(sb, prev2, &mp.wup8, 112, 8);
            }
            wg_wait<0>();
            if (w0 && elect1()) ring_full(sb, prev8, &mp.wup8, 128, 8);
            pin(acc);
            PT(3);
#pragma unroll
            for (int kk = 0; kk < 4; kk++)
                stsm4((sb + QS + loff) ^ (kk << 5), pack2(acc[96 + 8 * kk], acc[97 + 8 * kk]), pack2(acc[98 + 8 * kk], acc[99 + 8 * kk]),
                      pack2(acc[100 + 8 * kk], acc[101 + 8 * kk]), pack2(acc[102 + 8 * kk], acc[103 + 8 * kk]));
            fence_async();
#pragma unroll
            for (int i = 47; i >= 0; i--) q[64 + i] = pack2v(acc[2 * i], acc[2 * i + 1]);
        }
        if (el) {
            asm volatile("cp.async.bulk.wait_group 0;" ::: "memory");
            if (mode == 0) {
                fence_async_g();
                flag_add(&g_sync[b]);
                flag_wait(&g_sync[b], TPB);
            }
        }
        __syncwarp();
        mbar_wait(sb + B_H3, 0);
        PT(4);
        slot8 = 48; par = 1;
#pragma unroll
        for (int half = 0; half < 2; half++) {
            float acc[64];
            fresh(acc);
            auto step = [&](int m) {
                const uint32_t aa = adA + m * 512, bb = bd0 + ((8192u >> 4) << 16) + slot8 * 128;
                mbar_wait(sb + B_R1 + slot8, par);
                wg_fence();
#pragma unroll
                for (int kk = 0; kk < 4; kk++) wgmma_ss_n128_tb1(acc, mkd(aa + 2 * kk), mkd(bb + 128 * kk), 1);
                wg_commit();
                wg_wait<1 + LAGB>();
            };
#pragma unroll 1
            for (int m = 0; m < 8; m++) {
                step(m);
                if (8 * half + m == GST) asm volatile("bar.arrive 6, 384;" ::: "memory");
                if (m > LAGB && w0 && elect1()) {
                    if (half == 0) ring_full(sb, LAGB ? prev2 : prev8, &mp.mqb2, 64 * (m - LAGB), 2);
                    else if (m < 4 + LAGB) tma4(sb + (LAGB ? prev2 : prev8) * 2048, &mp.xa2, 0, 0, 2 * (m - LAGB), b, sb + B_KV + 8);
                }
                adv();
            }
            if (LAGB && half == 0) {
                wg_wait<1>();
                if (w0 && elect1()) ring_full(sb, prev2, &mp.mqb2, 448, 2);
            }
            wg_wait<0>();
            if (w0 && elect1()) {
                if (half == 0) {
                    mbar_expect_tx(sb + B_KV + 8, 65536);
                    for (int i = 0; i < 3; i++) mbar_arrive(sb + B_KV + 8 * i);
                    tma4(sb + prev8 * 2048, &mp.xa2, 0, 0, 0, b, sb + B_KV + 8);
                } else {
                    mbar_expect_tx(sb + B_KV + 16, 65536);
                    tma4(sb + R2, &mp.xa, 0, 64, 0, b, sb + B_KV + 16);
                    mbar_expect_tx(sb + B_KV, 65536);
                    tma4(sb + R0, &mp.xa, 0, 128, 0, b, sb + B_KV);
                }
            }
            pin(acc);
#pragma unroll
            for (int i = 31; i >= 0; i--) q[32 * half + i] = pack2v(acc[2 * i], acc[2 * i + 1]);
        }
        bar_sync(1, 128);
        PT(5);

        const float CS = 0.04419417382415922f * 1.4426950408889634f;
        float m0 = -INFINITY, m1 = -INFINITY, l0 = 0.f, l1 = 0.f;
        int s = 0, sn = 1, ph = 0;
        float S[32];
        const bool l0w = lane == 0, q0 = (lane & 3) == 0;
#pragma unroll 1
        for (int j = -1;; j++) {
            if (j >= 0) {
                PL(j, 1);
                if (j == NKV - 1) {
#pragma unroll
                    for (int i = (T_ - 64 * (NKV - 1)) / 2; i < 32; i++) asm volatile("mov.b32 %0, 0xff800000;" : "=f"(S[i]));
                }
                const bool kv = mbar_test(sb + B_KV + sn * 8, ph);
                const uint32_t pb = sb + R3 + (s == 0 ? 2 : s - 1) * 8192;
                float a0 = 0.f, a1 = 0.f, sc0 = 1.f, sc1 = 1.f;
                auto expo = [&]() {
                    const float n0 = -m0 * CS, n1 = -m1 * CS;
                    a0 = 0.f; a1 = 0.f;
#pragma unroll
                    for (int kk = 0; kk < 4; kk++) {
                        float p[8];
#pragma unroll
                        for (int e = 0; e < 8; e++) p[e] = ex2(fmaf(S[8 * kk + e], CS, (e & 2) ? n1 : n0));
                        a0 += (p[0] + p[1]) + (p[4] + p[5]);
                        a1 += (p[2] + p[3]) + (p[6] + p[7]);
                        stsm4((pb + loff) ^ (kk << 5), pack2(p[0], p[1]), pack2(p[2], p[3]), pack2(p[4], p[5]), pack2(p[6], p[7]));
                    }
                };
                if (j > 0 || !SK0) expo();
                if ((SK0 && j == 0) || __any_sync(0xffffffffu, !(a0 <= LAZY) || !(a1 <= LAZY))) {
                    float x0 = m0, x1 = m1;
#pragma unroll
                    for (int n = 0; n < 8; n++) { x0 = fmaxf(x0, fmaxf(S[4 * n], S[4 * n + 1])); x1 = fmaxf(x1, fmaxf(S[4 * n + 2], S[4 * n + 3])); }
                    x0 = fmaxf(x0, __shfl_xor_sync(0xffffffffu, x0, 1));
                    x1 = fmaxf(x1, __shfl_xor_sync(0xffffffffu, x1, 1));
                    x0 = fmaxf(x0, __shfl_xor_sync(0xffffffffu, x0, 2));
                    x1 = fmaxf(x1, __shfl_xor_sync(0xffffffffu, x1, 2));
                    sc0 = ex2((m0 - x0) * CS); sc1 = ex2((m1 - x1) * CS);
                    m0 = x0; m1 = x1;
                    expo();
                }
                if (q0) { sts_f32(sb + SCL + s * 256 + r0 * 4, sc0); sts_f32(sb + SCL + s * 256 + r0 * 4 + 32, sc1); }
                __syncwarp();
                if (l0w) mbar_arrive(sb + B_P + s * 8);
                l0 = fmaf(l0, sc0, a0); l1 = fmaf(l1, sc1, a1);
                PL(j, 2);
                if (j == NKV - 1) break;
                if (!kv) mbar_wait(sb + B_KV + sn * 8, ph);
            } else {
                mbar_wait(sb + B_KV + 8, 0);
            }
            const uint32_t kd = sd + sn * 4096;
            if (TRIM & 2 && j == NKV - 2) {
                float Sn[16];
                wg_fence();
#pragma unroll
                for (int kk = 0; kk < 28; kk++) {
                    wgmma_rs_n32_tb0(Sn, q[4 * kk], q[4 * kk + 1], q[4 * kk + 2], q[4 * kk + 3], dsc(kd, (kk >> 2) * 8192 + (kk & 3) * 32, 16), kk > 0);
                    if (kk == FENCE_AT) { fence_async(); __syncwarp(); }
                    if (kk == GO_LAST && l0w) mbar_arrive(sb + B_GO + s * 8);
                }
#pragma unroll
                for (int kk = 0; kk < 4; kk++)
                    wgmma_ss_n32_tb0(Sn, dsc(sd, QS + kk * 32, 16), dsc(kd, 7 * 8192 + kk * 32, 16), 1);
                wg_commit();
                wg_wait<0>();
                pin(Sn);
#pragma unroll
                for (int i = 0; i < 16; i++) S[i] = Sn[i];
            } else {
            float Sn[32];
            wg_fence();
#pragma unroll
            for (int kk = 0; kk < 28; kk++) {
                wgmma_rs_n64_tb0(Sn, q[4 * kk], q[4 * kk + 1], q[4 * kk + 2], q[4 * kk + 3], dsc(kd, (kk >> 2) * 8192 + (kk & 3) * 32, 16), kk > 0);
                if (kk == FENCE_AT) { fence_async(); __syncwarp(); }
                if (kk == GO_AT) { PL(j, 3); if (j >= 0 && l0w) mbar_arrive(sb + B_GO + s * 8); }
            }
#pragma unroll
            for (int kk = 0; kk < 4; kk++)
                wgmma_ss_n64_tb0(Sn, dsc(sd, QS + kk * 32, 16), dsc(kd, 7 * 8192 + kk * 32, 16), 1);
            wg_commit();
            PL(j, 0);
            wg_wait<0>();
            pin(Sn);
#pragma unroll
            for (int i = 0; i < 32; i++) S[i] = Sn[i];
            }
            s = sn;
            if (++sn == 3) sn = 0;
            if (sn == 1) ph ^= 1;
        }
        l0 += __shfl_xor_sync(0xffffffffu, l0, 1); l1 += __shfl_xor_sync(0xffffffffu, l1, 1);
        l0 += __shfl_xor_sync(0xffffffffu, l0, 2); l1 += __shfl_xor_sync(0xffffffffu, l1, 2);
        if (q0) { sts_f32(sb + LINV + r0 * 4, rcp(l0)); sts_f32(sb + LINV + r0 * 4 + 32, rcp(l1)); }
        fence_async();
        __syncwarp();
        if (l0w) {
            mbar_arrive(sb + B_GO + s * 8);
            uint32_t slot8 = 8 * w, par = 0;
#pragma unroll 1
            for (int n = 20 + w; n < 136; n += 4) {
                mbar_wait(sb + B_E2 + slot8, par);
                if (n < 128) ring_ld(sb, slot8, n);
                else {
                    mbar_expect_tx(sb + B_X, 8192);
                    tma4(sb + R1 + slot8 * 1024, &mp.x, 0, 62 * ti, n - 128, b, sb + B_X);
                }
                slot8 += 32;
                if (slot8 >= 160) { slot8 -= 160; par ^= 1; }
            }
        }
        PDUMP();
    } else {
        asm volatile("setmaxnreg.dec.sync.aligned.u32 160;");
        const int h = wg - 1;
        uint32_t v[4][8], v2[4][8];
        if (SU != 0) bar_sync(5, 384);
        PG(206);
#pragma unroll
        for (int i = 0; i < 8; i++) {
            const int t = 62 * ti - 1 + 32 * (i >> 2) + 16 * h + 4 * w + (i & 3);
            const uint4* p = reinterpret_cast<const uint4*>(x + ((size_t)b * T_ + t) * D_) + lane;
            uint32_t* d = i < 4 ? v[i & 3] : v2[i & 3];
#pragma unroll
            for (int c = 0; c < 2; c++)
                asm volatile("{\n.reg .pred p;\nsetp.lt.u32 p, %5, %6;\nmov.b32 %0, 0;\nmov.b32 %1, 0;\nmov.b32 %2, 0;\nmov.b32 %3, 0;\n"
                             "@p ld.global.nc.v4.u32 {%0, %1, %2, %3}, [%4];\n}\n"
                             : "=r"(d[4 * c]), "=r"(d[4 * c + 1]), "=r"(d[4 * c + 2]), "=r"(d[4 * c + 3]) : "l"(p + 32 * c), "r"(t), "n"(T_));
        }
#pragma unroll 1
        for (int bt = 0; bt < 2; bt++) {
            PT(bt ? 13 : 0);
            float a[8];
            const uint32_t la = sb + AT + (lane >> 3) * 8192 + (32 * bt + 16 * h + 4 * w) * 128 + (((lane & 7) ^ ((w & 1) * 4)) << 4);
            const bool b4 = lane & 16, b3 = lane & 8, b2 = lane & 4;
#pragma unroll
            for (int r = 0; r < 4; r++) {
                float c[4] = {0.f, 0.f, 0.f, 0.f};
#pragma unroll
                for (int i = 0; i < 8; i += 2) hmma(c, v[r][i], v[r][i], v[r][i + 1], v[r][i + 1], v[r][i], v[r][i + 1]);
                a[4 + r] = (lane & 3) == (lane >> 3) ? (b2 ? c[1] : c[0]) : 0.f;
                if (r & 1) {
                    float e[4] = {0.f, 0.f, 0.f, 0.f};
#pragma unroll
                    for (int i = 0; i < 8; i += 2) hmma(e, v[r - 1][i], v[r][i], v[r - 1][i + 1], v[r][i + 1], 0x3f803f80u, 0x3f803f80u);
                    a[r - 1] = e[0]; a[r] = e[2];
                }
            }
            float k[4];
#pragma unroll
            for (int i = 0; i < 4; i++) {
                const int lo = (i & 1) + 4 * (i >> 1);
                k[i] = (b4 ? a[lo + 2] : a[lo]) + __shfl_xor_sync(0xffffffffu, b4 ? a[lo] : a[lo + 2], 16);
            }
            const float k0 = (b3 ? k[1] : k[0]) + __shfl_xor_sync(0xffffffffu, b3 ? k[0] : k[1], 8);
            const float k1 = (b3 ? k[3] : k[2]) + __shfl_xor_sync(0xffffffffu, b3 ? k[2] : k[3], 8);
            float z = (b2 ? k1 : k0) + __shfl_xor_sync(0xffffffffu, b2 ? k0 : k1, 4);
            z += __shfl_xor_sync(0xffffffffu, z, 2);
            z += __shfl_xor_sync(0xffffffffu, z, 1);
            const float zo = __shfl_xor_sync(0xffffffffu, z, 4);
            PG(204 + bt);
            const float mu = (b2 ? zo : z) * (0.25f / D_);
            float sd_ = bfr(bfr(fmaxf(fmaf(b2 ? z : zo, 1.f / D_, -mu * mu), 0.f)) + 1e-5f);
            asm("sqrt.approx.f32 %0, %0;" : "+f"(sd_));
            const float ri = rcp(bfr(sd_));
            const uint32_t w1 = pack2(mu, ri), w2 = pack2(ri - bhi(w1), ri - bhi(w1));
#pragma unroll
            for (int r = 0; r < 4; r++) {
                const uint32_t s1 = __shfl_sync(0xffffffffu, w1, 8 * r), rl = __shfl_sync(0xffffffffu, w2, 8 * r);
                const uint32_t m2 = __byte_perm(s1, 0, 0x1010), rh = __byte_perm(s1, 0, 0x3232);
#pragma unroll
                for (int i = 0; i < 8; i++) { const uint32_t d = bsub2(v[r][i], m2); v[r][i] = bfma2(d, rh, bmul2(d, rl)); }
                sts4((la ^ (r << 4)) + r * 128, v[r][0], v[r][1], v[r][2], v[r][3]);
                sts4((la ^ (r << 4)) + r * 128 + 32768, v[r][4], v[r][5], v[r][6], v[r][7]);
#pragma unroll
                for (int i = 0; i < 8; i++) v[r][i] = v2[r][i];
            }
        }
        fence_async();
        if (SU == 0) bar_sync(5, 384); else bar_sync(2, 256);
        if (tid == 128) mbar_arrive(sb + B_LN);
        PG(202);
        if (mode == 1) return;
        float acc[128];
#pragma unroll
        for (int pass = 0; pass < 2; pass++) {
            if (pass == 1) mbar_wait(sb + B_H2, 0);
            PT(1 + 3 * pass);
            fresh(acc);
            uint32_t slot8 = pass ? 8 : 56, par = 0, prev8 = 0;
            auto adv = [&]() { prev8 = slot8; slot8 += 8; if (slot8 == 72) { slot8 = 0; par ^= 1; } };
            auto step = [&](int kk) {
                wg_fence();
                wgmma_ss_n256_tb1(acc, mkd(adA + (kk >> 2) * 512 + (kk & 3) * 2), mkd(bd2k + h * 512 + slot8 * 128), 1);
                wg_commit();
                wg_wait<1>();
            };
#pragma unroll 1
            for (int kk = 0; kk < 24; kk++) {
                mbar_wait(sb + B_R1 + slot8, par);
                step(kk);
                if (kk > 0 && w0 && elect1()) ring_half(sb, prev8, h * 8192, &mp.wup4, 16 * kk + 128, (pass ? 8 : 0) + 4 * h);
                adv();
            }
            if (pass == 0 && w0) mbar_wait(sb + B_MQ, 0);
#pragma unroll 1
            for (int kk = 24; kk < 32; kk++) {
                mbar_wait(sb + B_R1 + slot8, par);
                if (kk == 31 && el) mbar_arrive(sb + (pass ? B_H3 : B_H1));
                step(kk);
                if (w0 && elect1()) ring_half(sb, prev8, h * 8192, pass ? &mp.mqb1 : &mp.mqa2, (pass ? 64 : 32) * (kk - 24), pass ? h : 4 + 2 * h);
                adv();
            }
            wg_wait<0>();
            if (w0 && elect1()) ring_half(sb, prev8, h * 8192, pass ? &mp.mqb1 : &mp.mqa2, pass ? 0 : 256, pass ? 2 + h : 4 + 2 * h);
            pin(acc);
            PT(2 + 3 * pass);
            bf16* ucp = g_uc + ((size_t)blockIdx.x * 128 + r0) * D_ + 256 * h + 8 * (lane & 3);
            if (pass == 1) {
                if (GST >= 0) bar_sync(6, 384);
                PT(12);
                float s0 = 0.f, s1 = 0.f, v0 = 0.f, v1 = 0.f;
#pragma unroll
                for (int n = 0; n < 32; n++) {
#pragma unroll
                    for (int e = 0; e < 4; e++) acc[4 * n + e] = gelu2(acc[4 * n + e]);
                    s0 += acc[4 * n] + acc[4 * n + 1]; s1 += acc[4 * n + 2] + acc[4 * n + 3];
                    v0 = fmaf(acc[4 * n], acc[4 * n], v0); v0 = fmaf(acc[4 * n + 1], acc[4 * n + 1], v0);
                    v1 = fmaf(acc[4 * n + 2], acc[4 * n + 2], v1); v1 = fmaf(acc[4 * n + 3], acc[4 * n + 3], v1);
                }
#pragma unroll
                for (int o = 1; o < 4; o <<= 1) {
                    s0 += __shfl_xor_sync(0xffffffffu, s0, o); s1 += __shfl_xor_sync(0xffffffffu, s1, o);
                    v0 += __shfl_xor_sync(0xffffffffu, v0, o); v1 += __shfl_xor_sync(0xffffffffu, v1, o);
                }
                const uint32_t a = sb + STAT + r0 * 8;
                if ((lane & 3) == 0) { red_f32(a, s0); red_f32(a + 4, v0); red_f32(a + 64, s1); red_f32(a + 68, v1); }
                bar_sync(2, 256);
                s0 = lds_f32(a) * (1.f / 512.f); v0 = lds_f32(a + 4) * (1.f / 512.f);
                s1 = lds_f32(a + 64) * (1.f / 512.f); v1 = lds_f32(a + 68) * (1.f / 512.f);
                v0 = rsqrtf(fmaxf(fmaf(-s0, s0, v0), 0.f) + 4e-5f); v1 = rsqrtf(fmaxf(fmaf(-s1, s1, v1), 0.f) + 4e-5f);
                s0 = -s0 * v0; s1 = -s1 * v1;
#pragma unroll
                for (int m = 0; m < 8; m++) {
                    const float* a_ = acc + 16 * m;
                    stg4(ucp + 64 * D_ + 32 * m, pack2(fmaf(a_[0], v0, s0), fmaf(a_[1], v0, s0)), pack2(fmaf(a_[4], v0, s0), fmaf(a_[5], v0, s0)),
                         pack2(fmaf(a_[8], v0, s0), fmaf(a_[9], v0, s0)), pack2(fmaf(a_[12], v0, s0), fmaf(a_[13], v0, s0)));
                    stg4(ucp + 72 * D_ + 32 * m, pack2(fmaf(a_[2], v1, s1), fmaf(a_[3], v1, s1)), pack2(fmaf(a_[6], v1, s1), fmaf(a_[7], v1, s1)),
                         pack2(fmaf(a_[10], v1, s1), fmaf(a_[11], v1, s1)), pack2(fmaf(a_[14], v1, s1), fmaf(a_[15], v1, s1)));
                }
            } else {
#pragma unroll
                for (int m = 0; m < 8; m++) {
                    const float* a_ = acc + 16 * m;
                    stg4(ucp + 32 * m, pack2(a_[0], a_[1]), pack2(a_[4], a_[5]), pack2(a_[8], a_[9]), pack2(a_[12], a_[13]));
                    stg4(ucp + 8 * D_ + 32 * m, pack2(a_[2], a_[3]), pack2(a_[6], a_[7]), pack2(a_[10], a_[11]), pack2(a_[14], a_[15]));
                }
            }
            if (pass == 1) bar_sync(3 + h, 128);
            PT(3 + 3 * pass);
        }
        int s = 1, ph = 0;
        uint32_t* cp = reinterpret_cast<uint32_t*>(g_uc + (size_t)blockIdx.x * 128 * D_) + (tid - 128);
        const uint32_t* dp = reinterpret_cast<const uint32_t*>(dw) + (((tid - 128) & ~15) | ((lane & 3) << 2) | ((lane >> 2) & 3));
        const uint32_t d0 = ldg_v(dp), d1 = ldg_v(dp + D_ / 2), d2 = ldg_v(dp + D_);
        uint32_t ga = ldg_cg(cp + 64 * (D_ / 2)), gb = ldg_cg(cp + 65 * (D_ / 2));
        fresh(acc);
#pragma unroll 1
        for (int j = 0; j < NKV; j++) {
            cp += D_ / 2;
            uint32_t gc = 0, uu = 0;
            if (j < NKV - 1) { gc = ldg_cg(cp + 65 * (D_ / 2)); uu = ldg_cg(cp); }
            mbar_wait(sb + B_P + s * 8, ph);
            PL(j, 0);
            if (j > 0) {
                const float sc0 = lds_f32(sb + SCL + s * 256 + r0 * 4), sc1 = lds_f32(sb + SCL + s * 256 + r0 * 4 + 32);
                if (__any_sync(0xffffffffu, sc0 != 1.f || sc1 != 1.f)) {
#pragma unroll
                    for (int n = 0; n < 32; n++) { acc[4 * n] *= sc0; acc[4 * n + 1] *= sc0; acc[4 * n + 2] *= sc1; acc[4 * n + 3] *= sc1; }
                }
            }
            mbar_wait(sb + B_GO + s * 8, ph);
            PL(j, 1);
            const uint32_t vd = sd + s * 4096 + h * 2048, pd = sd + (s == 0 ? 2 : s - 1) * 512;
            pin(acc);
            if (TRIM & 1 && j == NKV - 1) {
                wg_fence();
#pragma unroll
                for (int kk = 0; kk < 2; kk++) wgmma_ss_n256_tb1(acc, dsc(pd, R3 + kk * 32, 16), dsc(vd, kk * 2048, 8192), 1);
                wg_commit();
                wg_wait<0>();
                pin(acc);
                break;
            }
            wg_fence();
#pragma unroll
            for (int kk = 0; kk < 4; kk++) wgmma_ss_n256_tb1(acc, dsc(pd, R3 + kk * 32, 16), dsc(vd, kk * 2048, 8192), 1);
            wg_commit();
            wg_wait<0>();
            pin(acc);
            PL(j, 2);
            if (w0 && elect1()) {
                if (j + 3 < NKV) {
                    mbar_expect_tx(sb + B_KV + s * 8, 32768);
                    tma4(sb + s * 65536 + h * 32768, &mp.xa4, 0, 64 * (j + 3), 4 * h, b, sb + B_KV + s * 8);
                } else if (j < NKV - 1) {
                    const int n0 = (j == NKV - 3 ? 0 : 8) + 4 * h;
#pragma unroll 1
                    for (int n = n0; n < n0 + 4; n++) ring_ld(sb, n * 8, n);
                }
                if (j == NKV - 5 && mode == 0) flag_wait(&g_sync[3], 4);
                if (j >= XPF && j < XPF + 4) {
                    const int t0 = 62 * ti + 32 * h + 8 * (j - XPF), nr = min(8, T_ - t0);
                    if (nr > 0) l2_prefetch(x + ((size_t)b * T_ + t0) * D_, nr * 1024);
                }
                if (KPF && h == 0 && 64 * (j + KPF) + ti < T_) l2_prefetch(g_xa + ((size_t)b * (T_ + 8) + 1 + 64 * (j + KPF) + ti) * D_, 1024);
            }
            uu = pack2(gelu2(blo(uu)), gelu2(bhi(uu)));
            if (j < NKV - 1) asm volatile("st.global.u32 [%0], %1;" ::"l"(cp), "r"(bmul2(uu, bfma2(gc, d2, bfma2(gb, d1, bmul2(ga, d0))))) : "memory");
            ga = gb; gb = gc;
            if (++s == 3) s = 0;
            if (s == 1) ph ^= 1;
        }
        {
            const float i0 = lds_f32(sb + LINV + r0 * 4), i1 = lds_f32(sb + LINV + r0 * 4 + 32);
#pragma unroll
            for (int p = 0; p < 16; p++)
                stsm4(((sb + R0 + h * 32768 + loff) ^ ((p & 3) << 5)) + (p >> 2) * 8192,
                      pack2(acc[8 * p] * i0, acc[8 * p + 1] * i0), pack2(acc[8 * p + 2] * i1, acc[8 * p + 3] * i1),
                      pack2(acc[8 * p + 4] * i0, acc[8 * p + 5] * i0), pack2(acc[8 * p + 6] * i1, acc[8 * p + 7] * i1));
        }
        fence_async();
        fence_async_g();
        bar_sync(2, 256);
        if (lane == 0 && w < 2) ring_ld(sb, 128 + 16 * w + 8 * h, 16 + 2 * w + h);
        PT(7);
        fresh(acc);
        {
            uint32_t slot8 = 8 * h, par = 0, prev8 = 0;
#pragma unroll 1
            for (int kk = 0; kk < 64; kk++) {
                if (kk == 32 || kk == 48) mbar_wait(sb + B_UC + (kk >> 1 & 8), 0);
                mbar_wait(sb + B_R2 + slot8, par);
                wg_fence();
                wgmma_ss_n256_tb1(acc, mkd(sd + (1u << 16) + (R0 >> 4) + (kk >> 2 & 7) * 512 + (kk & 3) * 2), mkd(bd2k + (R1 >> 4) + slot8 * 64), 1);
                wg_commit();
                wg_wait<1>();
                if (kk > 0 && lane == 0) mbar_arrive(sb + B_E2 + prev8);
                if ((kk == 16 || kk == 32) && w0 && elect1() && (atom_inc_s(sb + CNT + 12 + (kk >> 3 & 4)) & 1)) {
                    mbar_expect_tx(sb + B_UC + (kk >> 2 & 8), 32768);
                    tma3(sb + R0 + (kk & 32) * 1024, &mp.uc, 0, 128 * blockIdx.x, kk >> 3 & 4, sb + B_UC + (kk >> 2 & 8));
                }
                prev8 = slot8;
                slot8 += 16;
                if (slot8 >= 160) { slot8 -= 160; par ^= 1; }
            }
        }
        wg_wait<0>();
        pin(acc);
        PT(8);
        mbar_wait(sb + B_X, 0);
        PT(9);
        {
            const uint32_t sr = (lrow + 63) & 63;
            const uint32_t xoff = sr * 128 + ((((lane >> 4) ^ sr) & 7) << 4);
#pragma unroll
            for (int p = 0; p < 16; p++) {
                const uint32_t a = ((sb + R2 + h * 32768 + xoff) ^ ((p & 3) << 5)) + (p >> 2) * 8192;
                uint32_t xv[4];
                ldsm4(a, xv);
#pragma unroll
                for (int e = 0; e < 4; e++)
                    xv[e] = pack2(acc[8 * p + 2 * e] + __uint_as_float(xv[e] << 16), acc[8 * p + 2 * e + 1] + __uint_as_float(xv[e] & 0xffff0000u));
                stsm4(a, xv[0], xv[1], xv[2], xv[3]);
            }
        }
        fence_async();
        bar_sync(3 + h, 128);
        if (el) {
            for (int c = 0; c < 4; c++) tma4_store(&mp.out, sb + R2 + (4 * h + c) * 8192, 0, 62 * ti, 4 * h + c, b);
            asm volatile("cp.async.bulk.commit_group;" ::: "memory");
            PT(10);
            if (h == 0) cta_done(mode);
            asm volatile("cp.async.bulk.wait_group.read 0;" ::: "memory");
        }
        PT(11);
        PG(201);
        PDUMP();
    }
}

typedef CUresult (*PFN_enc)(CUtensorMap*, CUtensorMapDataType, cuuint32_t, void*, const cuuint64_t*, const cuuint64_t*,
                            const cuuint32_t*, const cuuint32_t*, CUtensorMapInterleave, CUtensorMapSwizzle,
                            CUtensorMapL2promotion, CUtensorMapFloatOOBfill);

static void enc(PFN_enc f, CUtensorMap* m, void* base, int rank, const cuuint64_t* dims, const cuuint64_t* strides, const cuuint32_t* box) {
    cuuint32_t es[5] = {1, 1, 1, 1, 1};
    f(m, CU_TENSOR_MAP_DATA_TYPE_BFLOAT16, rank, base, dims, strides, box, es, CU_TENSOR_MAP_INTERLEAVE_NONE,
      CU_TENSOR_MAP_SWIZZLE_128B, CU_TENSOR_MAP_L2_PROMOTION_L2_256B, CU_TENSOR_MAP_FLOAT_OOB_FILL_NONE);
}
static void enc_act(PFN_enc f, CUtensorMap* m, void* base, int rows, int chunks, int trows = T_, int pitch = T_) {
    cuuint64_t dims[4] = {64, (cuuint64_t)trows, 8, (cuuint64_t)NB_};
    cuuint64_t st[3] = {1024, 128, (cuuint64_t)pitch * 1024};
    cuuint32_t box[4] = {64, (cuuint32_t)rows, (cuuint32_t)chunks, 1};
    enc(f, m, base, 4, dims, st, box);
}
static void enc_w(PFN_enc f, CUtensorMap* m, void* base, int krows, int ncols, int bk, int bc) {
    cuuint64_t dims[3] = {64, (cuuint64_t)krows, (cuuint64_t)(ncols / 64)};
    cuuint64_t st[2] = {(cuuint64_t)ncols * 2, 128};
    cuuint32_t box[3] = {64, (cuuint32_t)bk, (cuuint32_t)bc};
    enc(f, m, base, 3, dims, st, box);
}

extern "C" void kernel_launch(void* const* d_in, const int* in_sizes, int n_in, void* d_out, int out_size) {
    const bf16* x = (const bf16*)d_in[0];
    static PFN_enc fenc = nullptr;
    static void *p_xa, *p_mqk, *p_uc, *p_t1;
    static int fused = 0;
    if (!fenc) {
        void* fn = nullptr;
        cudaDriverEntryPointQueryResult qr;
        cudaGetDriverEntryPoint("cuTensorMapEncodeTiled", &fn, cudaEnableDefault, &qr);
        fenc = (PFN_enc)fn;
        cudaGetSymbolAddress(&p_xa, g_xa);
        cudaGetSymbolAddress(&p_mqk, g_mqk);
        cudaGetSymbolAddress(&p_uc, g_uc);
        cudaGetSymbolAddress(&p_t1, g_t1);
        cudaFuncSetAttribute(main_kernel, cudaFuncAttributeMaxDynamicSharedMemorySize, SMEM_BYTES);
        int dev = 0, sms = 0, occ = 0;
        cudaGetDevice(&dev);
        cudaDeviceGetAttribute(&sms, cudaDevAttrMultiProcessorCount, dev);
        cudaOccupancyMaxActiveBlocksPerMultiprocessor(&occ, main_kernel, 384, SMEM_BYTES);
        fused = sms * occ >= NCTA + 2;
    }
    Maps mp;
    enc_act(fenc, &mp.xa, (char*)p_xa + 1024, 64, 8, T_, T_ + 8);
    enc_act(fenc, &mp.xa2, (char*)p_xa + 1024, 64, 2, T_, T_ + 8);
    enc_act(fenc, &mp.xa4, (char*)p_xa + 1024, 64, 4, T_, T_ + 8);
    enc_act(fenc, &mp.xas, p_xa, 64, 1, T_ + 1, T_ + 8);
    enc_act(fenc, &mp.x, (void*)x, 64, 1);
    enc_act(fenc, &mp.out, d_out, 62, 1);
    enc_w(fenc, &mp.wup4, d_in[5], 512, 1024, 16, 4);
    enc_w(fenc, &mp.wup8, d_in[5], 512, 1024, 16, 8);
    enc_w(fenc, &mp.mqa2, p_mqk, 512, 512, 32, 2);
    enc_w(fenc, &mp.mqa4, p_mqk, 512, 512, 32, 4);
    enc_w(fenc, &mp.mqb1, p_mqk, 512, 512, 64, 1);
    enc_w(fenc, &mp.mqb2, p_mqk, 512, 512, 64, 2);
    enc_w(fenc, &mp.uc, p_uc, NCTA * 128, 512, 64, 4);
    enc_w(fenc, &mp.wq, d_in[1], 512, 512, 64, 8);
    enc_w(fenc, &mp.wk, d_in[2], 512, 512, 32, 8);
    enc_w(fenc, &mp.fa[0], d_in[3], 512, 512, 128, 1);
    enc_w(fenc, &mp.fa[1], d_in[7], 512, 512, 128, 1);
    enc_w(fenc, &mp.fa[2], p_t1, 512, 512, 128, 1);
    enc_w(fenc, &mp.fb[0], d_in[4], 512, 512, 64, 4);
    enc_w(fenc, &mp.fb[1], d_in[8], 1024, 512, 64, 4);
    enc_w(fenc, &mp.fc, p_t1, 512, 512, 64, 4);
    cudaStream_t st = cudaStreamPerThread;
    if (fused) {
        main_kernel<<<NCTA + 2, 384, SMEM_BYTES, st>>>(mp, x, (const bf16*)d_in[6], (const bf16*)d_in[5], 0);
    } else {
        main_kernel<<<NCTA + 2, 384, SMEM_BYTES, st>>>(mp, x, (const bf16*)d_in[6], (const bf16*)d_in[5], 1);
        main_kernel<<<NCTA + 2, 384, SMEM_BYTES, st>>>(mp, x, (const bf16*)d_in[6], (const bf16*)d_in[5], 2);
    }
}
```

```cpp
#define LAZY 4.0f
#include <cuda_runtime.h>
#include <cuda_bf16.h>
#include <cuda.h>
#include <stdint.h>

typedef __nv_bfloat16 bf16;

constexpr int T_ = 4000, D_ = 512, NB_ = 2;
constexpr int TPB = 65;
constexpr int NCTA = TPB * NB_;
constexpr int NKV = 63;

__device__ __align__(1024) bf16 g_xa[NB_ * (T_ + 8) * D_];
__device__ __align__(1024) bf16 g_mqk[D_ * D_];
__device__ __align__(1024) bf16 g_t1[D_ * D_];
__device__ __align__(1024) bf16 g_wepi[2 * D_ * D_];
__device__ __align__(1024) bf16 g_uc[NCTA * 128 * D_];
__device__ unsigned g_sync[8];

#define PT(i) do { if (el) asm volatile("st.shared.u32 [%0], %1;" ::"r"(sb + MISC + 2560), "r"((unsigned)clock())); } while (0)
#define PG(i)
#define PE()
#define PLM 15
#define PL(j, q) do { if ((PLM >> ((q) + (wg ? 4 : 0))) & 1) PT(0); } while (0)
#define PDUMP()

#define FENCE_AT 1
#define GO_AT 25
#define SU 2
#define XS_GAP 800
#define XPF 50
#define URAW 1
#define LAGA 0
#define LAGB 0
#define DPOS 1
#define KPF 0
#define XEF 0
#define SK0 0
#define TRIM 3
#define GO_LAST 20
#define PFW 1
constexpr uint32_t R0 = 0, R1 = 65536, R2 = 131072, R3 = 196608, QS = 221184, MISC = 229376;
constexpr uint32_t AT = 147456;
constexpr uint32_t SMEM_BYTES = 232448;
constexpr uint32_t B_R1 = MISC + 1856  , B_MK = MISC + 48, B_LN = MISC + 56, B_MQ = MISC + 64,
                   B_H1 = MISC + 88, B_H2 = MISC + 96, B_H3 = MISC + 104,
                   B_KV = MISC + 112, B_P = MISC + 136, B_GO = MISC + 160, B_UC = MISC + 184  ,
                   B_X = MISC + 200, CNT = MISC + 208  , SCL = MISC + 512  ,
                   LINV = MISC + 1280  , STAT = MISC + 512  ,
                   B_R2 = MISC + 1536  , B_E2 = MISC + 1696  ;

__device__ __forceinline__ uint32_t smem_u32(const void* p) { return (uint32_t)__cvta_generic_to_shared(p); }
__device__ __forceinline__ void wg_fence() { asm volatile("wgmma.fence.sync.aligned;" ::: "memory"); }
__device__ __forceinline__ void wg_commit() { asm volatile("wgmma.commit_group.sync.aligned;" ::: "memory"); }
template <int N> __device__ __forceinline__ void wg_wait() { asm volatile("wgmma.wait_group.sync.aligned %0;" ::"n"(N) : "memory"); }
__device__ __forceinline__ uint64_t dsc(uint32_t sd, uint32_t off, uint32_t lbo) {
    uint32_t lo = sd + (off >> 4) + ((lbo >> 4) << 16);
    uint64_t d;
    asm("mov.b64 %0, {%1, %2};" : "=l"(d) : "r"(lo), "r"((1024u >> 4) | (1u << 30)));
    return d;
}
__device__ __forceinline__ bool elect1() {
    uint32_t p;
    asm volatile("{\n.reg .pred p;\nelect.sync _|p, 0xffffffff;\nselp.u32 %0, 1, 0, p;\n}\n" : "=r"(p));
    return p != 0;
}
__device__ __forceinline__ void mbar_init(uint32_t bar, int cnt) { asm volatile("mbarrier.init.shared::cta.b64 [%0], %1;" ::"r"(bar), "r"(cnt) : "memory"); }
__device__ __forceinline__ void mbar_expect_tx(uint32_t bar, uint32_t bytes) { asm volatile("mbarrier.arrive.expect_tx.shared::cta.b64 _, [%0], %1;" ::"r"(bar), "r"(bytes) : "memory"); }
__device__ __forceinline__ void mbar_arrive(uint32_t bar) { asm volatile("mbarrier.arrive.shared::cta.b64 _, [%0];" ::"r"(bar) : "memory"); }
__device__ __forceinline__ void mbar_wait(uint32_t bar, uint32_t parity) {
    uint32_t ok;
#pragma unroll 1
    for (uint32_t it = 0;; ++it) {
        asm volatile("{\n.reg .pred p;\nmbarrier.try_wait.parity.shared::cta.b64 p, [%1], %2;\nselp.u32 %0, 1, 0, p;\n}\n" : "=r"(ok) : "r"(bar), "r"(parity) : "memory");
        if (ok) break;
        if (it > (1u << 20)) __trap();
    }
}
__device__ __forceinline__ bool mbar_test(uint32_t bar, uint32_t parity) {
    uint32_t ok;
    asm volatile("{\n.reg .pred p;\nmbarrier.test_wait.parity.shared::cta.b64 p, [%1], %2;\nselp.u32 %0, 1, 0, p;\n}\n" : "=r"(ok) : "r"(bar), "r"(parity) : "memory");
    return ok != 0;
}
__device__ __forceinline__ void fence_async() { asm volatile("fence.proxy.async.shared::cta;" ::: "memory"); }
__device__ __forceinline__ void fence_async_g() { asm volatile("fence.proxy.async.global;" ::: "memory"); }
__device__ __forceinline__ void bar_sync(int id, int n) { asm volatile("bar.sync %0, %1;" ::"r"(id), "r"(n) : "memory"); }
__device__ __forceinline__ void tma3(uint32_t dst, const CUtensorMap* tm, int c0, int c1, int c2, uint32_t bar) {
    asm volatile("cp.async.bulk.tensor.3d.shared::cluster.global.mbarrier::complete_tx::bytes [%0], [%1, {%3, %4, %5}], [%2];"
                 ::"r"(dst), "l"(tm), "r"(bar), "r"(c0), "r"(c1), "r"(c2) : "memory");
}
__device__ __forceinline__ void tma4(uint32_t dst, const CUtensorMap* tm, int c0, int c1, int c2, int c3, uint32_t bar) {
    asm volatile("cp.async.bulk.tensor.4d.shared::cluster.global.mbarrier::complete_tx::bytes [%0], [%1, {%3, %4, %5, %6}], [%2];"
                 ::"r"(dst), "l"(tm), "r"(bar), "r"(c0), "r"(c1), "r"(c2), "r"(c3) : "memory");
}
__device__ __forceinline__ void tma4_store(const CUtensorMap* tm, uint32_t src, int c0, int c1, int c2, int c3) {
    asm volatile("cp.async.bulk.tensor.4d.global.shared::cta.bulk_group [%0, {%2, %3, %4, %5}], [%1];"
                 ::"l"(tm), "r"(src), "r"(c0), "r"(c1), "r"(c2), "r"(c3) : "memory");
}
__device__ __forceinline__ void tma3_store(const CUtensorMap* tm, uint32_t src, int c0, int c1, int c2) {
    asm volatile("cp.async.bulk.tensor.3d.global.shared::cta.bulk_group [%0, {%2, %3, %4}], [%1];"
                 ::"l"(tm), "r"(src), "r"(c0), "r"(c1), "r"(c2) : "memory");
}
__device__ __forceinline__ void stsm4(uint32_t addr, uint32_t a, uint32_t b, uint32_t c, uint32_t d) {
    asm volatile("stmatrix.sync.aligned.m8n8.x4.shared.b16 [%0], {%1, %2, %3, %4};" ::"r"(addr), "r"(a), "r"(b), "r"(c), "r"(d) : "memory");
}
__device__ __forceinline__ void ldsm4(uint32_t addr, uint32_t (&r)[4]) {
    asm volatile("ldmatrix.sync.aligned.m8n8.x4.shared.b16 {%0, %1, %2, %3}, [%4];" : "=r"(r[0]), "=r"(r[1]), "=r"(r[2]), "=r"(r[3]) : "r"(addr) : "memory");
}
__device__ __forceinline__ void ldsm2(uint32_t addr, uint32_t (&r)[2]) {
    asm volatile("ldmatrix.sync.aligned.m8n8.x2.shared.b16 {%0, %1}, [%2];" : "=r"(r[0]), "=r"(r[1]) : "r"(addr) : "memory");
}
__device__ __forceinline__ void stg4(void* p, uint32_t a, uint32_t b, uint32_t c, uint32_t d) {
    asm volatile("st.global.v4.u32 [%0], {%1, %2, %3, %4};" ::"l"(p), "r"(a), "r"(b), "r"(c), "r"(d) : "memory");
}
__device__ __forceinline__ void hmma(float (&c)[4], uint32_t a0, uint32_t a1, uint32_t a2, uint32_t a3, uint32_t b0, uint32_t b1) {
    asm("mma.sync.aligned.m16n8k16.row.col.f32.bf16.bf16.f32 {%0, %1, %2, %3}, {%4, %5, %6, %7}, {%8, %9}, {%0, %1, %2, %3};"
        : "+f"(c[0]), "+f"(c[1]), "+f"(c[2]), "+f"(c[3]) : "r"(a0), "r"(a1), "r"(a2), "r"(a3), "r"(b0), "r"(b1));
}
__device__ __forceinline__ uint32_t pack2(float lo, float hi) {
    uint32_t r;
    asm("cvt.rn.bf16x2.f32 %0, %1, %2;" : "=r"(r) : "f"(hi), "f"(lo));
    return r;
}
__device__ __forceinline__ uint32_t pack2v(float lo, float hi) {
    uint32_t r;
    asm volatile("cvt.rn.bf16x2.f32 %0, %1, %2;" : "=r"(r) : "f"(hi), "f"(lo));
    return r;
}
__device__ __forceinline__ uint32_t bmul2(uint32_t a, uint32_t b) { uint32_t r; asm("mul.rn.bf16x2 %0, %1, %2;" : "=r"(r) : "r"(a), "r"(b)); return r; }
__device__ __forceinline__ uint32_t bfma2(uint32_t a, uint32_t b, uint32_t c) { uint32_t r; asm("fma.rn.bf16x2 %0, %1, %2, %3;" : "=r"(r) : "r"(a), "r"(b), "r"(c)); return r; }
__device__ __forceinline__ float ex2(float x) { float r; asm("ex2.approx.ftz.f32 %0, %1;" : "=f"(r) : "f"(x)); return r; }
__device__ __forceinline__ float rcp(float x) { float r; asm("rcp.approx.ftz.f32 %0, %1;" : "=f"(r) : "f"(x)); return r; }
__device__ __forceinline__ float gelu2(float x) {
    float t = fmaf(x * x, 0.044715f * 0.7978845608028654f, 0.7978845608028654f), th;
    asm("tanh.approx.f32 %0, %1;" : "=f"(th) : "f"(x * t));
    return fmaf(x, th, x);
}
__device__ __forceinline__ uint32_t ldg_v(const uint32_t* p) { uint32_t v; asm volatile("ld.global.nc.u32 %0, [%1];" : "=r"(v) : "l"(p)); return v; }
__device__ __forceinline__ uint32_t ldg_cg(const uint32_t* p) { uint32_t v; asm volatile("ld.global.cg.u32 %0, [%1];" : "=r"(v) : "l"(p) : "memory"); return v; }
__device__ __forceinline__ float lds_f32(uint32_t a) { float v; asm volatile("ld.shared.f32 %0, [%1];" : "=f"(v) : "r"(a) : "memory"); return v; }
__device__ __forceinline__ void sts_f32(uint32_t a, float v) { asm volatile("st.shared.f32 [%0], %1;" ::"r"(a), "f"(v) : "memory"); }
__device__ __forceinline__ uint32_t atom_inc_s(uint32_t a) { uint32_t v; asm volatile("atom.relaxed.cta.shared.add.u32 %0, [%1], 1;" : "=r"(v) : "r"(a) : "memory"); return v; }
__device__ __forceinline__ void lds4(uint32_t a, uint32_t* r) {
    asm volatile("ld.shared.v4.u32 {%0, %1, %2, %3}, [%4];" : "=r"(r[0]), "=r"(r[1]), "=r"(r[2]), "=r"(r[3]) : "r"(a) : "memory");
}
__device__ __forceinline__ void sts4(uint32_t a, uint32_t x, uint32_t y, uint32_t z, uint32_t t) {
    asm volatile("st.shared.v4.u32 [%0], {%1, %2, %3, %4};" ::"r"(a), "r"(x), "r"(y), "r"(z), "r"(t) : "memory");
}
__device__ __forceinline__ uint32_t bsub2(uint32_t a, uint32_t b) { uint32_t r; asm("sub.rn.bf16x2 %0, %1, %2;" : "=r"(r) : "r"(a), "r"(b)); return r; }
__device__ __forceinline__ float blo(uint32_t v) { return __uint_as_float(v << 16); }
__device__ __forceinline__ float bhi(uint32_t v) { return __uint_as_float(v & 0xffff0000u); }
__device__ __forceinline__ float bfr(float x) { return __bfloat162float(__float2bfloat16_rn(x)); }
__device__ __forceinline__ void l2_prefetch(const void* p, uint32_t bytes) { asm volatile("cp.async.bulk.prefetch.L2.global [%0], %1;" ::"l"(p), "r"(bytes) : "memory"); }
__device__ __forceinline__ void flag_add(unsigned* p) { asm volatile("red.release.gpu.global.add.u32 [%0], 1;" ::"l"(p) : "memory"); }
__device__ __forceinline__ void flag_wait(const unsigned* p, unsigned target) {
#pragma unroll 1
    for (uint32_t it = 0;; ++it) {
        unsigned v;
        asm volatile("ld.acquire.gpu.global.u32 %0, [%1];" : "=r"(v) : "l"(p) : "memory");
        if (v >= target) break;
        if (it > (1u << 20)) __trap();
    }
    fence_async_g();
}
template <int N> __device__ __forceinline__ void pin(float (&a)[N]) {
#pragma unroll
    for (int i = 0; i < N; i++) asm volatile("" : "+f"(a[i])::"memory");
}

template <int N> __device__ __forceinline__ void fresh(float (&a)[N]) {
#pragma unroll
    for (int i = 0; i < N; i++) a[i] = 0.f;
    pin(a);
}

__device__ __forceinline__ void wgmma_rs_n32_tb0(float (&d)[16], uint32_t a0, uint32_t a1, uint32_t a2, uint32_t a3, uint64_t db, int scale_d) {
    asm volatile("{\n.reg .pred p;\nsetp.ne.b32 p, %21, 0;\n"
        "wgmma.mma_async.sync.aligned.m64n32k16.f32.bf16.bf16 {%0, %1, %2, %3, %4, %5, %6, %7, %8, %9, %10, %11, %12, %13, %14, %15}, {%16, %17, %18, %19}, %20, p, 1, 1, 0;\n}\n"
        : "+f"(d[0]), "+f"(d[1]), "+f"(d[2]), "+f"(d[3]), "+f"(d[4]), "+f"(d[5]), "+f"(d[6]), "+f"(d[7]), "+f"(d[8]), "+f"(d[9]), "+f"(d[10]), "+f"(d[11]), "+f"(d[12]), "+f"(d[13]), "+f"(d[14]), "+f"(d[15])
        : "r"(a0), "r"(a1), "r"(a2), "r"(a3), "l"(db), "r"(scale_d));
}

__device__ __forceinline__ void wgmma_rs_n64_tb0(float (&d)[32], uint32_t a0, uint32_t a1, uint32_t a2, uint32_t a3, uint64_t db, int scale_d) {
    asm volatile("{\n.reg .pred p;\nsetp.ne.b32 p, %37, 0;\n"
        "wgmma.mma_async.sync.aligned.m64n64k16.f32.bf16.bf16 {%0, %1, %2, %3, %4, %5, %6, %7, %8, %9, %10, %11, %12, %13, %14, %15, %16, %17, %18, %19, %20, %21, %22, %23, %24, %25, %26, %27, %28, %29, %30, %31}, {%32, %33, %34, %35}, %36, p, 1, 1, 0;\n}\n"
        : "+f"(d[0]), "+f"(d[1]), "+f"(d[2]), "+f"(d[3]), "+f"(d[4]), "+f"(d[5]), "+f"(d[6]), "+f"(d[7]), "+f"(d[8]), "+f"(d[9]), "+f"(d[10]), "+f"(d[11]), "+f"(d[12]), "+f"(d[13]), "+f"(d[14]), "+f"(d[15]), "+f"(d[16]), "+f"(d[17]), "+f"(d[18]), "+f"(d[19]), "+f"(d[20]), "+f"(d[21]), "+f"(d[22]), "+f"(d[23]), "+f"(d[24]), "+f"(d[25]), "+f"(d[26]), "+f"(d[27]), "+f"(d[28]), "+f"(d[29]), "+f"(d[30]), "+f"(d[31])
        : "r"(a0), "r"(a1), "r"(a2), "r"(a3), "l"(db), "r"(scale_d));
}

__device__ __forceinline__ void wgmma_ss_n128_tb1(float (&d)[64], uint64_t da, uint64_t db, int scale_d) {
    asm volatile("{\n.reg .pred p;\nsetp.ne.b32 p, %66, 0;\n"
        "wgmma.mma_async.sync.aligned.m64n128k16.f32.bf16.bf16 {%0, %1, %2, %3, %4, %5, %6, %7, %8, %9, %10, %11, %12, %13, %14, %15, %16, %17, %18, %19, %20, %21, %22, %23, %24, %25, %26, %27, %28, %29, %30, %31, %32, %33, %34, %35, %36, %37, %38, %39, %40, %41, %42, %43, %44, %45, %46, %47, %48, %49, %50, %51, %52, %53, %54, %55, %56, %57, %58, %59, %60, %61, %62, %63}, %64, %65, p, 1, 1, 0, 1;\n}\n"
        : "+f"(d[0]), "+f"(d[1]), "+f"(d[2]), "+f"(d[3]), "+f"(d[4]), "+f"(d[5]), "+f"(d[6]), "+f"(d[7]), "+f"(d[8]), "+f"(d[9]), "+f"(d[10]), "+f"(d[11]), "+f"(d[12]), "+f"(d[13]), "+f"(d[14]), "+f"(d[15]), "+f"(d[16]), "+f"(d[17]), "+f"(d[18]), "+f"(d[19]), "+f"(d[20]), "+f"(d[21]), "+f"(d[22]), "+f"(d[23]), "+f"(d[24]), "+f"(d[25]), "+f"(d[26]), "+f"(d[27]), "+f"(d[28]), "+f"(d[29]), "+f"(d[30]), "+f"(d[31]), "+f"(d[32]), "+f"(d[33]), "+f"(d[34]), "+f"(d[35]), "+f"(d[36]), "+f"(d[37]), "+f"(d[38]), "+f"(d[39]), "+f"(d[40]), "+f"(d[41]), "+f"(d[42]), "+f"(d[43]), "+f"(d[44]), "+f"(d[45]), "+f"(d[46]), "+f"(d[47]), "+f"(d[48]), "+f"(d[49]), "+f"(d[50]), "+f"(d[51]), "+f"(d[52]), "+f"(d[53]), "+f"(d[54]), "+f"(d[55]), "+f"(d[56]), "+f"(d[57]), "+f"(d[58]), "+f"(d[59]), "+f"(d[60]), "+f"(d[61]), "+f"(d[62]), "+f"(d[63])
        : "l"(da), "l"(db), "r"(scale_d));
}

__device__ __forceinline__ void wgmma_ss_n256_tb1(float (&d)[128], uint64_t da, uint64_t db, int scale_d) {
    asm volatile("{\n.reg .pred p;\nsetp.ne.b32 p, %130, 0;\n"
        "wgmma.mma_async.sync.aligned.m64n256k16.f32.bf16.bf16 {%0, %1, %2, %3, %4, %5, %6, %7, %8, %9, %10, %11, %12, %13, %14, %15, %16, %17, %18, %19, %20, %21, %22, %23, %24, %25, %26, %27, %28, %29, %30, %31, %32, %33, %34, %35, %36, %37, %38, %39, %40, %41, %42, %43, %44, %45, %46, %47, %48, %49, %50, %51, %52, %53, %54, %55, %56, %57, %58, %59, %60, %61, %62, %63, %64, %65, %66, %67, %68, %69, %70, %71, %72, %73, %74, %75, %76, %77, %78, %79, %80, %81, %82, %83, %84, %85, %86, %87, %88, %89, %90, %91, %92, %93, %94, %95, %96, %97, %98, %99, %100, %101, %102, %103, %104, %105, %106, %107, %108, %109, %110, %111, %112, %113, %114, %115, %116, %117, %118, %119, %120, %121, %122, %123, %124, %125, %126, %127}, %128, %129, p, 1, 1, 0, 1;\n}\n"
        : "+f"(d[0]), "+f"(d[1]), "+f"(d[2]), "+f"(d[3]), "+f"(d[4]), "+f"(d[5]), "+f"(d[6]), "+f"(d[7]), "+f"(d[8]), "+f"(d[9]), "+f"(d[10]), "+f"(d[11]), "+f"(d[12]), "+f"(d[13]), "+f"(d[14]), "+f"(d[15]), "+f"(d[16]), "+f"(d[17]), "+f"(d[18]), "+f"(d[19]), "+f"(d[20]), "+f"(d[21]), "+f"(d[22]), "+f"(d[23]), "+f"(d[24]), "+f"(d[25]), "+f"(d[26]), "+f"(d[27]), "+f"(d[28]), "+f"(d[29]), "+f"(d[30]), "+f"(d[31]), "+f"(d[32]), "+f"(d[33]), "+f"(d[34]), "+f"(d[35]), "+f"(d[36]), "+f"(d[37]), "+f"(d[38]), "+f"(d[39]), "+f"(d[40]), "+f"(d[41]), "+f"(d[42]), "+f"(d[43]), "+f"(d[44]), "+f"(d[45]), "+f"(d[46]), "+f"(d[47]), "+f"(d[48]), "+f"(d[49]), "+f"(d[50]), "+f"(d[51]), "+f"(d[52]), "+f"(d[53]), "+f"(d[54]), "+f"(d[55]), "+f"(d[56]), "+f"(d[57]), "+f"(d[58]), "+f"(d[59]), "+f"(d[60]), "+f"(d[61]), "+f"(d[62]), "+f"(d[63]), "+f"(d[64]), "+f"(d[65]), "+f"(d[66]), "+f"(d[67]), "+f"(d[68]), "+f"(d[69]), "+f"(d[70]), "+f"(d[71]), "+f"(d[72]), "+f"(d[73]), "+f"(d[74]), "+f"(d[75]), "+f"(d[76]), "+f"(d[77]), "+f"(d[78]), "+f"(d[79]), "+f"(d[80]), "+f"(d[81]), "+f"(d[82]), "+f"(d[83]), "+f"(d[84]), "+f"(d[85]), "+f"(d[86]), "+f"(d[87]), "+f"(d[88]), "+f"(d[89]), "+f"(d[90]), "+f"(d[91]), "+f"(d[92]), "+f"(d[93]), "+f"(d[94]), "+f"(d[95]), "+f"(d[96]), "+f"(d[97]), "+f"(d[98]), "+f"(d[99]), "+f"(d[100]), "+f"(d[101]), "+f"(d[102]), "+f"(d[103]), "+f"(d[104]), "+f"(d[105]), "+f"(d[106]), "+f"(d[107]), "+f"(d[108]), "+f"(d[109]), "+f"(d[110]), "+f"(d[111]), "+f"(d[112]), "+f"(d[113]), "+f"(d[114]), "+f"(d[115]), "+f"(d[116]), "+f"(d[117]), "+f"(d[118]), "+f"(d[119]), "+f"(d[120]), "+f"(d[121]), "+f"(d[122]), "+f"(d[123]), "+f"(d[124]), "+f"(d[125]), "+f"(d[126]), "+f"(d[127])
        : "l"(da), "l"(db), "r"(scale_d));
}

__device__ __forceinline__ void wgmma_ss_n32_tb0(float (&d)[16], uint64_t da, uint64_t db, int scale_d) {
    asm volatile("{\n.reg .pred p;\nsetp.ne.b32 p, %18, 0;\n"
        "wgmma.mma_async.sync.aligned.m64n32k16.f32.bf16.bf16 {%0, %1, %2, %3, %4, %5, %6, %7, %8, %9, %10, %11, %12, %13, %14, %15}, %16, %17, p, 1, 1, 0, 0;\n}\n"
        : "+f"(d[0]), "+f"(d[1]), "+f"(d[2]), "+f"(d[3]), "+f"(d[4]), "+f"(d[5]), "+f"(d[6]), "+f"(d[7]), "+f"(d[8]), "+f"(d[9]), "+f"(d[10]), "+f"(d[11]), "+f"(d[12]), "+f"(d[13]), "+f"(d[14]), "+f"(d[15])
        : "l"(da), "l"(db), "r"(scale_d));
}

__device__ __forceinline__ void wgmma_ss_n64_tb0(float (&d)[32], uint64_t da, uint64_t db, int scale_d) {
    asm volatile("{\n.reg .pred p;\nsetp.ne.b32 p, %34, 0;\n"
        "wgmma.mma_async.sync.aligned.m64n64k16.f32.bf16.bf16 {%0, %1, %2, %3, %4, %5, %6, %7, %8, %9, %10, %11, %12, %13, %14, %15, %16, %17, %18, %19, %20, %21, %22, %23, %24, %25, %26, %27, %28, %29, %30, %31}, %32, %33, p, 1, 1, 0, 0;\n}\n"
        : "+f"(d[0]), "+f"(d[1]), "+f"(d[2]), "+f"(d[3]), "+f"(d[4]), "+f"(d[5]), "+f"(d[6]), "+f"(d[7]), "+f"(d[8]), "+f"(d[9]), "+f"(d[10]), "+f"(d[11]), "+f"(d[12]), "+f"(d[13]), "+f"(d[14]), "+f"(d[15]), "+f"(d[16]), "+f"(d[17]), "+f"(d[18]), "+f"(d[19]), "+f"(d[20]), "+f"(d[21]), "+f"(d[22]), "+f"(d[23]), "+f"(d[24]), "+f"(d[25]), "+f"(d[26]), "+f"(d[27]), "+f"(d[28]), "+f"(d[29]), "+f"(d[30]), "+f"(d[31])
        : "l"(da), "l"(db), "r"(scale_d));
}

struct Maps {
    CUtensorMap xa, xa2, xa4, xas, wup4, wup8, mqa2, mqa4, mqb1, mqb2, uc, x, out, wq, wk, fa[3], fb[2], fc;
};

__device__ __forceinline__ uint64_t mkd(uint32_t lo) {
    uint64_t d;
    asm("mov.b64 %0, {%1, %2};" : "=l"(d) : "r"(lo), "r"((1024u >> 4) | (1u << 30)));
    return d;
}
__device__ __forceinline__ void bulk_ld(uint32_t dst, const void* src, uint32_t bytes, uint32_t bar) {
    asm volatile("cp.async.bulk.shared::cluster.global.mbarrier::complete_tx::bytes [%0], [%1], %2, [%3];" ::"r"(dst), "l"(src), "r"(bytes), "r"(bar) : "memory");
}
__device__ __forceinline__ void bulk_st(void* dst, uint32_t src, uint32_t bytes) {
    asm volatile("cp.async.bulk.global.shared::cta.bulk_group [%0], [%1], %2;" ::"l"(dst), "r"(src), "r"(bytes) : "memory");
}
__device__ __forceinline__ void ring_ld(uint32_t sb, uint32_t slot8, int n) {
    mbar_expect_tx(sb + B_R2 + slot8, 8192);
    bulk_ld(sb + R1 + slot8 * 1024, (const char*)g_wepi + n * 8192, 8192, sb + B_R2 + slot8);
}

__device__ __forceinline__ void ring_half(uint32_t sb, uint32_t slot8, uint32_t hoff, const CUtensorMap* tm, int c1, int c2) {
    mbar_expect_tx(sb + B_R1 + slot8, 8192);
    tma3(sb + slot8 * 2048 + hoff, tm, 0, c1, c2, sb + B_R1 + slot8);
}
__device__ __forceinline__ void ring_full(uint32_t sb, uint32_t slot8, const CUtensorMap* tm, int c1, int c2) {
    mbar_expect_tx(sb + B_R1 + slot8, 16384);
    mbar_arrive(sb + B_R1 + slot8);
    tma3(sb + slot8 * 2048, tm, 0, c1, c2, sb + B_R1 + slot8);
}
__device__ __forceinline__ void cta_done(int mode) {
    if (mode == 0 && atomicAdd(&g_sync[4], 1) == NCTA + 1) {
#pragma unroll
        for (int i = 0; i < 5; i++) g_sync[i] = 0;
    }
}

__device__ __forceinline__ void fold_cta(const Maps& mp, uint32_t sb, int mode) {
    constexpr uint32_t F_FULL = MISC, F_EMPTY = MISC + 32, F_T1 = MISC + 64, STG = 49152, FOUT = 3 * STG;
    const int tid = threadIdx.x, f = blockIdx.x - NCTA;
    if (mode == 2) return;
    if (tid == 0) {
        for (int i = 0; i < 3; i++) { mbar_init(sb + F_FULL + 8 * i, 1); mbar_init(sb + F_EMPTY + 8 * i, 2); }
        mbar_init(sb + F_T1, 2);
        asm volatile("fence.mbarrier_init.release.cluster;" ::: "memory");
        fence_async();
    }
    __syncthreads();
    const int wg = __shfl_sync(0xffffffffu, tid >> 7, 0);
    int st = 0, ph = 0;
    if (wg == 0) {
        if (tid == 0) {
#pragma unroll 1
            for (int it = 0; it < 96; it++) {
                const int p = it >> 3, kc = it & 7, job = p >> 2;
                if (it == 64) mbar_wait(sb + F_T1, 0);
                mbar_wait(sb + F_EMPTY + 8 * st, ph ^ 1);
                mbar_expect_tx(sb + F_FULL + 8 * st, STG);
                tma3(sb + st * STG, &mp.fa[job], 0, 256 * f + 128 * ((p >> 1) & 1), kc, sb + F_FULL + 8 * st);
                tma3(sb + st * STG + 16384, &mp.fb[job != 0], 0, 64 * kc + (job == 1 ? 512 : 0), 4 * (p & 1), sb + F_FULL + 8 * st);
                if (++st == 3) { st = 0; ph ^= 1; }
            }
        }
        return;
    }
    const int h = wg - 1, lane = tid & 31, w = (tid >> 5) & 3;
    const uint32_t sd = (sb & 0x3FFFF) >> 4;
    const bool el = (tid & 127) == 0;
#pragma unroll 1
    for (int p = 0; p < 12; p++) {
        float acc[128];
        fresh(acc);
#pragma unroll 1
        for (int kc = 0; kc < 8; kc++) {
            mbar_wait(sb + F_FULL + 8 * st, ph);
            wg_fence();
#pragma unroll
            for (int kk = 0; kk < 4; kk++)
                wgmma_ss_n256_tb1(acc, dsc(sd, st * STG + h * 8192 + kk * 32, 16), dsc(sd, st * STG + 16384 + kk * 2048, 8192), 1);
            wg_commit();
            wg_wait<0>();
            if (el) mbar_arrive(sb + F_EMPTY + 8 * st);
            if (++st == 3) { st = 0; ph ^= 1; }
        }
        pin(acc);
        const int job = p >> 2;
        if (el) {
            asm volatile("cp.async.bulk.wait_group 0;" ::: "memory");
            if (p == 4) { fence_async_g(); mbar_arrive(sb + F_T1); }
        }
        bar_sync(3 + h, 128);
        uint32_t r = 16 * w + (lane & 7) + ((lane >> 3) & 1) * 8;
        const float fs = job == 1 ? 0.5f : 1.f;
        if (job == 1) r = (r & ~31) | (((r >> 1) & 3) << 3) | (((r >> 3) & 3) << 1) | (r & 1);
        const uint32_t oa = sb + FOUT + h * 32768 + r * 128 + ((((lane >> 4) ^ r) & 7) << 4);
#pragma unroll
        for (int i = 0; i < 16; i++)
            stsm4((oa ^ ((i & 3) << 5)) + (i >> 2) * 8192, pack2(acc[8 * i] * fs, acc[8 * i + 1] * fs), pack2(acc[8 * i + 2] * fs, acc[8 * i + 3] * fs),
                  pack2(acc[8 * i + 4] * fs, acc[8 * i + 5] * fs), pack2(acc[8 * i + 6] * fs, acc[8 * i + 7] * fs));
        fence_async();
        bar_sync(3 + h, 128);
        if (el) {
            const int row0 = 256 * f + 128 * ((p >> 1) & 1) + 64 * h + (job == 1 ? 512 : 0);
            if (job == 0) tma3_store(&mp.fc, sb + FOUT + h * 32768, 0, row0, 4 * (p & 1));
            else {
#pragma unroll 1
                for (int i = 0; i < 16; i++)
                    bulk_st((char*)g_wepi + (row0 / 8 + 2 * (i & 3) + (p & 1)) * 8192 + (i >> 2) * 2048, sb + FOUT + h * 32768 + i * 2048, 2048);
            }
            asm volatile("cp.async.bulk.commit_group;" ::: "memory");
        }
    }
    if (el) {
        asm volatile("cp.async.bulk.wait_group 0;" ::: "memory");
        fence_async_g();
        if (mode == 0) flag_add(&g_sync[3]);
    }
    bar_sync(2, 256);
    if (tid == 128) cta_done(mode);
}

__global__ void __launch_bounds__(384, 1) main_kernel(const __grid_constant__ Maps mp, const bf16* __restrict__ x, const bf16* __restrict__ dw, const bf16* wup, const int mode) {
    extern __shared__ __align__(1024) uint8_t smem[];
    const uint32_t sb = smem_u32(smem);
    const int tid = threadIdx.x;
    PE();
    if (blockIdx.x >= NCTA) { fold_cta(mp, sb, mode); return; }
    const int b = blockIdx.x / TPB, ti = blockIdx.x % TPB;
    const int piece = blockIdx.x & 127;
    const int wg = __shfl_sync(0xffffffffu, tid >> 7, 0);
    const int lane = tid & 31, w = (tid >> 5) & 3;
    const bool w0 = __shfl_sync(0xffffffffu, w, 0) == 0;
    const uint32_t sd = (sb & 0x3FFFF) >> 4;
    const uint32_t adA = sd + (AT >> 4) + (1u << 16);
    const uint32_t bd0 = sd;
    const uint32_t bd2k = bd0 + ((2048u >> 4) << 16);
    const bool el = (tid & 127) == 0;
    const uint32_t lrow = 16 * w + (lane & 7) + ((lane >> 3) & 1) * 8;
    const uint32_t loff = lrow * 128 + ((((lane >> 4) ^ lrow) & 7) << 4);
    const int r0 = 16 * w + (lane >> 2);

    if (wg == 0) {
        asm volatile("setmaxnreg.inc.sync.aligned.u32 184;");
        uint32_t q[112];
        PG(206);
        if (tid == 0) {
            mbar_init(sb + B_MK, 1);
            for (int i = 0; i < 9; i++) mbar_init(sb + B_R1 + 8 * i, 2);
            for (int i = 0; i < 5; i++) asm volatile("st.shared.u32 [%0], 0;" ::"r"(sb + CNT + 4 * i) : "memory");
        } else if (tid == 32) {
            mbar_init(sb + B_LN, 1); mbar_init(sb + B_MQ, 1);
            mbar_init(sb + B_H1, 2); mbar_init(sb + B_H2, 1); mbar_init(sb + B_H3, 2);
            for (int i = 0; i < 3; i++) { mbar_init(sb + B_KV + 8 * i, 2); mbar_init(sb + B_P + 8 * i, 4); mbar_init(sb + B_GO + 8 * i, 4); }
            mbar_init(sb + B_UC, 1); mbar_init(sb + B_UC + 8, 1); mbar_init(sb + B_X, 8);
        } else if (tid == 64) {
            for (int i = 0; i < 20; i++) mbar_init(sb + B_R2 + 8 * i, 1);
        } else if (tid == 96) {
            for (int i = 0; i < 20; i++) mbar_init(sb + B_E2 + 8 * i, 4);
        }
        if (lane == 0) {
            asm volatile("fence.mbarrier_init.release.cluster;" ::: "memory");
            fence_async();
        }
        PG(207);
        __syncwarp();
        if (SU != 2) asm volatile("bar.arrive 5, 384;" ::: "memory");
        if (tid == 0) {
            mbar_expect_tx(sb + B_MK, 65536 + 32768);
            tma3(sb + 16384, &mp.wq, 0, 64 * (piece >> 4), 0, sb + B_MK);
            tma3(sb + 81920, &mp.wk, 0, 32 * (piece & 15), 0, sb + B_MK);
            for (int i = 0; i < 14; i++) mbar_arrive(sb + B_R1 + 8 * (i >> 1));
            if (mode != 1) {
                ring_full(sb, 56, &mp.wup8, 0, 8);
                ring_full(sb, 64, &mp.wup8, 16, 8);
                ring_full(sb, 0, &mp.wup8, 32, 8);
            }
        }
        PG(208);
        bar_sync(1, 128);
        if (SU == 2) asm volatile("bar.arrive 5, 384;" ::: "memory");
        PT(0);
        PG(200);
        {
            float mq[16];
            fresh(mq);
            mbar_wait(sb + B_MK, 0);
            PT(1);
            if (tid == 32) l2_prefetch((const char*)wup + piece * 8192, 8192);
            wg_fence();
#pragma unroll 1
            for (int c = 0; c < 8; c++)
#pragma unroll
                for (int kk = 0; kk < 4; kk++)
                    wgmma_ss_n32_tb0(mq, dsc(sd, 16384 + c * 8192 + kk * 32, 16), dsc(sd, 81920 + c * 4096 + kk * 32, 16), 1);
            wg_commit();
            wg_wait<0>();
            if (mode != 1 && w0 && elect1()) {
#pragma unroll 1
                for (int i = 1; i < 7; i++) ring_full(sb, 8 * i, &mp.wup8, 32 + 16 * i, 8);
            }
            pin(mq);
            uint32_t* c = reinterpret_cast<uint32_t*>(g_mqk + (64 * (piece >> 4) + r0) * D_ + 32 * (piece & 15) + 2 * (lane & 3));
#pragma unroll
            for (int n = 0; n < 4; n++) { c[4 * n] = pack2(mq[4 * n], mq[4 * n + 1]); c[4 * n + 4 * D_] = pack2(mq[4 * n + 2], mq[4 * n + 3]); }
            fence_async_g();
            bar_sync(1, 128);
            if (el) {
                if (mode == 0) flag_add(&g_sync[2]);
                if (mode == 0) flag_wait(&g_sync[2], NCTA);
                mbar_arrive(sb + B_MQ);
                PG(203);
                PT(12);
                mbar_wait(sb + B_LN, 0);
#pragma unroll 1
                for (int c = 0; c < 8; c++) {
                    tma4_store(&mp.xas, sb + AT + c * 8192, 0, 62 * ti, c, b);
                    const unsigned t0 = (unsigned)clock();
                    while (c < 7 && (unsigned)clock() - t0 < XS_GAP) __nanosleep(20);
                }
                asm volatile("cp.async.bulk.commit_group;" ::: "memory");
                if (mode == 1) asm volatile("cp.async.bulk.wait_group 0;" ::: "memory");
            }
            PT(13);
            if (mode == 1) return;
        }
        mbar_wait(sb + B_H1, 0);
        PT(2);
        uint32_t slot8 = 24, par = 0, prev8 = 0, prev2 = 0;
        auto adv = [&]() { prev2 = prev8; prev8 = slot8; slot8 += 8; if (slot8 == 72) { slot8 = 0; par ^= 1; } };
        {
            float acc[128];
            fresh(acc);
            auto step = [&](int i) {
                const uint32_t aa = adA + (i >> 1) * 512 + (i & 1) * 4, bb = bd0 + ((4096u >> 4) << 16) + slot8 * 128;
                wg_fence();
                wgmma_ss_n256_tb1(acc, mkd(aa), mkd(bb), 1);
                wgmma_ss_n256_tb1(acc, mkd(aa + 2), mkd(bb + 128), 1);
                wg_commit();
                wg_wait<1 + LAGA>();
            };
#pragma unroll 1
            for (int i = 0; i < 8 + LAGA; i++) {
                mbar_wait(sb + B_R1 + slot8, par);
                step(i);
                if (i > LAGA && w0 && elect1()) ring_full(sb, LAGA ? prev2 : prev8, &mp.mqa4, 32 * (i - LAGA) + 256, 4);
                adv();
            }
#pragma unroll 1
            for (int i = 8 + LAGA; i < 16; i++) {
                mbar_wait(sb + B_R1 + slot8, par);
                if (i == 15 && el) mbar_arrive(sb + B_H2);
                step(i);
                if (w0 && elect1()) ring_full(sb, LAGA ? prev2 : prev8, &mp.wup8, 16 * (i - LAGA) - 128, 0);
                adv();
            }
            if (LAGA) {
                wg_wait<1>();
                if (w0 && elect1()) ring_full(sb, prev2, &mp.wup8, 112, 0);
            }
            wg_wait<0>();
            if (w0 && elect1()) ring_full(sb, prev8, &mp.wup8, 128, 0);
            pin(acc);
            PT(3);
#pragma unroll
            for (int kk = 0; kk < 4; kk++)
                stsm4((sb + QS + loff) ^ (kk << 5), pack2(acc[96 + 8 * kk], acc[97 + 8 * kk]), pack2(acc[98 + 8 * kk], acc[99 + 8 * kk]),
                      pack2(acc[100 + 8 * kk], acc[101 + 8 * kk]), pack2(acc[102 + 8 * kk], acc[103 + 8 * kk]));
            fence_async();
#pragma unroll
            for (int i = 47; i >= 0; i--) q[64 + i] = pack2v(acc[2 * i], acc[2 * i + 1]);
        }
        if (el) {
            asm volatile("cp.async.bulk.wait_group 0;" ::: "memory");
            if (mode == 0) {
                fence_async_g();
                flag_add(&g_sync[b]);
                flag_wait(&g_sync[b], TPB);
            }
        }
        __syncwarp();
        mbar_wait(sb + B_H3, 0);
        PT(4);
        slot8 = 48; par = 1;
#pragma unroll
        for (int half = 0; half < 2; half++) {
            float acc[64];
            fresh(acc);
            auto step = [&](int m) {
                const uint32_t aa = adA + m * 512, bb = bd0 + ((8192u >> 4) << 16) + slot8 * 128;
                mbar_wait(sb + B_R1 + slot8, par);
                wg_fence();
#pragma unroll
                for (int kk = 0; kk < 4; kk++) wgmma_ss_n128_tb1(acc, mkd(aa + 2 * kk), mkd(bb + 128 * kk), 1);
                wg_commit();
                wg_wait<1 + LAGB>();
            };
#pragma unroll 1
            for (int m = 0; m < 8; m++) {
                step(m);
                if (m > LAGB && w0 && elect1()) {
                    if (half == 0) ring_full(sb, LAGB ? prev2 : prev8, &mp.mqb2, 64 * (m - LAGB), 2);
                    else if (m < 4 + LAGB) tma4(sb + (LAGB ? prev2 : prev8) * 2048, &mp.xa2, 0, 0, 2 * (m - LAGB), b, sb + B_KV + 8);
                }
                adv();
            }
            if (LAGB && half == 0) {
                wg_wait<1>();
                if (w0 && elect1()) ring_full(sb, prev2, &mp.mqb2, 448, 2);
            }
            wg_wait<0>();
            if (w0 && elect1()) {
                if (half == 0) {
                    mbar_expect_tx(sb + B_KV + 8, 65536);
                    for (int i = 0; i < 3; i++) mbar_arrive(sb + B_KV + 8 * i);
                    tma4(sb + prev8 * 2048, &mp.xa2, 0, 0, 0, b, sb + B_KV + 8);
                } else {
                    mbar_expect_tx(sb + B_KV + 16, 65536);
                    tma4(sb + R2, &mp.xa, 0, 64, 0, b, sb + B_KV + 16);
                    mbar_expect_tx(sb + B_KV, 65536);
                    tma4(sb + R0, &mp.xa, 0, 128, 0, b, sb + B_KV);
                }
            }
            pin(acc);
#pragma unroll
            for (int i = 31; i >= 0; i--) q[32 * half + i] = pack2v(acc[2 * i], acc[2 * i + 1]);
        }
        bar_sync(1, 128);
        PT(5);

        const float CS = 0.04419417382415922f * 1.4426950408889634f;
        float m0 = -INFINITY, m1 = -INFINITY, l0 = 0.f, l1 = 0.f;
        int s = 0, sn = 1, ph = 0;
        float S[32];
        const bool l0w = lane == 0, q0 = (lane & 3) == 0;
#pragma unroll 1
        for (int j = -1;; j++) {
            if (j >= 0) {
                PL(j, 1);
                if (j == NKV - 1) {
#pragma unroll
                    for (int i = (T_ - 64 * (NKV - 1)) / 2; i < 32; i++) asm volatile("mov.b32 %0, 0xff800000;" : "=f"(S[i]));
                }
                const bool kv = mbar_test(sb + B_KV + sn * 8, ph);
                const uint32_t pb = sb + R3 + (s == 0 ? 2 : s - 1) * 8192;
                float a0 = 0.f, a1 = 0.f, sc0 = 1.f, sc1 = 1.f;
                auto expo = [&]() {
                    const float n0 = -m0 * CS, n1 = -m1 * CS;
                    a0 = 0.f; a1 = 0.f;
#pragma unroll
                    for (int kk = 0; kk < 4; kk++) {
                        float p[8];
#pragma unroll
                        for (int e = 0; e < 8; e++) p[e] = ex2(fmaf(S[8 * kk + e], CS, (e & 2) ? n1 : n0));
                        a0 += (p[0] + p[1]) + (p[4] + p[5]);
                        a1 += (p[2] + p[3]) + (p[6] + p[7]);
                        stsm4((pb + loff) ^ (kk << 5), pack2(p[0], p[1]), pack2(p[2], p[3]), pack2(p[4], p[5]), pack2(p[6], p[7]));
                    }
                };
                if (j > 0 || !SK0) expo();
                if ((SK0 && j == 0) || __any_sync(0xffffffffu, !(a0 <= LAZY) || !(a1 <= LAZY))) {
                    float x0 = m0, x1 = m1;
#pragma unroll
                    for (int n = 0; n < 8; n++) { x0 = fmaxf(x0, fmaxf(S[4 * n], S[4 * n + 1])); x1 = fmaxf(x1, fmaxf(S[4 * n + 2], S[4 * n + 3])); }
                    x0 = fmaxf(x0, __shfl_xor_sync(0xffffffffu, x0, 1));
                    x1 = fmaxf(x1, __shfl_xor_sync(0xffffffffu, x1, 1));
                    x0 = fmaxf(x0, __shfl_xor_sync(0xffffffffu, x0, 2));
                    x1 = fmaxf(x1, __shfl_xor_sync(0xffffffffu, x1, 2));
                    sc0 = ex2((m0 - x0) * CS); sc1 = ex2((m1 - x1) * CS);
                    m0 = x0; m1 = x1;
                    expo();
                }
                if (q0) { sts_f32(sb + SCL + s * 256 + r0 * 4, sc0); sts_f32(sb + SCL + s * 256 + r0 * 4 + 32, sc1); }
                __syncwarp();
                if (l0w) mbar_arrive(sb + B_P + s * 8);
                l0 = fmaf(l0, sc0, a0); l1 = fmaf(l1, sc1, a1);
                PL(j, 2);
                if (j == NKV - 1) break;
                if (!kv) mbar_wait(sb + B_KV + sn * 8, ph);
            } else {
                mbar_wait(sb + B_KV + 8, 0);
            }
            const uint32_t kd = sd + sn * 4096;
            if (TRIM & 2 && j == NKV - 2) {
                float Sn[16];
                wg_fence();
#pragma unroll
                for (int kk = 0; kk < 28; kk++) {
                    wgmma_rs_n32_tb0(Sn, q[4 * kk], q[4 * kk + 1], q[4 * kk + 2], q[4 * kk + 3], dsc(kd, (kk >> 2) * 8192 + (kk & 3) * 32, 16), kk > 0);
                    if (kk == FENCE_AT) { fence_async(); __syncwarp(); }
                    if (kk == GO_LAST && l0w) mbar_arrive(sb + B_GO + s * 8);
                }
#pragma unroll
                for (int kk = 0; kk < 4; kk++)
                    wgmma_ss_n32_tb0(Sn, dsc(sd, QS + kk * 32, 16), dsc(kd, 7 * 8192 + kk * 32, 16), 1);
                wg_commit();
                wg_wait<0>();
                pin(Sn);
#pragma unroll
                for (int i = 0; i < 16; i++) S[i] = Sn[i];
            } else {
            float Sn[32];
            wg_fence();
#pragma unroll
            for (int kk = 0; kk < 28; kk++) {
                wgmma_rs_n64_tb0(Sn, q[4 * kk], q[4 * kk + 1], q[4 * kk + 2], q[4 * kk + 3], dsc(kd, (kk >> 2) * 8192 + (kk & 3) * 32, 16), kk > 0);
                if (kk == FENCE_AT) { fence_async(); __syncwarp(); }
                if (kk == GO_AT) { PL(j, 3); if (j >= 0 && l0w) mbar_arrive(sb + B_GO + s * 8); }
            }
#pragma unroll
            for (int kk = 0; kk < 4; kk++)
                wgmma_ss_n64_tb0(Sn, dsc(sd, QS + kk * 32, 16), dsc(kd, 7 * 8192 + kk * 32, 16), 1);
            wg_commit();
            PL(j, 0);
            wg_wait<0>();
            pin(Sn);
#pragma unroll
            for (int i = 0; i < 32; i++) S[i] = Sn[i];
            }
            s = sn;
            if (++sn == 3) sn = 0;
            if (sn == 1) ph ^= 1;
        }
        l0 += __shfl_xor_sync(0xffffffffu, l0, 1); l1 += __shfl_xor_sync(0xffffffffu, l1, 1);
        l0 += __shfl_xor_sync(0xffffffffu, l0, 2); l1 += __shfl_xor_sync(0xffffffffu, l1, 2);
        if (q0) { sts_f32(sb + LINV + r0 * 4, rcp(l0)); sts_f32(sb + LINV + r0 * 4 + 32, rcp(l1)); }
        fence_async();
        __syncwarp();
        if (l0w) {
            mbar_arrive(sb + B_GO + s * 8);
            uint32_t slot8 = 8 * w, par = 0;
#pragma unroll 1
            for (int n = 20 + w; n < 136; n += 4) {
                mbar_wait(sb + B_E2 + slot8, par);
                if (n < 128) ring_ld(sb, slot8, n);
                else {
                    mbar_expect_tx(sb + B_X, 8192);
                    tma4(sb + R1 + slot8 * 1024, &mp.x, 0, 62 * ti, n - 128, b, sb + B_X);
                }
                slot8 += 32;
                if (slot8 >= 160) { slot8 -= 160; par ^= 1; }
            }
        }
        PDUMP();
    } else {
        asm volatile("setmaxnreg.dec.sync.aligned.u32 160;");
        const int h = wg - 1;
        uint32_t v[4][8], v2[4][8];
        if (SU != 0) bar_sync(5, 384);
        PG(206);
#pragma unroll
        for (int i = 0; i < 8; i++) {
            const int t = 62 * ti - 1 + 32 * (i >> 2) + 16 * h + 4 * w + (i & 3);
            const uint4* p = reinterpret_cast<const uint4*>(x + ((size_t)b * T_ + t) * D_) + lane;
            uint32_t* d = i < 4 ? v[i & 3] : v2[i & 3];
#pragma unroll
            for (int c = 0; c < 2; c++)
                asm volatile("{\n.reg .pred p;\nsetp.lt.u32 p, %5, %6;\nmov.b32 %0, 0;\nmov.b32 %1, 0;\nmov.b32 %2, 0;\nmov.b32 %3, 0;\n"
                             "@p ld.global.nc.v4.u32 {%0, %1, %2, %3}, [%4];\n}\n"
                             : "=r"(d[4 * c]), "=r"(d[4 * c + 1]), "=r"(d[4 * c + 2]), "=r"(d[4 * c + 3]) : "l"(p + 32 * c), "r"(t), "n"(T_));
        }
#pragma unroll 1
        for (int bt = 0; bt < 2; bt++) {
            PT(bt ? 13 : 0);
            float a[8];
            const uint32_t la = sb + AT + (lane >> 3) * 8192 + (32 * bt + 16 * h + 4 * w) * 128 + (((lane & 7) ^ ((w & 1) * 4)) << 4);
            const bool b4 = lane & 16, b3 = lane & 8, b2 = lane & 4;
#pragma unroll
            for (int r = 0; r < 4; r++) {
                float c[4] = {0.f, 0.f, 0.f, 0.f};
#pragma unroll
                for (int i = 0; i < 8; i += 2) hmma(c, v[r][i], v[r][i], v[r][i + 1], v[r][i + 1], v[r][i], v[r][i + 1]);
                a[4 + r] = (lane & 3) == (lane >> 3) ? (b2 ? c[1] : c[0]) : 0.f;
                if (r & 1) {
                    float e[4] = {0.f, 0.f, 0.f, 0.f};
#pragma unroll
                    for (int i = 0; i < 8; i += 2) hmma(e, v[r - 1][i], v[r][i], v[r - 1][i + 1], v[r][i + 1], 0x3f803f80u, 0x3f803f80u);
                    a[r - 1] = e[0]; a[r] = e[2];
                }
            }
            float k[4];
#pragma unroll
            for (int i = 0; i < 4; i++) {
                const int lo = (i & 1) + 4 * (i >> 1);
                k[i] = (b4 ? a[lo + 2] : a[lo]) + __shfl_xor_sync(0xffffffffu, b4 ? a[lo] : a[lo + 2], 16);
            }
            const float k0 = (b3 ? k[1] : k[0]) + __shfl_xor_sync(0xffffffffu, b3 ? k[0] : k[1], 8);
            const float k1 = (b3 ? k[3] : k[2]) + __shfl_xor_sync(0xffffffffu, b3 ? k[2] : k[3], 8);
            float z = (b2 ? k1 : k0) + __shfl_xor_sync(0xffffffffu, b2 ? k0 : k1, 4);
            z += __shfl_xor_sync(0xffffffffu, z, 2);
            z += __shfl_xor_sync(0xffffffffu, z, 1);
            const float zo = __shfl_xor_sync(0xffffffffu, z, 4);
            PG(204 + bt);
            const float mu = (b2 ? zo : z) * (0.25f / D_);
            float sd_ = bfr(bfr(fmaxf(fmaf(b2 ? z : zo, 1.f / D_, -mu * mu), 0.f)) + 1e-5f);
            asm("sqrt.approx.f32 %0, %0;" : "+f"(sd_));
            const float ri = rcp(bfr(sd_));
            const uint32_t w1 = pack2(mu, ri), w2 = pack2(ri - bhi(w1), ri - bhi(w1));
#pragma unroll
            for (int r = 0; r < 4; r++) {
                const uint32_t s1 = __shfl_sync(0xffffffffu, w1, 8 * r), rl = __shfl_sync(0xffffffffu, w2, 8 * r);
                const uint32_t m2 = __byte_perm(s1, 0, 0x1010), rh = __byte_perm(s1, 0, 0x3232);
#pragma unroll
                for (int i = 0; i < 8; i++) { const uint32_t d = bsub2(v[r][i], m2); v[r][i] = bfma2(d, rh, bmul2(d, rl)); }
                sts4((la ^ (r << 4)) + r * 128, v[r][0], v[r][1], v[r][2], v[r][3]);
                sts4((la ^ (r << 4)) + r * 128 + 32768, v[r][4], v[r][5], v[r][6], v[r][7]);
#pragma unroll
                for (int i = 0; i < 8; i++) v[r][i] = v2[r][i];
            }
        }
        fence_async();
        if (SU == 0) bar_sync(5, 384); else bar_sync(2, 256);
        if (tid == 128) mbar_arrive(sb + B_LN);
        PG(202);
        if (mode == 1) return;
        float acc[128];
#pragma unroll
        for (int pass = 0; pass < 2; pass++) {
            if (pass == 1) mbar_wait(sb + B_H2, 0);
            PT(1 + 3 * pass);
            fresh(acc);
            uint32_t slot8 = pass ? 8 : 56, par = 0, prev8 = 0;
            auto adv = [&]() { prev8 = slot8; slot8 += 8; if (slot8 == 72) { slot8 = 0; par ^= 1; } };
            auto step = [&](int kk) {
                wg_fence();
                wgmma_ss_n256_tb1(acc, mkd(adA + (kk >> 2) * 512 + (kk & 3) * 2), mkd(bd2k + h * 512 + slot8 * 128), 1);
                wg_commit();
                wg_wait<1>();
            };
#pragma unroll 1
            for (int kk = 0; kk < 24; kk++) {
                mbar_wait(sb + B_R1 + slot8, par);
                step(kk);
                if (kk > 0 && w0 && elect1()) ring_half(sb, prev8, h * 8192, &mp.wup4, 16 * kk + 128, (pass ? 0 : 8) + 4 * h);
                adv();
            }
            if (pass == 0 && w0) mbar_wait(sb + B_MQ, 0);
#pragma unroll 1
            for (int kk = 24; kk < 32; kk++) {
                mbar_wait(sb + B_R1 + slot8, par);
                if (kk == 31 && el) mbar_arrive(sb + (pass ? B_H3 : B_H1));
                step(kk);
                if (w0 && elect1()) ring_half(sb, prev8, h * 8192, pass ? &mp.mqb1 : &mp.mqa2, (pass ? 64 : 32) * (kk - 24), pass ? h : 4 + 2 * h);
                adv();
            }
            wg_wait<0>();
            if (w0 && elect1()) ring_half(sb, prev8, h * 8192, pass ? &mp.mqb1 : &mp.mqa2, pass ? 0 : 256, pass ? 2 + h : 4 + 2 * h);
            pin(acc);
            PT(2 + 3 * pass);
            bf16* ucp = g_uc + ((size_t)blockIdx.x * 128 + r0) * D_ + 256 * h + 8 * (lane & 3);
            if (pass == 0) {
                float s0 = 0.f, s1 = 0.f, v0 = 0.f, v1 = 0.f;
#pragma unroll
                for (int n = 0; n < 32; n++) {
#pragma unroll
                    for (int e = 0; e < 4; e++) acc[4 * n + e] = gelu2(acc[4 * n + e]);
                    s0 += acc[4 * n] + acc[4 * n + 1]; s1 += acc[4 * n + 2] + acc[4 * n + 3];
                    v0 = fmaf(acc[4 * n], acc[4 * n], v0); v0 = fmaf(acc[4 * n + 1], acc[4 * n + 1], v0);
                    v1 = fmaf(acc[4 * n + 2], acc[4 * n + 2], v1); v1 = fmaf(acc[4 * n + 3], acc[4 * n + 3], v1);
                }
#pragma unroll
                for (int o = 1; o < 4; o <<= 1) {
                    s0 += __shfl_xor_sync(0xffffffffu, s0, o); s1 += __shfl_xor_sync(0xffffffffu, s1, o);
                    v0 += __shfl_xor_sync(0xffffffffu, v0, o); v1 += __shfl_xor_sync(0xffffffffu, v1, o);
                }
                if ((lane & 3) == 0) {
                    uint32_t a = sb + STAT + h * 512 + r0 * 8;
                    sts_f32(a, s0); sts_f32(a + 4, v0); sts_f32(a + 64, s1); sts_f32(a + 68, v1);
                }
                bar_sync(2, 256);
                {
                    uint32_t a = sb + STAT + (h ^ 1) * 512 + r0 * 8;
                    s0 = (s0 + lds_f32(a)) * (1.f / 512.f); v0 = (v0 + lds_f32(a + 4)) * (1.f / 512.f);
                    s1 = (s1 + lds_f32(a + 64)) * (1.f / 512.f); v1 = (v1 + lds_f32(a + 68)) * (1.f / 512.f);
                }
                v0 = rsqrtf(fmaxf(fmaf(-s0, s0, v0), 0.f) + 4e-5f); v1 = rsqrtf(fmaxf(fmaf(-s1, s1, v1), 0.f) + 4e-5f);
                s0 = -s0 * v0; s1 = -s1 * v1;
#pragma unroll
                for (int m = 0; m < 8; m++) {
                    const float* a_ = acc + 16 * m;
                    stg4(ucp + 64 * D_ + 32 * m, pack2(fmaf(a_[0], v0, s0), fmaf(a_[1], v0, s0)), pack2(fmaf(a_[4], v0, s0), fmaf(a_[5], v0, s0)),
                         pack2(fmaf(a_[8], v0, s0), fmaf(a_[9], v0, s0)), pack2(fmaf(a_[12], v0, s0), fmaf(a_[13], v0, s0)));
                    stg4(ucp + 72 * D_ + 32 * m, pack2(fmaf(a_[2], v1, s1), fmaf(a_[3], v1, s1)), pack2(fmaf(a_[6], v1, s1), fmaf(a_[7], v1, s1)),
                         pack2(fmaf(a_[10], v1, s1), fmaf(a_[11], v1, s1)), pack2(fmaf(a_[14], v1, s1), fmaf(a_[15], v1, s1)));
                }
            } else {
#pragma unroll
                for (int m = 0; m < 8; m++) {
                    const float* a_ = acc + 16 * m;
                    stg4(ucp + 32 * m, pack2(a_[0], a_[1]), pack2(a_[4], a_[5]), pack2(a_[8], a_[9]), pack2(a_[12], a_[13]));
                    stg4(ucp + 8 * D_ + 32 * m, pack2(a_[2], a_[3]), pack2(a_[6], a_[7]), pack2(a_[10], a_[11]), pack2(a_[14], a_[15]));
                }
                bar_sync(3 + h, 128);
            }
            PT(3 + 3 * pass);
        }
        int s = 1, ph = 0;
        uint32_t* cp = reinterpret_cast<uint32_t*>(g_uc + (size_t)blockIdx.x * 128 * D_) + (tid - 128);
        const uint32_t* dp = reinterpret_cast<const uint32_t*>(dw) + (((tid - 128) & ~15) | ((lane & 3) << 2) | ((lane >> 2) & 3));
        const uint32_t d0 = ldg_v(dp), d1 = ldg_v(dp + D_ / 2), d2 = ldg_v(dp + D_);
        uint32_t ga = ldg_cg(cp + 64 * (D_ / 2)), gb = ldg_cg(cp + 65 * (D_ / 2));
        fresh(acc);
#pragma unroll 1
        for (int j = 0; j < NKV; j++) {
            cp += D_ / 2;
            uint32_t gc = 0, uu = 0;
            if (j < NKV - 1) { gc = ldg_cg(cp + 65 * (D_ / 2)); uu = ldg_cg(cp); }
            mbar_wait(sb + B_P + s * 8, ph);
            PL(j, 0);
            if (j > 0) {
                const float sc0 = lds_f32(sb + SCL + s * 256 + r0 * 4), sc1 = lds_f32(sb + SCL + s * 256 + r0 * 4 + 32);
                if (__any_sync(0xffffffffu, sc0 != 1.f || sc1 != 1.f)) {
#pragma unroll
                    for (int n = 0; n < 32; n++) { acc[4 * n] *= sc0; acc[4 * n + 1] *= sc0; acc[4 * n + 2] *= sc1; acc[4 * n + 3] *= sc1; }
                }
            }
            mbar_wait(sb + B_GO + s * 8, ph);
            PL(j, 1);
            const uint32_t vd = sd + s * 4096 + h * 2048, pd = sd + (s == 0 ? 2 : s - 1) * 512;
            pin(acc);
            if (TRIM & 1 && j == NKV - 1) {
                wg_fence();
#pragma unroll
                for (int kk = 0; kk < 2; kk++) wgmma_ss_n256_tb1(acc, dsc(pd, R3 + kk * 32, 16), dsc(vd, kk * 2048, 8192), 1);
                wg_commit();
                wg_wait<0>();
                pin(acc);
                break;
            }
            wg_fence();
#pragma unroll
            for (int kk = 0; kk < 4; kk++) wgmma_ss_n256_tb1(acc, dsc(pd, R3 + kk * 32, 16), dsc(vd, kk * 2048, 8192), 1);
            wg_commit();
            wg_wait<0>();
            pin(acc);
            PL(j, 2);
            if (w0 && elect1()) {
                if (j + 3 < NKV) {
                    mbar_expect_tx(sb + B_KV + s * 8, 32768);
                    tma4(sb + s * 65536 + h * 32768, &mp.xa4, 0, 64 * (j + 3), 4 * h, b, sb + B_KV + s * 8);
                } else if (j < NKV - 1) {
                    const int n0 = (j == NKV - 3 ? 0 : 8) + 4 * h;
#pragma unroll 1
                    for (int n = n0; n < n0 + 4; n++) ring_ld(sb, n * 8, n);
                }
                if (j == NKV - 5 && mode == 0) flag_wait(&g_sync[3], 4);
                if (j >= XPF && j < XPF + 4) {
                    const int t0 = 62 * ti + 32 * h + 8 * (j - XPF), nr = min(8, T_ - t0);
                    if (nr > 0) l2_prefetch(x + ((size_t)b * T_ + t0) * D_, nr * 1024);
                }
                if (KPF && h == 0 && 64 * (j + KPF) + ti < T_) l2_prefetch(g_xa + ((size_t)b * (T_ + 8) + 1 + 64 * (j + KPF) + ti) * D_, 1024);
            }
            uu = pack2(gelu2(blo(uu)), gelu2(bhi(uu)));
            if (j < NKV - 1) asm volatile("st.global.u32 [%0], %1;" ::"l"(cp), "r"(bmul2(uu, bfma2(gc, d2, bfma2(gb, d1, bmul2(ga, d0))))) : "memory");
            ga = gb; gb = gc;
            if (++s == 3) s = 0;
            if (s == 1) ph ^= 1;
        }
        {
            const float i0 = lds_f32(sb + LINV + r0 * 4), i1 = lds_f32(sb + LINV + r0 * 4 + 32);
#pragma unroll
            for (int p = 0; p < 16; p++)
                stsm4(((sb + R0 + h * 32768 + loff) ^ ((p & 3) << 5)) + (p >> 2) * 8192,
                      pack2(acc[8 * p] * i0, acc[8 * p + 1] * i0), pack2(acc[8 * p + 2] * i1, acc[8 * p + 3] * i1),
                      pack2(acc[8 * p + 4] * i0, acc[8 * p + 5] * i0), pack2(acc[8 * p + 6] * i1, acc[8 * p + 7] * i1));
        }
        fence_async();
        fence_async_g();
        bar_sync(2, 256);
        if (lane == 0 && w < 2) ring_ld(sb, 128 + 16 * w + 8 * h, 16 + 2 * w + h);
        PT(7);
        fresh(acc);
        {
            uint32_t slot8 = 8 * h, par = 0, prev8 = 0;
#pragma unroll 1
            for (int kk = 0; kk < 64; kk++) {
                if (kk == 32 || kk == 48) mbar_wait(sb + B_UC + (kk >> 1 & 8), 0);
                mbar_wait(sb + B_R2 + slot8, par);
                wg_fence();
                wgmma_ss_n256_tb1(acc, mkd(sd + (1u << 16) + (R0 >> 4) + (kk >> 2 & 7) * 512 + (kk & 3) * 2), mkd(bd2k + (R1 >> 4) + slot8 * 64), 1);
                wg_commit();
                wg_wait<1>();
                if (kk > 0 && lane == 0) mbar_arrive(sb + B_E2 + prev8);
                if ((kk == 16 || kk == 32) && w0 && elect1() && (atom_inc_s(sb + CNT + 12 + (kk >> 3 & 4)) & 1)) {
                    mbar_expect_tx(sb + B_UC + (kk >> 2 & 8), 32768);
                    tma3(sb + R0 + (kk & 32) * 1024, &mp.uc, 0, 128 * blockIdx.x, kk >> 3 & 4, sb + B_UC + (kk >> 2 & 8));
                }
                prev8 = slot8;
                slot8 += 16;
                if (slot8 >= 160) { slot8 -= 160; par ^= 1; }
            }
        }
        wg_wait<0>();
        pin(acc);
        PT(8);
        mbar_wait(sb + B_X, 0);
        PT(9);
        {
            const uint32_t sr = (lrow + 63) & 63;
            const uint32_t xoff = sr * 128 + ((((lane >> 4) ^ sr) & 7) << 4);
#pragma unroll
            for (int p = 0; p < 16; p++) {
                const uint32_t a = ((sb + R2 + h * 32768 + xoff) ^ ((p & 3) << 5)) + (p >> 2) * 8192;
                uint32_t xv[4];
                ldsm4(a, xv);
#pragma unroll
                for (int e = 0; e < 4; e++)
                    xv[e] = pack2(acc[8 * p + 2 * e] + __uint_as_float(xv[e] << 16), acc[8 * p + 2 * e + 1] + __uint_as_float(xv[e] & 0xffff0000u));
                stsm4(a, xv[0], xv[1], xv[2], xv[3]);
            }
        }
        fence_async();
        bar_sync(3 + h, 128);
        if (el) {
            for (int c = 0; c < 4; c++) tma4_store(&mp.out, sb + R2 + (4 * h + c) * 8192, 0, 62 * ti, 4 * h + c, b);
            asm volatile("cp.async.bulk.commit_group;" ::: "memory");
            PT(10);
            if (h == 0) cta_done(mode);
            asm volatile("cp.async.bulk.wait_group.read 0;" ::: "memory");
        }
        PT(11);
        PG(201);
        PDUMP();
    }
}

typedef CUresult (*PFN_enc)(CUtensorMap*, CUtensorMapDataType, cuuint32_t, void*, const cuuint64_t*, const cuuint64_t*,
                            const cuuint32_t*, const cuuint32_t*, CUtensorMapInterleave, CUtensorMapSwizzle,
                            CUtensorMapL2promotion, CUtensorMapFloatOOBfill);

static void enc(PFN_enc f, CUtensorMap* m, void* base, int rank, const cuuint64_t* dims, const cuuint64_t* strides, const cuuint32_t* box) {
    cuuint32_t es[5] = {1, 1, 1, 1, 1};
    f(m, CU_TENSOR_MAP_DATA_TYPE_BFLOAT16, rank, base, dims, strides, box, es, CU_TENSOR_MAP_INTERLEAVE_NONE,
      CU_TENSOR_MAP_SWIZZLE_128B, CU_TENSOR_MAP_L2_PROMOTION_L2_256B, CU_TENSOR_MAP_FLOAT_OOB_FILL_NONE);
}
static void enc_act(PFN_enc f, CUtensorMap* m, void* base, int rows, int chunks, int trows = T_, int pitch = T_) {
    cuuint64_t dims[4] = {64, (cuuint64_t)trows, 8, (cuuint64_t)NB_};
    cuuint64_t st[3] = {1024, 128, (cuuint64_t)pitch * 1024};
    cuuint32_t box[4] = {64, (cuuint32_t)rows, (cuuint32_t)chunks, 1};
    enc(f, m, base, 4, dims, st, box);
}
static void enc_w(PFN_enc f, CUtensorMap* m, void* base, int krows, int ncols, int bk, int bc) {
    cuuint64_t dims[3] = {64, (cuuint64_t)krows, (cuuint64_t)(ncols / 64)};
    cuuint64_t st[2] = {(cuuint64_t)ncols * 2, 128};
    cuuint32_t box[3] = {64, (cuuint32_t)bk, (cuuint32_t)bc};
    enc(f, m, base, 3, dims, st, box);
}

extern "C" void kernel_launch(void* const* d_in, const int* in_sizes, int n_in, void* d_out, int out_size) {
    const bf16* x = (const bf16*)d_in[0];
    static PFN_enc fenc = nullptr;
    static void *p_xa, *p_mqk, *p_uc, *p_t1;
    static int fused = 0;
    if (!fenc) {
        void* fn = nullptr;
        cudaDriverEntryPointQueryResult qr;
        cudaGetDriverEntryPoint("cuTensorMapEncodeTiled", &fn, cudaEnableDefault, &qr);
        fenc = (PFN_enc)fn;
        cudaGetSymbolAddress(&p_xa, g_xa);
        cudaGetSymbolAddress(&p_mqk, g_mqk);
        cudaGetSymbolAddress(&p_uc, g_uc);
        cudaGetSymbolAddress(&p_t1, g_t1);
        cudaFuncSetAttribute(main_kernel, cudaFuncAttributeMaxDynamicSharedMemorySize, SMEM_BYTES);
        int dev = 0, sms = 0, occ = 0;
        cudaGetDevice(&dev);
        cudaDeviceGetAttribute(&sms, cudaDevAttrMultiProcessorCount, dev);
        cudaOccupancyMaxActiveBlocksPerMultiprocessor(&occ, main_kernel, 384, SMEM_BYTES);
        fused = sms * occ >= NCTA + 2;
    }
    Maps mp;
    enc_act(fenc, &mp.xa, (char*)p_xa + 1024, 64, 8, T_, T_ + 8);
    enc_act(fenc, &mp.xa2, (char*)p_xa + 1024, 64, 2, T_, T_ + 8);
    enc_act(fenc, &mp.xa4, (char*)p_xa + 1024, 64, 4, T_, T_ + 8);
    enc_act(fenc, &mp.xas, p_xa, 64, 1, T_ + 1, T_ + 8);
    enc_act(fenc, &mp.x, (void*)x, 64, 1);
    enc_act(fenc, &mp.out, d_out, 62, 1);
    enc_w(fenc, &mp.wup4, d_in[5], 512, 1024, 16, 4);
    enc_w(fenc, &mp.wup8, d_in[5], 512, 1024, 16, 8);
    enc_w(fenc, &mp.mqa2, p_mqk, 512, 512, 32, 2);
    enc_w(fenc, &mp.mqa4, p_mqk, 512, 512, 32, 4);
    enc_w(fenc, &mp.mqb1, p_mqk, 512, 512, 64, 1);
    enc_w(fenc, &mp.mqb2, p_mqk, 512, 512, 64, 2);
    enc_w(fenc, &mp.uc, p_uc, NCTA * 128, 512, 64, 4);
    enc_w(fenc, &mp.wq, d_in[1], 512, 512, 64, 8);
    enc_w(fenc, &mp.wk, d_in[2], 512, 512, 32, 8);
    enc_w(fenc, &mp.fa[0], d_in[3], 512, 512, 128, 1);
    enc_w(fenc, &mp.fa[1], d_in[7], 512, 512, 128, 1);
    enc_w(fenc, &mp.fa[2], p_t1, 512, 512, 128, 1);
    enc_w(fenc, &mp.fb[0], d_in[4], 512, 512, 64, 4);
    enc_w(fenc, &mp.fb[1], d_in[8], 1024, 512, 64, 4);
    enc_w(fenc, &mp.fc, p_t1, 512, 512, 64, 4);
    cudaStream_t st = cudaStreamPerThread;
    if (fused) {
        main_kernel<<<NCTA + 2, 384, SMEM_BYTES, st>>>(mp, x, (const bf16*)d_in[6], (const bf16*)d_in[5], 0);
    } else {
        main_kernel<<<NCTA + 2, 384, SMEM_BYTES, st>>>(mp, x, (const bf16*)d_in[6], (const bf16*)d_in[5], 1);
        main_kernel<<<NCTA + 2, 384, SMEM_BYTES, st>>>(mp, x, (const bf16*)d_in[6], (const bf16*)d_in[5], 2);
    }
}
```

```cpp
#include <cuda_runtime.h>
#include <cuda_bf16.h>
#include <cuda.h>
#include <stdint.h>

typedef __nv_bfloat16 bf16;

constexpr int T_ = 4000, D_ = 512, NB_ = 2;
constexpr int TPB = 65;
constexpr int NCTA = TPB * NB_;
constexpr int NKV = 63;

__device__ __align__(1024) bf16 g_xa[NB_ * (T_ + 8) * D_];
__device__ __align__(1024) bf16 g_mqk[D_ * D_];
__device__ __align__(1024) bf16 g_t1[D_ * D_];
__device__ __align__(1024) bf16 g_wepi[2 * D_ * D_];
__device__ __align__(1024) bf16 g_uc[NCTA * 128 * D_];
__device__ unsigned g_sync[8];

#define PT(i) do { if (el) asm volatile("st.shared.u32 [%0], %1;" ::"r"(sb + MISC + 2560), "r"((unsigned)clock())); } while (0)
#define PG(i)
#define PE()
#define PLM 15
#define PL(j, q) do { if ((PLM >> ((q) + (wg ? 4 : 0))) & 1) PT(0); } while (0)
#define PDUMP()

#define FENCE_AT 1
#define GO_AT 25
#define LAZY 4294967296.f
#define SU 2
#define XS_GAP 800
#define XPF 50
#define URAW 1
#define LAGA 0
#define LAGB 0
#define DPOS 1
#define KPF 0
#define XEF 0
#define SK0 0
#define TRIM 3
#define GO_LAST 20
#define PFW 1
constexpr uint32_t R0 = 0, R1 = 65536, R2 = 131072, R3 = 196608, QS = 221184, MISC = 229376;
constexpr uint32_t AT = 147456;
constexpr uint32_t SMEM_BYTES = 232448;
constexpr uint32_t B_R1 = MISC + 1856  , B_MK = MISC + 48, B_LN = MISC + 56, B_MQ = MISC + 64,
                   B_H1 = MISC + 88, B_H2 = MISC + 96, B_H3 = MISC + 104,
                   B_KV = MISC + 112, B_P = MISC + 136, B_GO = MISC + 160, B_UC = MISC + 184  ,
                   B_X = MISC + 200, CNT = MISC + 208  , SCL = MISC + 512  ,
                   LINV = MISC + 1280  , STAT = MISC + 512  ,
                   B_R2 = MISC + 1536  , B_E2 = MISC + 1696  ;

__device__ __forceinline__ uint32_t smem_u32(const void* p) { return (uint32_t)__cvta_generic_to_shared(p); }
__device__ __forceinline__ void wg_fence() { asm volatile("wgmma.fence.sync.aligned;" ::: "memory"); }
__device__ __forceinline__ void wg_commit() { asm volatile("wgmma.commit_group.sync.aligned;" ::: "memory"); }
template <int N> __device__ __forceinline__ void wg_wait() { asm volatile("wgmma.wait_group.sync.aligned %0;" ::"n"(N) : "memory"); }
__device__ __forceinline__ uint64_t dsc(uint32_t sd, uint32_t off, uint32_t lbo) {
    uint32_t lo = sd + (off >> 4) + ((lbo >> 4) << 16);
    uint64_t d;
    asm("mov.b64 %0, {%1, %2};" : "=l"(d) : "r"(lo), "r"((1024u >> 4) | (1u << 30)));
    return d;
}
__device__ __forceinline__ bool elect1() {
    uint32_t p;
    asm volatile("{\n.reg .pred p;\nelect.sync _|p, 0xffffffff;\nselp.u32 %0, 1, 0, p;\n}\n" : "=r"(p));
    return p != 0;
}
__device__ __forceinline__ void mbar_init(uint32_t bar, int cnt) { asm volatile("mbarrier.init.shared::cta.b64 [%0], %1;" ::"r"(bar), "r"(cnt) : "memory"); }
__device__ __forceinline__ void mbar_expect_tx(uint32_t bar, uint32_t bytes) { asm volatile("mbarrier.arrive.expect_tx.shared::cta.b64 _, [%0], %1;" ::"r"(bar), "r"(bytes) : "memory"); }
__device__ __forceinline__ void mbar_arrive(uint32_t bar) { asm volatile("mbarrier.arrive.shared::cta.b64 _, [%0];" ::"r"(bar) : "memory"); }
__device__ __forceinline__ void mbar_wait(uint32_t bar, uint32_t parity) {
    uint32_t ok;
#pragma unroll 1
    for (uint32_t it = 0;; ++it) {
        asm volatile("{\n.reg .pred p;\nmbarrier.try_wait.parity.shared::cta.b64 p, [%1], %2;\nselp.u32 %0, 1, 0, p;\n}\n" : "=r"(ok) : "r"(bar), "r"(parity) : "memory");
        if (ok) break;
        if (it > (1u << 20)) __trap();
    }
}
__device__ __forceinline__ bool mbar_test(uint32_t bar, uint32_t parity) {
    uint32_t ok;
    asm volatile("{\n.reg .pred p;\nmbarrier.test_wait.parity.shared::cta.b64 p, [%1], %2;\nselp.u32 %0, 1, 0, p;\n}\n" : "=r"(ok) : "r"(bar), "r"(parity) : "memory");
    return ok != 0;
}
__device__ __forceinline__ void fence_async() { asm volatile("fence.proxy.async.shared::cta;" ::: "memory"); }
__device__ __forceinline__ void fence_async_g() { asm volatile("fence.proxy.async.global;" ::: "memory"); }
__device__ __forceinline__ void bar_sync(int id, int n) { asm volatile("bar.sync %0, %1;" ::"r"(id), "r"(n) : "memory"); }
__device__ __forceinline__ void tma3(uint32_t dst, const CUtensorMap* tm, int c0, int c1, int c2, uint32_t bar) {
    asm volatile("cp.async.bulk.tensor.3d.shared::cluster.global.mbarrier::complete_tx::bytes [%0], [%1, {%3, %4, %5}], [%2];"
                 ::"r"(dst), "l"(tm), "r"(bar), "r"(c0), "r"(c1), "r"(c2) : "memory");
}
__device__ __forceinline__ void tma4(uint32_t dst, const CUtensorMap* tm, int c0, int c1, int c2, int c3, uint32_t bar) {
    asm volatile("cp.async.bulk.tensor.4d.shared::cluster.global.mbarrier::complete_tx::bytes [%0], [%1, {%3, %4, %5, %6}], [%2];"
                 ::"r"(dst), "l"(tm), "r"(bar), "r"(c0), "r"(c1), "r"(c2), "r"(c3) : "memory");
}
__device__ __forceinline__ void tma4_store(const CUtensorMap* tm, uint32_t src, int c0, int c1, int c2, int c3) {
    asm volatile("cp.async.bulk.tensor.4d.global.shared::cta.bulk_group [%0, {%2, %3, %4, %5}], [%1];"
                 ::"l"(tm), "r"(src), "r"(c0), "r"(c1), "r"(c2), "r"(c3) : "memory");
}
__device__ __forceinline__ void tma3_store(const CUtensorMap* tm, uint32_t src, int c0, int c1, int c2) {
    asm volatile("cp.async.bulk.tensor.3d.global.shared::cta.bulk_group [%0, {%2, %3, %4}], [%1];"
                 ::"l"(tm), "r"(src), "r"(c0), "r"(c1), "r"(c2) : "memory");
}
__device__ __forceinline__ void stsm4(uint32_t addr, uint32_t a, uint32_t b, uint32_t c, uint32_t d) {
    asm volatile("stmatrix.sync.aligned.m8n8.x4.shared.b16 [%0], {%1, %2, %3, %4};" ::"r"(addr), "r"(a), "r"(b), "r"(c), "r"(d) : "memory");
}
__device__ __forceinline__ void ldsm4(uint32_t addr, uint32_t (&r)[4]) {
    asm volatile("ldmatrix.sync.aligned.m8n8.x4.shared.b16 {%0, %1, %2, %3}, [%4];" : "=r"(r[0]), "=r"(r[1]), "=r"(r[2]), "=r"(r[3]) : "r"(addr) : "memory");
}
__device__ __forceinline__ void ldsm2(uint32_t addr, uint32_t (&r)[2]) {
    asm volatile("ldmatrix.sync.aligned.m8n8.x2.shared.b16 {%0, %1}, [%2];" : "=r"(r[0]), "=r"(r[1]) : "r"(addr) : "memory");
}
__device__ __forceinline__ void stg4(void* p, uint32_t a, uint32_t b, uint32_t c, uint32_t d) {
    asm volatile("st.global.v4.u32 [%0], {%1, %2, %3, %4};" ::"l"(p), "r"(a), "r"(b), "r"(c), "r"(d) : "memory");
}
__device__ __forceinline__ void hmma(float (&c)[4], uint32_t a0, uint32_t a1, uint32_t a2, uint32_t a3, uint32_t b0, uint32_t b1) {
    asm("mma.sync.aligned.m16n8k16.row.col.f32.bf16.bf16.f32 {%0, %1, %2, %3}, {%4, %5, %6, %7}, {%8, %9}, {%0, %1, %2, %3};"
        : "+f"(c[0]), "+f"(c[1]), "+f"(c[2]), "+f"(c[3]) : "r"(a0), "r"(a1), "r"(a2), "r"(a3), "r"(b0), "r"(b1));
}
__device__ __forceinline__ uint32_t pack2(float lo, float hi) {
    uint32_t r;
    asm("cvt.rn.bf16x2.f32 %0, %1, %2;" : "=r"(r) : "f"(hi), "f"(lo));
    return r;
}
__device__ __forceinline__ uint32_t pack2v(float lo, float hi) {
    uint32_t r;
    asm volatile("cvt.rn.bf16x2.f32 %0, %1, %2;" : "=r"(r) : "f"(hi), "f"(lo));
    return r;
}
__device__ __forceinline__ uint32_t bmul2(uint32_t a, uint32_t b) { uint32_t r; asm("mul.rn.bf16x2 %0, %1, %2;" : "=r"(r) : "r"(a), "r"(b)); return r; }
__device__ __forceinline__ uint32_t bfma2(uint32_t a, uint32_t b, uint32_t c) { uint32_t r; asm("fma.rn.bf16x2 %0, %1, %2, %3;" : "=r"(r) : "r"(a), "r"(b), "r"(c)); return r; }
__device__ __forceinline__ float ex2(float x) { float r; asm("ex2.approx.ftz.f32 %0, %1;" : "=f"(r) : "f"(x)); return r; }
__device__ __forceinline__ float rcp(float x) { float r; asm("rcp.approx.ftz.f32 %0, %1;" : "=f"(r) : "f"(x)); return r; }
__device__ __forceinline__ float gelu2(float x) {
    float t = fmaf(x * x, 0.044715f * 0.7978845608028654f, 0.7978845608028654f), th;
    asm("tanh.approx.f32 %0, %1;" : "=f"(th) : "f"(x * t));
    return fmaf(x, th, x);
}
__device__ __forceinline__ uint32_t ldg_v(const uint32_t* p) { uint32_t v; asm volatile("ld.global.nc.u32 %0, [%1];" : "=r"(v) : "l"(p)); return v; }
__device__ __forceinline__ uint32_t ldg_cg(const uint32_t* p) { uint32_t v; asm volatile("ld.global.cg.u32 %0, [%1];" : "=r"(v) : "l"(p) : "memory"); return v; }
__device__ __forceinline__ float lds_f32(uint32_t a) { float v; asm volatile("ld.shared.f32 %0, [%1];" : "=f"(v) : "r"(a) : "memory"); return v; }
__device__ __forceinline__ void sts_f32(uint32_t a, float v) { asm volatile("st.shared.f32 [%0], %1;" ::"r"(a), "f"(v) : "memory"); }
__device__ __forceinline__ uint32_t atom_inc_s(uint32_t a) { uint32_t v; asm volatile("atom.relaxed.cta.shared.add.u32 %0, [%1], 1;" : "=r"(v) : "r"(a) : "memory"); return v; }
__device__ __forceinline__ void lds4(uint32_t a, uint32_t* r) {
    asm volatile("ld.shared.v4.u32 {%0, %1, %2, %3}, [%4];" : "=r"(r[0]), "=r"(r[1]), "=r"(r[2]), "=r"(r[3]) : "r"(a) : "memory");
}
__device__ __forceinline__ void sts4(uint32_t a, uint32_t x, uint32_t y, uint32_t z, uint32_t t) {
    asm volatile("st.shared.v4.u32 [%0], {%1, %2, %3, %4};" ::"r"(a), "r"(x), "r"(y), "r"(z), "r"(t) : "memory");
}
__device__ __forceinline__ uint32_t bsub2(uint32_t a, uint32_t b) { uint32_t r; asm("sub.rn.bf16x2 %0, %1, %2;" : "=r"(r) : "r"(a), "r"(b)); return r; }
__device__ __forceinline__ float blo(uint32_t v) { return __uint_as_float(v << 16); }
__device__ __forceinline__ float bhi(uint32_t v) { return __uint_as_float(v & 0xffff0000u); }
__device__ __forceinline__ float bfr(float x) { return __bfloat162float(__float2bfloat16_rn(x)); }
__device__ __forceinline__ void l2_prefetch(const void* p, uint32_t bytes) { asm volatile("cp.async.bulk.prefetch.L2.global [%0], %1;" ::"l"(p), "r"(bytes) : "memory"); }
__device__ __forceinline__ void flag_add(unsigned* p) { asm volatile("red.release.gpu.global.add.u32 [%0], 1;" ::"l"(p) : "memory"); }
__device__ __forceinline__ void flag_wait(const unsigned* p, unsigned target) {
#pragma unroll 1
    for (uint32_t it = 0;; ++it) {
        unsigned v;
        asm volatile("ld.acquire.gpu.global.u32 %0, [%1];" : "=r"(v) : "l"(p) : "memory");
        if (v >= target) break;
        if (it > (1u << 20)) __trap();
    }
    fence_async_g();
}
template <int N> __device__ __forceinline__ void pin(float (&a)[N]) {
#pragma unroll
    for (int i = 0; i < N; i++) asm volatile("" : "+f"(a[i])::"memory");
}

template <int N> __device__ __forceinline__ void fresh(float (&a)[N]) {
#pragma unroll
    for (int i = 0; i < N; i++) a[i] = 0.f;
    pin(a);
}

__device__ __forceinline__ void wgmma_rs_n32_tb0(float (&d)[16], uint32_t a0, uint32_t a1, uint32_t a2, uint32_t a3, uint64_t db, int scale_d) {
    asm volatile("{\n.reg .pred p;\nsetp.ne.b32 p, %21, 0;\n"
        "wgmma.mma_async.sync.aligned.m64n32k16.f32.bf16.bf16 {%0, %1, %2, %3, %4, %5, %6, %7, %8, %9, %10, %11, %12, %13, %14, %15}, {%16, %17, %18, %19}, %20, p, 1, 1, 0;\n}\n"
        : "+f"(d[0]), "+f"(d[1]), "+f"(d[2]), "+f"(d[3]), "+f"(d[4]), "+f"(d[5]), "+f"(d[6]), "+f"(d[7]), "+f"(d[8]), "+f"(d[9]), "+f"(d[10]), "+f"(d[11]), "+f"(d[12]), "+f"(d[13]), "+f"(d[14]), "+f"(d[15])
        : "r"(a0), "r"(a1), "r"(a2), "r"(a3), "l"(db), "r"(scale_d));
}

__device__ __forceinline__ void wgmma_rs_n64_tb0(float (&d)[32], uint32_t a0, uint32_t a1, uint32_t a2, uint32_t a3, uint64_t db, int scale_d) {
    asm volatile("{\n.reg .pred p;\nsetp.ne.b32 p, %37, 0;\n"
        "wgmma.mma_async.sync.aligned.m64n64k16.f32.bf16.bf16 {%0, %1, %2, %3, %4, %5, %6, %7, %8, %9, %10, %11, %12, %13, %14, %15, %16, %17, %18, %19, %20, %21, %22, %23, %24, %25, %26, %27, %28, %29, %30, %31}, {%32, %33, %34, %35}, %36, p, 1, 1, 0;\n}\n"
        : "+f"(d[0]), "+f"(d[1]), "+f"(d[2]), "+f"(d[3]), "+f"(d[4]), "+f"(d[5]), "+f"(d[6]), "+f"(d[7]), "+f"(d[8]), "+f"(d[9]), "+f"(d[10]), "+f"(d[11]), "+f"(d[12]), "+f"(d[13]), "+f"(d[14]), "+f"(d[15]), "+f"(d[16]), "+f"(d[17]), "+f"(d[18]), "+f"(d[19]), "+f"(d[20]), "+f"(d[21]), "+f"(d[22]), "+f"(d[23]), "+f"(d[24]), "+f"(d[25]), "+f"(d[26]), "+f"(d[27]), "+f"(d[28]), "+f"(d[29]), "+f"(d[30]), "+f"(d[31])
        : "r"(a0), "r"(a1), "r"(a2), "r"(a3), "l"(db), "r"(scale_d));
}

__device__ __forceinline__ void wgmma_ss_n128_tb1(float (&d)[64], uint64_t da, uint64_t db, int scale_d) {
    asm volatile("{\n.reg .pred p;\nsetp.ne.b32 p, %66, 0;\n"
        "wgmma.mma_async.sync.aligned.m64n128k16.f32.bf16.bf16 {%0, %1, %2, %3, %4, %5, %6, %7, %8, %9, %10, %11, %12, %13, %14, %15, %16, %17, %18, %19, %20, %21, %22, %23, %24, %25, %26, %27, %28, %29, %30, %31, %32, %33, %34, %35, %36, %37, %38, %39, %40, %41, %42, %43, %44, %45, %46, %47, %48, %49, %50, %51, %52, %53, %54, %55, %56, %57, %58, %59, %60, %61, %62, %63}, %64, %65, p, 1, 1, 0, 1;\n}\n"
        : "+f"(d[0]), "+f"(d[1]), "+f"(d[2]), "+f"(d[3]), "+f"(d[4]), "+f"(d[5]), "+f"(d[6]), "+f"(d[7]), "+f"(d[8]), "+f"(d[9]), "+f"(d[10]), "+f"(d[11]), "+f"(d[12]), "+f"(d[13]), "+f"(d[14]), "+f"(d[15]), "+f"(d[16]), "+f"(d[17]), "+f"(d[18]), "+f"(d[19]), "+f"(d[20]), "+f"(d[21]), "+f"(d[22]), "+f"(d[23]), "+f"(d[24]), "+f"(d[25]), "+f"(d[26]), "+f"(d[27]), "+f"(d[28]), "+f"(d[29]), "+f"(d[30]), "+f"(d[31]), "+f"(d[32]), "+f"(d[33]), "+f"(d[34]), "+f"(d[35]), "+f"(d[36]), "+f"(d[37]), "+f"(d[38]), "+f"(d[39]), "+f"(d[40]), "+f"(d[41]), "+f"(d[42]), "+f"(d[43]), "+f"(d[44]), "+f"(d[45]), "+f"(d[46]), "+f"(d[47]), "+f"(d[48]), "+f"(d[49]), "+f"(d[50]), "+f"(d[51]), "+f"(d[52]), "+f"(d[53]), "+f"(d[54]), "+f"(d[55]), "+f"(d[56]), "+f"(d[57]), "+f"(d[58]), "+f"(d[59]), "+f"(d[60]), "+f"(d[61]), "+f"(d[62]), "+f"(d[63])
        : "l"(da), "l"(db), "r"(scale_d));
}

__device__ __forceinline__ void wgmma_ss_n256_tb1(float (&d)[128], uint64_t da, uint64_t db, int scale_d) {
    asm volatile("{\n.reg .pred p;\nsetp.ne.b32 p, %130, 0;\n"
        "wgmma.mma_async.sync.aligned.m64n256k16.f32.bf16.bf16 {%0, %1, %2, %3, %4, %5, %6, %7, %8, %9, %10, %11, %12, %13, %14, %15, %16, %17, %18, %19, %20, %21, %22, %23, %24, %25, %26, %27, %28, %29, %30, %31, %32, %33, %34, %35, %36, %37, %38, %39, %40, %41, %42, %43, %44, %45, %46, %47, %48, %49, %50, %51, %52, %53, %54, %55, %56, %57, %58, %59, %60, %61, %62, %63, %64, %65, %66, %67, %68, %69, %70, %71, %72, %73, %74, %75, %76, %77, %78, %79, %80, %81, %82, %83, %84, %85, %86, %87, %88, %89, %90, %91, %92, %93, %94, %95, %96, %97, %98, %99, %100, %101, %102, %103, %104, %105, %106, %107, %108, %109, %110, %111, %112, %113, %114, %115, %116, %117, %118, %119, %120, %121, %122, %123, %124, %125, %126, %127}, %128, %129, p, 1, 1, 0, 1;\n}\n"
        : "+f"(d[0]), "+f"(d[1]), "+f"(d[2]), "+f"(d[3]), "+f"(d[4]), "+f"(d[5]), "+f"(d[6]), "+f"(d[7]), "+f"(d[8]), "+f"(d[9]), "+f"(d[10]), "+f"(d[11]), "+f"(d[12]), "+f"(d[13]), "+f"(d[14]), "+f"(d[15]), "+f"(d[16]), "+f"(d[17]), "+f"(d[18]), "+f"(d[19]), "+f"(d[20]), "+f"(d[21]), "+f"(d[22]), "+f"(d[23]), "+f"(d[24]), "+f"(d[25]), "+f"(d[26]), "+f"(d[27]), "+f"(d[28]), "+f"(d[29]), "+f"(d[30]), "+f"(d[31]), "+f"(d[32]), "+f"(d[33]), "+f"(d[34]), "+f"(d[35]), "+f"(d[36]), "+f"(d[37]), "+f"(d[38]), "+f"(d[39]), "+f"(d[40]), "+f"(d[41]), "+f"(d[42]), "+f"(d[43]), "+f"(d[44]), "+f"(d[45]), "+f"(d[46]), "+f"(d[47]), "+f"(d[48]), "+f"(d[49]), "+f"(d[50]), "+f"(d[51]), "+f"(d[52]), "+f"(d[53]), "+f"(d[54]), "+f"(d[55]), "+f"(d[56]), "+f"(d[57]), "+f"(d[58]), "+f"(d[59]), "+f"(d[60]), "+f"(d[61]), "+f"(d[62]), "+f"(d[63]), "+f"(d[64]), "+f"(d[65]), "+f"(d[66]), "+f"(d[67]), "+f"(d[68]), "+f"(d[69]), "+f"(d[70]), "+f"(d[71]), "+f"(d[72]), "+f"(d[73]), "+f"(d[74]), "+f"(d[75]), "+f"(d[76]), "+f"(d[77]), "+f"(d[78]), "+f"(d[79]), "+f"(d[80]), "+f"(d[81]), "+f"(d[82]), "+f"(d[83]), "+f"(d[84]), "+f"(d[85]), "+f"(d[86]), "+f"(d[87]), "+f"(d[88]), "+f"(d[89]), "+f"(d[90]), "+f"(d[91]), "+f"(d[92]), "+f"(d[93]), "+f"(d[94]), "+f"(d[95]), "+f"(d[96]), "+f"(d[97]), "+f"(d[98]), "+f"(d[99]), "+f"(d[100]), "+f"(d[101]), "+f"(d[102]), "+f"(d[103]), "+f"(d[104]), "+f"(d[105]), "+f"(d[106]), "+f"(d[107]), "+f"(d[108]), "+f"(d[109]), "+f"(d[110]), "+f"(d[111]), "+f"(d[112]), "+f"(d[113]), "+f"(d[114]), "+f"(d[115]), "+f"(d[116]), "+f"(d[117]), "+f"(d[118]), "+f"(d[119]), "+f"(d[120]), "+f"(d[121]), "+f"(d[122]), "+f"(d[123]), "+f"(d[124]), "+f"(d[125]), "+f"(d[126]), "+f"(d[127])
        : "l"(da), "l"(db), "r"(scale_d));
}

__device__ __forceinline__ void wgmma_ss_n32_tb0(float (&d)[16], uint64_t da, uint64_t db, int scale_d) {
    asm volatile("{\n.reg .pred p;\nsetp.ne.b32 p, %18, 0;\n"
        "wgmma.mma_async.sync.aligned.m64n32k16.f32.bf16.bf16 {%0, %1, %2, %3, %4, %5, %6, %7, %8, %9, %10, %11, %12, %13, %14, %15}, %16, %17, p, 1, 1, 0, 0;\n}\n"
        : "+f"(d[0]), "+f"(d[1]), "+f"(d[2]), "+f"(d[3]), "+f"(d[4]), "+f"(d[5]), "+f"(d[6]), "+f"(d[7]), "+f"(d[8]), "+f"(d[9]), "+f"(d[10]), "+f"(d[11]), "+f"(d[12]), "+f"(d[13]), "+f"(d[14]), "+f"(d[15])
        : "l"(da), "l"(db), "r"(scale_d));
}

__device__ __forceinline__ void wgmma_ss_n64_tb0(float (&d)[32], uint64_t da, uint64_t db, int scale_d) {
    asm volatile("{\n.reg .pred p;\nsetp.ne.b32 p, %34, 0;\n"
        "wgmma.mma_async.sync.aligned.m64n64k16.f32.bf16.bf16 {%0, %1, %2, %3, %4, %5, %6, %7, %8, %9, %10, %11, %12, %13, %14, %15, %16, %17, %18, %19, %20, %21, %22, %23, %24, %25, %26, %27, %28, %29, %30, %31}, %32, %33, p, 1, 1, 0, 0;\n}\n"
        : "+f"(d[0]), "+f"(d[1]), "+f"(d[2]), "+f"(d[3]), "+f"(d[4]), "+f"(d[5]), "+f"(d[6]), "+f"(d[7]), "+f"(d[8]), "+f"(d[9]), "+f"(d[10]), "+f"(d[11]), "+f"(d[12]), "+f"(d[13]), "+f"(d[14]), "+f"(d[15]), "+f"(d[16]), "+f"(d[17]), "+f"(d[18]), "+f"(d[19]), "+f"(d[20]), "+f"(d[21]), "+f"(d[22]), "+f"(d[23]), "+f"(d[24]), "+f"(d[25]), "+f"(d[26]), "+f"(d[27]), "+f"(d[28]), "+f"(d[29]), "+f"(d[30]), "+f"(d[31])
        : "l"(da), "l"(db), "r"(scale_d));
}

struct Maps {
    CUtensorMap xa, xa2, xa4, xas, wup4, wup8, mqa2, mqa4, mqb1, mqb2, uc, x, out, wq, wk, fa[3], fb[2], fc;
};

__device__ __forceinline__ uint64_t mkd(uint32_t lo) {
    uint64_t d;
    asm("mov.b64 %0, {%1, %2};" : "=l"(d) : "r"(lo), "r"((1024u >> 4) | (1u << 30)));
    return d;
}
__device__ __forceinline__ void bulk_ld(uint32_t dst, const void* src, uint32_t bytes, uint32_t bar) {
    asm volatile("cp.async.bulk.shared::cluster.global.mbarrier::complete_tx::bytes [%0], [%1], %2, [%3];" ::"r"(dst), "l"(src), "r"(bytes), "r"(bar) : "memory");
}
__device__ __forceinline__ void bulk_st(void* dst, uint32_t src, uint32_t bytes) {
    asm volatile("cp.async.bulk.global.shared::cta.bulk_group [%0], [%1], %2;" ::"l"(dst), "r"(src), "r"(bytes) : "memory");
}
__device__ __forceinline__ void ring_ld(uint32_t sb, uint32_t slot8, int n) {
    mbar_expect_tx(sb + B_R2 + slot8, 8192);
    bulk_ld(sb + R2 + slot8 * 1024, (const char*)g_wepi + (2 * n + (blockIdx.x & 1)) * 8192, 8192, sb + B_R2 + slot8);
}
constexpr uint32_t B_RO = B_R2 + 96  , B_U2 = B_R2 + 128  , B_ACK = B_E2 + 128  , B_PF = B_E2 + 152, XB = R2 + 32768;
__device__ __forceinline__ uint32_t peer(uint32_t a) {
    uint32_t r;
    asm volatile("mapa.shared::cluster.u32 %0, %1, %2;" : "=r"(r) : "r"(a), "r"((blockIdx.x & 1) ^ 1));
    return r;
}
__device__ __forceinline__ void peer_arrive(uint32_t bar) { asm volatile("mbarrier.arrive.release.cluster.shared::cluster.b64 _, [%0];" ::"r"(peer(bar)) : "memory"); }
__device__ __forceinline__ void cl_arrive() { asm volatile("barrier.cluster.arrive.release.aligned;" ::: "memory"); }
__device__ __forceinline__ void cl_wait() { asm volatile("barrier.cluster.wait.acquire.aligned;" ::: "memory"); }

__device__ __forceinline__ void ring_half(uint32_t sb, uint32_t slot8, uint32_t hoff, const CUtensorMap* tm, int c1, int c2) {
    mbar_expect_tx(sb + B_R1 + slot8, 8192);
    tma3(sb + slot8 * 2048 + hoff, tm, 0, c1, c2, sb + B_R1 + slot8);
}
__device__ __forceinline__ void ring_full(uint32_t sb, uint32_t slot8, const CUtensorMap* tm, int c1, int c2) {
    mbar_expect_tx(sb + B_R1 + slot8, 16384);
    mbar_arrive(sb + B_R1 + slot8);
    tma3(sb + slot8 * 2048, tm, 0, c1, c2, sb + B_R1 + slot8);
}
__device__ __forceinline__ void cta_done(int mode) {
    if (mode == 0 && atomicAdd(&g_sync[4], 1) == NCTA + 1) {
#pragma unroll
        for (int i = 0; i < 5; i++) g_sync[i] = 0;
    }
}

__device__ __forceinline__ void fold_cta(const Maps& mp, uint32_t sb, int mode) {
    constexpr uint32_t F_FULL = MISC, F_EMPTY = MISC + 32, F_T1 = MISC + 64, STG = 49152, FOUT = 3 * STG;
    const int tid = threadIdx.x, f = blockIdx.x - NCTA;
    if (mode == 2) return;
    if (tid == 0) {
        for (int i = 0; i < 3; i++) { mbar_init(sb + F_FULL + 8 * i, 1); mbar_init(sb + F_EMPTY + 8 * i, 2); }
        mbar_init(sb + F_T1, 2);
        asm volatile("fence.mbarrier_init.release.cluster;" ::: "memory");
        fence_async();
    }
    __syncthreads();
    const int wg = __shfl_sync(0xffffffffu, tid >> 7, 0);
    int st = 0, ph = 0;
    if (wg == 0) {
        if (tid == 0) {
#pragma unroll 1
            for (int it = 0; it < 96; it++) {
                const int p = it >> 3, kc = it & 7, job = p >> 2;
                if (it == 64) mbar_wait(sb + F_T1, 0);
                mbar_wait(sb + F_EMPTY + 8 * st, ph ^ 1);
                mbar_expect_tx(sb + F_FULL + 8 * st, STG);
                tma3(sb + st * STG, &mp.fa[job], 0, 256 * f + 128 * ((p >> 1) & 1), kc, sb + F_FULL + 8 * st);
                tma3(sb + st * STG + 16384, &mp.fb[job != 0], 0, 64 * kc + (job == 1 ? 512 : 0), 4 * (p & 1), sb + F_FULL + 8 * st);
                if (++st == 3) { st = 0; ph ^= 1; }
            }
        }
        return;
    }
    const int h = wg - 1, lane = tid & 31, w = (tid >> 5) & 3;
    const uint32_t sd = (sb & 0x3FFFF) >> 4;
    const bool el = (tid & 127) == 0;
#pragma unroll 1
    for (int p = 0; p < 12; p++) {
        float acc[128];
        fresh(acc);
#pragma unroll 1
        for (int kc = 0; kc < 8; kc++) {
            mbar_wait(sb + F_FULL + 8 * st, ph);
            wg_fence();
#pragma unroll
            for (int kk = 0; kk < 4; kk++)
                wgmma_ss_n256_tb1(acc, dsc(sd, st * STG + h * 8192 + kk * 32, 16), dsc(sd, st * STG + 16384 + kk * 2048, 8192), 1);
            wg_commit();
            wg_wait<0>();
            if (el) mbar_arrive(sb + F_EMPTY + 8 * st);
            if (++st == 3) { st = 0; ph ^= 1; }
        }
        pin(acc);
        const int job = p >> 2;
        if (el) {
            asm volatile("cp.async.bulk.wait_group 0;" ::: "memory");
            if (p == 4) { fence_async_g(); mbar_arrive(sb + F_T1); }
        }
        bar_sync(3 + h, 128);
        uint32_t r = 16 * w + (lane & 7) + ((lane >> 3) & 1) * 8;
        const float fs = job == 1 ? 0.5f : 1.f;
        if (job == 1) r = (r & ~31) | (((r >> 1) & 3) << 3) | (((r >> 3) & 3) << 1) | (r & 1);
        const uint32_t oa = sb + FOUT + h * 32768 + r * 128 + ((((lane >> 4) ^ r) & 7) << 4);
#pragma unroll
        for (int i = 0; i < 16; i++)
            stsm4((oa ^ ((i & 3) << 5)) + (i >> 2) * 8192, pack2(acc[8 * i] * fs, acc[8 * i + 1] * fs), pack2(acc[8 * i + 2] * fs, acc[8 * i + 3] * fs),
                  pack2(acc[8 * i + 4] * fs, acc[8 * i + 5] * fs), pack2(acc[8 * i + 6] * fs, acc[8 * i + 7] * fs));
        fence_async();
        bar_sync(3 + h, 128);
        if (el) {
            const int row0 = 256 * f + 128 * ((p >> 1) & 1) + 64 * h + (job == 1 ? 512 : 0);
            if (job == 0) tma3_store(&mp.fc, sb + FOUT + h * 32768, 0, row0, 4 * (p & 1));
            else {
#pragma unroll 1
                for (int i = 0; i < 16; i++)
                    bulk_st((char*)g_wepi + (row0 / 8 + 2 * (i & 3) + (p & 1)) * 8192 + (i >> 2) * 2048, sb + FOUT + h * 32768 + i * 2048, 2048);
            }
            asm volatile("cp.async.bulk.commit_group;" ::: "memory");
        }
    }
    if (el) {
        asm volatile("cp.async.bulk.wait_group 0;" ::: "memory");
        fence_async_g();
        if (mode == 0) flag_add(&g_sync[3]);
    }
    bar_sync(2, 256);
    if (tid == 128) cta_done(mode);
}

__global__ void __cluster_dims__(2, 1, 1) __launch_bounds__(384, 1) main_kernel(const __grid_constant__ Maps mp, const bf16* __restrict__ x, const bf16* __restrict__ dw, const bf16* wup, const int mode) {
    extern __shared__ __align__(1024) uint8_t smem[];
    const uint32_t sb = smem_u32(smem);
    const int tid = threadIdx.x;
    PE();
    if (blockIdx.x >= NCTA) { fold_cta(mp, sb, mode); return; }
    const int b = blockIdx.x / TPB, ti = blockIdx.x % TPB;
    const int piece = blockIdx.x & 127;
    const int wg = __shfl_sync(0xffffffffu, tid >> 7, 0);
    const int lane = tid & 31, w = (tid >> 5) & 3;
    const bool w0 = __shfl_sync(0xffffffffu, w, 0) == 0;
    const uint32_t sd = (sb & 0x3FFFF) >> 4;
    const uint32_t adA = sd + (AT >> 4) + (1u << 16);
    const uint32_t bd0 = sd;
    const uint32_t bd2k = bd0 + ((2048u >> 4) << 16);
    const bool el = (tid & 127) == 0;
    const uint32_t lrow = 16 * w + (lane & 7) + ((lane >> 3) & 1) * 8;
    const uint32_t loff = lrow * 128 + ((((lane >> 4) ^ lrow) & 7) << 4);
    const int r0 = 16 * w + (lane >> 2);

    if (wg == 0) {
        asm volatile("setmaxnreg.inc.sync.aligned.u32 184;");
        uint32_t q[112];
        PG(206);
        if (tid == 0) {
            mbar_init(sb + B_MK, 1);
            for (int i = 0; i < 9; i++) mbar_init(sb + B_R1 + 8 * i, 2);
            for (int i = 0; i < 5; i++) asm volatile("st.shared.u32 [%0], 0;" ::"r"(sb + CNT + 4 * i) : "memory");
        } else if (tid == 32) {
            mbar_init(sb + B_LN, 1); mbar_init(sb + B_MQ, 1);
            mbar_init(sb + B_H1, 2); mbar_init(sb + B_H2, 1); mbar_init(sb + B_H3, 2);
            for (int i = 0; i < 3; i++) { mbar_init(sb + B_KV + 8 * i, 2); mbar_init(sb + B_P + 8 * i, 4); mbar_init(sb + B_GO + 8 * i, 4); }
            mbar_init(sb + B_UC, 1); mbar_init(sb + B_UC + 8, 1); mbar_init(sb + B_X, 8);
        } else if (tid == 64) {
            for (int i = 0; i < 20; i++) mbar_init(sb + B_R2 + 8 * i, 1);
        } else if (tid == 96) {
            for (int i = 0; i < 20; i++) mbar_init(sb + B_E2 + 8 * i, (i & 30) == 16 ? 2 : 8);
        }
        if (lane == 0) {
            asm volatile("fence.mbarrier_init.release.cluster;" ::: "memory");
            fence_async();
        }
        PG(207);
        __syncwarp();
        if (SU != 2) asm volatile("bar.arrive 5, 384;" ::: "memory");
        if (tid == 0) {
            mbar_expect_tx(sb + B_MK, 65536 + 32768);
            tma3(sb + 16384, &mp.wq, 0, 64 * (piece >> 4), 0, sb + B_MK);
            tma3(sb + 81920, &mp.wk, 0, 32 * (piece & 15), 0, sb + B_MK);
            for (int i = 0; i < 14; i++) mbar_arrive(sb + B_R1 + 8 * (i >> 1));
            if (mode != 1) {
                ring_full(sb, 56, &mp.wup8, 0, 8);
                ring_full(sb, 64, &mp.wup8, 16, 8);
                ring_full(sb, 0, &mp.wup8, 32, 8);
            }
        }
        PG(208);
        bar_sync(1, 128);
        if (SU == 2) asm volatile("bar.arrive 5, 384;" ::: "memory");
        PT(0);
        PG(200);
        {
            float mq[16];
            fresh(mq);
            mbar_wait(sb + B_MK, 0);
            PT(1);
            if (tid == 32) l2_prefetch((const char*)wup + piece * 8192, 8192);
            wg_fence();
#pragma unroll 1
            for (int c = 0; c < 8; c++)
#pragma unroll
                for (int kk = 0; kk < 4; kk++)
                    wgmma_ss_n32_tb0(mq, dsc(sd, 16384 + c * 8192 + kk * 32, 16), dsc(sd, 81920 + c * 4096 + kk * 32, 16), 1);
            wg_commit();
            wg_wait<0>();
            if (mode != 1 && w0 && elect1()) {
#pragma unroll 1
                for (int i = 1; i < 7; i++) ring_full(sb, 8 * i, &mp.wup8, 32 + 16 * i, 8);
            }
            pin(mq);
            uint32_t* c = reinterpret_cast<uint32_t*>(g_mqk + (64 * (piece >> 4) + r0) * D_ + 32 * (piece & 15) + 2 * (lane & 3));
#pragma unroll
            for (int n = 0; n < 4; n++) { c[4 * n] = pack2(mq[4 * n], mq[4 * n + 1]); c[4 * n + 4 * D_] = pack2(mq[4 * n + 2], mq[4 * n + 3]); }
            fence_async_g();
            bar_sync(1, 128);
            if (el) {
                if (mode == 0) flag_add(&g_sync[2]);
                if (mode == 0) flag_wait(&g_sync[2], NCTA);
                mbar_arrive(sb + B_MQ);
                PG(203);
                PT(12);
                mbar_wait(sb + B_LN, 0);
#pragma unroll 1
                for (int c = 0; c < 8; c++) {
                    tma4_store(&mp.xas, sb + AT + c * 8192, 0, 62 * ti, c, b);
                    const unsigned t0 = (unsigned)clock();
                    while (c < 7 && (unsigned)clock() - t0 < XS_GAP) __nanosleep(20);
                }
                asm volatile("cp.async.bulk.commit_group;" ::: "memory");
                if (mode == 1) asm volatile("cp.async.bulk.wait_group 0;" ::: "memory");
            }
            PT(13);
            if (mode == 1) return;
            cl_arrive();
        }
        mbar_wait(sb + B_H1, 0);
        PT(2);
        uint32_t slot8 = 24, par = 0, prev8 = 0, prev2 = 0;
        auto adv = [&]() { prev2 = prev8; prev8 = slot8; slot8 += 8; if (slot8 == 72) { slot8 = 0; par ^= 1; } };
        {
            float acc[128];
            fresh(acc);
            auto step = [&](int i) {
                const uint32_t aa = adA + (i >> 1) * 512 + (i & 1) * 4, bb = bd0 + ((4096u >> 4) << 16) + slot8 * 128;
                wg_fence();
                wgmma_ss_n256_tb1(acc, mkd(aa), mkd(bb), 1);
                wgmma_ss_n256_tb1(acc, mkd(aa + 2), mkd(bb + 128), 1);
                wg_commit();
                wg_wait<1 + LAGA>();
            };
#pragma unroll 1
            for (int i = 0; i < 8 + LAGA; i++) {
                mbar_wait(sb + B_R1 + slot8, par);
                step(i);
                if (i > LAGA && w0 && elect1()) ring_full(sb, LAGA ? prev2 : prev8, &mp.mqa4, 32 * (i - LAGA) + 256, 4);
                adv();
            }
#pragma unroll 1
            for (int i = 8 + LAGA; i < 16; i++) {
                mbar_wait(sb + B_R1 + slot8, par);
                if (i == 15 && el) mbar_arrive(sb + B_H2);
                step(i);
                if (w0 && elect1()) ring_full(sb, LAGA ? prev2 : prev8, &mp.wup8, 16 * (i - LAGA) - 128, 0);
                adv();
            }
            if (LAGA) {
                wg_wait<1>();
                if (w0 && elect1()) ring_full(sb, prev2, &mp.wup8, 112, 0);
            }
            wg_wait<0>();
            if (w0 && elect1()) ring_full(sb, prev8, &mp.wup8, 128, 0);
            pin(acc);
            PT(3);
#pragma unroll
            for (int kk = 0; kk < 4; kk++)
                stsm4((sb + QS + loff) ^ (kk << 5), pack2(acc[96 + 8 * kk], acc[97 + 8 * kk]), pack2(acc[98 + 8 * kk], acc[99 + 8 * kk]),
                      pack2(acc[100 + 8 * kk], acc[101 + 8 * kk]), pack2(acc[102 + 8 * kk], acc[103 + 8 * kk]));
            fence_async();
#pragma unroll
            for (int i = 47; i >= 0; i--) q[64 + i] = pack2v(acc[2 * i], acc[2 * i + 1]);
        }
        if (el) {
            asm volatile("cp.async.bulk.wait_group 0;" ::: "memory");
            if (mode == 0) {
                fence_async_g();
                flag_add(&g_sync[b]);
                flag_wait(&g_sync[b], TPB);
            }
        }
        __syncwarp();
        mbar_wait(sb + B_H3, 0);
        PT(4);
        slot8 = 48; par = 1;
#pragma unroll
        for (int half = 0; half < 2; half++) {
            float acc[64];
            fresh(acc);
            auto step = [&](int m) {
                const uint32_t aa = adA + m * 512, bb = bd0 + ((8192u >> 4) << 16) + slot8 * 128;
                mbar_wait(sb + B_R1 + slot8, par);
                wg_fence();
#pragma unroll
                for (int kk = 0; kk < 4; kk++) wgmma_ss_n128_tb1(acc, mkd(aa + 2 * kk), mkd(bb + 128 * kk), 1);
                wg_commit();
                wg_wait<1 + LAGB>();
            };
#pragma unroll 1
            for (int m = 0; m < 8; m++) {
                step(m);
                if (m > LAGB && w0 && elect1()) {
                    if (half == 0) ring_full(sb, LAGB ? prev2 : prev8, &mp.mqb2, 64 * (m - LAGB), 2);
                    else if (m < 4 + LAGB) tma4(sb + (LAGB ? prev2 : prev8) * 2048, &mp.xa2, 0, 0, 2 * (m - LAGB), b, sb + B_KV + 8);
                }
                adv();
            }
            if (LAGB && half == 0) {
                wg_wait<1>();
                if (w0 && elect1()) ring_full(sb, prev2, &mp.mqb2, 448, 2);
            }
            wg_wait<0>();
            if (w0 && elect1()) {
                if (half == 0) {
                    mbar_expect_tx(sb + B_KV + 8, 65536);
                    for (int i = 0; i < 3; i++) mbar_arrive(sb + B_KV + 8 * i);
                    tma4(sb + prev8 * 2048, &mp.xa2, 0, 0, 0, b, sb + B_KV + 8);
                } else {
                    mbar_expect_tx(sb + B_KV + 16, 65536);
                    tma4(sb + R2, &mp.xa, 0, 64, 0, b, sb + B_KV + 16);
                    mbar_expect_tx(sb + B_KV, 65536);
                    tma4(sb + R0, &mp.xa, 0, 128, 0, b, sb + B_KV);
                }
            }
            pin(acc);
#pragma unroll
            for (int i = 31; i >= 0; i--) q[32 * half + i] = pack2v(acc[2 * i], acc[2 * i + 1]);
        }
        bar_sync(1, 128);
        cl_wait();
        PT(5);

        const float CS = 0.04419417382415922f * 1.4426950408889634f;
        float m0 = -INFINITY, m1 = -INFINITY, l0 = 0.f, l1 = 0.f;
        int s = 0, sn = 1, ph = 0;
        float S[32];
        const bool l0w = lane == 0, q0 = (lane & 3) == 0;
#pragma unroll 1
        for (int j = -1;; j++) {
            if (j >= 0) {
                PL(j, 1);
                if (j == NKV - 1) {
#pragma unroll
                    for (int i = (T_ - 64 * (NKV - 1)) / 2; i < 32; i++) asm volatile("mov.b32 %0, 0xff800000;" : "=f"(S[i]));
                }
                const bool kv = mbar_test(sb + B_KV + sn * 8, ph);
                const uint32_t pb = sb + R3 + (s == 0 ? 2 : s - 1) * 8192;
                float a0 = 0.f, a1 = 0.f, sc0 = 1.f, sc1 = 1.f;
                auto expo = [&]() {
                    const float n0 = -m0 * CS, n1 = -m1 * CS;
                    a0 = 0.f; a1 = 0.f;
#pragma unroll
                    for (int kk = 0; kk < 4; kk++) {
                        float p[8];
#pragma unroll
                        for (int e = 0; e < 8; e++) p[e] = ex2(fmaf(S[8 * kk + e], CS, (e & 2) ? n1 : n0));
                        a0 += (p[0] + p[1]) + (p[4] + p[5]);
                        a1 += (p[2] + p[3]) + (p[6] + p[7]);
                        stsm4((pb + loff) ^ (kk << 5), pack2(p[0], p[1]), pack2(p[2], p[3]), pack2(p[4], p[5]), pack2(p[6], p[7]));
                    }
                };
                if (j > 0 || !SK0) expo();
                if ((SK0 && j == 0) || __any_sync(0xffffffffu, !(a0 <= LAZY) || !(a1 <= LAZY))) {
                    float x0 = m0, x1 = m1;
#pragma unroll
                    for (int n = 0; n < 8; n++) { x0 = fmaxf(x0, fmaxf(S[4 * n], S[4 * n + 1])); x1 = fmaxf(x1, fmaxf(S[4 * n + 2], S[4 * n + 3])); }
                    x0 = fmaxf(x0, __shfl_xor_sync(0xffffffffu, x0, 1));
                    x1 = fmaxf(x1, __shfl_xor_sync(0xffffffffu, x1, 1));
                    x0 = fmaxf(x0, __shfl_xor_sync(0xffffffffu, x0, 2));
                    x1 = fmaxf(x1, __shfl_xor_sync(0xffffffffu, x1, 2));
                    sc0 = ex2((m0 - x0) * CS); sc1 = ex2((m1 - x1) * CS);
                    m0 = x0; m1 = x1;
                    expo();
                }
                if (q0) { sts_f32(sb + SCL + s * 256 + r0 * 4, sc0); sts_f32(sb + SCL + s * 256 + r0 * 4 + 32, sc1); }
                __syncwarp();
                if (l0w) mbar_arrive(sb + B_P + s * 8);
                l0 = fmaf(l0, sc0, a0); l1 = fmaf(l1, sc1, a1);
                PL(j, 2);
                if (j == NKV - 1) break;
                if (!kv) mbar_wait(sb + B_KV + sn * 8, ph);
            } else {
                mbar_wait(sb + B_KV + 8, 0);
            }
            const uint32_t kd = sd + sn * 4096;
            if (TRIM & 2 && j == NKV - 2) {
                float Sn[16];
                wg_fence();
#pragma unroll
                for (int kk = 0; kk < 28; kk++) {
                    wgmma_rs_n32_tb0(Sn, q[4 * kk], q[4 * kk + 1], q[4 * kk + 2], q[4 * kk + 3], dsc(kd, (kk >> 2) * 8192 + (kk & 3) * 32, 16), kk > 0);
                    if (kk == FENCE_AT) { fence_async(); __syncwarp(); }
                    if (kk == GO_LAST && l0w) mbar_arrive(sb + B_GO + s * 8);
                }
#pragma unroll
                for (int kk = 0; kk < 4; kk++)
                    wgmma_ss_n32_tb0(Sn, dsc(sd, QS + kk * 32, 16), dsc(kd, 7 * 8192 + kk * 32, 16), 1);
                wg_commit();
                wg_wait<0>();
                pin(Sn);
#pragma unroll
                for (int i = 0; i < 16; i++) S[i] = Sn[i];
            } else {
            float Sn[32];
            wg_fence();
#pragma unroll
            for (int kk = 0; kk < 28; kk++) {
                wgmma_rs_n64_tb0(Sn, q[4 * kk], q[4 * kk + 1], q[4 * kk + 2], q[4 * kk + 3], dsc(kd, (kk >> 2) * 8192 + (kk & 3) * 32, 16), kk > 0);
                if (kk == FENCE_AT) { fence_async(); __syncwarp(); }
                if (kk == GO_AT) { PL(j, 3); if (j >= 0 && l0w) mbar_arrive(sb + B_GO + s * 8); }
            }
#pragma unroll
            for (int kk = 0; kk < 4; kk++)
                wgmma_ss_n64_tb0(Sn, dsc(sd, QS + kk * 32, 16), dsc(kd, 7 * 8192 + kk * 32, 16), 1);
            wg_commit();
            PL(j, 0);
            wg_wait<0>();
            pin(Sn);
#pragma unroll
            for (int i = 0; i < 32; i++) S[i] = Sn[i];
            }
            s = sn;
            if (++sn == 3) sn = 0;
            if (sn == 1) ph ^= 1;
        }
        l0 += __shfl_xor_sync(0xffffffffu, l0, 1); l1 += __shfl_xor_sync(0xffffffffu, l1, 1);
        l0 += __shfl_xor_sync(0xffffffffu, l0, 2); l1 += __shfl_xor_sync(0xffffffffu, l1, 2);
        if (q0) { sts_f32(sb + LINV + r0 * 4, rcp(l0)); sts_f32(sb + LINV + r0 * 4 + 32, rcp(l1)); }
        fence_async();
        __syncwarp();
        if (l0w) {
            mbar_arrive(sb + B_GO + s * 8);
            uint32_t slot8 = 8 * w, par = 0;
#pragma unroll 1
            for (int n = 12 + w; n < 72; n += 4) {
                mbar_wait(sb + B_E2 + slot8, par);
                if (n < 64) ring_ld(sb, slot8, n);
                else {
                    const int bx = (blockIdx.x & ~1) + (n >> 2 & 1);
                    mbar_expect_tx(sb + B_X, 8192);
                    tma4(sb + R2 + slot8 * 1024, &mp.x, 0, 62 * (bx % TPB), 4 * (blockIdx.x & 1) + w, bx / TPB, sb + B_X);
                }
                slot8 += 32;
                if (slot8 >= 96) { slot8 -= 96; par ^= 1; }
            }
        }
        PDUMP();
    } else {
        asm volatile("setmaxnreg.dec.sync.aligned.u32 160;");
        const int h = wg - 1;
        uint32_t v[4][8], v2[4][8];
        if (SU != 0) bar_sync(5, 384);
        PG(206);
#pragma unroll
        for (int i = 0; i < 8; i++) {
            const int t = 62 * ti - 1 + 32 * (i >> 2) + 16 * h + 4 * w + (i & 3);
            const uint4* p = reinterpret_cast<const uint4*>(x + ((size_t)b * T_ + t) * D_) + lane;
            uint32_t* d = i < 4 ? v[i & 3] : v2[i & 3];
#pragma unroll
            for (int c = 0; c < 2; c++)
                asm volatile("{\n.reg .pred p;\nsetp.lt.u32 p, %5, %6;\nmov.b32 %0, 0;\nmov.b32 %1, 0;\nmov.b32 %2, 0;\nmov.b32 %3, 0;\n"
                             "@p ld.global.nc.v4.u32 {%0, %1, %2, %3}, [%4];\n}\n"
                             : "=r"(d[4 * c]), "=r"(d[4 * c + 1]), "=r"(d[4 * c + 2]), "=r"(d[4 * c + 3]) : "l"(p + 32 * c), "r"(t), "n"(T_));
        }
#pragma unroll 1
        for (int bt = 0; bt < 2; bt++) {
            PT(bt ? 13 : 0);
            float a[8];
            const uint32_t la = sb + AT + (lane >> 3) * 8192 + (32 * bt + 16 * h + 4 * w) * 128 + (((lane & 7) ^ ((w & 1) * 4)) << 4);
            const bool b4 = lane & 16, b3 = lane & 8, b2 = lane & 4;
#pragma unroll
            for (int r = 0; r < 4; r++) {
                float c[4] = {0.f, 0.f, 0.f, 0.f};
#pragma unroll
                for (int i = 0; i < 8; i += 2) hmma(c, v[r][i], v[r][i], v[r][i + 1], v[r][i + 1], v[r][i], v[r][i + 1]);
                a[4 + r] = (lane & 3) == (lane >> 3) ? (b2 ? c[1] : c[0]) : 0.f;
                if (r & 1) {
                    float e[4] = {0.f, 0.f, 0.f, 0.f};
#pragma unroll
                    for (int i = 0; i < 8; i += 2) hmma(e, v[r - 1][i], v[r][i], v[r - 1][i + 1], v[r][i + 1], 0x3f803f80u, 0x3f803f80u);
                    a[r - 1] = e[0]; a[r] = e[2];
                }
            }
            float k[4];
#pragma unroll
            for (int i = 0; i < 4; i++) {
                const int lo = (i & 1) + 4 * (i >> 1);
                k[i] = (b4 ? a[lo + 2] : a[lo]) + __shfl_xor_sync(0xffffffffu, b4 ? a[lo] : a[lo + 2], 16);
            }
            const float k0 = (b3 ? k[1] : k[0]) + __shfl_xor_sync(0xffffffffu, b3 ? k[0] : k[1], 8);
            const float k1 = (b3 ? k[3] : k[2]) + __shfl_xor_sync(0xffffffffu, b3 ? k[2] : k[3], 8);
            float z = (b2 ? k1 : k0) + __shfl_xor_sync(0xffffffffu, b2 ? k0 : k1, 4);
            z += __shfl_xor_sync(0xffffffffu, z, 2);
            z += __shfl_xor_sync(0xffffffffu, z, 1);
            const float zo = __shfl_xor_sync(0xffffffffu, z, 4);
            PG(204 + bt);
            const float mu = (b2 ? zo : z) * (0.25f / D_);
            float sd_ = bfr(bfr(fmaxf(fmaf(b2 ? z : zo, 1.f / D_, -mu * mu), 0.f)) + 1e-5f);
            asm("sqrt.approx.f32 %0, %0;" : "+f"(sd_));
            const float ri = rcp(bfr(sd_));
            const uint32_t w1 = pack2(mu, ri), w2 = pack2(ri - bhi(w1), ri - bhi(w1));
#pragma unroll
            for (int r = 0; r < 4; r++) {
                const uint32_t s1 = __shfl_sync(0xffffffffu, w1, 8 * r), rl = __shfl_sync(0xffffffffu, w2, 8 * r);
                const uint32_t m2 = __byte_perm(s1, 0, 0x1010), rh = __byte_perm(s1, 0, 0x3232);
#pragma unroll
                for (int i = 0; i < 8; i++) { const uint32_t d = bsub2(v[r][i], m2); v[r][i] = bfma2(d, rh, bmul2(d, rl)); }
                sts4((la ^ (r << 4)) + r * 128, v[r][0], v[r][1], v[r][2], v[r][3]);
                sts4((la ^ (r << 4)) + r * 128 + 32768, v[r][4], v[r][5], v[r][6], v[r][7]);
#pragma unroll
                for (int i = 0; i < 8; i++) v[r][i] = v2[r][i];
            }
        }
        fence_async();
        if (SU == 0) bar_sync(5, 384); else bar_sync(2, 256);
        if (tid == 128) mbar_arrive(sb + B_LN);
        PG(202);
        if (mode == 1) return;
        cl_arrive();
        float acc[128];
#pragma unroll
        for (int pass = 0; pass < 2; pass++) {
            if (pass == 1) mbar_wait(sb + B_H2, 0);
            PT(1 + 3 * pass);
            fresh(acc);
            uint32_t slot8 = pass ? 8 : 56, par = 0, prev8 = 0;
            auto adv = [&]() { prev8 = slot8; slot8 += 8; if (slot8 == 72) { slot8 = 0; par ^= 1; } };
            auto step = [&](int kk) {
                wg_fence();
                wgmma_ss_n256_tb1(acc, mkd(adA + (kk >> 2) * 512 + (kk & 3) * 2), mkd(bd2k + h * 512 + slot8 * 128), 1);
                wg_commit();
                wg_wait<1>();
            };
#pragma unroll 1
            for (int kk = 0; kk < 24; kk++) {
                mbar_wait(sb + B_R1 + slot8, par);
                step(kk);
                if (kk > 0 && w0 && elect1()) ring_half(sb, prev8, h * 8192, &mp.wup4, 16 * kk + 128, (pass ? 0 : 8) + 4 * h);
                adv();
            }
            if (pass == 0 && w0) mbar_wait(sb + B_MQ, 0);
#pragma unroll 1
            for (int kk = 24; kk < 32; kk++) {
                mbar_wait(sb + B_R1 + slot8, par);
                if (kk == 31 && el) mbar_arrive(sb + (pass ? B_H3 : B_H1));
                step(kk);
                if (w0 && elect1()) ring_half(sb, prev8, h * 8192, pass ? &mp.mqb1 : &mp.mqa2, (pass ? 64 : 32) * (kk - 24), pass ? h : 4 + 2 * h);
                adv();
            }
            wg_wait<0>();
            if (w0 && elect1()) ring_half(sb, prev8, h * 8192, pass ? &mp.mqb1 : &mp.mqa2, pass ? 0 : 256, pass ? 2 + h : 4 + 2 * h);
            pin(acc);
            PT(2 + 3 * pass);
            bf16* ucp = g_uc + ((size_t)blockIdx.x * 128 + r0) * D_ + 256 * h + 8 * (lane & 3);
            if (pass == 0) {
                float s0 = 0.f, s1 = 0.f, v0 = 0.f, v1 = 0.f;
#pragma unroll
                for (int n = 0; n < 32; n++) {
#pragma unroll
                    for (int e = 0; e < 4; e++) acc[4 * n + e] = gelu2(acc[4 * n + e]);
                    s0 += acc[4 * n] + acc[4 * n + 1]; s1 += acc[4 * n + 2] + acc[4 * n + 3];
                    v0 = fmaf(acc[4 * n], acc[4 * n], v0); v0 = fmaf(acc[4 * n + 1], acc[4 * n + 1], v0);
                    v1 = fmaf(acc[4 * n + 2], acc[4 * n + 2], v1); v1 = fmaf(acc[4 * n + 3], acc[4 * n + 3], v1);
                }
#pragma unroll
                for (int o = 1; o < 4; o <<= 1) {
                    s0 += __shfl_xor_sync(0xffffffffu, s0, o); s1 += __shfl_xor_sync(0xffffffffu, s1, o);
                    v0 += __shfl_xor_sync(0xffffffffu, v0, o); v1 += __shfl_xor_sync(0xffffffffu, v1, o);
                }
                if ((lane & 3) == 0) {
                    uint32_t a = sb + STAT + h * 512 + r0 * 8;
                    sts_f32(a, s0); sts_f32(a + 4, v0); sts_f32(a + 64, s1); sts_f32(a + 68, v1);
                }
                bar_sync(2, 256);
                {
                    uint32_t a = sb + STAT + (h ^ 1) * 512 + r0 * 8;
                    s0 = (s0 + lds_f32(a)) * (1.f / 512.f); v0 = (v0 + lds_f32(a + 4)) * (1.f / 512.f);
                    s1 = (s1 + lds_f32(a + 64)) * (1.f / 512.f); v1 = (v1 + lds_f32(a + 68)) * (1.f / 512.f);
                }
                v0 = rsqrtf(fmaxf(fmaf(-s0, s0, v0), 0.f) + 4e-5f); v1 = rsqrtf(fmaxf(fmaf(-s1, s1, v1), 0.f) + 4e-5f);
                s0 = -s0 * v0; s1 = -s1 * v1;
#pragma unroll
                for (int m = 0; m < 8; m++) {
                    const float* a_ = acc + 16 * m;
                    stg4(ucp + 64 * D_ + 32 * m, pack2(fmaf(a_[0], v0, s0), fmaf(a_[1], v0, s0)), pack2(fmaf(a_[4], v0, s0), fmaf(a_[5], v0, s0)),
                         pack2(fmaf(a_[8], v0, s0), fmaf(a_[9], v0, s0)), pack2(fmaf(a_[12], v0, s0), fmaf(a_[13], v0, s0)));
                    stg4(ucp + 72 * D_ + 32 * m, pack2(fmaf(a_[2], v1, s1), fmaf(a_[3], v1, s1)), pack2(fmaf(a_[6], v1, s1), fmaf(a_[7], v1, s1)),
                         pack2(fmaf(a_[10], v1, s1), fmaf(a_[11], v1, s1)), pack2(fmaf(a_[14], v1, s1), fmaf(a_[15], v1, s1)));
                }
            } else {
#pragma unroll
                for (int m = 0; m < 8; m++) {
                    const float* a_ = acc + 16 * m;
                    stg4(ucp + 32 * m, pack2(a_[0], a_[1]), pack2(a_[4], a_[5]), pack2(a_[8], a_[9]), pack2(a_[12], a_[13]));
                    stg4(ucp + 8 * D_ + 32 * m, pack2(a_[2], a_[3]), pack2(a_[6], a_[7]), pack2(a_[10], a_[11]), pack2(a_[14], a_[15]));
                }
                bar_sync(3 + h, 128);
            }
            PT(3 + 3 * pass);
        }
        int s = 1, ph = 0;
        uint32_t* cp = reinterpret_cast<uint32_t*>(g_uc + (size_t)blockIdx.x * 128 * D_) + (tid - 128);
        const uint32_t* dp = reinterpret_cast<const uint32_t*>(dw) + (((tid - 128) & ~15) | ((lane & 3) << 2) | ((lane >> 2) & 3));
        const uint32_t d0 = ldg_v(dp), d1 = ldg_v(dp + D_ / 2), d2 = ldg_v(dp + D_);
        uint32_t ga = ldg_cg(cp + 64 * (D_ / 2)), gb = ldg_cg(cp + 65 * (D_ / 2));
        fresh(acc);
        cl_wait();
#pragma unroll 1
        for (int j = 0; j < NKV; j++) {
            cp += D_ / 2;
            uint32_t gc = 0, uu = 0;
            if (j < NKV - 1) { gc = ldg_cg(cp + 65 * (D_ / 2)); uu = ldg_cg(cp); }
            mbar_wait(sb + B_P + s * 8, ph);
            PL(j, 0);
            if (j > 0) {
                const float sc0 = lds_f32(sb + SCL + s * 256 + r0 * 4), sc1 = lds_f32(sb + SCL + s * 256 + r0 * 4 + 32);
                if (__any_sync(0xffffffffu, sc0 != 1.f || sc1 != 1.f)) {
#pragma unroll
                    for (int n = 0; n < 32; n++) { acc[4 * n] *= sc0; acc[4 * n + 1] *= sc0; acc[4 * n + 2] *= sc1; acc[4 * n + 3] *= sc1; }
                }
            }
            mbar_wait(sb + B_GO + s * 8, ph);
            PL(j, 1);
            const uint32_t vd = sd + s * 4096 + h * 2048, pd = sd + (s == 0 ? 2 : s - 1) * 512;
            pin(acc);
            if (TRIM & 1 && j == NKV - 1) {
                wg_fence();
#pragma unroll
                for (int kk = 0; kk < 2; kk++) wgmma_ss_n256_tb1(acc, dsc(pd, R3 + kk * 32, 16), dsc(vd, kk * 2048, 8192), 1);
                wg_commit();
                wg_wait<0>();
                pin(acc);
                break;
            }
            wg_fence();
#pragma unroll
            for (int kk = 0; kk < 4; kk++) wgmma_ss_n256_tb1(acc, dsc(pd, R3 + kk * 32, 16), dsc(vd, kk * 2048, 8192), 1);
            wg_commit();
            wg_wait<0>();
            pin(acc);
            PL(j, 2);
            if (j == NKV - 3 && lane == 0) peer_arrive(sb + B_PF);
            if (w0 && elect1()) {
                if (j + 3 < NKV) {
                    mbar_expect_tx(sb + B_KV + s * 8, 32768);
                    tma4(sb + s * 65536 + h * 32768, &mp.xa4, 0, 64 * (j + 3), 4 * h, b, sb + B_KV + s * 8);
                } else if (j == NKV - 2) {
                    const int n0 = 4 * h;
                    mbar_expect_tx(sb + B_RO + 16 * h, 16384);
                    mbar_expect_tx(sb + B_RO + 16 * h + 8, 16384);
#pragma unroll 1
                    for (int n = n0; n < n0 + 4; n++) ring_ld(sb, n * 8, n);
                }
                if (j == NKV - 5 && mode == 0) flag_wait(&g_sync[3], 4);
                if (j >= XPF && j < XPF + 4) {
                    const int t0 = 62 * ti + 32 * h + 8 * (j - XPF), nr = min(8, T_ - t0);
                    if (nr > 0) l2_prefetch(x + ((size_t)b * T_ + t0) * D_, nr * 1024);
                }
                if (KPF && h == 0 && 64 * (j + KPF) + ti < T_) l2_prefetch(g_xa + ((size_t)b * (T_ + 8) + 1 + 64 * (j + KPF) + ti) * D_, 1024);
            }
            uu = pack2(gelu2(blo(uu)), gelu2(bhi(uu)));
            if (j < NKV - 1) asm volatile("st.global.u32 [%0], %1;" ::"l"(cp), "r"(bmul2(uu, bfma2(gc, d2, bfma2(gb, d1, bmul2(ga, d0))))) : "memory");
            ga = gb; gb = gc;
            if (++s == 3) s = 0;
            if (s == 1) ph ^= 1;
        }
        {
            const float i0 = lds_f32(sb + LINV + r0 * 4), i1 = lds_f32(sb + LINV + r0 * 4 + 32);
#pragma unroll
            for (int p = 0; p < 16; p++)
                stsm4(((sb + R0 + h * 32768 + loff) ^ ((p & 3) << 5)) + (p >> 2) * 8192,
                      pack2(acc[8 * p] * i0, acc[8 * p + 1] * i0), pack2(acc[8 * p + 2] * i1, acc[8 * p + 3] * i1),
                      pack2(acc[8 * p + 4] * i0, acc[8 * p + 5] * i0), pack2(acc[8 * p + 6] * i1, acc[8 * p + 7] * i1));
        }
        fence_async();
        fence_async_g();
        __threadfence();
        bar_sync(3 + h, 128);
        if (lane == 0 && w >= 2) {
            const uint32_t o = h * 32768 + (w & 1) * 16384;
            mbar_wait(sb + B_PF, 0);
            asm volatile("cp.async.bulk.shared::cluster.shared::cta.mbarrier::complete_tx::bytes [%0], [%1], 16384, [%2];"
                         ::"r"(peer(sb + R1 + o)), "r"(sb + R0 + o), "r"(peer(sb + B_RO + (o >> 11))) : "memory");
        }
        bar_sync(2, 256);
        if (lane == 0 && w < 2) ring_ld(sb, 64 + 16 * w + 8 * h, 8 + 2 * w + h);
        const bool own = h == (blockIdx.x & 1);
        const int bx = (blockIdx.x & ~1) + h;
        const uint32_t ar = own ? R0 : R1;
        PT(7);
        fresh(acc);
        {
            uint32_t slot8 = 0, par = 0, prev8 = 0;
#pragma unroll 1
            for (int kk = 0; kk < 64; kk++) {
                if (kk == 32 || kk == 48) mbar_wait(sb + B_U2 + 16 * h + (kk >> 1 & 8), 0);
                if (!own && kk < 32 && (kk & 7) == 0) {
                    mbar_wait(sb + B_RO + kk, 0);
                    if (el) peer_arrive(sb + B_ACK + (kk >> 1 & 8));
                }
                mbar_wait(sb + B_R2 + slot8, par);
                wg_fence();
                wgmma_ss_n256_tb1(acc, mkd(sd + (1u << 16) + (ar >> 4) + (kk >> 2 & 7) * 512 + (kk & 3) * 2), mkd(bd2k + (R2 >> 4) + slot8 * 64), 1);
                wg_commit();
                wg_wait<1>();
                if (kk > 0 && lane == 0) mbar_arrive(sb + B_E2 + prev8);
                if ((kk == 16 || kk == 32) && w0 && elect1()) {
                    if (own) mbar_wait(sb + B_ACK + (kk >> 2 & 8), 0);
                    mbar_expect_tx(sb + B_U2 + 16 * h + (kk >> 2 & 8), 32768);
                    tma3(sb + ar + (kk & 32) * 1024, &mp.uc, 0, 128 * bx, kk >> 3 & 4, sb + B_U2 + 16 * h + (kk >> 2 & 8));
                }
                prev8 = slot8;
                slot8 += 8;
                if (slot8 >= 96) { slot8 = 0; par ^= 1; }
            }
        }
        wg_wait<0>();
        pin(acc);
        PT(8);
        mbar_wait(sb + B_X, 0);
        PT(9);
        {
            const uint32_t sr = (lrow + 63) & 63;
            const uint32_t xoff = sr * 128 + ((((lane >> 4) ^ sr) & 7) << 4);
#pragma unroll
            for (int p = 0; p < 16; p++) {
                const uint32_t a = ((sb + XB + h * 32768 + xoff) ^ ((p & 3) << 5)) + (p >> 2) * 8192;
                uint32_t xv[4];
                ldsm4(a, xv);
#pragma unroll
                for (int e = 0; e < 4; e++)
                    xv[e] = pack2(acc[8 * p + 2 * e] + __uint_as_float(xv[e] << 16), acc[8 * p + 2 * e + 1] + __uint_as_float(xv[e] & 0xffff0000u));
                stsm4(a, xv[0], xv[1], xv[2], xv[3]);
            }
        }
        fence_async();
        bar_sync(3 + h, 128);
        if (el) {
            for (int c = 0; c < 4; c++) tma4_store(&mp.out, sb + XB + (4 * h + c) * 8192, 0, 62 * (bx % TPB), 4 * (blockIdx.x & 1) + c, bx / TPB);
            asm volatile("cp.async.bulk.commit_group;" ::: "memory");
            PT(10);
            if (h == 0) cta_done(mode);
            asm volatile("cp.async.bulk.wait_group.read 0;" ::: "memory");
        }
        PT(11);
        PG(201);
        PDUMP();
    }
}

typedef CUresult (*PFN_enc)(CUtensorMap*, CUtensorMapDataType, cuuint32_t, void*, const cuuint64_t*, const cuuint64_t*,
                            const cuuint32_t*, const cuuint32_t*, CUtensorMapInterleave, CUtensorMapSwizzle,
                            CUtensorMapL2promotion, CUtensorMapFloatOOBfill);

static void enc(PFN_enc f, CUtensorMap* m, void* base, int rank, const cuuint64_t* dims, const cuuint64_t* strides, const cuuint32_t* box) {
    cuuint32_t es[5] = {1, 1, 1, 1, 1};
    f(m, CU_TENSOR_MAP_DATA_TYPE_BFLOAT16, rank, base, dims, strides, box, es, CU_TENSOR_MAP_INTERLEAVE_NONE,
      CU_TENSOR_MAP_SWIZZLE_128B, CU_TENSOR_MAP_L2_PROMOTION_L2_256B, CU_TENSOR_MAP_FLOAT_OOB_FILL_NONE);
}
static void enc_act(PFN_enc f, CUtensorMap* m, void* base, int rows, int chunks, int trows = T_, int pitch = T_) {
    cuuint64_t dims[4] = {64, (cuuint64_t)trows, 8, (cuuint64_t)NB_};
    cuuint64_t st[3] = {1024, 128, (cuuint64_t)pitch * 1024};
    cuuint32_t box[4] = {64, (cuuint32_t)rows, (cuuint32_t)chunks, 1};
    enc(f, m, base, 4, dims, st, box);
}
static void enc_w(PFN_enc f, CUtensorMap* m, void* base, int krows, int ncols, int bk, int bc) {
    cuuint64_t dims[3] = {64, (cuuint64_t)krows, (cuuint64_t)(ncols / 64)};
    cuuint64_t st[2] = {(cuuint64_t)ncols * 2, 128};
    cuuint32_t box[3] = {64, (cuuint32_t)bk, (cuuint32_t)bc};
    enc(f, m, base, 3, dims, st, box);
}

extern "C" void kernel_launch(void* const* d_in, const int* in_sizes, int n_in, void* d_out, int out_size) {
    const bf16* x = (const bf16*)d_in[0];
    static PFN_enc fenc = nullptr;
    static void *p_xa, *p_mqk, *p_uc, *p_t1;
    static int fused = 0;
    if (!fenc) {
        void* fn = nullptr;
        cudaDriverEntryPointQueryResult qr;
        cudaGetDriverEntryPoint("cuTensorMapEncodeTiled", &fn, cudaEnableDefault, &qr);
        fenc = (PFN_enc)fn;
        cudaGetSymbolAddress(&p_xa, g_xa);
        cudaGetSymbolAddress(&p_mqk, g_mqk);
        cudaGetSymbolAddress(&p_uc, g_uc);
        cudaGetSymbolAddress(&p_t1, g_t1);
        cudaFuncSetAttribute(main_kernel, cudaFuncAttributeMaxDynamicSharedMemorySize, SMEM_BYTES);
        int dev = 0, sms = 0, occ = 0;
        cudaGetDevice(&dev);
        cudaDeviceGetAttribute(&sms, cudaDevAttrMultiProcessorCount, dev);
        cudaOccupancyMaxActiveBlocksPerMultiprocessor(&occ, main_kernel, 384, SMEM_BYTES);
        cudaLaunchConfig_t cfg = {};
        cudaLaunchAttribute at;
        at.id = cudaLaunchAttributeClusterDimension; at.val.clusterDim.x = 2; at.val.clusterDim.y = 1; at.val.clusterDim.z = 1;
        cfg.gridDim = dim3(NCTA + 2); cfg.blockDim = dim3(384); cfg.dynamicSmemBytes = SMEM_BYTES; cfg.attrs = &at; cfg.numAttrs = 1;
        int ncl = 0;
        cudaOccupancyMaxActiveClusters(&ncl, main_kernel, &cfg);
        fused = sms * occ >= NCTA + 2 && 2 * ncl >= NCTA + 2;
    }
    Maps mp;
    enc_act(fenc, &mp.xa, (char*)p_xa + 1024, 64, 8, T_, T_ + 8);
    enc_act(fenc, &mp.xa2, (char*)p_xa + 1024, 64, 2, T_, T_ + 8);
    enc_act(fenc, &mp.xa4, (char*)p_xa + 1024, 64, 4, T_, T_ + 8);
    enc_act(fenc, &mp.xas, p_xa, 64, 1, T_ + 1, T_ + 8);
    enc_act(fenc, &mp.x, (void*)x, 64, 1);
    enc_act(fenc, &mp.out, d_out, 62, 1);
    enc_w(fenc, &mp.wup4, d_in[5], 512, 1024, 16, 4);
    enc_w(fenc, &mp.wup8, d_in[5], 512, 1024, 16, 8);
    enc_w(fenc, &mp.mqa2, p_mqk, 512, 512, 32, 2);
    enc_w(fenc, &mp.mqa4, p_mqk, 512, 512, 32, 4);
    enc_w(fenc, &mp.mqb1, p_mqk, 512, 512, 64, 1);
    enc_w(fenc, &mp.mqb2, p_mqk, 512, 512, 64, 2);
    enc_w(fenc, &mp.uc, p_uc, NCTA * 128, 512, 64, 4);
    enc_w(fenc, &mp.wq, d_in[1], 512, 512, 64, 8);
    enc_w(fenc, &mp.wk, d_in[2], 512, 512, 32, 8);
    enc_w(fenc, &mp.fa[0], d_in[3], 512, 512, 128, 1);
    enc_w(fenc, &mp.fa[1], d_in[7], 512, 512, 128, 1);
    enc_w(fenc, &mp.fa[2], p_t1, 512, 512, 128, 1);
    enc_w(fenc, &mp.fb[0], d_in[4], 512, 512, 64, 4);
    enc_w(fenc, &mp.fb[1], d_in[8], 1024, 512, 64, 4);
    enc_w(fenc, &mp.fc, p_t1, 512, 512, 64, 4);
    cudaStream_t st = cudaStreamPerThread;
    if (fused) {
        main_kernel<<<NCTA + 2, 384, SMEM_BYTES, st>>>(mp, x, (const bf16*)d_in[6], (const bf16*)d_in[5], 0);
    } else {
        main_kernel<<<NCTA + 2, 384, SMEM_BYTES, st>>>(mp, x, (const bf16*)d_in[6], (const bf16*)d_in[5], 1);
        main_kernel<<<NCTA + 2, 384, SMEM_BYTES, st>>>(mp, x, (const bf16*)d_in[6], (const bf16*)d_in[5], 2);
    }
}
```

```cpp
#include <cuda_runtime.h>
#include <cuda_bf16.h>
#include <cuda.h>
#include <stdint.h>

typedef __nv_bfloat16 bf16;

constexpr int T_ = 4000, D_ = 512, NB_ = 2;
constexpr int TPB = 65;
constexpr int NCTA = TPB * NB_;
constexpr int NKV = 63;

__device__ __align__(1024) bf16 g_xa[NB_ * (T_ + 8) * D_];
__device__ __align__(1024) bf16 g_mqk[D_ * D_];
__device__ __align__(1024) bf16 g_t1[D_ * D_];
__device__ __align__(1024) bf16 g_wepi[2 * D_ * D_];
__device__ __align__(1024) bf16 g_uc[NCTA * 128 * D_];
__device__ unsigned g_sync[8];

#define PT(i) do { if (el) asm volatile("st.shared.u32 [%0], %1;" ::"r"(sb + MISC + 2560), "r"((unsigned)clock())); } while (0)
#define PG(i)
#define PE()
#define PLM 15
#define PL(j, q) do { if ((PLM >> ((q) + (wg ? 4 : 0))) & 1) PT(0); } while (0)
#define PDUMP()

#define FENCE_AT 1
#define SKEW 8
#define GO_AT 25
#define LAZY 4294967296.f
#define SU 2
#define XS_GAP 800
#define XPF 50
#define URAW 1
#define LAGA 0
#define LAGB 0
#define DPOS 1
#define KPF 0
#define XEF 0
#define SK0 0
#define TRIM 3
#define GO_LAST 20
#define PFW 1
constexpr uint32_t R0 = 0, R1 = 65536, R2 = 131072, R3 = 196608, QS = 221184, MISC = 229376;
constexpr uint32_t AT = 147456;
constexpr uint32_t SMEM_BYTES = 232448;
constexpr uint32_t B_R1 = MISC + 1856  , B_MK = MISC + 48, B_LN = MISC + 56, B_MQ = MISC + 64,
                   B_H1 = MISC + 88, B_H2 = MISC + 96, B_H3 = MISC + 104,
                   B_KV = MISC + 112, B_P = MISC + 136, B_GO = MISC + 160, B_UC = MISC + 184  ,
                   B_X = MISC + 200, CNT = MISC + 208  , SCL = MISC + 512  ,
                   LINV = MISC + 1280  , STAT = MISC + 512  ,
                   B_R2 = MISC + 1536  , B_E2 = MISC + 1696  , B_X2 = MISC + 1928  ;

__device__ __forceinline__ uint32_t smem_u32(const void* p) { return (uint32_t)__cvta_generic_to_shared(p); }
__device__ __forceinline__ void wg_fence() { asm volatile("wgmma.fence.sync.aligned;" ::: "memory"); }
__device__ __forceinline__ void wg_commit() { asm volatile("wgmma.commit_group.sync.aligned;" ::: "memory"); }
template <int N> __device__ __forceinline__ void wg_wait() { asm volatile("wgmma.wait_group.sync.aligned %0;" ::"n"(N) : "memory"); }
__device__ __forceinline__ uint64_t dsc(uint32_t sd, uint32_t off, uint32_t lbo) {
    uint32_t lo = sd + (off >> 4) + ((lbo >> 4) << 16);
    uint64_t d;
    asm("mov.b64 %0, {%1, %2};" : "=l"(d) : "r"(lo), "r"((1024u >> 4) | (1u << 30)));
    return d;
}
__device__ __forceinline__ bool elect1() {
    uint32_t p;
    asm volatile("{\n.reg .pred p;\nelect.sync _|p, 0xffffffff;\nselp.u32 %0, 1, 0, p;\n}\n" : "=r"(p));
    return p != 0;
}
__device__ __forceinline__ void mbar_init(uint32_t bar, int cnt) { asm volatile("mbarrier.init.shared::cta.b64 [%0], %1;" ::"r"(bar), "r"(cnt) : "memory"); }
__device__ __forceinline__ void mbar_expect_tx(uint32_t bar, uint32_t bytes) { asm volatile("mbarrier.arrive.expect_tx.shared::cta.b64 _, [%0], %1;" ::"r"(bar), "r"(bytes) : "memory"); }
__device__ __forceinline__ void mbar_arrive(uint32_t bar) { asm volatile("mbarrier.arrive.shared::cta.b64 _, [%0];" ::"r"(bar) : "memory"); }
__device__ __forceinline__ void mbar_wait(uint32_t bar, uint32_t parity) {
    uint32_t ok;
#pragma unroll 1
    for (uint32_t it = 0;; ++it) {
        asm volatile("{\n.reg .pred p;\nmbarrier.try_wait.parity.shared::cta.b64 p, [%1], %2;\nselp.u32 %0, 1, 0, p;\n}\n" : "=r"(ok) : "r"(bar), "r"(parity) : "memory");
        if (ok) break;
        if (it > (1u << 20)) __trap();
    }
}
__device__ __forceinline__ bool mbar_test(uint32_t bar, uint32_t parity) {
    uint32_t ok;
    asm volatile("{\n.reg .pred p;\nmbarrier.test_wait.parity.shared::cta.b64 p, [%1], %2;\nselp.u32 %0, 1, 0, p;\n}\n" : "=r"(ok) : "r"(bar), "r"(parity) : "memory");
    return ok != 0;
}
__device__ __forceinline__ void fence_async() { asm volatile("fence.proxy.async.shared::cta;" ::: "memory"); }
__device__ __forceinline__ void fence_async_g() { asm volatile("fence.proxy.async.global;" ::: "memory"); }
__device__ __forceinline__ void bar_sync(int id, int n) { asm volatile("bar.sync %0, %1;" ::"r"(id), "r"(n) : "memory"); }
__device__ __forceinline__ void tma3(uint32_t dst, const CUtensorMap* tm, int c0, int c1, int c2, uint32_t bar) {
    asm volatile("cp.async.bulk.tensor.3d.shared::cluster.global.mbarrier::complete_tx::bytes [%0], [%1, {%3, %4, %5}], [%2];"
                 ::"r"(dst), "l"(tm), "r"(bar), "r"(c0), "r"(c1), "r"(c2) : "memory");
}
__device__ __forceinline__ void tma4(uint32_t dst, const CUtensorMap* tm, int c0, int c1, int c2, int c3, uint32_t bar) {
    asm volatile("cp.async.bulk.tensor.4d.shared::cluster.global.mbarrier::complete_tx::bytes [%0], [%1, {%3, %4, %5, %6}], [%2];"
                 ::"r"(dst), "l"(tm), "r"(bar), "r"(c0), "r"(c1), "r"(c2), "r"(c3) : "memory");
}
__device__ __forceinline__ void tma4_store(const CUtensorMap* tm, uint32_t src, int c0, int c1, int c2, int c3) {
    asm volatile("cp.async.bulk.tensor.4d.global.shared::cta.bulk_group [%0, {%2, %3, %4, %5}], [%1];"
                 ::"l"(tm), "r"(src), "r"(c0), "r"(c1), "r"(c2), "r"(c3) : "memory");
}
__device__ __forceinline__ void tma3_store(const CUtensorMap* tm, uint32_t src, int c0, int c1, int c2) {
    asm volatile("cp.async.bulk.tensor.3d.global.shared::cta.bulk_group [%0, {%2, %3, %4}], [%1];"
                 ::"l"(tm), "r"(src), "r"(c0), "r"(c1), "r"(c2) : "memory");
}
__device__ __forceinline__ void stsm4(uint32_t addr, uint32_t a, uint32_t b, uint32_t c, uint32_t d) {
    asm volatile("stmatrix.sync.aligned.m8n8.x4.shared.b16 [%0], {%1, %2, %3, %4};" ::"r"(addr), "r"(a), "r"(b), "r"(c), "r"(d) : "memory");
}
__device__ __forceinline__ void ldsm4(uint32_t addr, uint32_t (&r)[4]) {
    asm volatile("ldmatrix.sync.aligned.m8n8.x4.shared.b16 {%0, %1, %2, %3}, [%4];" : "=r"(r[0]), "=r"(r[1]), "=r"(r[2]), "=r"(r[3]) : "r"(addr) : "memory");
}
__device__ __forceinline__ void ldsm2(uint32_t addr, uint32_t (&r)[2]) {
    asm volatile("ldmatrix.sync.aligned.m8n8.x2.shared.b16 {%0, %1}, [%2];" : "=r"(r[0]), "=r"(r[1]) : "r"(addr) : "memory");
}
__device__ __forceinline__ void stg4(void* p, uint32_t a, uint32_t b, uint32_t c, uint32_t d) {
    asm volatile("st.global.v4.u32 [%0], {%1, %2, %3, %4};" ::"l"(p), "r"(a), "r"(b), "r"(c), "r"(d) : "memory");
}
__device__ __forceinline__ void hmma(float (&c)[4], uint32_t a0, uint32_t a1, uint32_t a2, uint32_t a3, uint32_t b0, uint32_t b1) {
    asm("mma.sync.aligned.m16n8k16.row.col.f32.bf16.bf16.f32 {%0, %1, %2, %3}, {%4, %5, %6, %7}, {%8, %9}, {%0, %1, %2, %3};"
        : "+f"(c[0]), "+f"(c[1]), "+f"(c[2]), "+f"(c[3]) : "r"(a0), "r"(a1), "r"(a2), "r"(a3), "r"(b0), "r"(b1));
}
__device__ __forceinline__ uint32_t pack2(float lo, float hi) {
    uint32_t r;
    asm("cvt.rn.bf16x2.f32 %0, %1, %2;" : "=r"(r) : "f"(hi), "f"(lo));
    return r;
}
__device__ __forceinline__ uint32_t pack2v(float lo, float hi) {
    uint32_t r;
    asm volatile("cvt.rn.bf16x2.f32 %0, %1, %2;" : "=r"(r) : "f"(hi), "f"(lo));
    return r;
}
__device__ __forceinline__ uint32_t bmul2(uint32_t a, uint32_t b) { uint32_t r; asm("mul.rn.bf16x2 %0, %1, %2;" : "=r"(r) : "r"(a), "r"(b)); return r; }
__device__ __forceinline__ uint32_t bfma2(uint32_t a, uint32_t b, uint32_t c) { uint32_t r; asm("fma.rn.bf16x2 %0, %1, %2, %3;" : "=r"(r) : "r"(a), "r"(b), "r"(c)); return r; }
__device__ __forceinline__ float ex2(float x) { float r; asm("ex2.approx.ftz.f32 %0, %1;" : "=f"(r) : "f"(x)); return r; }
__device__ __forceinline__ float rcp(float x) { float r; asm("rcp.approx.ftz.f32 %0, %1;" : "=f"(r) : "f"(x)); return r; }
__device__ __forceinline__ float gelu2(float x) {
    float t = fmaf(x * x, 0.044715f * 0.7978845608028654f, 0.7978845608028654f), th;
    asm("tanh.approx.f32 %0, %1;" : "=f"(th) : "f"(x * t));
    return fmaf(x, th, x);
}
__device__ __forceinline__ uint32_t ldg_v(const uint32_t* p) { uint32_t v; asm volatile("ld.global.nc.u32 %0, [%1];" : "=r"(v) : "l"(p)); return v; }
__device__ __forceinline__ uint32_t ldg_cg(const uint32_t* p) { uint32_t v; asm volatile("ld.global.cg.u32 %0, [%1];" : "=r"(v) : "l"(p) : "memory"); return v; }
__device__ __forceinline__ float lds_f32(uint32_t a) { float v; asm volatile("ld.shared.f32 %0, [%1];" : "=f"(v) : "r"(a) : "memory"); return v; }
__device__ __forceinline__ void sts_f32(uint32_t a, float v) { asm volatile("st.shared.f32 [%0], %1;" ::"r"(a), "f"(v) : "memory"); }
__device__ __forceinline__ uint32_t atom_inc_s(uint32_t a) { uint32_t v; asm volatile("atom.relaxed.cta.shared.add.u32 %0, [%1], 1;" : "=r"(v) : "r"(a) : "memory"); return v; }
__device__ __forceinline__ void lds4(uint32_t a, uint32_t* r) {
    asm volatile("ld.shared.v4.u32 {%0, %1, %2, %3}, [%4];" : "=r"(r[0]), "=r"(r[1]), "=r"(r[2]), "=r"(r[3]) : "r"(a) : "memory");
}
__device__ __forceinline__ void sts4(uint32_t a, uint32_t x, uint32_t y, uint32_t z, uint32_t t) {
    asm volatile("st.shared.v4.u32 [%0], {%1, %2, %3, %4};" ::"r"(a), "r"(x), "r"(y), "r"(z), "r"(t) : "memory");
}
__device__ __forceinline__ uint32_t bsub2(uint32_t a, uint32_t b) { uint32_t r; asm("sub.rn.bf16x2 %0, %1, %2;" : "=r"(r) : "r"(a), "r"(b)); return r; }
__device__ __forceinline__ float blo(uint32_t v) { return __uint_as_float(v << 16); }
__device__ __forceinline__ float bhi(uint32_t v) { return __uint_as_float(v & 0xffff0000u); }
__device__ __forceinline__ float bfr(float x) { return __bfloat162float(__float2bfloat16_rn(x)); }
__device__ __forceinline__ void l2_prefetch(const void* p, uint32_t bytes) { asm volatile("cp.async.bulk.prefetch.L2.global [%0], %1;" ::"l"(p), "r"(bytes) : "memory"); }
__device__ __forceinline__ void flag_add(unsigned* p) { asm volatile("red.release.gpu.global.add.u32 [%0], 1;" ::"l"(p) : "memory"); }
__device__ __forceinline__ void flag_wait(const unsigned* p, unsigned target) {
#pragma unroll 1
    for (uint32_t it = 0;; ++it) {
        unsigned v;
        asm volatile("ld.acquire.gpu.global.u32 %0, [%1];" : "=r"(v) : "l"(p) : "memory");
        if (v >= target) break;
        if (it > (1u << 20)) __trap();
    }
    fence_async_g();
}
template <int N> __device__ __forceinline__ void pin(float (&a)[N]) {
#pragma unroll
    for (int i = 0; i < N; i++) asm volatile("" : "+f"(a[i])::"memory");
}

template <int N> __device__ __forceinline__ void fresh(float (&a)[N]) {
#pragma unroll
    for (int i = 0; i < N; i++) a[i] = 0.f;
    pin(a);
}

__device__ __forceinline__ void wgmma_rs_n32_tb0(float (&d)[16], uint32_t a0, uint32_t a1, uint32_t a2, uint32_t a3, uint64_t db, int scale_d) {
    asm volatile("{\n.reg .pred p;\nsetp.ne.b32 p, %21, 0;\n"
        "wgmma.mma_async.sync.aligned.m64n32k16.f32.bf16.bf16 {%0, %1, %2, %3, %4, %5, %6, %7, %8, %9, %10, %11, %12, %13, %14, %15}, {%16, %17, %18, %19}, %20, p, 1, 1, 0;\n}\n"
        : "+f"(d[0]), "+f"(d[1]), "+f"(d[2]), "+f"(d[3]), "+f"(d[4]), "+f"(d[5]), "+f"(d[6]), "+f"(d[7]), "+f"(d[8]), "+f"(d[9]), "+f"(d[10]), "+f"(d[11]), "+f"(d[12]), "+f"(d[13]), "+f"(d[14]), "+f"(d[15])
        : "r"(a0), "r"(a1), "r"(a2), "r"(a3), "l"(db), "r"(scale_d));
}

__device__ __forceinline__ void wgmma_rs_n64_tb0(float (&d)[32], uint32_t a0, uint32_t a1, uint32_t a2, uint32_t a3, uint64_t db, int scale_d) {
    asm volatile("{\n.reg .pred p;\nsetp.ne.b32 p, %37, 0;\n"
        "wgmma.mma_async.sync.aligned.m64n64k16.f32.bf16.bf16 {%0, %1, %2, %3, %4, %5, %6, %7, %8, %9, %10, %11, %12, %13, %14, %15, %16, %17, %18, %19, %20, %21, %22, %23, %24, %25, %26, %27, %28, %29, %30, %31}, {%32, %33, %34, %35}, %36, p, 1, 1, 0;\n}\n"
        : "+f"(d[0]), "+f"(d[1]), "+f"(d[2]), "+f"(d[3]), "+f"(d[4]), "+f"(d[5]), "+f"(d[6]), "+f"(d[7]), "+f"(d[8]), "+f"(d[9]), "+f"(d[10]), "+f"(d[11]), "+f"(d[12]), "+f"(d[13]), "+f"(d[14]), "+f"(d[15]), "+f"(d[16]), "+f"(d[17]), "+f"(d[18]), "+f"(d[19]), "+f"(d[20]), "+f"(d[21]), "+f"(d[22]), "+f"(d[23]), "+f"(d[24]), "+f"(d[25]), "+f"(d[26]), "+f"(d[27]), "+f"(d[28]), "+f"(d[29]), "+f"(d[30]), "+f"(d[31])
        : "r"(a0), "r"(a1), "r"(a2), "r"(a3), "l"(db), "r"(scale_d));
}

__device__ __forceinline__ void wgmma_ss_n128_tb1(float (&d)[64], uint64_t da, uint64_t db, int scale_d) {
    asm volatile("{\n.reg .pred p;\nsetp.ne.b32 p, %66, 0;\n"
        "wgmma.mma_async.sync.aligned.m64n128k16.f32.bf16.bf16 {%0, %1, %2, %3, %4, %5, %6, %7, %8, %9, %10, %11, %12, %13, %14, %15, %16, %17, %18, %19, %20, %21, %22, %23, %24, %25, %26, %27, %28, %29, %30, %31, %32, %33, %34, %35, %36, %37, %38, %39, %40, %41, %42, %43, %44, %45, %46, %47, %48, %49, %50, %51, %52, %53, %54, %55, %56, %57, %58, %59, %60, %61, %62, %63}, %64, %65, p, 1, 1, 0, 1;\n}\n"
        : "+f"(d[0]), "+f"(d[1]), "+f"(d[2]), "+f"(d[3]), "+f"(d[4]), "+f"(d[5]), "+f"(d[6]), "+f"(d[7]), "+f"(d[8]), "+f"(d[9]), "+f"(d[10]), "+f"(d[11]), "+f"(d[12]), "+f"(d[13]), "+f"(d[14]), "+f"(d[15]), "+f"(d[16]), "+f"(d[17]), "+f"(d[18]), "+f"(d[19]), "+f"(d[20]), "+f"(d[21]), "+f"(d[22]), "+f"(d[23]), "+f"(d[24]), "+f"(d[25]), "+f"(d[26]), "+f"(d[27]), "+f"(d[28]), "+f"(d[29]), "+f"(d[30]), "+f"(d[31]), "+f"(d[32]), "+f"(d[33]), "+f"(d[34]), "+f"(d[35]), "+f"(d[36]), "+f"(d[37]), "+f"(d[38]), "+f"(d[39]), "+f"(d[40]), "+f"(d[41]), "+f"(d[42]), "+f"(d[43]), "+f"(d[44]), "+f"(d[45]), "+f"(d[46]), "+f"(d[47]), "+f"(d[48]), "+f"(d[49]), "+f"(d[50]), "+f"(d[51]), "+f"(d[52]), "+f"(d[53]), "+f"(d[54]), "+f"(d[55]), "+f"(d[56]), "+f"(d[57]), "+f"(d[58]), "+f"(d[59]), "+f"(d[60]), "+f"(d[61]), "+f"(d[62]), "+f"(d[63])
        : "l"(da), "l"(db), "r"(scale_d));
}

__device__ __forceinline__ void wgmma_ss_n256_tb1(float (&d)[128], uint64_t da, uint64_t db, int scale_d) {
    asm volatile("{\n.reg .pred p;\nsetp.ne.b32 p, %130, 0;\n"
        "wgmma.mma_async.sync.aligned.m64n256k16.f32.bf16.bf16 {%0, %1, %2, %3, %4, %5, %6, %7, %8, %9, %10, %11, %12, %13, %14, %15, %16, %17, %18, %19, %20, %21, %22, %23, %24, %25, %26, %27, %28, %29, %30, %31, %32, %33, %34, %35, %36, %37, %38, %39, %40, %41, %42, %43, %44, %45, %46, %47, %48, %49, %50, %51, %52, %53, %54, %55, %56, %57, %58, %59, %60, %61, %62, %63, %64, %65, %66, %67, %68, %69, %70, %71, %72, %73, %74, %75, %76, %77, %78, %79, %80, %81, %82, %83, %84, %85, %86, %87, %88, %89, %90, %91, %92, %93, %94, %95, %96, %97, %98, %99, %100, %101, %102, %103, %104, %105, %106, %107, %108, %109, %110, %111, %112, %113, %114, %115, %116, %117, %118, %119, %120, %121, %122, %123, %124, %125, %126, %127}, %128, %129, p, 1, 1, 0, 1;\n}\n"
        : "+f"(d[0]), "+f"(d[1]), "+f"(d[2]), "+f"(d[3]), "+f"(d[4]), "+f"(d[5]), "+f"(d[6]), "+f"(d[7]), "+f"(d[8]), "+f"(d[9]), "+f"(d[10]), "+f"(d[11]), "+f"(d[12]), "+f"(d[13]), "+f"(d[14]), "+f"(d[15]), "+f"(d[16]), "+f"(d[17]), "+f"(d[18]), "+f"(d[19]), "+f"(d[20]), "+f"(d[21]), "+f"(d[22]), "+f"(d[23]), "+f"(d[24]), "+f"(d[25]), "+f"(d[26]), "+f"(d[27]), "+f"(d[28]), "+f"(d[29]), "+f"(d[30]), "+f"(d[31]), "+f"(d[32]), "+f"(d[33]), "+f"(d[34]), "+f"(d[35]), "+f"(d[36]), "+f"(d[37]), "+f"(d[38]), "+f"(d[39]), "+f"(d[40]), "+f"(d[41]), "+f"(d[42]), "+f"(d[43]), "+f"(d[44]), "+f"(d[45]), "+f"(d[46]), "+f"(d[47]), "+f"(d[48]), "+f"(d[49]), "+f"(d[50]), "+f"(d[51]), "+f"(d[52]), "+f"(d[53]), "+f"(d[54]), "+f"(d[55]), "+f"(d[56]), "+f"(d[57]), "+f"(d[58]), "+f"(d[59]), "+f"(d[60]), "+f"(d[61]), "+f"(d[62]), "+f"(d[63]), "+f"(d[64]), "+f"(d[65]), "+f"(d[66]), "+f"(d[67]), "+f"(d[68]), "+f"(d[69]), "+f"(d[70]), "+f"(d[71]), "+f"(d[72]), "+f"(d[73]), "+f"(d[74]), "+f"(d[75]), "+f"(d[76]), "+f"(d[77]), "+f"(d[78]), "+f"(d[79]), "+f"(d[80]), "+f"(d[81]), "+f"(d[82]), "+f"(d[83]), "+f"(d[84]), "+f"(d[85]), "+f"(d[86]), "+f"(d[87]), "+f"(d[88]), "+f"(d[89]), "+f"(d[90]), "+f"(d[91]), "+f"(d[92]), "+f"(d[93]), "+f"(d[94]), "+f"(d[95]), "+f"(d[96]), "+f"(d[97]), "+f"(d[98]), "+f"(d[99]), "+f"(d[100]), "+f"(d[101]), "+f"(d[102]), "+f"(d[103]), "+f"(d[104]), "+f"(d[105]), "+f"(d[106]), "+f"(d[107]), "+f"(d[108]), "+f"(d[109]), "+f"(d[110]), "+f"(d[111]), "+f"(d[112]), "+f"(d[113]), "+f"(d[114]), "+f"(d[115]), "+f"(d[116]), "+f"(d[117]), "+f"(d[118]), "+f"(d[119]), "+f"(d[120]), "+f"(d[121]), "+f"(d[122]), "+f"(d[123]), "+f"(d[124]), "+f"(d[125]), "+f"(d[126]), "+f"(d[127])
        : "l"(da), "l"(db), "r"(scale_d));
}

__device__ __forceinline__ void wgmma_ss_n32_tb0(float (&d)[16], uint64_t da, uint64_t db, int scale_d) {
    asm volatile("{\n.reg .pred p;\nsetp.ne.b32 p, %18, 0;\n"
        "wgmma.mma_async.sync.aligned.m64n32k16.f32.bf16.bf16 {%0, %1, %2, %3, %4, %5, %6, %7, %8, %9, %10, %11, %12, %13, %14, %15}, %16, %17, p, 1, 1, 0, 0;\n}\n"
        : "+f"(d[0]), "+f"(d[1]), "+f"(d[2]), "+f"(d[3]), "+f"(d[4]), "+f"(d[5]), "+f"(d[6]), "+f"(d[7]), "+f"(d[8]), "+f"(d[9]), "+f"(d[10]), "+f"(d[11]), "+f"(d[12]), "+f"(d[13]), "+f"(d[14]), "+f"(d[15])
        : "l"(da), "l"(db), "r"(scale_d));
}

__device__ __forceinline__ void wgmma_ss_n64_tb0(float (&d)[32], uint64_t da, uint64_t db, int scale_d) {
    asm volatile("{\n.reg .pred p;\nsetp.ne.b32 p, %34, 0;\n"
        "wgmma.mma_async.sync.aligned.m64n64k16.f32.bf16.bf16 {%0, %1, %2, %3, %4, %5, %6, %7, %8, %9, %10, %11, %12, %13, %14, %15, %16, %17, %18, %19, %20, %21, %22, %23, %24, %25, %26, %27, %28, %29, %30, %31}, %32, %33, p, 1, 1, 0, 0;\n}\n"
        : "+f"(d[0]), "+f"(d[1]), "+f"(d[2]), "+f"(d[3]), "+f"(d[4]), "+f"(d[5]), "+f"(d[6]), "+f"(d[7]), "+f"(d[8]), "+f"(d[9]), "+f"(d[10]), "+f"(d[11]), "+f"(d[12]), "+f"(d[13]), "+f"(d[14]), "+f"(d[15]), "+f"(d[16]), "+f"(d[17]), "+f"(d[18]), "+f"(d[19]), "+f"(d[20]), "+f"(d[21]), "+f"(d[22]), "+f"(d[23]), "+f"(d[24]), "+f"(d[25]), "+f"(d[26]), "+f"(d[27]), "+f"(d[28]), "+f"(d[29]), "+f"(d[30]), "+f"(d[31])
        : "l"(da), "l"(db), "r"(scale_d));
}

struct Maps {
    CUtensorMap xa, xa2, xa4, xas, wup4, wup8, mqa2, mqa4, mqb1, mqb2, uc, x, out, wq, wk, fa[3], fb[2], fc;
};

__device__ __forceinline__ uint64_t mkd(uint32_t lo) {
    uint64_t d;
    asm("mov.b64 %0, {%1, %2};" : "=l"(d) : "r"(lo), "r"((1024u >> 4) | (1u << 30)));
    return d;
}
__device__ __forceinline__ void bulk_ld(uint32_t dst, const void* src, uint32_t bytes, uint32_t bar) {
    asm volatile("cp.async.bulk.shared::cluster.global.mbarrier::complete_tx::bytes [%0], [%1], %2, [%3];" ::"r"(dst), "l"(src), "r"(bytes), "r"(bar) : "memory");
}
__device__ __forceinline__ void bulk_st(void* dst, uint32_t src, uint32_t bytes) {
    asm volatile("cp.async.bulk.global.shared::cta.bulk_group [%0], [%1], %2;" ::"l"(dst), "r"(src), "r"(bytes) : "memory");
}
__device__ __forceinline__ void ring_ld(uint32_t sb, uint32_t slot8, int n) {
    mbar_expect_tx(sb + B_R2 + slot8, 8192);
    bulk_ld(sb + R1 + slot8 * 1024, (const char*)g_wepi + n * 8192, 8192, sb + B_R2 + slot8);
}

__device__ __forceinline__ void ring_half(uint32_t sb, uint32_t slot8, uint32_t hoff, const CUtensorMap* tm, int c1, int c2) {
    mbar_expect_tx(sb + B_R1 + slot8, 8192);
    tma3(sb + slot8 * 2048 + hoff, tm, 0, c1, c2, sb + B_R1 + slot8);
}
__device__ __forceinline__ void ring_full(uint32_t sb, uint32_t slot8, const CUtensorMap* tm, int c1, int c2) {
    mbar_expect_tx(sb + B_R1 + slot8, 16384);
    mbar_arrive(sb + B_R1 + slot8);
    tma3(sb + slot8 * 2048, tm, 0, c1, c2, sb + B_R1 + slot8);
}
__device__ __forceinline__ void cta_done(int mode) {
    if (mode == 0 && atomicAdd(&g_sync[4], 1) == NCTA + 1) {
#pragma unroll
        for (int i = 0; i < 5; i++) g_sync[i] = 0;
    }
}

__device__ __forceinline__ void fold_cta(const Maps& mp, uint32_t sb, int mode) {
    constexpr uint32_t F_FULL = MISC, F_EMPTY = MISC + 32, F_T1 = MISC + 64, STG = 49152, FOUT = 3 * STG;
    const int tid = threadIdx.x, f = blockIdx.x - NCTA;
    if (mode == 2) return;
    if (tid == 0) {
        for (int i = 0; i < 3; i++) { mbar_init(sb + F_FULL + 8 * i, 1); mbar_init(sb + F_EMPTY + 8 * i, 2); }
        mbar_init(sb + F_T1, 2);
        asm volatile("fence.mbarrier_init.release.cluster;" ::: "memory");
        fence_async();
    }
    __syncthreads();
    const int wg = __shfl_sync(0xffffffffu, tid >> 7, 0);
    int st = 0, ph = 0;
    if (wg == 0) {
        if (tid == 0) {
#pragma unroll 1
            for (int it = 0; it < 96; it++) {
                const int p = it >> 3, kc = it & 7, job = p >> 2;
                if (it == 64) mbar_wait(sb + F_T1, 0);
                mbar_wait(sb + F_EMPTY + 8 * st, ph ^ 1);
                mbar_expect_tx(sb + F_FULL + 8 * st, STG);
                tma3(sb + st * STG, &mp.fa[job], 0, 256 * f + 128 * ((p >> 1) & 1), kc, sb + F_FULL + 8 * st);
                tma3(sb + st * STG + 16384, &mp.fb[job != 0], 0, 64 * kc + (job == 1 ? 512 : 0), 4 * (p & 1), sb + F_FULL + 8 * st);
                if (++st == 3) { st = 0; ph ^= 1; }
            }
        }
        return;
    }
    const int h = wg - 1, lane = tid & 31, w = (tid >> 5) & 3;
    const uint32_t sd = (sb & 0x3FFFF) >> 4;
    const bool el = (tid & 127) == 0;
#pragma unroll 1
    for (int p = 0; p < 12; p++) {
        float acc[128];
        fresh(acc);
#pragma unroll 1
        for (int kc = 0; kc < 8; kc++) {
            mbar_wait(sb + F_FULL + 8 * st, ph);
            wg_fence();
#pragma unroll
            for (int kk = 0; kk < 4; kk++)
                wgmma_ss_n256_tb1(acc, dsc(sd, st * STG + h * 8192 + kk * 32, 16), dsc(sd, st * STG + 16384 + kk * 2048, 8192), 1);
            wg_commit();
            wg_wait<0>();
            if (el) mbar_arrive(sb + F_EMPTY + 8 * st);
            if (++st == 3) { st = 0; ph ^= 1; }
        }
        pin(acc);
        const int job = p >> 2;
        if (el) {
            asm volatile("cp.async.bulk.wait_group 0;" ::: "memory");
            if (p == 4) { fence_async_g(); mbar_arrive(sb + F_T1); }
        }
        bar_sync(3 + h, 128);
        uint32_t r = 16 * w + (lane & 7) + ((lane >> 3) & 1) * 8;
        const float fs = job == 1 ? 0.5f : 1.f;
        if (job == 1) r = (r & ~31) | (((r >> 1) & 3) << 3) | (((r >> 3) & 3) << 1) | (r & 1);
        const uint32_t oa = sb + FOUT + h * 32768 + r * 128 + ((((lane >> 4) ^ r) & 7) << 4);
#pragma unroll
        for (int i = 0; i < 16; i++)
            stsm4((oa ^ ((i & 3) << 5)) + (i >> 2) * 8192, pack2(acc[8 * i] * fs, acc[8 * i + 1] * fs), pack2(acc[8 * i + 2] * fs, acc[8 * i + 3] * fs),
                  pack2(acc[8 * i + 4] * fs, acc[8 * i + 5] * fs), pack2(acc[8 * i + 6] * fs, acc[8 * i + 7] * fs));
        fence_async();
        bar_sync(3 + h, 128);
        if (el) {
            const int row0 = 256 * f + 128 * ((p >> 1) & 1) + 64 * h + (job == 1 ? 512 : 0);
            if (job == 0) tma3_store(&mp.fc, sb + FOUT + h * 32768, 0, row0, 4 * (p & 1));
            else {
#pragma unroll 1
                for (int i = 0; i < 16; i++)
                    bulk_st((char*)g_wepi + (row0 / 8 + 2 * (i & 3) + (p & 1)) * 8192 + (i >> 2) * 2048, sb + FOUT + h * 32768 + i * 2048, 2048);
            }
            asm volatile("cp.async.bulk.commit_group;" ::: "memory");
        }
    }
    if (el) {
        asm volatile("cp.async.bulk.wait_group 0;" ::: "memory");
        fence_async_g();
        if (mode == 0) flag_add(&g_sync[3]);
    }
    bar_sync(2, 256);
    if (tid == 128) cta_done(mode);
}

__global__ void __launch_bounds__(384, 1) main_kernel(const __grid_constant__ Maps mp, const bf16* __restrict__ x, const bf16* __restrict__ dw, const bf16* wup, const int mode) {
    extern __shared__ __align__(1024) uint8_t smem[];
    const uint32_t sb = smem_u32(smem);
    const int tid = threadIdx.x;
    PE();
    if (blockIdx.x >= NCTA) { fold_cta(mp, sb, mode); return; }
    const int b = blockIdx.x / TPB, ti = blockIdx.x % TPB;
    const int piece = blockIdx.x & 127;
    const int wg = __shfl_sync(0xffffffffu, tid >> 7, 0);
    const int lane = tid & 31, w = (tid >> 5) & 3;
    const bool w0 = __shfl_sync(0xffffffffu, w, 0) == 0;
    const uint32_t sd = (sb & 0x3FFFF) >> 4;
    const uint32_t adA = sd + (AT >> 4) + (1u << 16);
    const uint32_t bd0 = sd;
    const uint32_t bd2k = bd0 + ((2048u >> 4) << 16);
    const bool el = (tid & 127) == 0;
    const uint32_t lrow = 16 * w + (lane & 7) + ((lane >> 3) & 1) * 8;
    const uint32_t loff = lrow * 128 + ((((lane >> 4) ^ lrow) & 7) << 4);
    const int r0 = 16 * w + (lane >> 2);

    if (wg == 0) {
        asm volatile("setmaxnreg.inc.sync.aligned.u32 184;");
        uint32_t q[112];
        PG(206);
        if (tid == 0) {
            mbar_init(sb + B_MK, 1);
            for (int i = 0; i < 9; i++) mbar_init(sb + B_R1 + 8 * i, 2);
            for (int i = 0; i < 5; i++) asm volatile("st.shared.u32 [%0], 0;" ::"r"(sb + CNT + 4 * i) : "memory");
        } else if (tid == 32) {
            mbar_init(sb + B_LN, 1); mbar_init(sb + B_MQ, 1);
            mbar_init(sb + B_H1, 2); mbar_init(sb + B_H2, 1); mbar_init(sb + B_H3, 2);
            for (int i = 0; i < 3; i++) { mbar_init(sb + B_KV + 8 * i, 2); mbar_init(sb + B_P + 8 * i, 4); mbar_init(sb + B_GO + 8 * i, 4); }
            mbar_init(sb + B_UC, 1); mbar_init(sb + B_UC + 8, 1); mbar_init(sb + B_X2, 4); mbar_init(sb + B_X2 + 8, 4);
        } else if (tid == 64) {
            for (int i = 0; i < 20; i++) mbar_init(sb + B_R2 + 8 * i, 1);
        } else if (tid == 96) {
            for (int i = 0; i < 20; i++) mbar_init(sb + B_E2 + 8 * i, 4);
        }
        if (lane == 0) {
            asm volatile("fence.mbarrier_init.release.cluster;" ::: "memory");
            fence_async();
        }
        PG(207);
        __syncwarp();
        if (SU != 2) asm volatile("bar.arrive 5, 384;" ::: "memory");
        if (tid == 0) {
            mbar_expect_tx(sb + B_MK, 65536 + 32768);
            tma3(sb + 16384, &mp.wq, 0, 64 * (piece >> 4), 0, sb + B_MK);
            tma3(sb + 81920, &mp.wk, 0, 32 * (piece & 15), 0, sb + B_MK);
            for (int i = 0; i < 14; i++) mbar_arrive(sb + B_R1 + 8 * (i >> 1));
            if (mode != 1) {
                ring_full(sb, 56, &mp.wup8, 0, 8);
                ring_full(sb, 64, &mp.wup8, 16, 8);
                ring_full(sb, 0, &mp.wup8, 32, 8);
            }
        }
        PG(208);
        bar_sync(1, 128);
        if (SU == 2) asm volatile("bar.arrive 5, 384;" ::: "memory");
        PT(0);
        PG(200);
        {
            float mq[16];
            fresh(mq);
            mbar_wait(sb + B_MK, 0);
            PT(1);
            if (tid == 32) l2_prefetch((const char*)wup + piece * 8192, 8192);
            wg_fence();
#pragma unroll 1
            for (int c = 0; c < 8; c++)
#pragma unroll
                for (int kk = 0; kk < 4; kk++)
                    wgmma_ss_n32_tb0(mq, dsc(sd, 16384 + c * 8192 + kk * 32, 16), dsc(sd, 81920 + c * 4096 + kk * 32, 16), 1);
            wg_commit();
            wg_wait<0>();
            if (mode != 1 && w0 && elect1()) {
#pragma unroll 1
                for (int i = 1; i < 7; i++) ring_full(sb, 8 * i, &mp.wup8, 32 + 16 * i, 8);
            }
            pin(mq);
            uint32_t* c = reinterpret_cast<uint32_t*>(g_mqk + (64 * (piece >> 4) + r0) * D_ + 32 * (piece & 15) + 2 * (lane & 3));
#pragma unroll
            for (int n = 0; n < 4; n++) { c[4 * n] = pack2(mq[4 * n], mq[4 * n + 1]); c[4 * n + 4 * D_] = pack2(mq[4 * n + 2], mq[4 * n + 3]); }
            fence_async_g();
            bar_sync(1, 128);
            if (el) {
                if (mode == 0) flag_add(&g_sync[2]);
                if (mode == 0) flag_wait(&g_sync[2], NCTA);
                mbar_arrive(sb + B_MQ);
                PG(203);
                PT(12);
                mbar_wait(sb + B_LN, 0);
#pragma unroll 1
                for (int c = 0; c < 8; c++) {
                    tma4_store(&mp.xas, sb + AT + c * 8192, 0, 62 * ti, c, b);
                    const unsigned t0 = (unsigned)clock();
                    while (c < 7 && (unsigned)clock() - t0 < XS_GAP) __nanosleep(20);
                }
                asm volatile("cp.async.bulk.commit_group;" ::: "memory");
                if (mode == 1) asm volatile("cp.async.bulk.wait_group 0;" ::: "memory");
            }
            PT(13);
            if (mode == 1) return;
        }
        mbar_wait(sb + B_H1, 0);
        PT(2);
        uint32_t slot8 = 24, par = 0, prev8 = 0, prev2 = 0;
        auto adv = [&]() { prev2 = prev8; prev8 = slot8; slot8 += 8; if (slot8 == 72) { slot8 = 0; par ^= 1; } };
        {
            float acc[128];
            fresh(acc);
            auto step = [&](int i) {
                const uint32_t aa = adA + (i >> 1) * 512 + (i & 1) * 4, bb = bd0 + ((4096u >> 4) << 16) + slot8 * 128;
                wg_fence();
                wgmma_ss_n256_tb1(acc, mkd(aa), mkd(bb), 1);
                wgmma_ss_n256_tb1(acc, mkd(aa + 2), mkd(bb + 128), 1);
                wg_commit();
                wg_wait<1 + LAGA>();
            };
#pragma unroll 1
            for (int i = 0; i < 8 + LAGA; i++) {
                mbar_wait(sb + B_R1 + slot8, par);
                step(i);
                if (i > LAGA && w0 && elect1()) ring_full(sb, LAGA ? prev2 : prev8, &mp.mqa4, 32 * (i - LAGA) + 256, 4);
                adv();
            }
#pragma unroll 1
            for (int i = 8 + LAGA; i < 16; i++) {
                mbar_wait(sb + B_R1 + slot8, par);
                if (i == 15 && el) mbar_arrive(sb + B_H2);
                step(i);
                if (w0 && elect1()) ring_full(sb, LAGA ? prev2 : prev8, &mp.wup8, 16 * (i - LAGA) - 128, 0);
                adv();
            }
            if (LAGA) {
                wg_wait<1>();
                if (w0 && elect1()) ring_full(sb, prev2, &mp.wup8, 112, 0);
            }
            wg_wait<0>();
            if (w0 && elect1()) ring_full(sb, prev8, &mp.wup8, 128, 0);
            pin(acc);
            PT(3);
#pragma unroll
            for (int kk = 0; kk < 4; kk++)
                stsm4((sb + QS + loff) ^ (kk << 5), pack2(acc[96 + 8 * kk], acc[97 + 8 * kk]), pack2(acc[98 + 8 * kk], acc[99 + 8 * kk]),
                      pack2(acc[100 + 8 * kk], acc[101 + 8 * kk]), pack2(acc[102 + 8 * kk], acc[103 + 8 * kk]));
            fence_async();
#pragma unroll
            for (int i = 47; i >= 0; i--) q[64 + i] = pack2v(acc[2 * i], acc[2 * i + 1]);
        }
        if (el) {
            asm volatile("cp.async.bulk.wait_group 0;" ::: "memory");
            if (mode == 0) {
                fence_async_g();
                flag_add(&g_sync[b]);
                flag_wait(&g_sync[b], TPB);
            }
        }
        __syncwarp();
        mbar_wait(sb + B_H3, 0);
        PT(4);
        slot8 = 48; par = 1;
#pragma unroll
        for (int half = 0; half < 2; half++) {
            float acc[64];
            fresh(acc);
            auto step = [&](int m) {
                const uint32_t aa = adA + m * 512, bb = bd0 + ((8192u >> 4) << 16) + slot8 * 128;
                mbar_wait(sb + B_R1 + slot8, par);
                wg_fence();
#pragma unroll
                for (int kk = 0; kk < 4; kk++) wgmma_ss_n128_tb1(acc, mkd(aa + 2 * kk), mkd(bb + 128 * kk), 1);
                wg_commit();
                wg_wait<1 + LAGB>();
            };
#pragma unroll 1
            for (int m = 0; m < 8; m++) {
                step(m);
                if (m > LAGB && w0 && elect1()) {
                    if (half == 0) ring_full(sb, LAGB ? prev2 : prev8, &mp.mqb2, 64 * (m - LAGB), 2);
                    else if (m < 4 + LAGB) tma4(sb + (LAGB ? prev2 : prev8) * 2048, &mp.xa2, 0, 0, 2 * (m - LAGB), b, sb + B_KV + 8);
                }
                adv();
            }
            if (LAGB && half == 0) {
                wg_wait<1>();
                if (w0 && elect1()) ring_full(sb, prev2, &mp.mqb2, 448, 2);
            }
            wg_wait<0>();
            if (w0 && elect1()) {
                if (half == 0) {
                    mbar_expect_tx(sb + B_KV + 8, 65536);
                    for (int i = 0; i < 3; i++) mbar_arrive(sb + B_KV + 8 * i);
                    tma4(sb + prev8 * 2048, &mp.xa2, 0, 0, 0, b, sb + B_KV + 8);
                } else {
                    mbar_expect_tx(sb + B_KV + 16, 65536);
                    tma4(sb + R2, &mp.xa, 0, 64, 0, b, sb + B_KV + 16);
                    mbar_expect_tx(sb + B_KV, 65536);
                    tma4(sb + R0, &mp.xa, 0, 128, 0, b, sb + B_KV);
                }
            }
            pin(acc);
#pragma unroll
            for (int i = 31; i >= 0; i--) q[32 * half + i] = pack2v(acc[2 * i], acc[2 * i + 1]);
        }
        bar_sync(1, 128);
        PT(5);

        const float CS = 0.04419417382415922f * 1.4426950408889634f;
        float m0 = -INFINITY, m1 = -INFINITY, l0 = 0.f, l1 = 0.f;
        int s = 0, sn = 1, ph = 0;
        float S[32];
        const bool l0w = lane == 0, q0 = (lane & 3) == 0;
#pragma unroll 1
        for (int j = -1;; j++) {
            if (j >= 0) {
                PL(j, 1);
                if (j == NKV - 1) {
#pragma unroll
                    for (int i = (T_ - 64 * (NKV - 1)) / 2; i < 32; i++) asm volatile("mov.b32 %0, 0xff800000;" : "=f"(S[i]));
                }
                const bool kv = mbar_test(sb + B_KV + sn * 8, ph);
                const uint32_t pb = sb + R3 + (s == 0 ? 2 : s - 1) * 8192;
                float a0 = 0.f, a1 = 0.f, sc0 = 1.f, sc1 = 1.f;
                auto expo = [&]() {
                    const float n0 = -m0 * CS, n1 = -m1 * CS;
                    a0 = 0.f; a1 = 0.f;
#pragma unroll
                    for (int kk = 0; kk < 4; kk++) {
                        float p[8];
#pragma unroll
                        for (int e = 0; e < 8; e++) p[e] = ex2(fmaf(S[8 * kk + e], CS, (e & 2) ? n1 : n0));
                        a0 += (p[0] + p[1]) + (p[4] + p[5]);
                        a1 += (p[2] + p[3]) + (p[6] + p[7]);
                        stsm4((pb + loff) ^ (kk << 5), pack2(p[0], p[1]), pack2(p[2], p[3]), pack2(p[4], p[5]), pack2(p[6], p[7]));
                    }
                };
                if (j > 0 || !SK0) expo();
                if ((SK0 && j == 0) || __any_sync(0xffffffffu, !(a0 <= LAZY) || !(a1 <= LAZY))) {
                    float x0 = m0, x1 = m1;
#pragma unroll
                    for (int n = 0; n < 8; n++) { x0 = fmaxf(x0, fmaxf(S[4 * n], S[4 * n + 1])); x1 = fmaxf(x1, fmaxf(S[4 * n + 2], S[4 * n + 3])); }
                    x0 = fmaxf(x0, __shfl_xor_sync(0xffffffffu, x0, 1));
                    x1 = fmaxf(x1, __shfl_xor_sync(0xffffffffu, x1, 1));
                    x0 = fmaxf(x0, __shfl_xor_sync(0xffffffffu, x0, 2));
                    x1 = fmaxf(x1, __shfl_xor_sync(0xffffffffu, x1, 2));
                    sc0 = ex2((m0 - x0) * CS); sc1 = ex2((m1 - x1) * CS);
                    m0 = x0; m1 = x1;
                    expo();
                }
                if (q0) { sts_f32(sb + SCL + s * 256 + r0 * 4, sc0); sts_f32(sb + SCL + s * 256 + r0 * 4 + 32, sc1); }
                __syncwarp();
                if (l0w) mbar_arrive(sb + B_P + s * 8);
                l0 = fmaf(l0, sc0, a0); l1 = fmaf(l1, sc1, a1);
                PL(j, 2);
                if (j == NKV - 1) break;
                if (!kv) mbar_wait(sb + B_KV + sn * 8, ph);
            } else {
                mbar_wait(sb + B_KV + 8, 0);
            }
            const uint32_t kd = sd + sn * 4096;
            if (TRIM & 2 && j == NKV - 2) {
                float Sn[16];
                wg_fence();
#pragma unroll
                for (int kk = 0; kk < 28; kk++) {
                    wgmma_rs_n32_tb0(Sn, q[4 * kk], q[4 * kk + 1], q[4 * kk + 2], q[4 * kk + 3], dsc(kd, (kk >> 2) * 8192 + (kk & 3) * 32, 16), kk > 0);
                    if (kk == FENCE_AT) { fence_async(); __syncwarp(); }
                    if (kk == GO_LAST && l0w) mbar_arrive(sb + B_GO + s * 8);
                }
#pragma unroll
                for (int kk = 0; kk < 4; kk++)
                    wgmma_ss_n32_tb0(Sn, dsc(sd, QS + kk * 32, 16), dsc(kd, 7 * 8192 + kk * 32, 16), 1);
                wg_commit();
                wg_wait<0>();
                pin(Sn);
#pragma unroll
                for (int i = 0; i < 16; i++) S[i] = Sn[i];
            } else {
            float Sn[32];
            wg_fence();
#pragma unroll
            for (int kk = 0; kk < 28; kk++) {
                wgmma_rs_n64_tb0(Sn, q[4 * kk], q[4 * kk + 1], q[4 * kk + 2], q[4 * kk + 3], dsc(kd, (kk >> 2) * 8192 + (kk & 3) * 32, 16), kk > 0);
                if (kk == FENCE_AT) { fence_async(); __syncwarp(); }
                if (kk == GO_AT) { PL(j, 3); if (j >= 0 && l0w) mbar_arrive(sb + B_GO + s * 8); }
            }
#pragma unroll
            for (int kk = 0; kk < 4; kk++)
                wgmma_ss_n64_tb0(Sn, dsc(sd, QS + kk * 32, 16), dsc(kd, 7 * 8192 + kk * 32, 16), 1);
            wg_commit();
            PL(j, 0);
            wg_wait<0>();
            pin(Sn);
#pragma unroll
            for (int i = 0; i < 32; i++) S[i] = Sn[i];
            }
            s = sn;
            if (++sn == 3) sn = 0;
            if (sn == 1) ph ^= 1;
        }
        l0 += __shfl_xor_sync(0xffffffffu, l0, 1); l1 += __shfl_xor_sync(0xffffffffu, l1, 1);
        l0 += __shfl_xor_sync(0xffffffffu, l0, 2); l1 += __shfl_xor_sync(0xffffffffu, l1, 2);
        if (q0) { sts_f32(sb + LINV + r0 * 4, rcp(l0)); sts_f32(sb + LINV + r0 * 4 + 32, rcp(l1)); }
        fence_async();
        __syncwarp();
        if (l0w) {
            mbar_arrive(sb + B_GO + s * 8);
            uint32_t slot8 = 8 * w, par = 0;
#pragma unroll 1
            for (int n = 20 + w; n < 136; n += 4) {
                mbar_wait(sb + B_E2 + slot8, par);
                if (n < 128) ring_ld(sb, slot8, n);
                else {
                    mbar_expect_tx(sb + B_X2 + 8 * (n & 1), 8192);
                    tma4(sb + R1 + slot8 * 1024, &mp.x, 0, 62 * ti, 4 * (n & 1) + (n >> 1 & 3), b, sb + B_X2 + 8 * (n & 1));
                }
                slot8 += 32;
                if (slot8 >= 160) { slot8 -= 160; par ^= 1; }
            }
        }
        PDUMP();
    } else {
        asm volatile("setmaxnreg.dec.sync.aligned.u32 160;");
        const int h = wg - 1;
        uint32_t v[4][8], v2[4][8];
        if (SU != 0) bar_sync(5, 384);
        PG(206);
#pragma unroll
        for (int i = 0; i < 8; i++) {
            const int t = 62 * ti - 1 + 32 * (i >> 2) + 16 * h + 4 * w + (i & 3);
            const uint4* p = reinterpret_cast<const uint4*>(x + ((size_t)b * T_ + t) * D_) + lane;
            uint32_t* d = i < 4 ? v[i & 3] : v2[i & 3];
#pragma unroll
            for (int c = 0; c < 2; c++)
                asm volatile("{\n.reg .pred p;\nsetp.lt.u32 p, %5, %6;\nmov.b32 %0, 0;\nmov.b32 %1, 0;\nmov.b32 %2, 0;\nmov.b32 %3, 0;\n"
                             "@p ld.global.nc.v4.u32 {%0, %1, %2, %3}, [%4];\n}\n"
                             : "=r"(d[4 * c]), "=r"(d[4 * c + 1]), "=r"(d[4 * c + 2]), "=r"(d[4 * c + 3]) : "l"(p + 32 * c), "r"(t), "n"(T_));
        }
#pragma unroll 1
        for (int bt = 0; bt < 2; bt++) {
            PT(bt ? 13 : 0);
            float a[8];
            const uint32_t la = sb + AT + (lane >> 3) * 8192 + (32 * bt + 16 * h + 4 * w) * 128 + (((lane & 7) ^ ((w & 1) * 4)) << 4);
            const bool b4 = lane & 16, b3 = lane & 8, b2 = lane & 4;
#pragma unroll
            for (int r = 0; r < 4; r++) {
                float c[4] = {0.f, 0.f, 0.f, 0.f};
#pragma unroll
                for (int i = 0; i < 8; i += 2) hmma(c, v[r][i], v[r][i], v[r][i + 1], v[r][i + 1], v[r][i], v[r][i + 1]);
                a[4 + r] = (lane & 3) == (lane >> 3) ? (b2 ? c[1] : c[0]) : 0.f;
                if (r & 1) {
                    float e[4] = {0.f, 0.f, 0.f, 0.f};
#pragma unroll
                    for (int i = 0; i < 8; i += 2) hmma(e, v[r - 1][i], v[r][i], v[r - 1][i + 1], v[r][i + 1], 0x3f803f80u, 0x3f803f80u);
                    a[r - 1] = e[0]; a[r] = e[2];
                }
            }
            float k[4];
#pragma unroll
            for (int i = 0; i < 4; i++) {
                const int lo = (i & 1) + 4 * (i >> 1);
                k[i] = (b4 ? a[lo + 2] : a[lo]) + __shfl_xor_sync(0xffffffffu, b4 ? a[lo] : a[lo + 2], 16);
            }
            const float k0 = (b3 ? k[1] : k[0]) + __shfl_xor_sync(0xffffffffu, b3 ? k[0] : k[1], 8);
            const float k1 = (b3 ? k[3] : k[2]) + __shfl_xor_sync(0xffffffffu, b3 ? k[2] : k[3], 8);
            float z = (b2 ? k1 : k0) + __shfl_xor_sync(0xffffffffu, b2 ? k0 : k1, 4);
            z += __shfl_xor_sync(0xffffffffu, z, 2);
            z += __shfl_xor_sync(0xffffffffu, z, 1);
            const float zo = __shfl_xor_sync(0xffffffffu, z, 4);
            PG(204 + bt);
            const float mu = (b2 ? zo : z) * (0.25f / D_);
            float sd_ = bfr(bfr(fmaxf(fmaf(b2 ? z : zo, 1.f / D_, -mu * mu), 0.f)) + 1e-5f);
            asm("sqrt.approx.f32 %0, %0;" : "+f"(sd_));
            const float ri = rcp(bfr(sd_));
            const uint32_t w1 = pack2(mu, ri), w2 = pack2(ri - bhi(w1), ri - bhi(w1));
#pragma unroll
            for (int r = 0; r < 4; r++) {
                const uint32_t s1 = __shfl_sync(0xffffffffu, w1, 8 * r), rl = __shfl_sync(0xffffffffu, w2, 8 * r);
                const uint32_t m2 = __byte_perm(s1, 0, 0x1010), rh = __byte_perm(s1, 0, 0x3232);
#pragma unroll
                for (int i = 0; i < 8; i++) { const uint32_t d = bsub2(v[r][i], m2); v[r][i] = bfma2(d, rh, bmul2(d, rl)); }
                sts4((la ^ (r << 4)) + r * 128, v[r][0], v[r][1], v[r][2], v[r][3]);
                sts4((la ^ (r << 4)) + r * 128 + 32768, v[r][4], v[r][5], v[r][6], v[r][7]);
#pragma unroll
                for (int i = 0; i < 8; i++) v[r][i] = v2[r][i];
            }
        }
        fence_async();
        if (SU == 0) bar_sync(5, 384); else bar_sync(2, 256);
        if (tid == 128) mbar_arrive(sb + B_LN);
        PG(202);
        if (mode == 1) return;
        float acc[128];
#pragma unroll
        for (int pass = 0; pass < 2; pass++) {
            if (pass == 1) mbar_wait(sb + B_H2, 0);
            PT(1 + 3 * pass);
            fresh(acc);
            uint32_t slot8 = pass ? 8 : 56, par = 0, prev8 = 0;
            auto adv = [&]() { prev8 = slot8; slot8 += 8; if (slot8 == 72) { slot8 = 0; par ^= 1; } };
            auto step = [&](int kk) {
                wg_fence();
                wgmma_ss_n256_tb1(acc, mkd(adA + (kk >> 2) * 512 + (kk & 3) * 2), mkd(bd2k + h * 512 + slot8 * 128), 1);
                wg_commit();
                wg_wait<1>();
            };
#pragma unroll 1
            for (int kk = 0; kk < 24; kk++) {
                mbar_wait(sb + B_R1 + slot8, par);
                step(kk);
                if (kk > 0 && w0 && elect1()) ring_half(sb, prev8, h * 8192, &mp.wup4, 16 * kk + 128, (pass ? 0 : 8) + 4 * h);
                adv();
            }
            if (pass == 0 && w0) mbar_wait(sb + B_MQ, 0);
#pragma unroll 1
            for (int kk = 24; kk < 32; kk++) {
                mbar_wait(sb + B_R1 + slot8, par);
                if (kk == 31 && el) mbar_arrive(sb + (pass ? B_H3 : B_H1));
                step(kk);
                if (w0 && elect1()) ring_half(sb, prev8, h * 8192, pass ? &mp.mqb1 : &mp.mqa2, (pass ? 64 : 32) * (kk - 24), pass ? h : 4 + 2 * h);
                adv();
            }
            wg_wait<0>();
            if (w0 && elect1()) ring_half(sb, prev8, h * 8192, pass ? &mp.mqb1 : &mp.mqa2, pass ? 0 : 256, pass ? 2 + h : 4 + 2 * h);
            pin(acc);
            PT(2 + 3 * pass);
            bf16* ucp = g_uc + ((size_t)blockIdx.x * 128 + r0) * D_ + 256 * h + 8 * (lane & 3);
            if (pass == 0) {
                float s0 = 0.f, s1 = 0.f, v0 = 0.f, v1 = 0.f;
#pragma unroll
                for (int n = 0; n < 32; n++) {
#pragma unroll
                    for (int e = 0; e < 4; e++) acc[4 * n + e] = gelu2(acc[4 * n + e]);
                    s0 += acc[4 * n] + acc[4 * n + 1]; s1 += acc[4 * n + 2] + acc[4 * n + 3];
                    v0 = fmaf(acc[4 * n], acc[4 * n], v0); v0 = fmaf(acc[4 * n + 1], acc[4 * n + 1], v0);
                    v1 = fmaf(acc[4 * n + 2], acc[4 * n + 2], v1); v1 = fmaf(acc[4 * n + 3], acc[4 * n + 3], v1);
                }
#pragma unroll
                for (int o = 1; o < 4; o <<= 1) {
                    s0 += __shfl_xor_sync(0xffffffffu, s0, o); s1 += __shfl_xor_sync(0xffffffffu, s1, o);
                    v0 += __shfl_xor_sync(0xffffffffu, v0, o); v1 += __shfl_xor_sync(0xffffffffu, v1, o);
                }
                if ((lane & 3) == 0) {
                    uint32_t a = sb + STAT + h * 512 + r0 * 8;
                    sts_f32(a, s0); sts_f32(a + 4, v0); sts_f32(a + 64, s1); sts_f32(a + 68, v1);
                }
                bar_sync(2, 256);
                {
                    uint32_t a = sb + STAT + (h ^ 1) * 512 + r0 * 8;
                    s0 = (s0 + lds_f32(a)) * (1.f / 512.f); v0 = (v0 + lds_f32(a + 4)) * (1.f / 512.f);
                    s1 = (s1 + lds_f32(a + 64)) * (1.f / 512.f); v1 = (v1 + lds_f32(a + 68)) * (1.f / 512.f);
                }
                v0 = rsqrtf(fmaxf(fmaf(-s0, s0, v0), 0.f) + 4e-5f); v1 = rsqrtf(fmaxf(fmaf(-s1, s1, v1), 0.f) + 4e-5f);
                s0 = -s0 * v0; s1 = -s1 * v1;
#pragma unroll
                for (int m = 0; m < 8; m++) {
                    const float* a_ = acc + 16 * m;
                    stg4(ucp + 64 * D_ + 32 * m, pack2(fmaf(a_[0], v0, s0), fmaf(a_[1], v0, s0)), pack2(fmaf(a_[4], v0, s0), fmaf(a_[5], v0, s0)),
                         pack2(fmaf(a_[8], v0, s0), fmaf(a_[9], v0, s0)), pack2(fmaf(a_[12], v0, s0), fmaf(a_[13], v0, s0)));
                    stg4(ucp + 72 * D_ + 32 * m, pack2(fmaf(a_[2], v1, s1), fmaf(a_[3], v1, s1)), pack2(fmaf(a_[6], v1, s1), fmaf(a_[7], v1, s1)),
                         pack2(fmaf(a_[10], v1, s1), fmaf(a_[11], v1, s1)), pack2(fmaf(a_[14], v1, s1), fmaf(a_[15], v1, s1)));
                }
            } else {
#pragma unroll
                for (int m = 0; m < 8; m++) {
                    const float* a_ = acc + 16 * m;
                    stg4(ucp + 32 * m, pack2(a_[0], a_[1]), pack2(a_[4], a_[5]), pack2(a_[8], a_[9]), pack2(a_[12], a_[13]));
                    stg4(ucp + 8 * D_ + 32 * m, pack2(a_[2], a_[3]), pack2(a_[6], a_[7]), pack2(a_[10], a_[11]), pack2(a_[14], a_[15]));
                }
                bar_sync(3 + h, 128);
            }
            PT(3 + 3 * pass);
        }
        int s = 1, ph = 0;
        uint32_t* cp = reinterpret_cast<uint32_t*>(g_uc + (size_t)blockIdx.x * 128 * D_) + (tid - 128);
        const uint32_t* dp = reinterpret_cast<const uint32_t*>(dw) + (((tid - 128) & ~15) | ((lane & 3) << 2) | ((lane >> 2) & 3));
        const uint32_t d0 = ldg_v(dp), d1 = ldg_v(dp + D_ / 2), d2 = ldg_v(dp + D_);
        uint32_t ga = ldg_cg(cp + 64 * (D_ / 2)), gb = ldg_cg(cp + 65 * (D_ / 2));
        fresh(acc);
#pragma unroll 1
        for (int j = 0; j < NKV; j++) {
            cp += D_ / 2;
            uint32_t gc = 0, uu = 0;
            if (j < NKV - 1) { gc = ldg_cg(cp + 65 * (D_ / 2)); uu = ldg_cg(cp); }
            mbar_wait(sb + B_P + s * 8, ph);
            PL(j, 0);
            if (j > 0) {
                const float sc0 = lds_f32(sb + SCL + s * 256 + r0 * 4), sc1 = lds_f32(sb + SCL + s * 256 + r0 * 4 + 32);
                if (__any_sync(0xffffffffu, sc0 != 1.f || sc1 != 1.f)) {
#pragma unroll
                    for (int n = 0; n < 32; n++) { acc[4 * n] *= sc0; acc[4 * n + 1] *= sc0; acc[4 * n + 2] *= sc1; acc[4 * n + 3] *= sc1; }
                }
            }
            mbar_wait(sb + B_GO + s * 8, ph);
            PL(j, 1);
            const uint32_t vd = sd + s * 4096 + h * 2048, pd = sd + (s == 0 ? 2 : s - 1) * 512;
            pin(acc);
            if (TRIM & 1 && j == NKV - 1) {
                wg_fence();
#pragma unroll
                for (int kk = 0; kk < 2; kk++) wgmma_ss_n256_tb1(acc, dsc(pd, R3 + kk * 32, 16), dsc(vd, kk * 2048, 8192), 1);
                wg_commit();
                wg_wait<0>();
                pin(acc);
                break;
            }
            wg_fence();
#pragma unroll
            for (int kk = 0; kk < 4; kk++) wgmma_ss_n256_tb1(acc, dsc(pd, R3 + kk * 32, 16), dsc(vd, kk * 2048, 8192), 1);
            wg_commit();
            wg_wait<0>();
            pin(acc);
            PL(j, 2);
            if (w0 && elect1()) {
                if (j + 3 < NKV) {
                    mbar_expect_tx(sb + B_KV + s * 8, 32768);
                    tma4(sb + s * 65536 + h * 32768, &mp.xa4, 0, 64 * (j + 3), 4 * h, b, sb + B_KV + s * 8);
                } else if (j < NKV - 1) {
                    const int n0 = (j == NKV - 3 ? 0 : 8) + 4 * h;
#pragma unroll 1
                    for (int n = n0; n < n0 + 4; n++) ring_ld(sb, n * 8, n);
                }
                if (j == NKV - 5 && mode == 0) flag_wait(&g_sync[3], 4);
                if (j >= XPF && j < XPF + 4) {
                    const int t0 = 62 * ti + 32 * h + 8 * (j - XPF), nr = min(8, T_ - t0);
                    if (nr > 0) l2_prefetch(x + ((size_t)b * T_ + t0) * D_, nr * 1024);
                }
                if (KPF && h == 0 && 64 * (j + KPF) + ti < T_) l2_prefetch(g_xa + ((size_t)b * (T_ + 8) + 1 + 64 * (j + KPF) + ti) * D_, 1024);
            }
            uu = pack2(gelu2(blo(uu)), gelu2(bhi(uu)));
            if (j < NKV - 1) asm volatile("st.global.u32 [%0], %1;" ::"l"(cp), "r"(bmul2(uu, bfma2(gc, d2, bfma2(gb, d1, bmul2(ga, d0))))) : "memory");
            ga = gb; gb = gc;
            if (++s == 3) s = 0;
            if (s == 1) ph ^= 1;
        }
        {
            const float i0 = lds_f32(sb + LINV + r0 * 4), i1 = lds_f32(sb + LINV + r0 * 4 + 32);
#pragma unroll
            for (int p = 0; p < 16; p++)
                stsm4(((sb + R0 + h * 32768 + loff) ^ ((p & 3) << 5)) + (p >> 2) * 8192,
                      pack2(acc[8 * p] * i0, acc[8 * p + 1] * i0), pack2(acc[8 * p + 2] * i1, acc[8 * p + 3] * i1),
                      pack2(acc[8 * p + 4] * i0, acc[8 * p + 5] * i0), pack2(acc[8 * p + 6] * i1, acc[8 * p + 7] * i1));
        }
        fence_async();
        fence_async_g();
        bar_sync(2, 256);
        if (lane == 0 && w < 2) ring_ld(sb, 128 + 16 * w + 8 * h, 16 + 2 * w + h);
        PT(7);
        fresh(acc);
        if (SKEW && h == 1) mbar_wait(sb + B_E2 + 16 * (SKEW - 1), 0);
        {
            uint32_t slot8 = 8 * h, par = 0, prev8 = 0;
#pragma unroll 1
            for (int kk = 0; kk < 64; kk++) {
                if (kk == 32 || kk == 48) mbar_wait(sb + B_UC + (kk >> 1 & 8), 0);
                mbar_wait(sb + B_R2 + slot8, par);
                wg_fence();
                wgmma_ss_n256_tb1(acc, mkd(sd + (1u << 16) + (R0 >> 4) + (kk >> 2 & 7) * 512 + (kk & 3) * 2), mkd(bd2k + (R1 >> 4) + slot8 * 64), 1);
                wg_commit();
                wg_wait<1>();
                if (kk > 0 && lane == 0) mbar_arrive(sb + B_E2 + prev8);
                if ((kk == 16 || kk == 32) && w0 && elect1() && (atom_inc_s(sb + CNT + 12 + (kk >> 3 & 4)) & 1)) {
                    mbar_expect_tx(sb + B_UC + (kk >> 2 & 8), 32768);
                    tma3(sb + R0 + (kk & 32) * 1024, &mp.uc, 0, 128 * blockIdx.x, kk >> 3 & 4, sb + B_UC + (kk >> 2 & 8));
                }
                prev8 = slot8;
                slot8 += 16;
                if (slot8 >= 160) { slot8 -= 160; par ^= 1; }
            }
        }
        wg_wait<0>();
        pin(acc);
        PT(8);
        mbar_wait(sb + B_X2 + 8 * h, 0);
        PT(9);
        {
            const uint32_t sr = (lrow + 63) & 63;
            const uint32_t xoff = sr * 128 + ((((lane >> 4) ^ sr) & 7) << 4);
#pragma unroll
            for (int p = 0; p < 16; p++) {
                const uint32_t a = ((sb + R2 + h * 8192 + xoff) ^ ((p & 3) << 5)) + (p >> 2) * 16384;
                uint32_t xv[4];
                ldsm4(a, xv);
#pragma unroll
                for (int e = 0; e < 4; e++)
                    xv[e] = pack2(acc[8 * p + 2 * e] + __uint_as_float(xv[e] << 16), acc[8 * p + 2 * e + 1] + __uint_as_float(xv[e] & 0xffff0000u));
                stsm4(a, xv[0], xv[1], xv[2], xv[3]);
            }
        }
        fence_async();
        bar_sync(3 + h, 128);
        if (el) {
            for (int c = 0; c < 4; c++) tma4_store(&mp.out, sb + R2 + (2 * c + h) * 8192, 0, 62 * ti, 4 * h + c, b);
            asm volatile("cp.async.bulk.commit_group;" ::: "memory");
            PT(10);
            if (h == 1) cta_done(mode);
            asm volatile("cp.async.bulk.wait_group.read 0;" ::: "memory");
        }
        PT(11);
        PG(201);
        PDUMP();
    }
}

typedef CUresult (*PFN_enc)(CUtensorMap*, CUtensorMapDataType, cuuint32_t, void*, const cuuint64_t*, const cuuint64_t*,
                            const cuuint32_t*, const cuuint32_t*, CUtensorMapInterleave, CUtensorMapSwizzle,
                            CUtensorMapL2promotion, CUtensorMapFloatOOBfill);

static void enc(PFN_enc f, CUtensorMap* m, void* base, int rank, const cuuint64_t* dims, const cuuint64_t* strides, const cuuint32_t* box) {
    cuuint32_t es[5] = {1, 1, 1, 1, 1};
    f(m, CU_TENSOR_MAP_DATA_TYPE_BFLOAT16, rank, base, dims, strides, box, es, CU_TENSOR_MAP_INTERLEAVE_NONE,
      CU_TENSOR_MAP_SWIZZLE_128B, CU_TENSOR_MAP_L2_PROMOTION_L2_256B, CU_TENSOR_MAP_FLOAT_OOB_FILL_NONE);
}
static void enc_act(PFN_enc f, CUtensorMap* m, void* base, int rows, int chunks, int trows = T_, int pitch = T_) {
    cuuint64_t dims[4] = {64, (cuuint64_t)trows, 8, (cuuint64_t)NB_};
    cuuint64_t st[3] = {1024, 128, (cuuint64_t)pitch * 1024};
    cuuint32_t box[4] = {64, (cuuint32_t)rows, (cuuint32_t)chunks, 1};
    enc(f, m, base, 4, dims, st, box);
}
static void enc_w(PFN_enc f, CUtensorMap* m, void* base, int krows, int ncols, int bk, int bc) {
    cuuint64_t dims[3] = {64, (cuuint64_t)krows, (cuuint64_t)(ncols / 64)};
    cuuint64_t st[2] = {(cuuint64_t)ncols * 2, 128};
    cuuint32_t box[3] = {64, (cuuint32_t)bk, (cuuint32_t)bc};
    enc(f, m, base, 3, dims, st, box);
}

extern "C" void kernel_launch(void* const* d_in, const int* in_sizes, int n_in, void* d_out, int out_size) {
    const bf16* x = (const bf16*)d_in[0];
    static PFN_enc fenc = nullptr;
    static void *p_xa, *p_mqk, *p_uc, *p_t1;
    static int fused = 0;
    if (!fenc) {
        void* fn = nullptr;
        cudaDriverEntryPointQueryResult qr;
        cudaGetDriverEntryPoint("cuTensorMapEncodeTiled", &fn, cudaEnableDefault, &qr);
        fenc = (PFN_enc)fn;
        cudaGetSymbolAddress(&p_xa, g_xa);
        cudaGetSymbolAddress(&p_mqk, g_mqk);
        cudaGetSymbolAddress(&p_uc, g_uc);
        cudaGetSymbolAddress(&p_t1, g_t1);
        cudaFuncSetAttribute(main_kernel, cudaFuncAttributeMaxDynamicSharedMemorySize, SMEM_BYTES);
        int dev = 0, sms = 0, occ = 0;
        cudaGetDevice(&dev);
        cudaDeviceGetAttribute(&sms, cudaDevAttrMultiProcessorCount, dev);
        cudaOccupancyMaxActiveBlocksPerMultiprocessor(&occ, main_kernel, 384, SMEM_BYTES);
        fused = sms * occ >= NCTA + 2;
    }
    Maps mp;
    enc_act(fenc, &mp.xa, (char*)p_xa + 1024, 64, 8, T_, T_ + 8);
    enc_act(fenc, &mp.xa2, (char*)p_xa + 1024, 64, 2, T_, T_ + 8);
    enc_act(fenc, &mp.xa4, (char*)p_xa + 1024, 64, 4, T_, T_ + 8);
    enc_act(fenc, &mp.xas, p_xa, 64, 1, T_ + 1, T_ + 8);
    enc_act(fenc, &mp.x, (void*)x, 64, 1);
    enc_act(fenc, &mp.out, d_out, 62, 1);
    enc_w(fenc, &mp.wup4, d_in[5], 512, 1024, 16, 4);
    enc_w(fenc, &mp.wup8, d_in[5], 512, 1024, 16, 8);
    enc_w(fenc, &mp.mqa2, p_mqk, 512, 512, 32, 2);
    enc_w(fenc, &mp.mqa4, p_mqk, 512, 512, 32, 4);
    enc_w(fenc, &mp.mqb1, p_mqk, 512, 512, 64, 1);
    enc_w(fenc, &mp.mqb2, p_mqk, 512, 512, 64, 2);
    enc_w(fenc, &mp.uc, p_uc, NCTA * 128, 512, 64, 4);
    enc_w(fenc, &mp.wq, d_in[1], 512, 512, 64, 8);
    enc_w(fenc, &mp.wk, d_in[2], 512, 512, 32, 8);
    enc_w(fenc, &mp.fa[0], d_in[3], 512, 512, 128, 1);
    enc_w(fenc, &mp.fa[1], d_in[7], 512, 512, 128, 1);
    enc_w(fenc, &mp.fa[2], p_t1, 512, 512, 128, 1);
    enc_w(fenc, &mp.fb[0], d_in[4], 512, 512, 64, 4);
    enc_w(fenc, &mp.fb[1], d_in[8], 1024, 512, 64, 4);
    enc_w(fenc, &mp.fc, p_t1, 512, 512, 64, 4);
    cudaStream_t st = cudaStreamPerThread;
    if (fused) {
        main_kernel<<<NCTA + 2, 384, SMEM_BYTES, st>>>(mp, x, (const bf16*)d_in[6], (const bf16*)d_in[5], 0);
    } else {
        main_kernel<<<NCTA + 2, 384, SMEM_BYTES, st>>>(mp, x, (const bf16*)d_in[6], (const bf16*)d_in[5], 1);
        main_kernel<<<NCTA + 2, 384, SMEM_BYTES, st>>>(mp, x, (const bf16*)d_in[6], (const bf16*)d_in[5], 2);
    }
}
```

```cpp
#include <cuda_runtime.h>
#include <cuda_bf16.h>
#include <cuda.h>
#include <stdint.h>

typedef __nv_bfloat16 bf16;

constexpr int T_ = 4000, D_ = 512, NB_ = 2;
constexpr int TPB = 65;
constexpr int NCTA = TPB * NB_;
constexpr int NKV = 63;

__device__ __align__(1024) bf16 g_xa[NB_ * (T_ + 8) * D_];
__device__ __align__(1024) bf16 g_mqk[D_ * D_];
__device__ __align__(1024) bf16 g_t1[D_ * D_];
__device__ __align__(1024) bf16 g_wepi[2 * D_ * D_];
__device__ __align__(1024) bf16 g_uc[NCTA * 128 * D_];
__device__ unsigned g_sync[8];

#define PT(i) do { if (el) asm volatile("st.shared.u32 [%0], %1;" ::"r"(sb + MISC + 2560), "r"((unsigned)clock())); } while (0)
#define PG(i)
#define PE()
#define PLM 15
#define PL(j, q) do { if ((PLM >> ((q) + (wg ? 4 : 0))) & 1) PT(0); } while (0)
#define PDUMP()

#define FENCE_AT 1
#define GO_AT 25
#define LAZY 4294967296.f
#define SU 2
#define XS_GAP 800
#define XPF 56
#define URAW 1
#define LAGA 0
#define LAGB 0
#define DPOS 1
#define KPF 0
#define XEF 0
#define SK0 0
#define TRIM 3
#define GO_LAST 20
#define PFW 1
constexpr uint32_t R0 = 0, R1 = 65536, R2 = 131072, R3 = 196608, QS = 221184, MISC = 229376;
constexpr uint32_t AT = 147456;
constexpr uint32_t SMEM_BYTES = 232448;
constexpr uint32_t B_R1 = MISC + 1856  , B_MK = MISC + 48, B_LN = MISC + 56, B_MQ = MISC + 64,
                   B_H1 = MISC + 88, B_H2 = MISC + 96, B_H3 = MISC + 104,
                   B_KV = MISC + 112, B_P = MISC + 136, B_GO = MISC + 160, B_UC = MISC + 184  ,
                   B_X = MISC + 200, CNT = MISC + 208  , SCL = MISC + 512  ,
                   LINV = MISC + 1280  , STAT = MISC + 512  ,
                   B_R2 = MISC + 1536  , B_E2 = MISC + 1696  ;

__device__ __forceinline__ uint32_t smem_u32(const void* p) { return (uint32_t)__cvta_generic_to_shared(p); }
__device__ __forceinline__ void wg_fence() { asm volatile("wgmma.fence.sync.aligned;" ::: "memory"); }
__device__ __forceinline__ void wg_commit() { asm volatile("wgmma.commit_group.sync.aligned;" ::: "memory"); }
template <int N> __device__ __forceinline__ void wg_wait() { asm volatile("wgmma.wait_group.sync.aligned %0;" ::"n"(N) : "memory"); }
__device__ __forceinline__ uint64_t dsc(uint32_t sd, uint32_t off, uint32_t lbo) {
    uint32_t lo = sd + (off >> 4) + ((lbo >> 4) << 16);
    uint64_t d;
    asm("mov.b64 %0, {%1, %2};" : "=l"(d) : "r"(lo), "r"((1024u >> 4) | (1u << 30)));
    return d;
}
__device__ __forceinline__ bool elect1() {
    uint32_t p;
    asm volatile("{\n.reg .pred p;\nelect.sync _|p, 0xffffffff;\nselp.u32 %0, 1, 0, p;\n}\n" : "=r"(p));
    return p != 0;
}
__device__ __forceinline__ void mbar_init(uint32_t bar, int cnt) { asm volatile("mbarrier.init.shared::cta.b64 [%0], %1;" ::"r"(bar), "r"(cnt) : "memory"); }
__device__ __forceinline__ void mbar_expect_tx(uint32_t bar, uint32_t bytes) { asm volatile("mbarrier.arrive.expect_tx.shared::cta.b64 _, [%0], %1;" ::"r"(bar), "r"(bytes) : "memory"); }
__device__ __forceinline__ void mbar_arrive(uint32_t bar) { asm volatile("mbarrier.arrive.shared::cta.b64 _, [%0];" ::"r"(bar) : "memory"); }
__device__ __forceinline__ void mbar_wait(uint32_t bar, uint32_t parity) {
    uint32_t ok;
#pragma unroll 1
    for (uint32_t it = 0;; ++it) {
        asm volatile("{\n.reg .pred p;\nmbarrier.try_wait.parity.shared::cta.b64 p, [%1], %2;\nselp.u32 %0, 1, 0, p;\n}\n" : "=r"(ok) : "r"(bar), "r"(parity) : "memory");
        if (ok) break;
        if (it > (1u << 20)) __trap();
    }
}
__device__ __forceinline__ bool mbar_test(uint32_t bar, uint32_t parity) {
    uint32_t ok;
    asm volatile("{\n.reg .pred p;\nmbarrier.test_wait.parity.shared::cta.b64 p, [%1], %2;\nselp.u32 %0, 1, 0, p;\n}\n" : "=r"(ok) : "r"(bar), "r"(parity) : "memory");
    return ok != 0;
}
__device__ __forceinline__ void fence_async() { asm volatile("fence.proxy.async.shared::cta;" ::: "memory"); }
__device__ __forceinline__ void fence_async_g() { asm volatile("fence.proxy.async.global;" ::: "memory"); }
__device__ __forceinline__ void bar_sync(int id, int n) { asm volatile("bar.sync %0, %1;" ::"r"(id), "r"(n) : "memory"); }
__device__ __forceinline__ void tma3(uint32_t dst, const CUtensorMap* tm, int c0, int c1, int c2, uint32_t bar) {
    asm volatile("cp.async.bulk.tensor.3d.shared::cluster.global.mbarrier::complete_tx::bytes [%0], [%1, {%3, %4, %5}], [%2];"
                 ::"r"(dst), "l"(tm), "r"(bar), "r"(c0), "r"(c1), "r"(c2) : "memory");
}
__device__ __forceinline__ void tma4(uint32_t dst, const CUtensorMap* tm, int c0, int c1, int c2, int c3, uint32_t bar) {
    asm volatile("cp.async.bulk.tensor.4d.shared::cluster.global.mbarrier::complete_tx::bytes [%0], [%1, {%3, %4, %5, %6}], [%2];"
                 ::"r"(dst), "l"(tm), "r"(bar), "r"(c0), "r"(c1), "r"(c2), "r"(c3) : "memory");
}
__device__ __forceinline__ void tma4_store(const CUtensorMap* tm, uint32_t src, int c0, int c1, int c2, int c3) {
    asm volatile("cp.async.bulk.tensor.4d.global.shared::cta.bulk_group [%0, {%2, %3, %4, %5}], [%1];"
                 ::"l"(tm), "r"(src), "r"(c0), "r"(c1), "r"(c2), "r"(c3) : "memory");
}
__device__ __forceinline__ void tma3_store(const CUtensorMap* tm, uint32_t src, int c0, int c1, int c2) {
    asm volatile("cp.async.bulk.tensor.3d.global.shared::cta.bulk_group [%0, {%2, %3, %4}], [%1];"
                 ::"l"(tm), "r"(src), "r"(c0), "r"(c1), "r"(c2) : "memory");
}
__device__ __forceinline__ void stsm4(uint32_t addr, uint32_t a, uint32_t b, uint32_t c, uint32_t d) {
    asm volatile("stmatrix.sync.aligned.m8n8.x4.shared.b16 [%0], {%1, %2, %3, %4};" ::"r"(addr), "r"(a), "r"(b), "r"(c), "r"(d) : "memory");
}
__device__ __forceinline__ void ldsm4(uint32_t addr, uint32_t (&r)[4]) {
    asm volatile("ldmatrix.sync.aligned.m8n8.x4.shared.b16 {%0, %1, %2, %3}, [%4];" : "=r"(r[0]), "=r"(r[1]), "=r"(r[2]), "=r"(r[3]) : "r"(addr) : "memory");
}
__device__ __forceinline__ void ldsm2(uint32_t addr, uint32_t (&r)[2]) {
    asm volatile("ldmatrix.sync.aligned.m8n8.x2.shared.b16 {%0, %1}, [%2];" : "=r"(r[0]), "=r"(r[1]) : "r"(addr) : "memory");
}
__device__ __forceinline__ void stg4(void* p, uint32_t a, uint32_t b, uint32_t c, uint32_t d) {
    asm volatile("st.global.v4.u32 [%0], {%1, %2, %3, %4};" ::"l"(p), "r"(a), "r"(b), "r"(c), "r"(d) : "memory");
}
__device__ __forceinline__ void hmma(float (&c)[4], uint32_t a0, uint32_t a1, uint32_t a2, uint32_t a3, uint32_t b0, uint32_t b1) {
    asm("mma.sync.aligned.m16n8k16.row.col.f32.bf16.bf16.f32 {%0, %1, %2, %3}, {%4, %5, %6, %7}, {%8, %9}, {%0, %1, %2, %3};"
        : "+f"(c[0]), "+f"(c[1]), "+f"(c[2]), "+f"(c[3]) : "r"(a0), "r"(a1), "r"(a2), "r"(a3), "r"(b0), "r"(b1));
}
__device__ __forceinline__ uint32_t pack2(float lo, float hi) {
    uint32_t r;
    asm("cvt.rn.bf16x2.f32 %0, %1, %2;" : "=r"(r) : "f"(hi), "f"(lo));
    return r;
}
__device__ __forceinline__ uint32_t pack2v(float lo, float hi) {
    uint32_t r;
    asm volatile("cvt.rn.bf16x2.f32 %0, %1, %2;" : "=r"(r) : "f"(hi), "f"(lo));
    return r;
}
__device__ __forceinline__ uint32_t bmul2(uint32_t a, uint32_t b) { uint32_t r; asm("mul.rn.bf16x2 %0, %1, %2;" : "=r"(r) : "r"(a), "r"(b)); return r; }
__device__ __forceinline__ uint32_t bfma2(uint32_t a, uint32_t b, uint32_t c) { uint32_t r; asm("fma.rn.bf16x2 %0, %1, %2, %3;" : "=r"(r) : "r"(a), "r"(b), "r"(c)); return r; }
__device__ __forceinline__ float ex2(float x) { float r; asm("ex2.approx.ftz.f32 %0, %1;" : "=f"(r) : "f"(x)); return r; }
__device__ __forceinline__ float rcp(float x) { float r; asm("rcp.approx.ftz.f32 %0, %1;" : "=f"(r) : "f"(x)); return r; }
__device__ __forceinline__ float gelu2(float x) {
    float t = fmaf(x * x, 0.044715f * 0.7978845608028654f, 0.7978845608028654f), th;
    asm("tanh.approx.f32 %0, %1;" : "=f"(th) : "f"(x * t));
    return fmaf(x, th, x);
}
__device__ __forceinline__ uint32_t ldg_v(const uint32_t* p) { uint32_t v; asm volatile("ld.global.nc.u32 %0, [%1];" : "=r"(v) : "l"(p)); return v; }
__device__ __forceinline__ uint32_t ldg_cg(const uint32_t* p) { uint32_t v; asm volatile("ld.global.cg.u32 %0, [%1];" : "=r"(v) : "l"(p) : "memory"); return v; }
__device__ __forceinline__ float lds_f32(uint32_t a) { float v; asm volatile("ld.shared.f32 %0, [%1];" : "=f"(v) : "r"(a) : "memory"); return v; }
__device__ __forceinline__ void sts_f32(uint32_t a, float v) { asm volatile("st.shared.f32 [%0], %1;" ::"r"(a), "f"(v) : "memory"); }
__device__ __forceinline__ uint32_t atom_inc_s(uint32_t a) { uint32_t v; asm volatile("atom.relaxed.cta.shared.add.u32 %0, [%1], 1;" : "=r"(v) : "r"(a) : "memory"); return v; }
__device__ __forceinline__ void lds4(uint32_t a, uint32_t* r) {
    asm volatile("ld.shared.v4.u32 {%0, %1, %2, %3}, [%4];" : "=r"(r[0]), "=r"(r[1]), "=r"(r[2]), "=r"(r[3]) : "r"(a) : "memory");
}
__device__ __forceinline__ void sts4(uint32_t a, uint32_t x, uint32_t y, uint32_t z, uint32_t t) {
    asm volatile("st.shared.v4.u32 [%0], {%1, %2, %3, %4};" ::"r"(a), "r"(x), "r"(y), "r"(z), "r"(t) : "memory");
}
__device__ __forceinline__ uint32_t bsub2(uint32_t a, uint32_t b) { uint32_t r; asm("sub.rn.bf16x2 %0, %1, %2;" : "=r"(r) : "r"(a), "r"(b)); return r; }
__device__ __forceinline__ float blo(uint32_t v) { return __uint_as_float(v << 16); }
__device__ __forceinline__ float bhi(uint32_t v) { return __uint_as_float(v & 0xffff0000u); }
__device__ __forceinline__ float bfr(float x) { return __bfloat162float(__float2bfloat16_rn(x)); }
__device__ __forceinline__ void l2_prefetch(const void* p, uint32_t bytes) { asm volatile("cp.async.bulk.prefetch.L2.global [%0], %1;" ::"l"(p), "r"(bytes) : "memory"); }
__device__ __forceinline__ void flag_add(unsigned* p) { asm volatile("red.release.gpu.global.add.u32 [%0], 1;" ::"l"(p) : "memory"); }
__device__ __forceinline__ void flag_wait(const unsigned* p, unsigned target) {
#pragma unroll 1
    for (uint32_t it = 0;; ++it) {
        unsigned v;
        asm volatile("ld.acquire.gpu.global.u32 %0, [%1];" : "=r"(v) : "l"(p) : "memory");
        if (v >= target) break;
        if (it > (1u << 20)) __trap();
    }
    fence_async_g();
}
template <int N> __device__ __forceinline__ void pin(float (&a)[N]) {
#pragma unroll
    for (int i = 0; i < N; i++) asm volatile("" : "+f"(a[i])::"memory");
}

template <int N> __device__ __forceinline__ void fresh(float (&a)[N]) {
#pragma unroll
    for (int i = 0; i < N; i++) a[i] = 0.f;
    pin(a);
}

__device__ __forceinline__ void wgmma_rs_n32_tb0(float (&d)[16], uint32_t a0, uint32_t a1, uint32_t a2, uint32_t a3, uint64_t db, int scale_d) {
    asm volatile("{\n.reg .pred p;\nsetp.ne.b32 p, %21, 0;\n"
        "wgmma.mma_async.sync.aligned.m64n32k16.f32.bf16.bf16 {%0, %1, %2, %3, %4, %5, %6, %7, %8, %9, %10, %11, %12, %13, %14, %15}, {%16, %17, %18, %19}, %20, p, 1, 1, 0;\n}\n"
        : "+f"(d[0]), "+f"(d[1]), "+f"(d[2]), "+f"(d[3]), "+f"(d[4]), "+f"(d[5]), "+f"(d[6]), "+f"(d[7]), "+f"(d[8]), "+f"(d[9]), "+f"(d[10]), "+f"(d[11]), "+f"(d[12]), "+f"(d[13]), "+f"(d[14]), "+f"(d[15])
        : "r"(a0), "r"(a1), "r"(a2), "r"(a3), "l"(db), "r"(scale_d));
}

__device__ __forceinline__ void wgmma_rs_n64_tb0(float (&d)[32], uint32_t a0, uint32_t a1, uint32_t a2, uint32_t a3, uint64_t db, int scale_d) {
    asm volatile("{\n.reg .pred p;\nsetp.ne.b32 p, %37, 0;\n"
        "wgmma.mma_async.sync.aligned.m64n64k16.f32.bf16.bf16 {%0, %1, %2, %3, %4, %5, %6, %7, %8, %9, %10, %11, %12, %13, %14, %15, %16, %17, %18, %19, %20, %21, %22, %23, %24, %25, %26, %27, %28, %29, %30, %31}, {%32, %33, %34, %35}, %36, p, 1, 1, 0;\n}\n"
        : "+f"(d[0]), "+f"(d[1]), "+f"(d[2]), "+f"(d[3]), "+f"(d[4]), "+f"(d[5]), "+f"(d[6]), "+f"(d[7]), "+f"(d[8]), "+f"(d[9]), "+f"(d[10]), "+f"(d[11]), "+f"(d[12]), "+f"(d[13]), "+f"(d[14]), "+f"(d[15]), "+f"(d[16]), "+f"(d[17]), "+f"(d[18]), "+f"(d[19]), "+f"(d[20]), "+f"(d[21]), "+f"(d[22]), "+f"(d[23]), "+f"(d[24]), "+f"(d[25]), "+f"(d[26]), "+f"(d[27]), "+f"(d[28]), "+f"(d[29]), "+f"(d[30]), "+f"(d[31])
        : "r"(a0), "r"(a1), "r"(a2), "r"(a3), "l"(db), "r"(scale_d));
}

__device__ __forceinline__ void wgmma_ss_n128_tb1(float (&d)[64], uint64_t da, uint64_t db, int scale_d) {
    asm volatile("{\n.reg .pred p;\nsetp.ne.b32 p, %66, 0;\n"
        "wgmma.mma_async.sync.aligned.m64n128k16.f32.bf16.bf16 {%0, %1, %2, %3, %4, %5, %6, %7, %8, %9, %10, %11, %12, %13, %14, %15, %16, %17, %18, %19, %20, %21, %22, %23, %24, %25, %26, %27, %28, %29, %30, %31, %32, %33, %34, %35, %36, %37, %38, %39, %40, %41, %42, %43, %44, %45, %46, %47, %48, %49, %50, %51, %52, %53, %54, %55, %56, %57, %58, %59, %60, %61, %62, %63}, %64, %65, p, 1, 1, 0, 1;\n}\n"
        : "+f"(d[0]), "+f"(d[1]), "+f"(d[2]), "+f"(d[3]), "+f"(d[4]), "+f"(d[5]), "+f"(d[6]), "+f"(d[7]), "+f"(d[8]), "+f"(d[9]), "+f"(d[10]), "+f"(d[11]), "+f"(d[12]), "+f"(d[13]), "+f"(d[14]), "+f"(d[15]), "+f"(d[16]), "+f"(d[17]), "+f"(d[18]), "+f"(d[19]), "+f"(d[20]), "+f"(d[21]), "+f"(d[22]), "+f"(d[23]), "+f"(d[24]), "+f"(d[25]), "+f"(d[26]), "+f"(d[27]), "+f"(d[28]), "+f"(d[29]), "+f"(d[30]), "+f"(d[31]), "+f"(d[32]), "+f"(d[33]), "+f"(d[34]), "+f"(d[35]), "+f"(d[36]), "+f"(d[37]), "+f"(d[38]), "+f"(d[39]), "+f"(d[40]), "+f"(d[41]), "+f"(d[42]), "+f"(d[43]), "+f"(d[44]), "+f"(d[45]), "+f"(d[46]), "+f"(d[47]), "+f"(d[48]), "+f"(d[49]), "+f"(d[50]), "+f"(d[51]), "+f"(d[52]), "+f"(d[53]), "+f"(d[54]), "+f"(d[55]), "+f"(d[56]), "+f"(d[57]), "+f"(d[58]), "+f"(d[59]), "+f"(d[60]), "+f"(d[61]), "+f"(d[62]), "+f"(d[63])
        : "l"(da), "l"(db), "r"(scale_d));
}

__device__ __forceinline__ void wgmma_ss_n256_tb1(float (&d)[128], uint64_t da, uint64_t db, int scale_d) {
    asm volatile("{\n.reg .pred p;\nsetp.ne.b32 p, %130, 0;\n"
        "wgmma.mma_async.sync.aligned.m64n256k16.f32.bf16.bf16 {%0, %1, %2, %3, %4, %5, %6, %7, %8, %9, %10, %11, %12, %13, %14, %15, %16, %17, %18, %19, %20, %21, %22, %23, %24, %25, %26, %27, %28, %29, %30, %31, %32, %33, %34, %35, %36, %37, %38, %39, %40, %41, %42, %43, %44, %45, %46, %47, %48, %49, %50, %51, %52, %53, %54, %55, %56, %57, %58, %59, %60, %61, %62, %63, %64, %65, %66, %67, %68, %69, %70, %71, %72, %73, %74, %75, %76, %77, %78, %79, %80, %81, %82, %83, %84, %85, %86, %87, %88, %89, %90, %91, %92, %93, %94, %95, %96, %97, %98, %99, %100, %101, %102, %103, %104, %105, %106, %107, %108, %109, %110, %111, %112, %113, %114, %115, %116, %117, %118, %119, %120, %121, %122, %123, %124, %125, %126, %127}, %128, %129, p, 1, 1, 0, 1;\n}\n"
        : "+f"(d[0]), "+f"(d[1]), "+f"(d[2]), "+f"(d[3]), "+f"(d[4]), "+f"(d[5]), "+f"(d[6]), "+f"(d[7]), "+f"(d[8]), "+f"(d[9]), "+f"(d[10]), "+f"(d[11]), "+f"(d[12]), "+f"(d[13]), "+f"(d[14]), "+f"(d[15]), "+f"(d[16]), "+f"(d[17]), "+f"(d[18]), "+f"(d[19]), "+f"(d[20]), "+f"(d[21]), "+f"(d[22]), "+f"(d[23]), "+f"(d[24]), "+f"(d[25]), "+f"(d[26]), "+f"(d[27]), "+f"(d[28]), "+f"(d[29]), "+f"(d[30]), "+f"(d[31]), "+f"(d[32]), "+f"(d[33]), "+f"(d[34]), "+f"(d[35]), "+f"(d[36]), "+f"(d[37]), "+f"(d[38]), "+f"(d[39]), "+f"(d[40]), "+f"(d[41]), "+f"(d[42]), "+f"(d[43]), "+f"(d[44]), "+f"(d[45]), "+f"(d[46]), "+f"(d[47]), "+f"(d[48]), "+f"(d[49]), "+f"(d[50]), "+f"(d[51]), "+f"(d[52]), "+f"(d[53]), "+f"(d[54]), "+f"(d[55]), "+f"(d[56]), "+f"(d[57]), "+f"(d[58]), "+f"(d[59]), "+f"(d[60]), "+f"(d[61]), "+f"(d[62]), "+f"(d[63]), "+f"(d[64]), "+f"(d[65]), "+f"(d[66]), "+f"(d[67]), "+f"(d[68]), "+f"(d[69]), "+f"(d[70]), "+f"(d[71]), "+f"(d[72]), "+f"(d[73]), "+f"(d[74]), "+f"(d[75]), "+f"(d[76]), "+f"(d[77]), "+f"(d[78]), "+f"(d[79]), "+f"(d[80]), "+f"(d[81]), "+f"(d[82]), "+f"(d[83]), "+f"(d[84]), "+f"(d[85]), "+f"(d[86]), "+f"(d[87]), "+f"(d[88]), "+f"(d[89]), "+f"(d[90]), "+f"(d[91]), "+f"(d[92]), "+f"(d[93]), "+f"(d[94]), "+f"(d[95]), "+f"(d[96]), "+f"(d[97]), "+f"(d[98]), "+f"(d[99]), "+f"(d[100]), "+f"(d[101]), "+f"(d[102]), "+f"(d[103]), "+f"(d[104]), "+f"(d[105]), "+f"(d[106]), "+f"(d[107]), "+f"(d[108]), "+f"(d[109]), "+f"(d[110]), "+f"(d[111]), "+f"(d[112]), "+f"(d[113]), "+f"(d[114]), "+f"(d[115]), "+f"(d[116]), "+f"(d[117]), "+f"(d[118]), "+f"(d[119]), "+f"(d[120]), "+f"(d[121]), "+f"(d[122]), "+f"(d[123]), "+f"(d[124]), "+f"(d[125]), "+f"(d[126]), "+f"(d[127])
        : "l"(da), "l"(db), "r"(scale_d));
}

__device__ __forceinline__ void wgmma_ss_n32_tb0(float (&d)[16], uint64_t da, uint64_t db, int scale_d) {
    asm volatile("{\n.reg .pred p;\nsetp.ne.b32 p, %18, 0;\n"
        "wgmma.mma_async.sync.aligned.m64n32k16.f32.bf16.bf16 {%0, %1, %2, %3, %4, %5, %6, %7, %8, %9, %10, %11, %12, %13, %14, %15}, %16, %17, p, 1, 1, 0, 0;\n}\n"
        : "+f"(d[0]), "+f"(d[1]), "+f"(d[2]), "+f"(d[3]), "+f"(d[4]), "+f"(d[5]), "+f"(d[6]), "+f"(d[7]), "+f"(d[8]), "+f"(d[9]), "+f"(d[10]), "+f"(d[11]), "+f"(d[12]), "+f"(d[13]), "+f"(d[14]), "+f"(d[15])
        : "l"(da), "l"(db), "r"(scale_d));
}

__device__ __forceinline__ void wgmma_ss_n64_tb0(float (&d)[32], uint64_t da, uint64_t db, int scale_d) {
    asm volatile("{\n.reg .pred p;\nsetp.ne.b32 p, %34, 0;\n"
        "wgmma.mma_async.sync.aligned.m64n64k16.f32.bf16.bf16 {%0, %1, %2, %3, %4, %5, %6, %7, %8, %9, %10, %11, %12, %13, %14, %15, %16, %17, %18, %19, %20, %21, %22, %23, %24, %25, %26, %27, %28, %29, %30, %31}, %32, %33, p, 1, 1, 0, 0;\n}\n"
        : "+f"(d[0]), "+f"(d[1]), "+f"(d[2]), "+f"(d[3]), "+f"(d[4]), "+f"(d[5]), "+f"(d[6]), "+f"(d[7]), "+f"(d[8]), "+f"(d[9]), "+f"(d[10]), "+f"(d[11]), "+f"(d[12]), "+f"(d[13]), "+f"(d[14]), "+f"(d[15]), "+f"(d[16]), "+f"(d[17]), "+f"(d[18]), "+f"(d[19]), "+f"(d[20]), "+f"(d[21]), "+f"(d[22]), "+f"(d[23]), "+f"(d[24]), "+f"(d[25]), "+f"(d[26]), "+f"(d[27]), "+f"(d[28]), "+f"(d[29]), "+f"(d[30]), "+f"(d[31])
        : "l"(da), "l"(db), "r"(scale_d));
}

struct Maps {
    CUtensorMap xa, xa2, xa4, xas, wup4, wup8, mqa2, mqa4, mqb1, mqb2, uc, x, out, wq, wk, fa[3], fb[2], fc;
};

__device__ __forceinline__ uint64_t mkd(uint32_t lo) {
    uint64_t d;
    asm("mov.b64 %0, {%1, %2};" : "=l"(d) : "r"(lo), "r"((1024u >> 4) | (1u << 30)));
    return d;
}
__device__ __forceinline__ void bulk_ld(uint32_t dst, const void* src, uint32_t bytes, uint32_t bar) {
    asm volatile("cp.async.bulk.shared::cluster.global.mbarrier::complete_tx::bytes [%0], [%1], %2, [%3];" ::"r"(dst), "l"(src), "r"(bytes), "r"(bar) : "memory");
}
__device__ __forceinline__ void bulk_st(void* dst, uint32_t src, uint32_t bytes) {
    asm volatile("cp.async.bulk.global.shared::cta.bulk_group [%0], [%1], %2;" ::"l"(dst), "r"(src), "r"(bytes) : "memory");
}
__device__ __forceinline__ void ring_ld(uint32_t sb, uint32_t slot8, int n) {
    mbar_expect_tx(sb + B_R2 + slot8, 8192);
    bulk_ld(sb + R1 + slot8 * 1024, (const char*)g_wepi + n * 8192, 8192, sb + B_R2 + slot8);
}

__device__ __forceinline__ void ring_half(uint32_t sb, uint32_t slot8, uint32_t hoff, const CUtensorMap* tm, int c1, int c2) {
    mbar_expect_tx(sb + B_R1 + slot8, 8192);
    tma3(sb + slot8 * 2048 + hoff, tm, 0, c1, c2, sb + B_R1 + slot8);
}
__device__ __forceinline__ void ring_full(uint32_t sb, uint32_t slot8, const CUtensorMap* tm, int c1, int c2) {
    mbar_expect_tx(sb + B_R1 + slot8, 16384);
    mbar_arrive(sb + B_R1 + slot8);
    tma3(sb + slot8 * 2048, tm, 0, c1, c2, sb + B_R1 + slot8);
}
__device__ __forceinline__ void cta_done(int mode) {
    if (mode == 0 && atomicAdd(&g_sync[4], 1) == NCTA + 1) {
#pragma unroll
        for (int i = 0; i < 5; i++) g_sync[i] = 0;
    }
}

__device__ __forceinline__ void fold_cta(const Maps& mp, uint32_t sb, int mode) {
    constexpr uint32_t F_FULL = MISC, F_EMPTY = MISC + 32, F_T1 = MISC + 64, STG = 49152, FOUT = 3 * STG;
    const int tid = threadIdx.x, f = blockIdx.x - NCTA;
    if (mode == 2) return;
    if (tid == 0) {
        for (int i = 0; i < 3; i++) { mbar_init(sb + F_FULL + 8 * i, 1); mbar_init(sb + F_EMPTY + 8 * i, 2); }
        mbar_init(sb + F_T1, 2);
        asm volatile("fence.mbarrier_init.release.cluster;" ::: "memory");
        fence_async();
    }
    __syncthreads();
    const int wg = __shfl_sync(0xffffffffu, tid >> 7, 0);
    int st = 0, ph = 0;
    if (wg == 0) {
        if (tid == 0) {
#pragma unroll 1
            for (int it = 0; it < 96; it++) {
                const int p = it >> 3, kc = it & 7, job = p >> 2;
                if (it == 64) mbar_wait(sb + F_T1, 0);
                mbar_wait(sb + F_EMPTY + 8 * st, ph ^ 1);
                mbar_expect_tx(sb + F_FULL + 8 * st, STG);
                tma3(sb + st * STG, &mp.fa[job], 0, 256 * f + 128 * ((p >> 1) & 1), kc, sb + F_FULL + 8 * st);
                tma3(sb + st * STG + 16384, &mp.fb[job != 0], 0, 64 * kc + (job == 1 ? 512 : 0), 4 * (p & 1), sb + F_FULL + 8 * st);
                if (++st == 3) { st = 0; ph ^= 1; }
            }
        }
        return;
    }
    const int h = wg - 1, lane = tid & 31, w = (tid >> 5) & 3;
    const uint32_t sd = (sb & 0x3FFFF) >> 4;
    const bool el = (tid & 127) == 0;
#pragma unroll 1
    for (int p = 0; p < 12; p++) {
        float acc[128];
        fresh(acc);
#pragma unroll 1
        for (int kc = 0; kc < 8; kc++) {
            mbar_wait(sb + F_FULL + 8 * st, ph);
            wg_fence();
#pragma unroll
            for (int kk = 0; kk < 4; kk++)
                wgmma_ss_n256_tb1(acc, dsc(sd, st * STG + h * 8192 + kk * 32, 16), dsc(sd, st * STG + 16384 + kk * 2048, 8192), 1);
            wg_commit();
            wg_wait<0>();
            if (el) mbar_arrive(sb + F_EMPTY + 8 * st);
            if (++st == 3) { st = 0; ph ^= 1; }
        }
        pin(acc);
        const int job = p >> 2;
        if (el) {
            asm volatile("cp.async.bulk.wait_group 0;" ::: "memory");
            if (p == 4) { fence_async_g(); mbar_arrive(sb + F_T1); }
        }
        bar_sync(3 + h, 128);
        uint32_t r = 16 * w + (lane & 7) + ((lane >> 3) & 1) * 8;
        const float fs = job == 1 ? 0.5f : 1.f;
        if (job == 1) r = (r & ~31) | (((r >> 1) & 3) << 3) | (((r >> 3) & 3) << 1) | (r & 1);
        const uint32_t oa = sb + FOUT + h * 32768 + r * 128 + ((((lane >> 4) ^ r) & 7) << 4);
#pragma unroll
        for (int i = 0; i < 16; i++)
            stsm4((oa ^ ((i & 3) << 5)) + (i >> 2) * 8192, pack2(acc[8 * i] * fs, acc[8 * i + 1] * fs), pack2(acc[8 * i + 2] * fs, acc[8 * i + 3] * fs),
                  pack2(acc[8 * i + 4] * fs, acc[8 * i + 5] * fs), pack2(acc[8 * i + 6] * fs, acc[8 * i + 7] * fs));
        fence_async();
        bar_sync(3 + h, 128);
        if (el) {
            const int row0 = 256 * f + 128 * ((p >> 1) & 1) + 64 * h + (job == 1 ? 512 : 0);
            if (job == 0) tma3_store(&mp.fc, sb + FOUT + h * 32768, 0, row0, 4 * (p & 1));
            else {
#pragma unroll 1
                for (int i = 0; i < 16; i++)
                    bulk_st((char*)g_wepi + (row0 / 8 + 2 * (i & 3) + (p & 1)) * 8192 + (i >> 2) * 2048, sb + FOUT + h * 32768 + i * 2048, 2048);
            }
            asm volatile("cp.async.bulk.commit_group;" ::: "memory");
        }
    }
    if (el) {
        asm volatile("cp.async.bulk.wait_group 0;" ::: "memory");
        fence_async_g();
        if (mode == 0) flag_add(&g_sync[3]);
    }
    bar_sync(2, 256);
    if (tid == 128) cta_done(mode);
}

__global__ void __launch_bounds__(384, 1) main_kernel(const __grid_constant__ Maps mp, const bf16* __restrict__ x, const bf16* __restrict__ dw, const bf16* wup, const int mode) {
    extern __shared__ __align__(1024) uint8_t smem[];
    const uint32_t sb = smem_u32(smem);
    const int tid = threadIdx.x;
    PE();
    if (blockIdx.x >= NCTA) { fold_cta(mp, sb, mode); return; }
    const int b = blockIdx.x / TPB, ti = blockIdx.x % TPB;
    const int piece = blockIdx.x & 127;
    const int wg = __shfl_sync(0xffffffffu, tid >> 7, 0);
    const int lane = tid & 31, w = (tid >> 5) & 3;
    const bool w0 = __shfl_sync(0xffffffffu, w, 0) == 0;
    const uint32_t sd = (sb & 0x3FFFF) >> 4;
    const uint32_t adA = sd + (AT >> 4) + (1u << 16);
    const uint32_t bd0 = sd;
    const uint32_t bd2k = bd0 + ((2048u >> 4) << 16);
    const bool el = (tid & 127) == 0;
    const uint32_t lrow = 16 * w + (lane & 7) + ((lane >> 3) & 1) * 8;
    const uint32_t loff = lrow * 128 + ((((lane >> 4) ^ lrow) & 7) << 4);
    const int r0 = 16 * w + (lane >> 2);

    if (wg == 0) {
        asm volatile("setmaxnreg.inc.sync.aligned.u32 184;");
        uint32_t q[112];
        PG(206);
        if (tid == 0) {
            mbar_init(sb + B_MK, 1);
            for (int i = 0; i < 9; i++) mbar_init(sb + B_R1 + 8 * i, 2);
            for (int i = 0; i < 5; i++) asm volatile("st.shared.u32 [%0], 0;" ::"r"(sb + CNT + 4 * i) : "memory");
        } else if (tid == 32) {
            mbar_init(sb + B_LN, 1); mbar_init(sb + B_MQ, 1);
            mbar_init(sb + B_H1, 2); mbar_init(sb + B_H2, 1); mbar_init(sb + B_H3, 2);
            for (int i = 0; i < 3; i++) { mbar_init(sb + B_KV + 8 * i, 2); mbar_init(sb + B_P + 8 * i, 4); mbar_init(sb + B_GO + 8 * i, 4); }
            mbar_init(sb + B_UC, 1); mbar_init(sb + B_UC + 8, 1); mbar_init(sb + B_X, 8);
        } else if (tid == 64) {
            for (int i = 0; i < 20; i++) mbar_init(sb + B_R2 + 8 * i, 1);
        } else if (tid == 96) {
            for (int i = 0; i < 20; i++) mbar_init(sb + B_E2 + 8 * i, 4);
        }
        if (lane == 0) {
            asm volatile("fence.mbarrier_init.release.cluster;" ::: "memory");
            fence_async();
        }
        PG(207);
        __syncwarp();
        if (SU != 2) asm volatile("bar.arrive 5, 384;" ::: "memory");
        if (tid == 0) {
            mbar_expect_tx(sb + B_MK, 65536 + 32768);
            tma3(sb + 16384, &mp.wq, 0, 64 * (piece >> 4), 0, sb + B_MK);
            tma3(sb + 81920, &mp.wk, 0, 32 * (piece & 15), 0, sb + B_MK);
            for (int i = 0; i < 14; i++) mbar_arrive(sb + B_R1 + 8 * (i >> 1));
            if (mode != 1) {
                ring_full(sb, 56, &mp.wup8, 0, 8);
                ring_full(sb, 64, &mp.wup8, 16, 8);
                ring_full(sb, 0, &mp.wup8, 32, 8);
            }
        }
        PG(208);
        bar_sync(1, 128);
        if (SU == 2) asm volatile("bar.arrive 5, 384;" ::: "memory");
        PT(0);
        PG(200);
        {
            float mq[16];
            fresh(mq);
            mbar_wait(sb + B_MK, 0);
            PT(1);
            if (tid == 32) l2_prefetch((const char*)wup + piece * 8192, 8192);
            wg_fence();
#pragma unroll 1
            for (int c = 0; c < 8; c++)
#pragma unroll
                for (int kk = 0; kk < 4; kk++)
                    wgmma_ss_n32_tb0(mq, dsc(sd, 16384 + c * 8192 + kk * 32, 16), dsc(sd, 81920 + c * 4096 + kk * 32, 16), 1);
            wg_commit();
            wg_wait<0>();
            if (mode != 1 && w0 && elect1()) {
#pragma unroll 1
                for (int i = 1; i < 7; i++) ring_full(sb, 8 * i, &mp.wup8, 32 + 16 * i, 8);
            }
            pin(mq);
            uint32_t* c = reinterpret_cast<uint32_t*>(g_mqk + (64 * (piece >> 4) + r0) * D_ + 32 * (piece & 15) + 2 * (lane & 3));
#pragma unroll
            for (int n = 0; n < 4; n++) { c[4 * n] = pack2(mq[4 * n], mq[4 * n + 1]); c[4 * n + 4 * D_] = pack2(mq[4 * n + 2], mq[4 * n + 3]); }
            fence_async_g();
            bar_sync(1, 128);
            if (el) {
                if (mode == 0) flag_add(&g_sync[2]);
                if (mode == 0) flag_wait(&g_sync[2], NCTA);
                mbar_arrive(sb + B_MQ);
                PG(203);
                PT(12);
                mbar_wait(sb + B_LN, 0);
#pragma unroll 1
                for (int c = 0; c < 8; c++) {
                    tma4_store(&mp.xas, sb + AT + c * 8192, 0, 62 * ti, c, b);
                    const unsigned t0 = (unsigned)clock();
                    while (c < 7 && (unsigned)clock() - t0 < XS_GAP) __nanosleep(20);
                }
                asm volatile("cp.async.bulk.commit_group;" ::: "memory");
                if (mode == 1) asm volatile("cp.async.bulk.wait_group 0;" ::: "memory");
            }
            PT(13);
            if (mode == 1) return;
        }
        mbar_wait(sb + B_H1, 0);
        PT(2);
        uint32_t slot8 = 24, par = 0, prev8 = 0, prev2 = 0;
        auto adv = [&]() { prev2 = prev8; prev8 = slot8; slot8 += 8; if (slot8 == 72) { slot8 = 0; par ^= 1; } };
        {
            float acc[128];
            fresh(acc);
            auto step = [&](int i) {
                const uint32_t aa = adA + (i >> 1) * 512 + (i & 1) * 4, bb = bd0 + ((4096u >> 4) << 16) + slot8 * 128;
                wg_fence();
                wgmma_ss_n256_tb1(acc, mkd(aa), mkd(bb), 1);
                wgmma_ss_n256_tb1(acc, mkd(aa + 2), mkd(bb + 128), 1);
                wg_commit();
                wg_wait<1 + LAGA>();
            };
#pragma unroll 1
            for (int i = 0; i < 8 + LAGA; i++) {
                mbar_wait(sb + B_R1 + slot8, par);
                step(i);
                if (i > LAGA && w0 && elect1()) ring_full(sb, LAGA ? prev2 : prev8, &mp.mqa4, 32 * (i - LAGA) + 256, 4);
                adv();
            }
#pragma unroll 1
            for (int i = 8 + LAGA; i < 16; i++) {
                mbar_wait(sb + B_R1 + slot8, par);
                if (i == 15 && el) mbar_arrive(sb + B_H2);
                step(i);
                if (w0 && elect1()) ring_full(sb, LAGA ? prev2 : prev8, &mp.wup8, 16 * (i - LAGA) - 128, 0);
                adv();
            }
            if (LAGA) {
                wg_wait<1>();
                if (w0 && elect1()) ring_full(sb, prev2, &mp.wup8, 112, 0);
            }
            wg_wait<0>();
            if (w0 && elect1()) ring_full(sb, prev8, &mp.wup8, 128, 0);
            pin(acc);
            PT(3);
#pragma unroll
            for (int kk = 0; kk < 4; kk++)
                stsm4((sb + QS + loff) ^ (kk << 5), pack2(acc[96 + 8 * kk], acc[97 + 8 * kk]), pack2(acc[98 + 8 * kk], acc[99 + 8 * kk]),
                      pack2(acc[100 + 8 * kk], acc[101 + 8 * kk]), pack2(acc[102 + 8 * kk], acc[103 + 8 * kk]));
            fence_async();
#pragma unroll
            for (int i = 47; i >= 0; i--) q[64 + i] = pack2v(acc[2 * i], acc[2 * i + 1]);
        }
        if (el) {
            asm volatile("cp.async.bulk.wait_group 0;" ::: "memory");
            if (mode == 0) {
                fence_async_g();
                flag_add(&g_sync[b]);
                flag_wait(&g_sync[b], TPB);
            }
        }
        __syncwarp();
        mbar_wait(sb + B_H3, 0);
        PT(4);
        slot8 = 48; par = 1;
#pragma unroll
        for (int half = 0; half < 2; half++) {
            float acc[64];
            fresh(acc);
            auto step = [&](int m) {
                const uint32_t aa = adA + m * 512, bb = bd0 + ((8192u >> 4) << 16) + slot8 * 128;
                mbar_wait(sb + B_R1 + slot8, par);
                wg_fence();
#pragma unroll
                for (int kk = 0; kk < 4; kk++) wgmma_ss_n128_tb1(acc, mkd(aa + 2 * kk), mkd(bb + 128 * kk), 1);
                wg_commit();
                wg_wait<1 + LAGB>();
            };
#pragma unroll 1
            for (int m = 0; m < 8; m++) {
                step(m);
                if (m > LAGB && w0 && elect1()) {
                    if (half == 0) ring_full(sb, LAGB ? prev2 : prev8, &mp.mqb2, 64 * (m - LAGB), 2);
                    else if (m < 4 + LAGB) tma4(sb + (LAGB ? prev2 : prev8) * 2048, &mp.xa2, 0, 0, 2 * (m - LAGB), b, sb + B_KV + 8);
                }
                adv();
            }
            if (LAGB && half == 0) {
                wg_wait<1>();
                if (w0 && elect1()) ring_full(sb, prev2, &mp.mqb2, 448, 2);
            }
            wg_wait<0>();
            if (w0 && elect1()) {
                if (half == 0) {
                    mbar_expect_tx(sb + B_KV + 8, 65536);
                    for (int i = 0; i < 3; i++) mbar_arrive(sb + B_KV + 8 * i);
                    tma4(sb + prev8 * 2048, &mp.xa2, 0, 0, 0, b, sb + B_KV + 8);
                } else {
                    mbar_expect_tx(sb + B_KV + 16, 65536);
                    tma4(sb + R2, &mp.xa, 0, 64, 0, b, sb + B_KV + 16);
                    mbar_expect_tx(sb + B_KV, 65536);
                    tma4(sb + R0, &mp.xa, 0, 128, 0, b, sb + B_KV);
                }
            }
            pin(acc);
#pragma unroll
            for (int i = 31; i >= 0; i--) q[32 * half + i] = pack2v(acc[2 * i], acc[2 * i + 1]);
        }
        bar_sync(1, 128);
        PT(5);

        const float CS = 0.04419417382415922f * 1.4426950408889634f;
        float m0 = -INFINITY, m1 = -INFINITY, l0 = 0.f, l1 = 0.f;
        int s = 0, sn = 1, ph = 0;
        float S[32];
        const bool l0w = lane == 0, q0 = (lane & 3) == 0;
#pragma unroll 1
        for (int j = -1;; j++) {
            if (j >= 0) {
                PL(j, 1);
                if (j == NKV - 1) {
#pragma unroll
                    for (int i = (T_ - 64 * (NKV - 1)) / 2; i < 32; i++) asm volatile("mov.b32 %0, 0xff800000;" : "=f"(S[i]));
                }
                const bool kv = mbar_test(sb + B_KV + sn * 8, ph);
                const uint32_t pb = sb + R3 + (s == 0 ? 2 : s - 1) * 8192;
                float a0 = 0.f, a1 = 0.f, sc0 = 1.f, sc1 = 1.f;
                auto expo = [&]() {
                    const float n0 = -m0 * CS, n1 = -m1 * CS;
                    a0 = 0.f; a1 = 0.f;
#pragma unroll
                    for (int kk = 0; kk < 4; kk++) {
                        float p[8];
#pragma unroll
                        for (int e = 0; e < 8; e++) p[e] = ex2(fmaf(S[8 * kk + e], CS, (e & 2) ? n1 : n0));
                        a0 += (p[0] + p[1]) + (p[4] + p[5]);
                        a1 += (p[2] + p[3]) + (p[6] + p[7]);
                        stsm4((pb + loff) ^ (kk << 5), pack2(p[0], p[1]), pack2(p[2], p[3]), pack2(p[4], p[5]), pack2(p[6], p[7]));
                    }
                };
                if (j > 0 || !SK0) expo();
                if ((SK0 && j == 0) || __any_sync(0xffffffffu, !(a0 <= LAZY) || !(a1 <= LAZY))) {
                    float x0 = m0, x1 = m1;
#pragma unroll
                    for (int n = 0; n < 8; n++) { x0 = fmaxf(x0, fmaxf(S[4 * n], S[4 * n + 1])); x1 = fmaxf(x1, fmaxf(S[4 * n + 2], S[4 * n + 3])); }
                    x0 = fmaxf(x0, __shfl_xor_sync(0xffffffffu, x0, 1));
                    x1 = fmaxf(x1, __shfl_xor_sync(0xffffffffu, x1, 1));
                    x0 = fmaxf(x0, __shfl_xor_sync(0xffffffffu, x0, 2));
                    x1 = fmaxf(x1, __shfl_xor_sync(0xffffffffu, x1, 2));
                    sc0 = ex2((m0 - x0) * CS); sc1 = ex2((m1 - x1) * CS);
                    m0 = x0; m1 = x1;
                    expo();
                }
                if (q0) { sts_f32(sb + SCL + s * 256 + r0 * 4, sc0); sts_f32(sb + SCL + s * 256 + r0 * 4 + 32, sc1); }
                __syncwarp();
                if (l0w) mbar_arrive(sb + B_P + s * 8);
                l0 = fmaf(l0, sc0, a0); l1 = fmaf(l1, sc1, a1);
                PL(j, 2);
                if (j == NKV - 1) break;
                if (!kv) mbar_wait(sb + B_KV + sn * 8, ph);
            } else {
                mbar_wait(sb + B_KV + 8, 0);
            }
            const uint32_t kd = sd + sn * 4096;
            if (TRIM & 2 && j == NKV - 2) {
                float Sn[16];
                wg_fence();
#pragma unroll
                for (int kk = 0; kk < 28; kk++) {
                    wgmma_rs_n32_tb0(Sn, q[4 * kk], q[4 * kk + 1], q[4 * kk + 2], q[4 * kk + 3], dsc(kd, (kk >> 2) * 8192 + (kk & 3) * 32, 16), kk > 0);
                    if (kk == FENCE_AT) { fence_async(); __syncwarp(); }
                    if (kk == GO_LAST && l0w) mbar_arrive(sb + B_GO + s * 8);
                }
#pragma unroll
                for (int kk = 0; kk < 4; kk++)
                    wgmma_ss_n32_tb0(Sn, dsc(sd, QS + kk * 32, 16), dsc(kd, 7 * 8192 + kk * 32, 16), 1);
                wg_commit();
                wg_wait<0>();
                pin(Sn);
#pragma unroll
                for (int i = 0; i < 16; i++) S[i] = Sn[i];
            } else {
            float Sn[32];
            wg_fence();
#pragma unroll
            for (int kk = 0; kk < 28; kk++) {
                wgmma_rs_n64_tb0(Sn, q[4 * kk], q[4 * kk + 1], q[4 * kk + 2], q[4 * kk + 3], dsc(kd, (kk >> 2) * 8192 + (kk & 3) * 32, 16), kk > 0);
                if (kk == FENCE_AT) { fence_async(); __syncwarp(); }
                if (kk == GO_AT) { PL(j, 3); if (j >= 0 && l0w) mbar_arrive(sb + B_GO + s * 8); }
            }
#pragma unroll
            for (int kk = 0; kk < 4; kk++)
                wgmma_ss_n64_tb0(Sn, dsc(sd, QS + kk * 32, 16), dsc(kd, 7 * 8192 + kk * 32, 16), 1);
            wg_commit();
            PL(j, 0);
            wg_wait<0>();
            pin(Sn);
#pragma unroll
            for (int i = 0; i < 32; i++) S[i] = Sn[i];
            }
            s = sn;
            if (++sn == 3) sn = 0;
            if (sn == 1) ph ^= 1;
        }
        l0 += __shfl_xor_sync(0xffffffffu, l0, 1); l1 += __shfl_xor_sync(0xffffffffu, l1, 1);
        l0 += __shfl_xor_sync(0xffffffffu, l0, 2); l1 += __shfl_xor_sync(0xffffffffu, l1, 2);
        if (q0) { sts_f32(sb + LINV + r0 * 4, rcp(l0)); sts_f32(sb + LINV + r0 * 4 + 32, rcp(l1)); }
        fence_async();
        __syncwarp();
        if (l0w) {
            mbar_arrive(sb + B_GO + s * 8);
            uint32_t slot8 = 8 * w, par = 0;
#pragma unroll 1
            for (int n = 20 + w; n < 136; n += 4) {
                mbar_wait(sb + B_E2 + slot8, par);
                if (n < 128) ring_ld(sb, slot8, n);
                else {
                    mbar_expect_tx(sb + B_X, 8192);
                    tma4(sb + R1 + slot8 * 1024, &mp.x, 0, 62 * ti, n - 128, b, sb + B_X);
                }
                slot8 += 32;
                if (slot8 >= 160) { slot8 -= 160; par ^= 1; }
            }
        }
        PDUMP();
    } else {
        asm volatile("setmaxnreg.dec.sync.aligned.u32 160;");
        const int h = wg - 1;
        uint32_t v[4][8], v2[4][8];
        if (SU != 0) bar_sync(5, 384);
        PG(206);
#pragma unroll
        for (int i = 0; i < 8; i++) {
            const int t = 62 * ti - 1 + 32 * (i >> 2) + 16 * h + 4 * w + (i & 3);
            const uint4* p = reinterpret_cast<const uint4*>(x + ((size_t)b * T_ + t) * D_) + lane;
            uint32_t* d = i < 4 ? v[i & 3] : v2[i & 3];
#pragma unroll
            for (int c = 0; c < 2; c++)
                asm volatile("{\n.reg .pred p;\nsetp.lt.u32 p, %5, %6;\nmov.b32 %0, 0;\nmov.b32 %1, 0;\nmov.b32 %2, 0;\nmov.b32 %3, 0;\n"
                             "@p ld.global.nc.v4.u32 {%0, %1, %2, %3}, [%4];\n}\n"
                             : "=r"(d[4 * c]), "=r"(d[4 * c + 1]), "=r"(d[4 * c + 2]), "=r"(d[4 * c + 3]) : "l"(p + 32 * c), "r"(t), "n"(T_));
        }
#pragma unroll 1
        for (int bt = 0; bt < 2; bt++) {
            PT(bt ? 13 : 0);
            float a[8];
            const uint32_t la = sb + AT + (lane >> 3) * 8192 + (32 * bt + 16 * h + 4 * w) * 128 + (((lane & 7) ^ ((w & 1) * 4)) << 4);
            const bool b4 = lane & 16, b3 = lane & 8, b2 = lane & 4;
#pragma unroll
            for (int r = 0; r < 4; r++) {
                float c[4] = {0.f, 0.f, 0.f, 0.f};
#pragma unroll
                for (int i = 0; i < 8; i += 2) hmma(c, v[r][i], v[r][i], v[r][i + 1], v[r][i + 1], v[r][i], v[r][i + 1]);
                a[4 + r] = (lane & 3) == (lane >> 3) ? (b2 ? c[1] : c[0]) : 0.f;
                if (r & 1) {
                    float e[4] = {0.f, 0.f, 0.f, 0.f};
#pragma unroll
                    for (int i = 0; i < 8; i += 2) hmma(e, v[r - 1][i], v[r][i], v[r - 1][i + 1], v[r][i + 1], 0x3f803f80u, 0x3f803f80u);
                    a[r - 1] = e[0]; a[r] = e[2];
                }
            }
            float k[4];
#pragma unroll
            for (int i = 0; i < 4; i++) {
                const int lo = (i & 1) + 4 * (i >> 1);
                k[i] = (b4 ? a[lo + 2] : a[lo]) + __shfl_xor_sync(0xffffffffu, b4 ? a[lo] : a[lo + 2], 16);
            }
            const float k0 = (b3 ? k[1] : k[0]) + __shfl_xor_sync(0xffffffffu, b3 ? k[0] : k[1], 8);
            const float k1 = (b3 ? k[3] : k[2]) + __shfl_xor_sync(0xffffffffu, b3 ? k[2] : k[3], 8);
            float z = (b2 ? k1 : k0) + __shfl_xor_sync(0xffffffffu, b2 ? k0 : k1, 4);
            z += __shfl_xor_sync(0xffffffffu, z, 2);
            z += __shfl_xor_sync(0xffffffffu, z, 1);
            const float zo = __shfl_xor_sync(0xffffffffu, z, 4);
            PG(204 + bt);
            const float mu = (b2 ? zo : z) * (0.25f / D_);
            float sd_ = bfr(bfr(fmaxf(fmaf(b2 ? z : zo, 1.f / D_, -mu * mu), 0.f)) + 1e-5f);
            asm("sqrt.approx.f32 %0, %0;" : "+f"(sd_));
            const float ri = rcp(bfr(sd_));
            const uint32_t w1 = pack2(mu, ri), w2 = pack2(ri - bhi(w1), ri - bhi(w1));
#pragma unroll
            for (int r = 0; r < 4; r++) {
                const uint32_t s1 = __shfl_sync(0xffffffffu, w1, 8 * r), rl = __shfl_sync(0xffffffffu, w2, 8 * r);
                const uint32_t m2 = __byte_perm(s1, 0, 0x1010), rh = __byte_perm(s1, 0, 0x3232);
#pragma unroll
                for (int i = 0; i < 8; i++) { const uint32_t d = bsub2(v[r][i], m2); v[r][i] = bfma2(d, rh, bmul2(d, rl)); }
                sts4((la ^ (r << 4)) + r * 128, v[r][0], v[r][1], v[r][2], v[r][3]);
                sts4((la ^ (r << 4)) + r * 128 + 32768, v[r][4], v[r][5], v[r][6], v[r][7]);
#pragma unroll
                for (int i = 0; i < 8; i++) v[r][i] = v2[r][i];
            }
        }
        fence_async();
        if (SU == 0) bar_sync(5, 384); else bar_sync(2, 256);
        if (tid == 128) mbar_arrive(sb + B_LN);
        PG(202);
        if (mode == 1) return;
        float acc[128];
#pragma unroll
        for (int pass = 0; pass < 2; pass++) {
            if (pass == 1) mbar_wait(sb + B_H2, 0);
            PT(1 + 3 * pass);
            fresh(acc);
            uint32_t slot8 = pass ? 8 : 56, par = 0, prev8 = 0;
            auto adv = [&]() { prev8 = slot8; slot8 += 8; if (slot8 == 72) { slot8 = 0; par ^= 1; } };
            auto step = [&](int kk) {
                wg_fence();
                wgmma_ss_n256_tb1(acc, mkd(adA + (kk >> 2) * 512 + (kk & 3) * 2), mkd(bd2k + h * 512 + slot8 * 128), 1);
                wg_commit();
                wg_wait<1>();
            };
#pragma unroll 1
            for (int kk = 0; kk < 24; kk++) {
                mbar_wait(sb + B_R1 + slot8, par);
                step(kk);
                if (kk > 0 && w0 && elect1()) ring_half(sb, prev8, h * 8192, &mp.wup4, 16 * kk + 128, (pass ? 0 : 8) + 4 * h);
                adv();
            }
            if (pass == 0 && w0) mbar_wait(sb + B_MQ, 0);
#pragma unroll 1
            for (int kk = 24; kk < 32; kk++) {
                mbar_wait(sb + B_R1 + slot8, par);
                if (kk == 31 && el) mbar_arrive(sb + (pass ? B_H3 : B_H1));
                step(kk);
                if (w0 && elect1()) ring_half(sb, prev8, h * 8192, pass ? &mp.mqb1 : &mp.mqa2, (pass ? 64 : 32) * (kk - 24), pass ? h : 4 + 2 * h);
                adv();
            }
            wg_wait<0>();
            if (w0 && elect1()) ring_half(sb, prev8, h * 8192, pass ? &mp.mqb1 : &mp.mqa2, pass ? 0 : 256, pass ? 2 + h : 4 + 2 * h);
            pin(acc);
            PT(2 + 3 * pass);
            bf16* ucp = g_uc + ((size_t)blockIdx.x * 128 + r0) * D_ + 256 * h + 8 * (lane & 3);
            if (pass == 0) {
                float s0 = 0.f, s1 = 0.f, v0 = 0.f, v1 = 0.f;
#pragma unroll
                for (int n = 0; n < 32; n++) {
#pragma unroll
                    for (int e = 0; e < 4; e++) acc[4 * n + e] = gelu2(acc[4 * n + e]);
                    s0 += acc[4 * n] + acc[4 * n + 1]; s1 += acc[4 * n + 2] + acc[4 * n + 3];
                    v0 = fmaf(acc[4 * n], acc[4 * n], v0); v0 = fmaf(acc[4 * n + 1], acc[4 * n + 1], v0);
                    v1 = fmaf(acc[4 * n + 2], acc[4 * n + 2], v1); v1 = fmaf(acc[4 * n + 3], acc[4 * n + 3], v1);
                }
#pragma unroll
                for (int o = 1; o < 4; o <<= 1) {
                    s0 += __shfl_xor_sync(0xffffffffu, s0, o); s1 += __shfl_xor_sync(0xffffffffu, s1, o);
                    v0 += __shfl_xor_sync(0xffffffffu, v0, o); v1 += __shfl_xor_sync(0xffffffffu, v1, o);
                }
                if ((lane & 3) == 0) {
                    uint32_t a = sb + STAT + h * 512 + r0 * 8;
                    sts_f32(a, s0); sts_f32(a + 4, v0); sts_f32(a + 64, s1); sts_f32(a + 68, v1);
                }
                bar_sync(2, 256);
                {
                    uint32_t a = sb + STAT + (h ^ 1) * 512 + r0 * 8;
                    s0 = (s0 + lds_f32(a)) * (1.f / 512.f); v0 = (v0 + lds_f32(a + 4)) * (1.f / 512.f);
                    s1 = (s1 + lds_f32(a + 64)) * (1.f / 512.f); v1 = (v1 + lds_f32(a + 68)) * (1.f / 512.f);
                }
                v0 = rsqrtf(fmaxf(fmaf(-s0, s0, v0), 0.f) + 4e-5f); v1 = rsqrtf(fmaxf(fmaf(-s1, s1, v1), 0.f) + 4e-5f);
                s0 = -s0 * v0; s1 = -s1 * v1;
#pragma unroll
                for (int m = 0; m < 8; m++) {
                    const float* a_ = acc + 16 * m;
                    stg4(ucp + 64 * D_ + 32 * m, pack2(fmaf(a_[0], v0, s0), fmaf(a_[1], v0, s0)), pack2(fmaf(a_[4], v0, s0), fmaf(a_[5], v0, s0)),
                         pack2(fmaf(a_[8], v0, s0), fmaf(a_[9], v0, s0)), pack2(fmaf(a_[12], v0, s0), fmaf(a_[13], v0, s0)));
                    stg4(ucp + 72 * D_ + 32 * m, pack2(fmaf(a_[2], v1, s1), fmaf(a_[3], v1, s1)), pack2(fmaf(a_[6], v1, s1), fmaf(a_[7], v1, s1)),
                         pack2(fmaf(a_[10], v1, s1), fmaf(a_[11], v1, s1)), pack2(fmaf(a_[14], v1, s1), fmaf(a_[15], v1, s1)));
                }
            } else {
#pragma unroll
                for (int m = 0; m < 8; m++) {
                    const float* a_ = acc + 16 * m;
                    stg4(ucp + 32 * m, pack2(a_[0], a_[1]), pack2(a_[4], a_[5]), pack2(a_[8], a_[9]), pack2(a_[12], a_[13]));
                    stg4(ucp + 8 * D_ + 32 * m, pack2(a_[2], a_[3]), pack2(a_[6], a_[7]), pack2(a_[10], a_[11]), pack2(a_[14], a_[15]));
                }
                bar_sync(3 + h, 128);
            }
            PT(3 + 3 * pass);
        }
        int s = 1, ph = 0;
        uint32_t* cp = reinterpret_cast<uint32_t*>(g_uc + (size_t)blockIdx.x * 128 * D_) + (tid - 128);
        const uint32_t* dp = reinterpret_cast<const uint32_t*>(dw) + (((tid - 128) & ~15) | ((lane & 3) << 2) | ((lane >> 2) & 3));
        const uint32_t d0 = ldg_v(dp), d1 = ldg_v(dp + D_ / 2), d2 = ldg_v(dp + D_);
        uint32_t ga = ldg_cg(cp + 64 * (D_ / 2)), gb = ldg_cg(cp + 65 * (D_ / 2));
        fresh(acc);
#pragma unroll 1
        for (int j = 0; j < NKV; j++) {
            cp += D_ / 2;
            uint32_t gc = 0, uu = 0;
            if (j < NKV - 1) { gc = ldg_cg(cp + 65 * (D_ / 2)); uu = ldg_cg(cp); }
            mbar_wait(sb + B_P + s * 8, ph);
            PL(j, 0);
            if (j > 0) {
                const float sc0 = lds_f32(sb + SCL + s * 256 + r0 * 4), sc1 = lds_f32(sb + SCL + s * 256 + r0 * 4 + 32);
                if (__any_sync(0xffffffffu, sc0 != 1.f || sc1 != 1.f)) {
#pragma unroll
                    for (int n = 0; n < 32; n++) { acc[4 * n] *= sc0; acc[4 * n + 1] *= sc0; acc[4 * n + 2] *= sc1; acc[4 * n + 3] *= sc1; }
                }
            }
            mbar_wait(sb + B_GO + s * 8, ph);
            PL(j, 1);
            const uint32_t vd = sd + s * 4096 + h * 2048, pd = sd + (s == 0 ? 2 : s - 1) * 512;
            pin(acc);
            if (TRIM & 1 && j == NKV - 1) {
                wg_fence();
#pragma unroll
                for (int kk = 0; kk < 2; kk++) wgmma_ss_n256_tb1(acc, dsc(pd, R3 + kk * 32, 16), dsc(vd, kk * 2048, 8192), 1);
                wg_commit();
                wg_wait<0>();
                pin(acc);
                break;
            }
            wg_fence();
#pragma unroll
            for (int kk = 0; kk < 4; kk++) wgmma_ss_n256_tb1(acc, dsc(pd, R3 + kk * 32, 16), dsc(vd, kk * 2048, 8192), 1);
            wg_commit();
            wg_wait<0>();
            pin(acc);
            PL(j, 2);
            if (w0 && elect1()) {
                if (j + 3 < NKV) {
                    mbar_expect_tx(sb + B_KV + s * 8, 32768);
                    tma4(sb + s * 65536 + h * 32768, &mp.xa4, 0, 64 * (j + 3), 4 * h, b, sb + B_KV + s * 8);
                } else if (j < NKV - 1) {
                    const int n0 = (j == NKV - 3 ? 0 : 8) + 4 * h;
#pragma unroll 1
                    for (int n = n0; n < n0 + 4; n++) ring_ld(sb, n * 8, n);
                }
                if (j == NKV - 5 && mode == 0) flag_wait(&g_sync[3], 4);
                if (j >= XPF && j < XPF + 4) {
                    const int t0 = 62 * ti + 32 * h + 8 * (j - XPF), nr = min(8, T_ - t0);
                    if (nr > 0) l2_prefetch(x + ((size_t)b * T_ + t0) * D_, nr * 1024);
                }
                if (KPF && h == 0 && 64 * (j + KPF) + ti < T_) l2_prefetch(g_xa + ((size_t)b * (T_ + 8) + 1 + 64 * (j + KPF) + ti) * D_, 1024);
            }
            uu = pack2(gelu2(blo(uu)), gelu2(bhi(uu)));
            if (j < NKV - 1) asm volatile("st.global.u32 [%0], %1;" ::"l"(cp), "r"(bmul2(uu, bfma2(gc, d2, bfma2(gb, d1, bmul2(ga, d0))))) : "memory");
            ga = gb; gb = gc;
            if (++s == 3) s = 0;
            if (s == 1) ph ^= 1;
        }
        {
            const float i0 = lds_f32(sb + LINV + r0 * 4), i1 = lds_f32(sb + LINV + r0 * 4 + 32);
#pragma unroll
            for (int p = 0; p < 16; p++)
                stsm4(((sb + R0 + h * 32768 + loff) ^ ((p & 3) << 5)) + (p >> 2) * 8192,
                      pack2(acc[8 * p] * i0, acc[8 * p + 1] * i0), pack2(acc[8 * p + 2] * i1, acc[8 * p + 3] * i1),
                      pack2(acc[8 * p + 4] * i0, acc[8 * p + 5] * i0), pack2(acc[8 * p + 6] * i1, acc[8 * p + 7] * i1));
        }
        fence_async();
        fence_async_g();
        bar_sync(2, 256);
        if (lane == 0 && w < 2) ring_ld(sb, 128 + 16 * w + 8 * h, 16 + 2 * w + h);
        PT(7);
        fresh(acc);
        {
            uint32_t slot8 = 8 * h, par = 0, prev8 = 0;
#pragma unroll 1
            for (int kk = 0; kk < 64; kk++) {
                if (kk == 32 || kk == 48) mbar_wait(sb + B_UC + (kk >> 1 & 8), 0);
                mbar_wait(sb + B_R2 + slot8, par);
                wg_fence();
                wgmma_ss_n256_tb1(acc, mkd(sd + (1u << 16) + (R0 >> 4) + (kk >> 2 & 7) * 512 + (kk & 3) * 2), mkd(bd2k + (R1 >> 4) + slot8 * 64), 1);
                wg_commit();
                wg_wait<1>();
                if (kk > 0 && lane == 0) mbar_arrive(sb + B_E2 + prev8);
                if ((kk == 16 || kk == 32) && w0 && elect1() && (atom_inc_s(sb + CNT + 12 + (kk >> 3 & 4)) & 1)) {
                    mbar_expect_tx(sb + B_UC + (kk >> 2 & 8), 32768);
                    tma3(sb + R0 + (kk & 32) * 1024, &mp.uc, 0, 128 * blockIdx.x, kk >> 3 & 4, sb + B_UC + (kk >> 2 & 8));
                }
                prev8 = slot8;
                slot8 += 16;
                if (slot8 >= 160) { slot8 -= 160; par ^= 1; }
            }
        }
        wg_wait<0>();
        pin(acc);
        PT(8);
        mbar_wait(sb + B_X, 0);
        PT(9);
        {
            const uint32_t sr = (lrow + 63) & 63;
            const uint32_t xoff = sr * 128 + ((((lane >> 4) ^ sr) & 7) << 4);
#pragma unroll
            for (int p = 0; p < 16; p++) {
                const uint32_t a = ((sb + R2 + h * 32768 + xoff) ^ ((p & 3) << 5)) + (p >> 2) * 8192;
                uint32_t xv[4];
                ldsm4(a, xv);
#pragma unroll
                for (int e = 0; e < 4; e++)
                    xv[e] = pack2(acc[8 * p + 2 * e] + __uint_as_float(xv[e] << 16), acc[8 * p + 2 * e + 1] + __uint_as_float(xv[e] & 0xffff0000u));
                stsm4(a, xv[0], xv[1], xv[2], xv[3]);
            }
        }
        fence_async();
        bar_sync(3 + h, 128);
        if (el) {
            for (int c = 0; c < 4; c++) tma4_store(&mp.out, sb + R2 + (4 * h + c) * 8192, 0, 62 * ti, 4 * h + c, b);
            asm volatile("cp.async.bulk.commit_group;" ::: "memory");
            PT(10);
            if (h == 0) cta_done(mode);
            asm volatile("cp.async.bulk.wait_group.read 0;" ::: "memory");
        }
        PT(11);
        PG(201);
        PDUMP();
    }
}

typedef CUresult (*PFN_enc)(CUtensorMap*, CUtensorMapDataType, cuuint32_t, void*, const cuuint64_t*, const cuuint64_t*,
                            const cuuint32_t*, const cuuint32_t*, CUtensorMapInterleave, CUtensorMapSwizzle,
                            CUtensorMapL2promotion, CUtensorMapFloatOOBfill);

static void enc(PFN_enc f, CUtensorMap* m, void* base, int rank, const cuuint64_t* dims, const cuuint64_t* strides, const cuuint32_t* box) {
    cuuint32_t es[5] = {1, 1, 1, 1, 1};
    f(m, CU_TENSOR_MAP_DATA_TYPE_BFLOAT16, rank, base, dims, strides, box, es, CU_TENSOR_MAP_INTERLEAVE_NONE,
      CU_TENSOR_MAP_SWIZZLE_128B, CU_TENSOR_MAP_L2_PROMOTION_L2_256B, CU_TENSOR_MAP_FLOAT_OOB_FILL_NONE);
}
static void enc_act(PFN_enc f, CUtensorMap* m, void* base, int rows, int chunks, int trows = T_, int pitch = T_) {
    cuuint64_t dims[4] = {64, (cuuint64_t)trows, 8, (cuuint64_t)NB_};
    cuuint64_t st[3] = {1024, 128, (cuuint64_t)pitch * 1024};
    cuuint32_t box[4] = {64, (cuuint32_t)rows, (cuuint32_t)chunks, 1};
    enc(f, m, base, 4, dims, st, box);
}
static void enc_w(PFN_enc f, CUtensorMap* m, void* base, int krows, int ncols, int bk, int bc) {
    cuuint64_t dims[3] = {64, (cuuint64_t)krows, (cuuint64_t)(ncols / 64)};
    cuuint64_t st[2] = {(cuuint64_t)ncols * 2, 128};
    cuuint32_t box[3] = {64, (cuuint32_t)bk, (cuuint32_t)bc};
    enc(f, m, base, 3, dims, st, box);
}

extern "C" void kernel_launch(void* const* d_in, const int* in_sizes, int n_in, void* d_out, int out_size) {
    const bf16* x = (const bf16*)d_in[0];
    static PFN_enc fenc = nullptr;
    static void *p_xa, *p_mqk, *p_uc, *p_t1;
    static int fused = 0;
    if (!fenc) {
        void* fn = nullptr;
        cudaDriverEntryPointQueryResult qr;
        cudaGetDriverEntryPoint("cuTensorMapEncodeTiled", &fn, cudaEnableDefault, &qr);
        fenc = (PFN_enc)fn;
        cudaGetSymbolAddress(&p_xa, g_xa);
        cudaGetSymbolAddress(&p_mqk, g_mqk);
        cudaGetSymbolAddress(&p_uc, g_uc);
        cudaGetSymbolAddress(&p_t1, g_t1);
        cudaFuncSetAttribute(main_kernel, cudaFuncAttributeMaxDynamicSharedMemorySize, SMEM_BYTES);
        int dev = 0, sms = 0, occ = 0;
        cudaGetDevice(&dev);
        cudaDeviceGetAttribute(&sms, cudaDevAttrMultiProcessorCount, dev);
        cudaOccupancyMaxActiveBlocksPerMultiprocessor(&occ, main_kernel, 384, SMEM_BYTES);
        fused = sms * occ >= NCTA + 2;
    }
    Maps mp;
    enc_act(fenc, &mp.xa, (char*)p_xa + 1024, 64, 8, T_, T_ + 8);
    enc_act(fenc, &mp.xa2, (char*)p_xa + 1024, 64, 2, T_, T_ + 8);
    enc_act(fenc, &mp.xa4, (char*)p_xa + 1024, 64, 4, T_, T_ + 8);
    enc_act(fenc, &mp.xas, p_xa, 64, 1, T_ + 1, T_ + 8);
    enc_act(fenc, &mp.x, (void*)x, 64, 1);
    enc_act(fenc, &mp.out, d_out, 62, 1);
    enc_w(fenc, &mp.wup4, d_in[5], 512, 1024, 16, 4);
    enc_w(fenc, &mp.wup8, d_in[5], 512, 1024, 16, 8);
    enc_w(fenc, &mp.mqa2, p_mqk, 512, 512, 32, 2);
    enc_w(fenc, &mp.mqa4, p_mqk, 512, 512, 32, 4);
    enc_w(fenc, &mp.mqb1, p_mqk, 512, 512, 64, 1);
    enc_w(fenc, &mp.mqb2, p_mqk, 512, 512, 64, 2);
    enc_w(fenc, &mp.uc, p_uc, NCTA * 128, 512, 64, 4);
    enc_w(fenc, &mp.wq, d_in[1], 512, 512, 64, 8);
    enc_w(fenc, &mp.wk, d_in[2], 512, 512, 32, 8);
    enc_w(fenc, &mp.fa[0], d_in[3], 512, 512, 128, 1);
    enc_w(fenc, &mp.fa[1], d_in[7], 512, 512, 128, 1);
    enc_w(fenc, &mp.fa[2], p_t1, 512, 512, 128, 1);
    enc_w(fenc, &mp.fb[0], d_in[4], 512, 512, 64, 4);
    enc_w(fenc, &mp.fb[1], d_in[8], 1024, 512, 64, 4);
    enc_w(fenc, &mp.fc, p_t1, 512, 512, 64, 4);
    cudaStream_t st = cudaStreamPerThread;
    if (fused) {
        main_kernel<<<NCTA + 2, 384, SMEM_BYTES, st>>>(mp, x, (const bf16*)d_in[6], (const bf16*)d_in[5], 0);
    } else {
        main_kernel<<<NCTA + 2, 384, SMEM_BYTES, st>>>(mp, x, (const bf16*)d_in[6], (const bf16*)d_in[5], 1);
        main_kernel<<<NCTA + 2, 384, SMEM_BYTES, st>>>(mp, x, (const bf16*)d_in[6], (const bf16*)d_in[5], 2);
    }
}
```
